```python
import torch

def _softmax(x, axis=-1):
    return torch.softmax(x, dim=axis)

def _gelu(x):
    return torch.nn.functional.gelu(x, approximate='tanh')

def _silu(x):
    return torch.nn.functional.silu(x)

def _sigmoid(x):
    return torch.sigmoid(x)

def _layernorm(x, axis=-1, eps=1e-05):
    m = x.mean(dim=axis, keepdim=True)
    v = x.var(dim=axis, keepdim=True, unbiased=False)
    return (x - m) / torch.sqrt(v + eps)

def _scatter_add(tgt, idx, src, axis=0):
    return tgt.clone().index_add_(axis, idx, src)

def _segment_sum(src, seg, n):
    out = torch.zeros((n,) + src.shape[1:], dtype=src.dtype)
    return out.index_add_(0, seg, src)

def _pad(x, pw):
    flat = tuple((v for pair in reversed(pw) for v in pair))
    return torch.nn.functional.pad(x, flat)
kernel_name = 'sequential_preLN__memory_aug_recurrent_mem_tr__moe_arch_mod__prompt'

def setup_inputs():

    _w = lambda a: (lambda t: t.to(torch.bfloat16) if t.is_floating_point() else t)(torch.as_tensor(a))

    def _A_setup():
        B, S, Dm = (1, 2048, 512)
        H, Dh = (32, 128)
        M, seg = (8, 32)
        seg = min(seg, S)
        S = S // seg * seg
        return {'x': _w((lambda *s: torch.randn(*s, dtype=torch.bfloat16) * 0.05)(B, S, Dm)), 'mem0': _w((lambda *s: torch.randn(*s, dtype=torch.bfloat16) * 0.2)(B, M, Dm)), 'Wq': _w((lambda *s: torch.randn(*s, dtype=torch.bfloat16) * 1.6)(Dm, H, Dh) * Dm ** (-0.5)), 'Wk': _w((lambda *s: torch.randn(*s, dtype=torch.bfloat16) * 1.6)(Dm, H, Dh) * Dm ** (-0.5)), 'Wv': _w((lambda *s: torch.randn(*s, dtype=torch.bfloat16) * 0.2)(Dm, H, Dh) * Dm ** (-0.5)), 'Wo': _w((lambda *s: torch.randn(*s, dtype=torch.bfloat16) * 0.2)(H, Dh, Dm) * (H * Dh) ** (-0.5)), 'seg_len': seg}
    _A_in = _A_setup()

    def _B_setup():
        B, S, D, F, C = (1, 2048, 512, 1792, 2)
        return {'x': _w((lambda *s: torch.randn(*s, dtype=torch.bfloat16) * 0.05)(B, S, D)), 'w_r': _w((lambda *s: torch.randn(*s, dtype=torch.bfloat16) * 0.05)(D)), 'w_gate': _w((lambda *s: torch.randn(*s, dtype=torch.bfloat16) * 0.05)(D, F)), 'w_up': _w((lambda *s: torch.randn(*s, dtype=torch.bfloat16) * 0.05)(D, F)), 'w_down': _w((lambda *s: torch.randn(*s, dtype=torch.bfloat16) * 0.05)(F, D))}
    _B_in = _B_setup()
    return {'A_x': _A_in['x'], 'A_mem0': _A_in['mem0'], 'A_Wq': _A_in['Wq'], 'A_Wk': _A_in['Wk'], 'A_Wv': _A_in['Wv'], 'A_Wo': _A_in['Wo'], 'A_seg_len': _A_in['seg_len'], 'B_x': _B_in['x'], 'B_w_r': _B_in['w_r'], 'B_w_gate': _B_in['w_gate'], 'B_w_up': _B_in['w_up'], 'B_w_down': _B_in['w_down']}

def reference(A_x, A_mem0, A_Wq, A_Wk, A_Wv, A_Wo, A_seg_len, B_x, B_w_r, B_w_gate, B_w_up, B_w_down):

    def _A_ref(x, mem0, Wq, Wk, Wv, Wo, seg_len):
        B, S, Dm = x.shape
        H, Dh = (Wq.shape[1], Wq.shape[2])
        M = mem0.shape[1]
        scale = Dh ** (-0.5)
        n_seg = S // seg_len
        L = M + seg_len
        idx = torch.arange(L)
        mask = (idx[:, None] < M) | (idx[:, None] >= idx[None, :])
        mem = mem0
        outs = []
        for s in range(n_seg):
            xs = x[:, s * seg_len:(s + 1) * seg_len, :].clone()
            h = torch.concatenate([mem, xs], axis=1)
            q = torch.einsum('btd,dhe->bhte', h, Wq)
            k = torch.einsum('btd,dhe->bhte', h, Wk)
            v = torch.einsum('btd,dhe->bhte', h, Wv)
            scores = torch.einsum('bhqe,bhke->bhqk', q, k) * scale
            scores = torch.where(mask[None, None], scores, -1000000000.0)
            p = _softmax(scores, axis=-1)
            o = torch.einsum('bhqk,bhke->bhqe', p, v)
            o = torch.einsum('bhte,hed->btd', o, Wo)
            mem = o[:, :M, :].clone()
            outs.append(o[:, M:, :])
        return torch.concatenate(outs, axis=1)

    def _B_ref(x, w_r, w_gate, w_up, w_down):
        B, S, D = x.shape
        C = 2
        r = x @ w_r
        idx = torch.argsort(-r, axis=-1)[:, :C]
        idx_e = (lambda x, n, axis: torch.repeat_interleave(x, n, dim=axis))(idx.reshape(B, C, 1), D, axis=2)
        x_sel = (lambda x, i, axis: torch.take_along_dim(x, i, dim=axis))(x, idx_e, axis=1)
        g = _silu(x_sel @ w_gate)
        u = x_sel @ w_up
        y = g * u @ w_down
        r_sel = _sigmoid((lambda x, i, axis: torch.take_along_dim(x, i, dim=axis))(r, idx, axis=1))
        y = y * r_sel.reshape(B, C, 1)
        b_off = (torch.arange(B) * S).reshape(B, 1)
        flat_idx = (idx + b_off).reshape(B * C)
        zero = (x * 0.0).reshape(B * S, D)
        upd = _scatter_add(zero, flat_idx, y.reshape(B * C, D), axis=0)
        return x + upd.reshape(B, S, D)
    x = A_x
    h = x + _A_ref(_layernorm(x, axis=-1), A_mem0, A_Wq, A_Wk, A_Wv, A_Wo, A_seg_len)
    h2 = h + _B_ref(_layernorm(h, axis=-1), B_w_r, B_w_gate, B_w_up, B_w_down)
    return h2
```

```cpp
#include <cuda_runtime.h>
#include <cuda_bf16.h>
#include <cuda.h>
#include <stdint.h>
#include <stddef.h>

typedef __nv_bfloat16 bf16;

constexpr int SQ = 2048, DM = 512, NH = 32, DH = 128, NSEG = 64, HD = 4096, FF = 1792;

constexpr int NT = 32;
#define SPEC_TILES 30
__device__ __align__(1024) bf16 g_xn[SQ * DM];
__device__ __align__(1024) bf16 g_K[SQ * HD];
__device__ __align__(1024) bf16 g_V[SQ * HD];
__device__ __align__(1024) bf16 g_O[SQ * HD];
__device__ __align__(1024) uint32_t g_KVf[NSEG][NH][1024];
__device__ __align__(1024) float g_acc[SQ * DM];
__device__ __align__(1024) bf16 g_h[SQ * DM];
__device__ __align__(1024) bf16 g_hn[SQ * DM];
__device__ uint8_t g_xraw[12 << 20];
#define XPG 0
__device__ __forceinline__ uint64_t xpage() { return (((uint64_t)g_xraw + (2 << 20) - 1) & ~(uint64_t)((2 << 20) - 1)) + ((uint64_t)XPG << 21); }
constexpr uint32_t XR3 = (1u << 20) | (1u << 19) | (1u << 12);
__device__ __forceinline__ uint32_t aslot(uint32_t s) { return ((s & 1) << 18) | ((s & 2) << 19) | ((s & 4) * 0xc000u); }
#define IL 1
constexpr int AC1 = IL ? 48 : 256;
__device__ __forceinline__ uint32_t acc_off(uint32_t W, uint32_t lane) {
    return ((W & 2) ? 0x3000u : 0u) + ((W & 4) << 12) + (W & 1) * 2048 + (IL ? (lane >> 2) * 256 : (lane >> 2) * 128 + (lane & 4) * 16) + (lane & 3) * 16;
}
#define XM 1
__device__ __forceinline__ uint32_t ext_base(uint32_t W) { return 0x8000u + ((W & 4) << 12) + (W & 3) * 1024; }
__device__ __forceinline__ uint32_t ext_lane(uint32_t lane) { return XM == 1 ? (lane >> 3) * 256 + (lane & 7) * 4 : (XM == 2 ? (lane >> 4) * 512 + (lane & 15) * 4 : lane * 4); }
__device__ __forceinline__ uint32_t zero_off(uint32_t c, uint32_t ln) {
    return ln < 16 ? ((c & 16) ? 0x3000u : 0u) + ((c & 32) << 9) + (c & 15) * 256 + ln * 16 : ext_base(c >> 3) + ext_lane((c & 7) * 4);
}
struct Flags {
    uint32_t kv[NT][NH][2];
    uint32_t o[NT][8][32];
    uint32_t rec[64];
    uint32_t xn[128];
    uint32_t rload[64];
    uint32_t zeroed[4];
    uint32_t rows[2][64];
    uint4 cand[2][64];
    uint4 norm[64];
    uint32_t acc[NT];
};
__device__ __align__(1024) Flags g_f;
__device__ __align__(1024) uint4 g_yp[2][FF / 32][DM];
__device__ __align__(1024) uint32_t g_table[66 * 8];
__device__ __align__(256) uint32_t g_ticket[64];
__device__ uint32_t g_epoch;
#define HOLD 2
#define HSPLIT 16
#define NPROBE 3
constexpr int NCTA = 132;
constexpr int NFW = 48;
__device__ uint32_t g_abort;
__device__ long long g_dbg[4096];
#define TR(slot, v)

__device__ __forceinline__ uint32_t smem_u32(const void* p) { return (uint32_t)__cvta_generic_to_shared(p); }
__device__ __forceinline__ void mbar_init(uint32_t a, uint32_t c) { asm volatile("mbarrier.init.shared::cta.b64 [%0], %1;" :: "r"(a), "r"(c) : "memory"); }
__device__ __forceinline__ void mbar_expect_tx(uint32_t a, uint32_t tx) { asm volatile("mbarrier.arrive.expect_tx.shared::cta.b64 _, [%0], %1;" :: "r"(a), "r"(tx) : "memory"); }
__device__ __forceinline__ void mbar_arrive(uint32_t a) { asm volatile("mbarrier.arrive.shared::cta.b64 _, [%0];" :: "r"(a) : "memory"); }
__device__ __forceinline__ void mbar_arrive_if(uint32_t a, uint32_t pred) {
    asm volatile("{\n.reg .pred p;\nsetp.ne.u32 p, %1, 0;\n@p mbarrier.arrive.shared::cta.b64 _, [%0];\n}" :: "r"(a), "r"(pred) : "memory");
}
__device__ __forceinline__ bool mbar_try(uint32_t a, uint32_t ph) {
    uint32_t ok;
    asm volatile("{\n.reg .pred p;\nmbarrier.try_wait.parity.shared::cta.b64 p, [%1], %2;\nselp.u32 %0, 1, 0, p;\n}" : "=r"(ok) : "r"(a), "r"(ph) : "memory");
    return ok != 0;
}
#define SPINLOG 20
constexpr uint32_t SPIN_LIMIT = 1u << SPINLOG;
#define ABORT(code_) atomicCAS(&g_abort, 0u, (code_))
__device__ __forceinline__ void mbar_wait(uint32_t a, uint32_t ph) {
    uint32_t n = 0;
#pragma unroll 1
    while (!mbar_try(a, ph)) { if (++n > SPIN_LIMIT) { ABORT(1); break; } }
}
__device__ __forceinline__ void bar_sync(int id, int n) { asm volatile("bar.sync %0, %1;" :: "r"(id), "r"(n) : "memory"); }
__device__ __forceinline__ void bar_arrive(int id, int n) { asm volatile("bar.arrive %0, %1;" :: "r"(id), "r"(n) : "memory"); }

__device__ __forceinline__ void ldsm4(uint32_t* r, uint32_t a) {
    asm volatile("ldmatrix.sync.aligned.m8n8.x4.shared.b16 {%0,%1,%2,%3}, [%4];" : "=r"(r[0]), "=r"(r[1]), "=r"(r[2]), "=r"(r[3]) : "r"(a) : "memory");
}
__device__ __forceinline__ void ldsm4t(uint32_t* r, uint32_t a) {
    asm volatile("ldmatrix.sync.aligned.m8n8.x4.trans.shared.b16 {%0,%1,%2,%3}, [%4];" : "=r"(r[0]), "=r"(r[1]), "=r"(r[2]), "=r"(r[3]) : "r"(a) : "memory");
}
__device__ __forceinline__ void stsm4t(uint32_t a, uint32_t r0, uint32_t r1, uint32_t r2, uint32_t r3) {
    asm volatile("stmatrix.sync.aligned.m8n8.x4.trans.shared.b16 [%0], {%1,%2,%3,%4};" :: "r"(a), "r"(r0), "r"(r1), "r"(r2), "r"(r3) : "memory");
}
__device__ __forceinline__ void stsm4(uint32_t a, uint32_t r0, uint32_t r1, uint32_t r2, uint32_t r3) {
    asm volatile("stmatrix.sync.aligned.m8n8.x4.shared.b16 [%0], {%1,%2,%3,%4};" :: "r"(a), "r"(r0), "r"(r1), "r"(r2), "r"(r3) : "memory");
}
__device__ __forceinline__ uint32_t movm(uint32_t a) { uint32_t d; asm volatile("movmatrix.sync.aligned.m8n8.trans.b16 %0, %1;" : "=r"(d) : "r"(a)); return d; }
__device__ __forceinline__ void mma16816(float* d, uint32_t a0, uint32_t a1, uint32_t a2, uint32_t a3, uint32_t b0, uint32_t b1) {
    asm volatile("mma.sync.aligned.m16n8k16.row.col.f32.bf16.bf16.f32 {%0,%1,%2,%3}, {%4,%5,%6,%7}, {%8,%9}, {%0,%1,%2,%3};"
        : "+f"(d[0]), "+f"(d[1]), "+f"(d[2]), "+f"(d[3]) : "r"(a0), "r"(a1), "r"(a2), "r"(a3), "r"(b0), "r"(b1));
}
__device__ __forceinline__ void mma1688(float* d, uint32_t a0, uint32_t a1, uint32_t b0) {
    asm volatile("mma.sync.aligned.m16n8k8.row.col.f32.bf16.bf16.f32 {%0,%1,%2,%3}, {%4,%5}, {%6}, {%0,%1,%2,%3};"
        : "+f"(d[0]), "+f"(d[1]), "+f"(d[2]), "+f"(d[3]) : "r"(a0), "r"(a1), "r"(b0));
}
__device__ __forceinline__ uint32_t pack2(float a, float b) { uint32_t d; asm("cvt.rn.bf16x2.f32 %0, %1, %2;" : "=r"(d) : "f"(b), "f"(a)); return d; }
__device__ __forceinline__ float bf_lo(uint32_t w) { return __uint_as_float(w << 16); }
__device__ __forceinline__ float bf_hi(uint32_t w) { return __uint_as_float(w & 0xffff0000u); }
__device__ __forceinline__ float rbf(float x) { return __bfloat162float(__float2bfloat16_rn(x)); }

__device__ __forceinline__ void sts128(uint32_t a, float x, float y, float z, float w) { asm volatile("st.shared.v4.f32 [%0], {%1,%2,%3,%4};" :: "r"(a), "f"(x), "f"(y), "f"(z), "f"(w) : "memory"); }
__device__ __forceinline__ void sts128u(uint32_t a, uint32_t x, uint32_t y, uint32_t z, uint32_t w) { asm volatile("st.shared.v4.b32 [%0], {%1,%2,%3,%4};" :: "r"(a), "r"(x), "r"(y), "r"(z), "r"(w) : "memory"); }
__device__ __forceinline__ void sts64(uint32_t a, float x, float y) { asm volatile("st.shared.v2.f32 [%0], {%1,%2};" :: "r"(a), "f"(x), "f"(y) : "memory"); }
__device__ __forceinline__ float4 lds128(uint32_t a) { float4 v; asm volatile("ld.shared.v4.f32 {%0,%1,%2,%3}, [%4];" : "=f"(v.x), "=f"(v.y), "=f"(v.z), "=f"(v.w) : "r"(a) : "memory"); return v; }
__device__ __forceinline__ float2 lds64(uint32_t a) { float2 v; asm volatile("ld.shared.v2.f32 {%0,%1}, [%2];" : "=f"(v.x), "=f"(v.y) : "r"(a) : "memory"); return v; }
__device__ __forceinline__ uint2 lds64u(uint32_t a) { uint2 v; asm volatile("ld.shared.v2.b32 {%0,%1}, [%2];" : "=r"(v.x), "=r"(v.y) : "r"(a) : "memory"); return v; }
__device__ __forceinline__ float4 lds128v(uint32_t a) { float4 v; asm volatile("ld.volatile.shared.v4.f32 {%0,%1,%2,%3}, [%4];" : "=f"(v.x), "=f"(v.y), "=f"(v.z), "=f"(v.w) : "r"(a) : "memory"); return v; }
__device__ __forceinline__ float2 lds64v(uint32_t a) { float2 v; asm volatile("ld.volatile.shared.v2.f32 {%0,%1}, [%2];" : "=f"(v.x), "=f"(v.y) : "r"(a) : "memory"); return v; }
__device__ __forceinline__ uint4 lds128uv(uint32_t a) { uint4 v; asm volatile("ld.volatile.shared.v4.b32 {%0,%1,%2,%3}, [%4];" : "=r"(v.x), "=r"(v.y), "=r"(v.z), "=r"(v.w) : "r"(a) : "memory"); return v; }
__device__ __forceinline__ void st_async4(uint32_t a, float x, float y, float z, float w, uint32_t mb) {
    asm volatile("st.async.weak.shared::cluster.mbarrier::complete_tx::bytes.v4.f32 [%0], {%1,%2,%3,%4}, [%5];" :: "r"(a), "f"(x), "f"(y), "f"(z), "f"(w), "r"(mb) : "memory");
}
__device__ __forceinline__ void st_async2(uint32_t a, uint32_t x, uint32_t y, uint32_t mb) {
    asm volatile("st.async.weak.shared::cluster.mbarrier::complete_tx::bytes.v2.b32 [%0], {%1,%2}, [%3];" :: "r"(a), "r"(x), "r"(y), "r"(mb) : "memory");
}
__device__ __forceinline__ uint32_t ldg_rlx(const uint32_t* p) { uint32_t v; asm volatile("ld.relaxed.gpu.global.b32 %0, [%1];" : "=r"(v) : "l"(p) : "memory"); return v; }
__device__ __forceinline__ uint4 ldg_rlx4(const uint32_t* p) { uint4 v; asm volatile("ld.relaxed.gpu.global.v4.b32 {%0,%1,%2,%3}, [%4];" : "=r"(v.x), "=r"(v.y), "=r"(v.z), "=r"(v.w) : "l"(p) : "memory"); return v; }
__device__ __forceinline__ void stg_rlx(uint32_t* p, uint32_t v) { asm volatile("st.relaxed.gpu.global.b32 [%0], %1;" :: "l"(p), "r"(v) : "memory"); }
__device__ __forceinline__ void tma2d(uint32_t dst, const CUtensorMap* tm, int c0, int c1, uint32_t mb) {
    asm volatile("cp.async.bulk.tensor.2d.shared::cluster.global.mbarrier::complete_tx::bytes [%0], [%1, {%3, %4}], [%2];"
        :: "r"(dst), "l"((uint64_t)tm), "r"(mb), "r"(c0), "r"(c1) : "memory");
}

__device__ __forceinline__ void tma3d(uint32_t dst, const CUtensorMap* tm, int row, int chunk, uint32_t mb) {
    asm volatile("cp.async.bulk.tensor.3d.shared::cluster.global.mbarrier::complete_tx::bytes [%0], [%1, {%3, %4, %5}], [%2];"
        :: "r"(dst), "l"((uint64_t)tm), "r"(mb), "r"(0), "r"(row), "r"(chunk) : "memory");
}
__device__ __forceinline__ void tma_store3d(const CUtensorMap* tm, uint32_t src, int row, int chunk) {
    asm volatile("cp.async.bulk.tensor.3d.global.shared::cta.bulk_group [%0, {%2, %3, %4}], [%1];" :: "l"((uint64_t)tm), "r"(src), "r"(0), "r"(row), "r"(chunk) : "memory");
}
__device__ __forceinline__ void bulk_store(void* dst, uint32_t src, uint32_t bytes) {
    asm volatile("cp.async.bulk.global.shared::cta.bulk_group [%0], [%1], %2;" :: "l"(dst), "r"(src), "r"(bytes) : "memory");
}
#define GT(slot)
#define CNT(k)
#define CNT2(k, c)
#define PS0 20
#define TS(i)
#define TSDECL
struct Maps { CUtensorMap wq, wk, wv, wo, wo2, kx, vx, kx3, vx3, ox3, xn3, acc, wg, wu; };
typedef Maps RecMaps;
__device__ __forceinline__ void st_rel(uint32_t* p, uint32_t v) { asm volatile("st.release.gpu.global.u32 [%0], %1;" :: "l"(p), "r"(v) : "memory"); }
#define PUBLISH(p, v) st_rel(p, v)
__device__ __forceinline__ uint2 ldg_rlx2(const uint32_t* p) { uint2 v; asm volatile("ld.relaxed.gpu.global.v2.b32 {%0,%1}, [%2];" : "=r"(v.x), "=r"(v.y) : "l"(p) : "memory"); return v; }
__device__ __forceinline__ void wait_eq2(const uint32_t* p, uint32_t e, int code) {
    uint32_t n = 0;
#pragma unroll 1
    while (true) { uint2 v = ldg_rlx2(p); if (v.x == e && v.y == e) break; __nanosleep(64); if (++n > SPIN_LIMIT) { ABORT(code); break; } }
}
__device__ __forceinline__ void wait_eq4(const uint32_t* p, uint32_t e, int code) {
    uint32_t n = 0;
#pragma unroll 1
    while (true) { uint4 v = ldg_rlx4(p); if (v.x == e && v.y == e && v.z == e && v.w == e) break; __nanosleep(64); if (++n > SPIN_LIMIT) { ABORT(code); break; } }
}
__device__ __forceinline__ void wait_rec(const uint32_t* p, uint32_t e, uint32_t steps) {
    uint32_t n = 0;
#pragma unroll 1
    while (true) {
        uint2 v = ldg_rlx2(p);
        if ((v.x >> 8) == e && (v.y >> 8) == e && (v.x & 255) >= steps && (v.y & 255) >= steps) break;
        __nanosleep(64); if (++n > SPIN_LIMIT) { ABORT(8); break; }
    }
}

constexpr int R_QK1 = 0;
constexpr int R_WO = 65536;
constexpr int R_T = 131072;
constexpr int R_SLOT1 = R_T;
constexpr int R_MEMB = R_T + 24576;
constexpr int R_QP = R_MEMB + 8192;
constexpr int R_VRED = R_QP + 4096;
constexpr int R_STG = R_VRED + 2048;
constexpr int R_AX = R_STG + 2048;
constexpr int R_SLOT0 = 196608;
constexpr int R_SLOC = R_SLOT0 + 24576;
constexpr int R_SREM = R_SLOC + 1536;
constexpr int R_VB = R_SREM + 1536;
constexpr int R_MISC = R_VB + 2048;
constexpr int R_LT = R_MISC + 128;
constexpr int R_BAR = 229888;
constexpr int R_TS = 229888 + 128;
static_assert(R_AX + 24576 <= R_SLOT0 && R_LT + 2560 <= 229376, "smem map");
enum { MB_W0 = 0, MB_W1, MB_WV, MB_WO, MB_S, MB_FULL0, MB_FULL1, MB_V, MB_N };

__device__ __forceinline__ float ex2(float x) { float y; asm("ex2.approx.ftz.f32 %0, %1;" : "=f"(y) : "f"(x)); return y; }
__device__ __forceinline__ float rcpf(float x) { float y; asm("rcp.approx.ftz.f32 %0, %1;" : "=f"(y) : "f"(x)); return y; }
__device__ __forceinline__ void mma16816z(float* d, uint32_t a0, uint32_t a1, uint32_t a2, uint32_t a3, uint32_t b0, uint32_t b1) {
    asm volatile("mma.sync.aligned.m16n8k16.row.col.f32.bf16.bf16.f32 {%0,%1,%2,%3}, {%4,%5,%6,%7}, {%8,%9}, {%10,%10,%10,%10};"
        : "=f"(d[0]), "=f"(d[1]), "=f"(d[2]), "=f"(d[3]) : "r"(a0), "r"(a1), "r"(a2), "r"(a3), "r"(b0), "r"(b1), "f"(0.f));
}
__device__ __forceinline__ void mma1688hz(float* d, uint32_t a0, uint32_t a1, uint32_t b0) {
    asm volatile("mma.sync.aligned.m16n8k8.row.col.f32.f16.f16.f32 {%0,%1,%2,%3}, {%4,%5}, {%6}, {%7,%7,%7,%7};"
        : "=f"(d[0]), "=f"(d[1]), "=f"(d[2]), "=f"(d[3]) : "r"(a0), "r"(a1), "r"(b0), "f"(0.f));
}
#define MMA(d, a, b0, b1) mma16816(d, a[0], a[1], a[2], a[3], b0, b1)
#define MMAZ(d, a, b0, b1) mma16816z(d, a[0], a[1], a[2], a[3], b0, b1)
#define MMAF(first, d, a, b0, b1) do { if (first) MMAZ(d, a, b0, b1); else MMA(d, a, b0, b1); } while (0)

__device__ __forceinline__ uint32_t uni(uint32_t x) { return __reduce_max_sync(0xffffffffu, x); }
__device__ __forceinline__ void mbar_wait_u(uint32_t a, uint32_t ph) {
    uint32_t n = 0;
#pragma unroll 1
    while (!__all_sync(0xffffffffu, mbar_try(a, ph))) { if (++n > SPIN_LIMIT) { ABORT(1); break; } }
}
__device__ __forceinline__ void mbar_wait_p(uint32_t a, uint32_t ph) {
    asm volatile("{\n.reg .pred p, q;\n.reg .u32 n;\nmov.u32 n, 0;\nWL: mbarrier.try_wait.parity.shared::cta.b64 p, [%0], %1;\nadd.u32 n, n, 1;\n"
                 "setp.lt.and.u32 q, n, %2, !p;\n@q bra.uni WL;\n}" :: "r"(a), "r"(ph), "n"(SPIN_LIMIT) : "memory");
}
__device__ __forceinline__ uint32_t mbar_test(uint32_t a, uint32_t ph) {
    uint32_t ok;
    asm volatile("{\n.reg .pred p;\nmbarrier.test_wait.parity.shared::cta.b64 p, [%1], %2;\nselp.u32 %0, 1, 0, p;\n}" : "=r"(ok) : "r"(a), "r"(ph) : "memory");
    return ok;
}
__device__ __forceinline__ uint32_t opaque(uint32_t x) { return __shfl_sync(0xffffffffu, x, threadIdx.x & 31); }
__device__ __forceinline__ const uint32_t* mkptr(uint32_t lo, uint32_t hi) { uint64_t r; asm("mov.b64 %0, {%1, %2};" : "=l"(r) : "r"(lo), "r"(hi)); return (const uint32_t*)r; }
__device__ __forceinline__ uint32_t prmt(uint32_t a, uint32_t b, uint32_t s) { uint32_t d; asm("prmt.b32 %0, %1, %2, %3;" : "=r"(d) : "r"(a), "r"(b), "r"(s)); return d; }
__device__ __forceinline__ uint32_t packh2(float a, float b) { uint32_t d; asm("cvt.rn.f16x2.f32 %0, %1, %2;" : "=r"(d) : "f"(b), "f"(a)); return d; }
__device__ __forceinline__ uint32_t hadd2b(uint32_t a, uint32_t b) { uint32_t d; asm("add.rn.bf16x2 %0, %1, %2;" : "=r"(d) : "r"(a), "r"(b)); return d; }
__device__ __forceinline__ uint32_t hmul2b(uint32_t a, uint32_t b) { uint32_t d; asm("mul.rn.bf16x2 %0, %1, %2;" : "=r"(d) : "r"(a), "r"(b)); return d; }
__device__ __forceinline__ uint32_t amax2b(uint32_t a, uint32_t b) { uint32_t d; asm("max.xorsign.abs.bf16x2 %0, %1, %2;" : "=r"(d) : "r"(a), "r"(b)); return d; }
__device__ __forceinline__ uint32_t amax2h(uint32_t a, uint32_t b) { uint32_t d; asm("max.xorsign.abs.f16x2 %0, %1, %2;" : "=r"(d) : "r"(a), "r"(b)); return d; }
__device__ __forceinline__ void sts32(uint32_t a, uint32_t x) { asm volatile("st.shared.b32 [%0], %1;" :: "r"(a), "r"(x) : "memory"); }
__device__ __forceinline__ uint32_t lds32v_(uint32_t a) { uint32_t v; asm volatile("ld.volatile.shared.b32 %0, [%1];" : "=r"(v) : "r"(a) : "memory"); return v; }
__device__ __forceinline__ void stg4(void* p, uint4 v) { asm volatile("st.relaxed.gpu.global.v4.b32 [%0], {%1,%2,%3,%4};" :: "l"(p), "r"(v.x), "r"(v.y), "r"(v.z), "r"(v.w) : "memory"); }
__device__ __forceinline__ void lds_frag(uint32_t* r, uint32_t a) {
    asm volatile("ld.shared.v4.b32 {%0,%1,%2,%3}, [%4];" : "=r"(r[0]), "=r"(r[1]), "=r"(r[2]), "=r"(r[3]) : "r"(a) : "memory");
}
__device__ __forceinline__ void lds_fragv(uint32_t* r, uint32_t a) {
    asm volatile("ld.volatile.shared.v4.b32 {%0,%1,%2,%3}, [%4];" : "=r"(r[0]), "=r"(r[1]), "=r"(r[2]), "=r"(r[3]) : "r"(a) : "memory");
}
__device__ __forceinline__ uint32_t xorv(uint32_t a, uint32_t b) { uint32_t d; asm volatile("xor.b32 %0, %1, %2;" : "=r"(d) : "r"(a), "r"(b)); return d; }
#define SCHED(k) asm volatile("{\n.reg .pred p;\nsetp.ne.u32 p, %0, %1;\n@p bra.uni SD;\nSL: nanosleep.u32 64;\nbra.uni SL;\nSD:\n}" :: "r"(sbu - s), "n"(k) : "memory")
__device__ __forceinline__ uint32_t pack2v(float a, float b) { uint32_t d; asm volatile("cvt.rn.bf16x2.f32 %0, %1, %2;" : "=r"(d) : "f"(b), "f"(a)); return d; }
#define FU(x) __float_as_uint(x)
__device__ __forceinline__ uint32_t clk32() { uint32_t t; asm volatile("mov.u32 %0, %%clock;" : "=r"(t) :: "memory"); return t; }
__device__ __forceinline__ void spin_until(uint32_t t0, uint32_t d) {
    if (d) {
#pragma unroll 1
        while (__any_sync(0xffffffffu, clk32() - t0 < d)) {}
    }
}
constexpr int SH_OFF = 229376 + 384;
constexpr uint32_t HONE2 = 0x3c003c00u, HCNT2 = 0x50005000u;

__device__ __forceinline__ uint64_t desc_sw128(uint32_t addr, uint32_t lbo, uint32_t sbo) {
    return (uint64_t)((addr & 0x3FFFF) >> 4) | ((uint64_t)(lbo >> 4) << 16) | ((uint64_t)(sbo >> 4) << 32) | (1ull << 62);
}
#define DP 480
#define NAX 4
#define NXL 1
#define NCX 2
#define NCL 2
#define DC 100
#define DEC 0
#define KXI 5
#define ANB 3
#define BNB 3
#define CNB 3
#define SMA 0x40
#define SMB 0
#define SMC 0x01
#define IVA 0
#define RGA 160
#define RGC 160
#define RGB (504 - RGA - RGC)
#define NRW 8
#define NBR 16
#define E0 0
#define E1 6
#define E2 4
#define E3 8
#define IV 2
#define DEX 0
#define STAG 1
#define VDEP 0
#define NB1 10
#define DB2 40
#define DITHER 0
#define DA 40
#define DB 40
#define DS 200

template <int K> __device__ __forceinline__ void sched(uint32_t key) {
    asm volatile("{\n.reg .pred p;\nsetp.ne.u32 p, %0, %1;\n@p bra.uni SD;\nSL: nanosleep.u32 64;\nbra.uni SL;\nSD:\n}" :: "r"(key), "n"(K) : "memory");
}
__device__ __forceinline__ void sched_i(int i, uint32_t key) {
    if (i == -1) sched<20>(key); if (i == 0) sched<21>(key); if (i == 1) sched<22>(key); if (i == 2) sched<23>(key);
    if (i == 3) sched<24>(key); if (i == 4) sched<25>(key); if (i == 5) sched<26>(key); if (i == 6) sched<27>(key);
}
template <int NB, int SM, class F>
__device__ __forceinline__ void g1(float* q0, float* k0, uint32_t (*wq)[4], uint32_t (*wk)[4], uint32_t ga, uint32_t key, F&& hook) {
    float q1[4], k1[4];
    uint32_t b[NB][4];
#pragma unroll
    for (int i = 0; i < NB; i++) ldsm4(b[i], ga + i * 512);
    hook(-1, b[0]);
    if (SM & 1) sched_i(-1, key);
#pragma unroll
    for (int i = 0; i < 8; i++) {
        uint32_t* c = b[i % NB];
        MMAF(i == 0, q0, wq[2 * i], c[0], c[1]); MMAF(i == 0, k0, wk[2 * i], c[0], c[1]);
        MMAF(i == 0, q1, wq[2 * i + 1], c[2], c[3]); MMAF(i == 0, k1, wk[2 * i + 1], c[2], c[3]);
        const uint32_t cc_[4] = {c[0], c[1], c[2], c[3]};
        if (i + NB < 8) ldsm4(b[i % NB], ga + (i + NB) * 512);
        hook(i, cc_);
        if ((SM >> (i + 1)) & 1) sched_i(i, key);
    }
#pragma unroll
    for (int i = 0; i < 4; i++) { q0[i] += q1[i]; k0[i] += k1[i]; }
}
__device__ __forceinline__ float frag_norm2(uint32_t (*w)[4]) {
    float d0[4], d1[4];
#pragma unroll
    for (int i = 0; i < 32; i++) { MMAF(i == 0, d0, w[i], w[i][0], w[i][2]); MMAF(i == 0, d1, w[i], w[i][1], w[i][3]); }
    const int lane = threadIdx.x & 31, g = lane >> 2, t = lane & 3;
    float v = g == 2 * t ? d0[0] + d1[2] : (g == 2 * t + 1 ? d0[1] + d1[3] : 0.f);
#pragma unroll
    for (int o = 16; o; o >>= 1) v += __shfl_xor_sync(0xffffffffu, v, o);
    return v;
}
__device__ __forceinline__ void load_slot(uint32_t sb, int c, int tile, const Maps& maps) {
    const uint32_t dst = sb + ((tile & 1) ? R_SLOT1 : R_SLOT0), mb = sb + R_BAR + 8 * (MB_FULL0 + (tile & 1));
    mbar_expect_tx(mb, 24576);
    tma2d(dst + 16384, &maps.kx, c * 64, tile * 64, mb);
    tma3d(dst, &maps.vx3, tile * 64, (c >> 1) * 2, mb);
}
__device__ __forceinline__ void put_mem0(uint32_t sb, int W, const bf16* __restrict__ mem0) {
    const int lane = threadIdx.x & 31;
    const uint4 m0 = *(const uint4*)(mem0 + (lane & 7) * DM + (W * 8 + (lane >> 3)) * 8), m1 = *(const uint4*)(mem0 + (lane & 7) * DM + (W * 8 + 4 + (lane >> 3)) * 8);
    bar_sync(3, 256);
    sts128u(sb + R_MEMB + W * 1024 + lane * 16, m0.x, m0.y, m0.z, m0.w);
    sts128u(sb + R_MEMB + W * 1024 + 512 + lane * 16, m1.x, m1.y, m1.z, m1.w);
}
#define GATHER1(HALF)                                                                                           \
        {                                                                                                       \
            float d0[4], d1[4], d2[4], d3[4];                                                                   \
            const uint4 x0 = ldg_rlx4(pm), x1 = ldg_rlx4(pm + AC1); const uint32_t y = ldg_rlx(px);               \
            mma1688hz(d0, x0.x, x0.y, lt.z); mma1688hz(d1, x1.x, x1.y, lt.z);                                   \
            cw = (lt.w & 0x4000u) ? prmt(x0.w, x1.w, 0x7632u) : y;                                              \
            mma1688hz(d2, x0.z, prmt(x0.w, y, lt.w), lt.z); mma1688hz(d3, x1.z, prmt(x1.w, y, lt.w | 0x2200u), lt.z);          \
            stsm4t(rG + R_MEMB + HALF * 4096, pack2(d0[0], d0[1]), pack2(d0[2], d0[3]), pack2(d2[0], d2[1]), pack2(d2[2], d2[3]));       \
            stsm4t(rG + R_MEMB + HALF * 4096 + 512, pack2(d1[0], d1[1]), pack2(d1[2], d1[3]), pack2(d3[0], d3[1]), pack2(d3[2], d3[3])); \
        }
__device__ __forceinline__ uint32_t h2b(uint32_t w) {
    uint32_t d;
    asm("{\n.reg .f16 l, h;\n.reg .f32 a, b;\nmov.b32 {l, h}, %1;\ncvt.f32.f16 a, l;\ncvt.f32.f16 b, h;\ncvt.rn.bf16x2.f32 %0, b, a;\n}" : "=r"(d) : "r"(w));
    return d;
}
#define GATHER2(HALF)                                                                                           \
        {                                                                                                       \
            const uint4 x0 = ldg_rlx4(pm), x1 = ldg_rlx4(pm + AC1); const uint32_t y = ldg_rlx(px);               \
            cw = (lt.w & 0x4000u) ? prmt(x0.w, x1.w, 0x7632u) : y;                                              \
            stsm4t(rG + R_MEMB + HALF * 4096, h2b(x0.x), h2b(x0.y), h2b(x0.z), h2b(prmt(x0.w, y, lt.w)));       \
            stsm4t(rG + R_MEMB + HALF * 4096 + 512, h2b(x1.x), h2b(x1.y), h2b(x1.z), h2b(prmt(x1.w, y, lt.w | 0x2200u))); \
        }
#define GATHER(HALF, PRE, SYNC, AFTER)                                                                                      \
        {                                                                                                       \
            const uint32_t so = aslot(s);                                                                       \
            const uint32_t ua = (glo + acc_off(HALF * 4 + fo, 0)) ^ so, ux = (glo + ext_base(HALF * 4 + fo)) ^ so; \
            uint4 lt;                                                                                           \
            lt.x = lds32v_(rL + R_LT); lt.y = lds32v_(rL + R_LT + 4); lt.z = DEC ? 0 : lds32v_(rL + R_LT + 8); lt.w = lds32v_(rL + R_LT + 12); \
            const uint32_t* pm = mkptr(ua + lt.x, ghi);                                                         \
            const uint32_t* px = mkptr(ux + lt.y, ghi);                                                         \
            PRE                                                                                                 \
            bar_sync(5, 384);                                                                                   \
            const uint32_t t0 = clk32();                                                                        \
            SYNC                                                                                                \
            spin_until(t0, DP + DITHER);                                                                                 \
            TS(11);                                                                                             \
            uint32_t cw, nr = 0;                                                                                \
            _Pragma("unroll 1") do {                                                                            \
                if (DEC) GATHER2(HALF) else GATHER1(HALF)                                                       \
                nr++;                                                                                           \
            } while (__any_sync(0xffffffffu, cw != HCNT2 && nr < SPIN_LIMIT));                                  \
            AFTER                                                                                               \
            CNT2(HALF * 4 + (s & 1) * 2 + (nr > 2), nr > 1);                                                    \
            TS(12);                                                                                             \
        }
#define GOBAR (fo == 3 ? 14 : 10 + fo)

__device__ __forceinline__ void rec_a(uint32_t sb, int c, const bf16* __restrict__ mem0, uint32_t epoch) {
    const int tid = threadIdx.x, lane = tid & 31, f = tid >> 5;
    uint32_t wq[16][4], wk[16][4];
    const int lrow = ((lane >> 4) << 3) + (lane & 7), lsel = (lane >> 3) & 1;
    {
        mbar_wait(sb + R_BAR + 8 * MB_W0, 0);
        if (c == 7 && tid == 0) GT(1421);
        const uint32_t a = sb + R_T + lrow * 128 + (((2 * f + lsel) ^ (lane & 7)) << 4);
#pragma unroll
        for (int kk = 0; kk < 16; kk++) { ldsm4t(wq[kk], a + kk * 2048); ldsm4t(wk[kk], a + 32768 + kk * 2048); }
        if (f == 3) wait_eq4(&g_f.xn[lane * 4], epoch, 13);
        __syncwarp();
        put_mem0(sb, f, mem0);
    }
    const uint32_t rL = opaque(sb + lane * 16), rG = opaque(sb + lane * 16 + f * 1024);
    const uint32_t sbu = uni(sb), fo = uni(f), cc = uni(c);
    const uint64_t gx = xpage();
    const uint32_t ghi = uni((uint32_t)(gx >> 32)), glo = uni((uint32_t)gx);
#pragma unroll
    for (int i = 0; i < NAX; i++) {
        sts128u(rG + R_AX + 4096 * i, wq[i][0], wq[i][1], wq[i][2], wq[i][3]);
        sts128u(rG + R_AX + 4096 * i + 512, wk[i][0], wk[i][1], wk[i][2], wk[i][3]);
    }
    sts128u(rL + R_LT + 512 + f * 512, (sb + R_SREM + (f >= 2 ? lane * 8 + f * 256 : lane * 16 + f * 1024)) ^ 0x01000000u, (sb + R_BAR + 8 * MB_S) ^ 0x01000000u,
            sb + R_QP + (lane >> 4) * 128 + lsel * 512 + (lane & 7) * 16 + (f == 3 ? 2048 : 0), sb + lrow * 128 + ((lsel ^ (lane & 7)) << 4));
    __syncwarp();
    if (tid == 0) GT(c * 8 + 1);
    TSDECL;
    const float cexp = 0.08838834764831845f * 1.4426950408889634f;
    float cs = cexp;
    mbar_wait_u(sbu + R_BAR + 8 * MB_FULL0, 0);
    auto step = [&](int s) -> bool {
        bar_sync(1, 128);
        TS(3);
        float q0[4], k0[4];
        uint32_t kx[4][4];
        uint4 ta;
        const uint32_t ro = ((s & 2) ? R_SLOT1 : R_SLOT0) + (s & 1) * 4096;
        g1<ANB, SMA>(q0, k0, wq, wk, rL + R_MEMB, sbu - s, [&](int i, const uint32_t*) {
            if (i == -1) {
#pragma unroll
                for (int n = NAX - NXL; n < NAX; n++) { lds_fragv(wq[n], rG + R_AX + 4096 * n); lds_fragv(wk[n], rG + R_AX + 4096 * n + 512); }
                ta = lds128uv(rL + R_LT + 512 + fo * 512);
            }
            if (i == KXI) {
#pragma unroll
                for (int kk = 0; kk < 4; kk++)
                    asm volatile("{\n.reg .pred p;\nsetp.lt.u32 p, %5, 2;\nmov.b32 %0, 0;\nmov.b32 %1, 0;\nmov.b32 %2, 0;\nmov.b32 %3, 0;\n"
                                 "@p ldmatrix.sync.aligned.m8n8.x4.shared.b16 {%0,%1,%2,%3}, [%4];\n}"
                                 : "=r"(kx[kk][0]), "=r"(kx[kk][1]), "=r"(kx[kk][2]), "=r"(kx[kk][3]) : "r"((ta.w ^ (kk * 32)) + (ro + 16384 + fo * 2048)), "r"(fo) : "memory");
            }
            if (i == IVA) bar_arrive(GOBAR, 96);
        });
        stsm4t(rG + R_QP, pack2(q0[0], q0[1]), pack2(q0[2], q0[3]), pack2(k0[0], k0[1]), pack2(k0[2], k0[3]));
        TS(4);
        if (fo < 2) {
            bar_sync(3, 256);
            TS(5);
            uint32_t qa[4][4];
#pragma unroll
            for (int kk = 0; kk < 4; kk++) { if (kk == 2) bar_arrive(13, 256); ldsm4(qa[kk], ta.z + kk * 1024); }
            float s0[4], s1[4], s2[4], s3[4];
            MMAZ(s0, qa[0], kx[0][0], kx[0][1]); MMAZ(s1, qa[0], kx[0][2], kx[0][3]);
            MMAZ(s2, qa[1], kx[1][0], kx[1][1]); MMAZ(s3, qa[1], kx[1][2], kx[1][3]);
            MMA(s0, qa[2], kx[2][0], kx[2][1]); MMA(s1, qa[2], kx[2][2], kx[2][3]);
            MMA(s2, qa[3], kx[3][0], kx[3][1]); MMA(s3, qa[3], kx[3][2], kx[3][3]);
            const float x = ((s0[0] + s0[2]) + (s2[0] + s2[2])) * cs, y = ((s0[1] + s0[3]) + (s2[1] + s2[3])) * cs;
            const float z = ((s1[0] + s1[2]) + (s3[0] + s3[2])) * cs, w = ((s1[1] + s1[3]) + (s3[1] + s3[3])) * cs;
            st_async4(ta.x, x, y, z, w, ta.y);
            sts128(rG + R_SLOC, x, y, z, w);
        } else {
            bar_sync(3, 256);
            TS(5);
            uint32_t kb[4], kc[4], qa[4], qc[4];
            ldsm4(kb, ta.z + 256); ldsm4(qa, ta.z); bar_arrive(13, 256); ldsm4(kc, ta.z + 1280); ldsm4(qc, ta.z + 1024);
            const uint32_t k0_ = hadd2b(kb[0], kb[1]), k1_ = hadd2b(kb[2], kb[3]), k2_ = hadd2b(kc[0], kc[1]), k3_ = hadd2b(kc[2], kc[3]);
            float s0[4], s2[4];
            MMAZ(s0, qa, k0_, k1_); MMAZ(s2, qc, k2_, k3_);
            const float x = ((s0[0] + s0[2]) + (s2[0] + s2[2])) * cs, y = ((s0[1] + s0[3]) + (s2[1] + s2[3])) * cs;
            st_async2(ta.x, FU(x), FU(y), ta.y);
            sts64((ta.x ^ 0x01000000u) + (R_SLOC - R_SREM), x, y);
            sts128u(rL + R_STG + (fo & 1) * 512, k0_, k1_, k2_, k3_);
            bar_arrive(9, 192);
        }
        TS(6);
        const uint32_t r8 = (rL + sbu) >> 1;
        uint32_t vt00[4], vt01[4], vt10[4], vt11[4];
        {
            const uint32_t rV = ta.w ^ ((fo & 1) * 64), vo = ro + (fo >> 1) * 8192;
            ldsm4t(vt00, rV + vo); ldsm4t(vt10, (rV ^ 32) + vo); ldsm4t(vt01, rV + vo + 2048); ldsm4t(vt11, (rV ^ 32) + vo + 2048);
        }
        bar_sync(4, 128);
        const float4 l0 = lds128v(rL + R_SLOC), l1 = lds128v(rL + R_SLOC + 1024);
        const float2 l2 = lds64v(r8 + R_SLOC + 512), l3 = lds64v(r8 + R_SLOC + 768);
        if (E2) bar_arrive(15, 256);
        TS(7);
        if (s == NSEG - 1) { mbar_wait_u(sbu + R_BAR + 8 * MB_S, 1); mbar_wait_u(sbu + R_BAR + 8 * MB_V, 1); return true; }
        mbar_wait_p(sbu + R_BAR + 8 * MB_S, s & 1);
        TS(8);
        {
            const float4 r0 = lds128v(rL + R_SREM), r1 = lds128v(rL + R_SREM + 1024);
            const float2 r2 = lds64v(r8 + R_SREM + 512), r3 = lds64v(r8 + R_SREM + 768);
            float sv[10];
            sv[0] = l0.x + r0.x; sv[1] = l0.y + r0.y; sv[2] = l0.z + r0.z; sv[3] = l0.w + r0.w;
            sv[4] = l1.x + r1.x; sv[5] = l1.y + r1.y; sv[6] = l1.z + r1.z; sv[7] = l1.w + r1.w;
            sv[8] = ((l2.x + l3.x) + r2.x) + r3.x; sv[9] = ((l2.y + l3.y) + r2.y) + r3.y;
            float m = fmaxf(fmaxf(fmaxf(sv[0], sv[1]), fmaxf(sv[2], sv[3])), fmaxf(fmaxf(sv[4], sv[5]), fmaxf(sv[6], sv[7])));
            m = fmaxf(m, fmaxf(sv[8], sv[9]));
            {
                const float m1 = __shfl_xor_sync(0xffffffffu, m, 1), m2 = __shfl_xor_sync(0xffffffffu, m, 2), m3 = __shfl_xor_sync(0xffffffffu, m, 3);
                m = fmaxf(fmaxf(m, m1), fmaxf(m2, m3));
            }
            const uint32_t ONE2 = 0x3f803f80u;
            float o0[4], o1[4], sm[4];
            const uint32_t pb0 = pack2(ex2(sv[0] - m), ex2(sv[1] - m)), pb1 = pack2(ex2(sv[2] - m), ex2(sv[3] - m));
            mma16816z(sm, ONE2, ONE2, ONE2, ONE2, pb0, pb1);
            MMAZ(o0, vt00, pb0, pb1); MMAZ(o1, vt10, pb0, pb1);
            const uint32_t z = (VDEP == 0 ? FU(m) : pb0) & (sbu & 8);
            const uint32_t vok = mbar_test(sbu + R_BAR + 8 * MB_V + z, s & 1);
            const uint32_t rv = r8 + vok * 8;
            float2 va = lds64v(rv + R_VB - 8 + fo * 512);
            bar_arrive(13, 256);
            float2 vb = lds64v(rv + R_VB - 8 + fo * 512 + 256);
            float sig = __uint_as_float(lds32v_(sbu + R_MISC + 40));
            const uint32_t pb2 = pack2(ex2(sv[4] - m), ex2(sv[5] - m)), pb3 = pack2(ex2(sv[6] - m), ex2(sv[7] - m));
            mma16816(sm, ONE2, ONE2, ONE2, ONE2, pb2, pb3);
            const uint32_t pb4 = pack2(ex2(sv[8] - m), ex2(sv[9] - m));
            MMA(o0, vt01, pb2, pb3); MMA(o1, vt11, pb2, pb3);
            mma1688(sm, ONE2, ONE2, pb4);
            const float z0 = rcpf(sm[0]), z1 = rcpf(sm[1]);
#define PUT_O()                                                                                                   \
            {                                                                                                     \
                float a0[4] = {o0[0], o0[1], o0[2], o0[3]}, a1[4] = {o1[0], o1[1], o1[2], o1[3]};                 \
                mma1688(a0, FU(va.x), FU(va.y), pb4); mma1688(a1, FU(vb.x), FU(vb.y), pb4);                       \
                const float i0 = z0 * sig, i1 = z1 * sig;                                                         \
                stsm4t(rG + R_QP, pack2(a0[0] * i0, a0[1] * i1), pack2(a0[2] * i0, a0[3] * i1), pack2(a1[0] * i0, a1[1] * i1), pack2(a1[2] * i0, a1[3] * i1)); \
            }
            PUT_O()
            asm volatile("{\n.reg .pred p;\nsetp.ne.u32 p, %0, 0;\n@p bar.arrive 8, 256;\n}" :: "r"(vok) : "memory");
            if (__builtin_expect(__any_sync(0xffffffffu, vok == 0), 0)) {
                mbar_wait_p(sbu + R_BAR + 8 * MB_V, s & 1);
                va = lds64v(r8 + R_VB + fo * 512); vb = lds64v(r8 + R_VB + fo * 512 + 256);
                sig = __uint_as_float(lds32v_(sbu + R_MISC + 40));
                PUT_O()
                bar_arrive(8, 256);
                CNT(8);
            }
            const float r = __uint_as_float(0x7f000000u - FU(sig));
            cs = cexp * r * (fo >= 2 ? r : 1.f);
        }
        TS(10);
        return false;
    };
    step(0);
#pragma unroll 1
    for (int s = 0;; s++) {
        if (s & 1) mbar_wait_p(sbu + R_BAR + 8 * (MB_FULL0 + (((s + 1) >> 1) & 1)), ((s + 1) >> 2) & 1);
        auto early = [&]() {
            SCHED(13);
#pragma unroll
            for (int i = 0; i < NAX - NXL; i++) { lds_fragv(wq[i], rG + R_AX + 4096 * i); lds_fragv(wk[i], rG + R_AX + 4096 * i + 512); }
        };
        GATHER(0, asm volatile("" :: "l"(pm), "l"(px)); early();, , )
        if (step(s + 1)) break;
    }
    CNT(9);
    if (rG == sbu) GT(cc * 8 + 4);
}

__device__ __forceinline__ void rec_b(uint32_t sb, int c, uint32_t epoch) {
    const int tid = threadIdx.x - 128, lane = tid & 31, f = tid >> 5;
    uint32_t wq[16][4], wk[16][4], wo[32][4];
    const int lrow = ((lane >> 4) << 3) + (lane & 7), lsel = (lane >> 3) & 1;
    const uint32_t rL = opaque(sb + lane * 16), rW = opaque(sb + lane * 16 + f * 16384);
    const uint32_t sbu = uni(sb), fo = uni(f), cc = uni(c), po = cc & 1, ep = uni(epoch);
    {
        mbar_wait(sb + R_BAR + 8 * MB_WO, 0);
        if (c == 7 && tid == 0) GT(1426);
        const uint32_t aO = sb + R_WO + f * 16384 + lrow * 128 + ((lsel ^ (lane & 7)) << 4);
#pragma unroll
        for (int i = 0; i < 32; i++) {
            const int tile = STAG ? (i >> 4) * 2 + (i & 1) : i & 3, kk = STAG ? (i >> 1) & 7 : i >> 2;
            ldsm4t(wo[i], (aO ^ (32 * tile)) + kk * 2048);
        }
        const float no = frag_norm2(wo);
        if (lane == 0) sts32(sb + R_MISC + 80 + f * 4, FU(no));
        __syncwarp();
        bar_arrive(15, 256);
#pragma unroll
        for (int i = NRW; i < 32; i++) sts128u(rW + R_WO + i * 512, wo[i][0], wo[i][1], wo[i][2], wo[i][3]);
        mbar_wait(sb + R_BAR + 8 * MB_W1, 0);
        if (c == 7 && tid == 0) GT(1422);
        if (tid == 0) stg_rlx(&g_f.rload[c], epoch);
        __syncwarp();
        const uint32_t a = sb + R_QK1 + lrow * 128 + (((2 * f + lsel) ^ (lane & 7)) << 4);
#pragma unroll
        for (int kk = 0; kk < 16; kk++) { ldsm4t(wq[kk], a + kk * 2048); ldsm4t(wk[kk], a + 32768 + kk * 2048); }
        bar_sync(13, 128);
#pragma unroll
        for (int i = 0; i < 16; i++) {
            sts128u(rW + R_QK1 + i * 1024, wq[i][0], wq[i][1], wq[i][2], wq[i][3]);
            sts128u(rW + R_QK1 + i * 1024 + 512, wk[i][0], wk[i][1], wk[i][2], wk[i][3]);
        }
        __syncwarp();
    }
    const uint64_t gx = xpage();
    const uint32_t ghi = uni((uint32_t)(gx >> 32)), glo = uni((uint32_t)gx);
    TSDECL;
#pragma unroll 1
    for (int s = 0;; s++) {
        bar_sync(2, 256);
        TS(3);
        float q0[4], k0[4];
        g1<BNB, SMB>(q0, k0, wq, wk, rL + R_MEMB + 4096, sbu - s, [&](int i, const uint32_t*) {
            if (i >= 2 && i < 6) {
#pragma unroll
                for (int n = NRW + (i - 2) * E0 / 4; n < NRW + (i - 1) * E0 / 4; n++) lds_fragv(wo[n], rW + R_WO + n * 512);
            }
            if (i == IV) bar_arrive(GOBAR, 96);
        });
        stsm4t(rL + fo * 1024 + R_QP + 512, pack2(q0[0], q0[1]), pack2(q0[2], q0[3]), pack2(k0[0], k0[1]), pack2(k0[2], k0[3]));
        bar_arrive(3, 256);
        TS(4);
        const uint32_t so = aslot(s);
        const uint4 lt = lds128uv(rL + R_LT);
        uint32_t* pm = (uint32_t*)mkptr(((glo + acc_off(po * 4 + fo, 0)) ^ so) + lt.x, ghi);
        uint32_t* px = (uint32_t*)mkptr(((glo + ext_base(po * 4 + fo)) ^ so) + lt.y, ghi);
        bar_sync(13, 256);
#pragma unroll
        for (int n = NRW + E0; n < NRW + E0 + E1; n++) lds_fragv(wo[n], rW + R_WO + n * 512);
        if (E2) bar_sync(15, 256);
        if (s == NSEG - 1) break;
        TS(5);
#pragma unroll
        for (int n = NRW + E0 + E1; n < NRW + E0 + E1 + E2; n++) lds_fragv(wo[n], rW + R_WO + n * 512);
        bar_sync(13, 256);
#pragma unroll
        for (int n = NRW + E0 + E1 + E2; n < NRW + E0 + E1 + E2 + E3; n++) lds_fragv(wo[n], rW + R_WO + n * 512);
        SCHED(4);
        TS(6);
        bar_sync(8, 256);
        TS(7);
        {
            float o[4][4];
            uint32_t b[4][4];
#pragma unroll
            for (int i = 0; i < 4; i++) ldsm4(b[i], rL + R_QP + i * 1024);
#pragma unroll
            for (int n = NRW + E0 + E1 + E2 + E3; n < 32; n++) lds_fragv(wo[n], rW + R_WO + n * 512);
            float p[4][4];
#define G2_STEP(o, hf, kk) _Pragma("unroll") for (int i = 0; i < 2; i++) MMAF((kk) < 2, o[((kk) & 1) * 2 + i], wo[(hf) * 16 + (kk) * 2 + i], b[(kk) >> 1][((kk) & 1) * 2], b[(kk) >> 1][((kk) & 1) * 2 + 1])
#define G2_RED(o, wl, ptr) const uint32_t wl = packh2(o[1][2] + o[3][2], o[1][3] + o[3][3]);                          \
                asm volatile("red.relaxed.gpu.global.add.noftz.v4.f16x2 [%0], {%1,%2,%3,%4};" :: "l"(ptr),           \
                    "r"(packh2(o[0][0] + o[2][0], o[0][1] + o[2][1])), "r"(packh2(o[0][2] + o[2][2], o[0][3] + o[2][3])), \
                    "r"(packh2(o[1][0] + o[3][0], o[1][1] + o[3][1])), "r"(prmt(wl, HONE2, lt.w)) : "memory")
#pragma unroll
            for (int kk = 0; kk < 8; kk++) { G2_STEP(o, 0, kk); }
            SCHED(11);
#pragma unroll
            for (int kk = 0; kk < 4; kk++) { G2_STEP(p, 1, kk); }
            G2_RED(o, w3, pm);
            SCHED(12);
#pragma unroll
            for (int kk = 4; kk < 8; kk++) { G2_STEP(p, 1, kk); }
            G2_RED(p, w7, pm + AC1);
            asm volatile("red.relaxed.gpu.global.add.noftz.f16x2 [%0], %1;" :: "l"(px), "r"((lt.w & 0x4000u) ? prmt(w3, w7, 0x7632u) : HONE2) : "memory");
        }
        bar_arrive(5, 384);
        asm volatile("{\n.reg .pred p;\nsetp.eq.u32 p, %0, %1;\n@p mbarrier.arrive.expect_tx.shared::cta.b64 _, [%2], 1536;\n}"
                     :: "r"(rW), "r"(sbu), "r"(sbu + R_BAR + 8 * MB_S) : "memory");
        const uint32_t tb = clk32();
        spin_until(tb, DB);
        TS(8);
#pragma unroll
        for (int i = 0; i < NBR; i++) {
            if (i == NB1) {
                if (fo == 1 && (s & 1)) {
                    bar_sync(0, 64);
                    if (rL == sbu) st_rel(&g_f.rec[cc], (ep << 8) | (s + 1));
                    __syncwarp();
                }
                spin_until(tb, DP + DB2);
            }
            lds_fragv(wq[i], rW + R_QK1 + i * 1024); lds_fragv(wk[i], rW + R_QK1 + i * 1024 + 512);
        }
        TS(9);
    }
}

#undef lds_fragv
__device__ __forceinline__ void rec_first_loads(uint32_t sb, int c, const Maps& maps) {
    const uint32_t bar = sb + R_BAR;
    const int F0 = c * 64;
    mbar_expect_tx(bar + 8 * MB_W0, 65536); mbar_expect_tx(bar + 8 * MB_WO, 65536); mbar_expect_tx(bar + 8 * MB_WV, 65536);
    tma2d(sb + R_QK1, &maps.wv, F0, 0, bar + 8 * MB_WV); tma2d(sb + R_QK1 + 32768, &maps.wv, F0, 256, bar + 8 * MB_WV);
    for (int i = 0; i < 4; i++) tma2d(sb + R_WO + i * 16384, &maps.wo, (c & 1) * 256 + i * 64, (c >> 1) * 128, bar + 8 * MB_WO);
    tma2d(sb + R_T + 32768, &maps.wk, F0, 0, bar + 8 * MB_W0); tma2d(sb + R_T, &maps.wq, F0, 0, bar + 8 * MB_W0);
    mbar_expect_tx(bar + 8 * MB_S, 1536);
}
__device__ __forceinline__ void rec_c(uint32_t sb, int c, const bf16* __restrict__ mem0, const Maps& maps, uint32_t epoch) {
    const int tid = threadIdx.x - 256, lane = tid & 31, u = tid >> 5;
    const uint32_t bar = sb + R_BAR;
    const int lrow = ((lane >> 4) << 3) + (lane & 7), lsel = (lane >> 3) & 1;
    const int kh = u >> 1, j = u & 1;
    uint32_t wv[32][4];
    {
        if (u == 0) {
            sts128u(sb + lane * 16 + R_LT, acc_off(0, lane), ext_lane(lane),
                    ((lane >> 2) == 2 * (lane & 3) ? 0x3c00u : 0u) | ((lane >> 2) == 2 * (lane & 3) + 1 ? 0x3c000000u : 0u), (lane & 1) ? 0x5410u : 0x3210u);
        }
        mbar_wait(bar + 8 * MB_WV, 0);
        if (c == 7 && tid == 0) GT(1425);
        const uint32_t aa = sb + R_QK1 + (kh * 256 + lrow) * 128 + (((4 * j + 2 * kh + lsel) ^ (lane & 7)) << 4);
#pragma unroll
        for (int kk = 0; kk < 16; kk++) { ldsm4t(wv[kk], aa + kk * 2048); ldsm4t(wv[16 + kk], (aa ^ 32) + kk * 2048); }
        bar_sync(9, 128);
        if (tid == 0) {
            asm volatile("fence.proxy.async.shared::cta;" ::: "memory");
            mbar_expect_tx(bar + 8 * MB_W1, 65536);
            tma2d(sb + R_QK1 + 32768, &maps.wk, c * 64, 256, bar + 8 * MB_W1); tma2d(sb + R_QK1, &maps.wq, c * 64, 256, bar + 8 * MB_W1);
        }
        __syncwarp();
        const float nv = frag_norm2(wv);
        if (lane == 0) sts32(sb + R_MISC + 64 + u * 4, FU(nv));
        if (tid == 96) { wait_eq2(&g_f.kv[0][c >> 1][0], epoch, 6); load_slot(sb, c, 0, maps); }
        __syncwarp();
        bar_sync(15, 256);
        if (u == 0) {
            if (lane == 0) {
                const float4 a = lds128(sb + R_MISC + 64), b = lds128(sb + R_MISC + 80);
                stg4(&g_f.norm[c], make_uint4(FU((a.x + a.y) + (a.z + a.w)), epoch, FU((b.x + b.y) + (b.z + b.w)), epoch));
            }
            __syncwarp();
            uint4 r, q; uint32_t n = 0;
#pragma unroll 1
            while (true) {
                r = ldg_rlx4((const uint32_t*)&g_f.norm[lane]); q = ldg_rlx4((const uint32_t*)&g_f.norm[lane + 32]);
                if (__all_sync(0xffffffffu, r.y == epoch && r.w == epoch && q.y == epoch && q.w == epoch)) break;
                __nanosleep(32);
                if (++n > SPIN_LIMIT) { ABORT(5); break; }
            }
            float nv2 = __uint_as_float(r.x) + __uint_as_float(q.x), no = __uint_as_float(r.z) + __uint_as_float(q.z);
#pragma unroll
            for (int o = 16; o; o >>= 1) { nv2 += __shfl_xor_sync(0xffffffffu, nv2, o); no += __shfl_xor_sync(0xffffffffu, no, o); }
            const int lc = ((int)(FU(nv2) >> 23) + (int)(FU(no) >> 23) - 252 + 9 + 1) >> 1;
            if (lane == 0) sts32(sb + R_MISC + 16, 140 - lc);
        }
        __syncwarp();
        put_mem0(sb, 4 + u, mem0);
    }
    const uint32_t rL = opaque(sb + lane * 16), rG = opaque(sb + lane * 16 + u * 1024);
    const uint32_t sbu = uni(sb), fo = uni(u), cc = uni(c), ep = uni(epoch);
    const uint64_t gx = xpage();
    const uint32_t ghi = uni((uint32_t)(gx >> 32)), glo = uni((uint32_t)gx);
    constexpr int CX = R_AX + NAX * 4096;
    static_assert(NAX + NCX <= 6, "AX");
#pragma unroll
    for (int i = 0; i < NCX; i++) {
        sts128u(rG + CX + 4096 * i, wv[i][0], wv[i][1], wv[i][2], wv[i][3]);
        sts128u(rG + CX + 4096 * i + 512, wv[16 + i][0], wv[16 + i][1], wv[16 + i][2], wv[16 + i][3]);
    }
    __syncwarp();
    TSDECL;
    uint32_t rpb = 0x3f800000u;
    bar_arrive(2, 256);
#pragma unroll 1
    for (int s = 0;; s++) {
        spin_until(clk32(), DC);
#pragma unroll
        for (int i = NCX - NCL; i < NCX; i++) { lds_fragv(wv[i], rG + CX + 4096 * i); lds_fragv(wv[16 + i], rG + CX + 4096 * i + 512); }
        bar_sync(GOBAR, 96);
        TS(3);
        float v0[4], v1[4];
        uint32_t mx, my;
        g1<CNB, SMC>(v0, v1, wv, wv + 16, rL + R_MEMB + (fo >> 1) * 4096, sbu - s, [&](int i, const uint32_t* c_) {
            if (i >= 0) {
                mx = amax2b(i == 0 ? c_[0] : amax2b(mx, c_[0]), c_[1]);
                my = amax2b(i == 0 ? c_[2] : amax2b(my, c_[2]), c_[3]);
            }
        });
        TS(4);
        const uint32_t l16 = (rL ^ sbu) | (lds32v_(rL + R_LT + 4) & 1);
        const uint32_t r8 = sbu + (l16 >> 1);
        {
            sts128(rL + R_VRED + fo * 512, v1[0], v1[1], v1[2], v1[3]);
            const uint32_t d = r8 + R_VB + ((cc & 1) * 4 + (fo & 1) * 2 + (fo >> 1)) * 256;
            const uint32_t dr = xorv(d, 0x01000000u), br = xorv(sbu + R_BAR + 8 * MB_V, 0x01000000u);
            bar_sync(6 + (fo & 1), 64);
            const float4 a0 = lds128(rL + R_VRED + (fo ^ 2) * 512);
            const float rp = __uint_as_float(rpb);
            const uint32_t w0 = pack2((v0[0] + a0.x) * rp, (v0[1] + a0.y) * rp), w1 = pack2((v0[2] + a0.z) * rp, (v0[3] + a0.w) * rp);
            st_async2(dr, w0, w1, br);
            sts64(d, __uint_as_float(w0), __uint_as_float(w1));
            mx = amax2b(mx, my);
            mx = __reduce_max_sync(0xffffffffu, amax2b(mx, mx << 16) & 0x7f800000u);
            if (fo == 2) { sts32(sbu + R_MISC + 8, mx); bar_arrive(6, 64); }
            if (fo == 0) {
                bar_sync(6, 64);
                const int em = (int)(max(mx, lds32v_(sbu + R_MISC + 8)) >> 23) + (int)(rpb >> 23) - 127;
                const int es = min(max((int)lds32v_(sbu + R_MISC + 16) - max(em, 127), -60), 60);
                sts32(sbu + R_MISC + 40, (127 + es) << 23);
            }
            __syncwarp();
            asm volatile("{\n.reg .pred p;\nsetp.eq.u32 p, %0, %1;\n@p mbarrier.arrive.expect_tx.shared::cta.b64 _, [%2], 256;\n}"
                         :: "r"(rL), "r"(sbu), "r"(sbu + R_BAR + 8 * MB_V) : "memory");
        }
        TS(5);
        if (fo == 1) {
            bar_sync(9, 192);
            uint8_t* dst = (uint8_t*)&g_KVf[s][cc >> 1][(cc & 1) * 256] + l16;
            const uint32_t r2 = prmt(rpb, 0, 0x3232u);
#pragma unroll
            for (int i = 0; i < 2; i++) {
                const uint4 a = lds128uv(rL + R_STG + i * 512);
                stg4(dst + i * 512, make_uint4(hmul2b(a.x, r2), hmul2b(a.y, r2), hmul2b(a.z, r2), hmul2b(a.w, r2)));
                const float2 b0 = lds64v(r8 + R_VB + (cc & 1) * 1024 + i * 512), b1 = lds64v(r8 + R_VB + (cc & 1) * 1024 + i * 512 + 256);
                stg4(dst + 2048 + i * 512, make_uint4(FU(b0.x), FU(b0.y), FU(b1.x), FU(b1.y)));
            }
            __syncwarp();
            if (s == NSEG - 1) {
                if (l16 == 0) { st_rel(&g_f.rec[cc], (ep << 8) | NSEG); GT(1500 + cc); }
            } else if (s & 1) bar_arrive(0, 64);
            __syncwarp();
        } else {
            bar_arrive(9, 192);
            if (fo == 2) {
                if (l16 < 272) stg4((void*)mkptr((glo + zero_off(cc, l16 >> 4)) ^ aslot(s + 4), ghi), make_uint4(0, 0, 0, 0));
                __syncwarp();
            } else if (fo == 3) {
                if (((s & 1) || s == 0) && s + 3 < NSEG) {
                    const uint32_t* fp = &g_f.kv[(s + 3) >> 1][cc >> 1][0];
                    uint32_t n = 0;
#pragma unroll 1
                    while (true) {
                        const uint2 v = ldg_rlx2(fp);
                        if (__all_sync(0xffffffffu, v.x == ep && v.y == ep)) break;
                        __nanosleep(64);
                        if (++n > SPIN_LIMIT) { ABORT(6); break; }
                    }
                }
                if (!(s & 1) && s + 2 < NSEG) {
                    if (s == 0) asm volatile("fence.proxy.async.shared::cta;" ::: "memory");
                    if (l16 == 0) load_slot(sbu, cc, (s + 2) >> 1, maps);
                    __syncwarp();
                }
            }
        }
        TS(6);
        if (s == NSEG - 1) break;
        auto early = [&]() {
#pragma unroll
            for (int i = 0; i < NCX - NCL; i++) { lds_fragv(wv[i], rG + CX + 4096 * i); lds_fragv(wv[16 + i], rG + CX + 4096 * i + 512); }
        };
        GATHER(1, , early(); rpb = 0x7f000000u - lds32v_(sbu + R_MISC + 40);, bar_arrive(2, 256);)
    }
}

__device__ __forceinline__ bool cand_better(float v, int i, float bv, int bi) { return v > bv || (v == bv && i < bi); }
constexpr int F_WG = 0, F_WU = 32768, F_WD = 65536, F_X = 98304, F_RED = F_X + 4096, F_ACT = F_RED + 8192, F_SEL = F_ACT + 256;

__device__ __noinline__ void ffn_phase(const Maps& maps, const bf16* __restrict__ wd, bf16* __restrict__ out) {
    extern __shared__ __align__(1024) uint8_t smem[];
    const uint32_t sb = smem_u32(smem);
    const int c = ((volatile int*)(smem + SH_OFF))[8];
    const uint32_t epoch = ((volatile uint32_t*)(smem + SH_OFF))[9];
    const int tid = threadIdx.x;
    constexpr int NWK = FF / 32;
    const bool worker = c < NWK;
    bar_sync(0, 384);
    const uint32_t mb = sb + R_BAR + 8 * MB_W0;
    if (tid == 32 && worker) {
        asm volatile("fence.proxy.async.shared::cta;" ::: "memory");
        mbar_expect_tx(mb, 98304);
        tma2d(sb + F_WG, &maps.wg, c * 32, 0, mb); tma2d(sb + F_WG + 16384, &maps.wg, c * 32, 256, mb);
        tma2d(sb + F_WU, &maps.wu, c * 32, 0, mb); tma2d(sb + F_WU + 16384, &maps.wu, c * 32, 256, mb);
        asm volatile("cp.async.bulk.shared::cluster.global.mbarrier::complete_tx::bytes [%0], [%1], %2, [%3];"
            :: "r"(sb + F_WD), "l"(wd + (size_t)c * 32 * DM), "r"(32768), "r"(mb) : "memory");
    }
    int p0 = -1, p1 = -1;
#pragma unroll 1
    for (int pass = 0; pass < 2; pass++) {
        if (tid < 32) {
            const uint32_t tag = epoch & 0xfffffu;
            uint4 r, q; uint32_t n = 0;
            const int t2 = tid + 32 < NFW ? tid + 32 : tid;
#pragma unroll 1
            while (true) {
                r = ldg_rlx4((const uint32_t*)&g_f.cand[pass][tid]); q = ldg_rlx4((const uint32_t*)&g_f.cand[pass][t2]);
                if (__all_sync(0xffffffffu, (r.y >> 12) == tag && (r.w >> 12) == tag && (q.y >> 12) == tag && (q.w >> 12) == tag)) break;
                __nanosleep(32);
                if (++n > SPIN_LIMIT) { ABORT(7); break; }
            }
            float b0 = __uint_as_float(r.x), b1 = __uint_as_float(r.z); int i0 = r.y & 4095, i1 = r.w & 4095;
            if (t2 != tid) {
                float c0 = __uint_as_float(q.x), c1 = __uint_as_float(q.z); int j0 = q.y & 4095, j1 = q.w & 4095;
                if (cand_better(c0, j0, b0, i0)) {
                    if (cand_better(c1, j1, b0, i0)) { b1 = c1; i1 = j1; } else { b1 = b0; i1 = i0; }
                    b0 = c0; i0 = j0;
                } else if (cand_better(c0, j0, b1, i1)) { b1 = c0; i1 = j0; }
            }
#pragma unroll
            for (int o = 16; o; o >>= 1) {
                float c0 = __shfl_xor_sync(0xffffffffu, b0, o), c1 = __shfl_xor_sync(0xffffffffu, b1, o);
                int j0 = __shfl_xor_sync(0xffffffffu, i0, o), j1 = __shfl_xor_sync(0xffffffffu, i1, o);
                if (cand_better(c0, j0, b0, i0)) {
                    if (cand_better(c1, j1, b0, i0)) { b1 = c1; i1 = j1; } else { b1 = b0; i1 = i0; }
                    b0 = c0; i0 = j0;
                } else if (cand_better(c0, j0, b1, i1)) { b1 = c0; i1 = j0; }
            }
            i0 = min(i0, SQ - 1); i1 = min(i1, SQ - 1);
            if (i0 != p0 || i1 != p1) {
                n = 0;
#pragma unroll 1
                while (!__all_sync(0xffffffffu, ldg_rlx(&g_f.rows[pass][tid]) == epoch && ldg_rlx(&g_f.rows[pass][t2]) == epoch)) { __nanosleep(32); if (++n > SPIN_LIMIT) { ABORT(7); break; } }
            }
            int* sel = (int*)(smem + F_SEL);
            if (pass && tid == 0) GT(c * 8 + 5);
            if (tid == 0) { sel[0] = i0; sel[1] = i1; ((float*)sel)[2] = b0; ((float*)sel)[3] = b1; }
        }
        bar_sync(0, 384);
        const int t0 = ((int*)(smem + F_SEL))[0], t1 = ((int*)(smem + F_SEL))[1];
        if (c == 3 && tid == 0 && pass == 0) GT(1430);
        if (t0 == p0 && t1 == p1) break;
        const uint32_t ytag = epoch * 2 + pass + 1;
        if (worker) {
            float2* xs = (float2*)(smem + F_X);
            if (tid < 256) {
                uint32_t a = __ldcg((const uint32_t*)(g_hn + (size_t)t0 * DM) + tid), b = __ldcg((const uint32_t*)(g_hn + (size_t)t1 * DM) + tid);
                *(float4*)(xs + tid * 2) = make_float4(bf_lo(a), bf_lo(b), bf_hi(a), bf_hi(b));
            }
            mbar_wait(mb, 1);
            if (c == 3 && tid == 0 && pass == 0) GT(1431);
            bar_sync(0, 384);
            float4* red = (float4*)(smem + F_RED);
            if (tid < 256) {
                const int cp = tid & 31, kg = tid >> 5;
                const uint32_t* wp = (const uint32_t*)(smem + (cp < 16 ? F_WG : F_WU)) + (cp & 15);
                float a0 = 0.f, a1 = 0.f, b0 = 0.f, b1 = 0.f;
#pragma unroll 16
                for (int k = kg * 64; k < kg * 64 + 64; k++) {
                    uint32_t w = wp[k * 16]; float2 x = xs[k];
                    a0 = fmaf(x.x, bf_lo(w), a0); a1 = fmaf(x.x, bf_hi(w), a1); b0 = fmaf(x.y, bf_lo(w), b0); b1 = fmaf(x.y, bf_hi(w), b1);
                }
                red[kg * 32 + cp] = make_float4(a0, a1, b0, b1);
            }
            bar_sync(0, 384);
            float2* act = (float2*)(smem + F_ACT);
            if (tid < 64) {
                const int f = tid & 31, tk = tid >> 5;
                const float* r = (const float*)red + (f >> 1) * 4 + tk * 2 + (f & 1);
                float gsum = 0.f, usum = 0.f;
#pragma unroll
                for (int kg = 0; kg < 8; kg++) { gsum += r[kg * 128]; usum += r[kg * 128 + 64]; }
                gsum = rbf(gsum); usum = rbf(usum);
                float sg = rbf(gsum / (1.f + __expf(-gsum)));
                ((float*)act)[f * 2 + tk] = rbf(sg * usum);
            }
            bar_sync(0, 384);
            if (tid < 256) {
                const uint32_t* wp = (const uint32_t*)(smem + F_WD) + tid;
                float a0 = 0.f, a1 = 0.f, b0 = 0.f, b1 = 0.f;
#pragma unroll 16
                for (int f = 0; f < 32; f++) {
                    uint32_t w = wp[f * 256]; float2 x = act[f];
                    a0 = fmaf(x.x, bf_lo(w), a0); a1 = fmaf(x.x, bf_hi(w), a1); b0 = fmaf(x.y, bf_lo(w), b0); b1 = fmaf(x.y, bf_hi(w), b1);
                }
                asm volatile("st.relaxed.gpu.global.v4.b32 [%0], {%1,%2,%3,%2};" :: "l"(&g_yp[pass][c][tid]), "r"(FU(a0)), "r"(ytag), "r"(FU(a1)) : "memory");
                asm volatile("st.relaxed.gpu.global.v4.b32 [%0], {%1,%2,%3,%2};" :: "l"(&g_yp[pass][c][256 + tid]), "r"(FU(b0)), "r"(ytag), "r"(FU(b1)) : "memory");
            }
            if (c == 3 && tid == 0 && pass == 0) GT(1432);
        } else {
            const int r = c - NWK, j = tid & 63, part = tid >> 6, tk = r >> 2, dp = (r & 3) * 64 + j;
            const int tok = tk ? t1 : t0, old = tk ? p1 : p0;
            uint32_t hw = 0, nw = 0;
            if (part == 0) {
                hw = __ldcg((const uint32_t*)(g_h + (size_t)tok * DM) + dp); nw = __ldcg((const uint32_t*)(g_hn + (size_t)tok * DM) + dp);
                if (old >= 0 && old != t0 && old != t1) {
                    uint32_t ho = __ldcg((const uint32_t*)(g_h + (size_t)old * DM) + dp), no = __ldcg((const uint32_t*)(g_hn + (size_t)old * DM) + dp);
                    ((uint32_t*)(out + (size_t)old * DM))[dp] = pack2(bf_lo(ho) + bf_lo(no), bf_hi(ho) + bf_hi(no));
                }
            }
            float s0 = 0.f, s1 = 0.f;
            uint4 v[10]; uint32_t n = 0;
            bool ok;
#pragma unroll 1
            do {
                ok = true;
#pragma unroll
                for (int i = 0; i < 10; i++) {
                    const int src = part + 6 * i;
                    v[i] = src < NWK ? ldg_rlx4((const uint32_t*)&g_yp[pass][src][tk * 256 + dp]) : make_uint4(0, ytag, 0, ytag);
                }
#pragma unroll
                for (int i = 0; i < 10; i++) ok = ok && v[i].y == ytag && v[i].w == ytag;
                if (!ok) __nanosleep(100);
                if (++n > SPIN_LIMIT) { ABORT(7); break; }
            } while (!ok);
#pragma unroll
            for (int i = 0; i < 10; i++) { s0 += __uint_as_float(v[i].x); s1 += __uint_as_float(v[i].z); }
            float2* red = (float2*)(smem + F_RED);
            red[part * 64 + j] = make_float2(s0, s1);
            bar_sync(0, 384);
            if (part == 0) {
#pragma unroll
                for (int i = 1; i < 6; i++) { float2 q = red[i * 64 + j]; s0 += q.x; s1 += q.y; }
                const float rs = rbf(1.f / (1.f + __expf(-((float*)(smem + F_SEL))[2 + tk])));
                const float y0 = rbf(rbf(s0) * rs), y1 = rbf(rbf(s1) * rs);
                ((uint32_t*)(out + (size_t)tok * DM))[dp] = pack2(bf_lo(hw) + rbf(bf_lo(nw) + y0), bf_hi(hw) + rbf(bf_hi(nw) + y1));
            }
            if (tid == 0 && pass == 0 && r == 0) GT(1434);
        }
        p0 = t0; p1 = t1;
        if (c == 3 && tid == 0 && pass == 0) GT(1433);
        bar_sync(0, 384);
    }
}

constexpr int G_W = 0;
constexpr int G_RING = 131072;
constexpr int G_BUF = 163840;
constexpr int G_BAR = 229376;
constexpr int G_SMEM = G_BAR + 512;
enum { GB_W0 = 0, GB_W1, GB_WFREE, GB_FULL, GB_EMPTY = GB_FULL + 8, GB_KV = GB_EMPTY + 8, GB_STG = GB_KV + 2, GB_FREE = GB_STG + 2, GB_XN = GB_FREE + 2, GB_N };
constexpr int SMEM_TOTAL = 232448;

__device__ __forceinline__ void wgmma_n128(float* d, uint64_t da, uint64_t db, int scale_d) {
    asm volatile("{\n.reg .pred p;\nsetp.ne.b32 p, %66, 0;\n"
        "wgmma.mma_async.sync.aligned.m64n128k16.f32.bf16.bf16 "
        "{%0,%1,%2,%3,%4,%5,%6,%7,%8,%9,%10,%11,%12,%13,%14,%15,%16,%17,%18,%19,%20,%21,%22,%23,%24,%25,%26,%27,%28,%29,%30,%31,"
        "%32,%33,%34,%35,%36,%37,%38,%39,%40,%41,%42,%43,%44,%45,%46,%47,%48,%49,%50,%51,%52,%53,%54,%55,%56,%57,%58,%59,%60,%61,%62,%63}, "
        "%64, %65, p, 1, 1, 0, 1;\n}"
        : "+f"(d[0]), "+f"(d[1]), "+f"(d[2]), "+f"(d[3]), "+f"(d[4]), "+f"(d[5]), "+f"(d[6]), "+f"(d[7]), "+f"(d[8]), "+f"(d[9]), "+f"(d[10]), "+f"(d[11]),
          "+f"(d[12]), "+f"(d[13]), "+f"(d[14]), "+f"(d[15]), "+f"(d[16]), "+f"(d[17]), "+f"(d[18]), "+f"(d[19]), "+f"(d[20]), "+f"(d[21]), "+f"(d[22]), "+f"(d[23]),
          "+f"(d[24]), "+f"(d[25]), "+f"(d[26]), "+f"(d[27]), "+f"(d[28]), "+f"(d[29]), "+f"(d[30]), "+f"(d[31]), "+f"(d[32]), "+f"(d[33]), "+f"(d[34]), "+f"(d[35]),
          "+f"(d[36]), "+f"(d[37]), "+f"(d[38]), "+f"(d[39]), "+f"(d[40]), "+f"(d[41]), "+f"(d[42]), "+f"(d[43]), "+f"(d[44]), "+f"(d[45]), "+f"(d[46]), "+f"(d[47]),
          "+f"(d[48]), "+f"(d[49]), "+f"(d[50]), "+f"(d[51]), "+f"(d[52]), "+f"(d[53]), "+f"(d[54]), "+f"(d[55]), "+f"(d[56]), "+f"(d[57]), "+f"(d[58]), "+f"(d[59]),
          "+f"(d[60]), "+f"(d[61]), "+f"(d[62]), "+f"(d[63])
        : "l"(da), "l"(db), "r"(scale_d));
}

__device__ __forceinline__ constexpr uint32_t slot_off(int slot, int mode = 0) {
    return slot < 2 ? G_RING + slot * 16384 : (mode == 0 ? G_BUF + (slot - 2) * 32768 + 16384 : G_BUF + 32768 + (slot - 2) * 16384);
}
template <int NSLOT, int MODE = 0>
__device__ __forceinline__ void gemm_tile(float* acc, uint32_t sb, int tile, bool first, uint32_t wpar, int wg, bool pass, uint32_t l0) {
    const uint32_t bar = sb + G_BAR;
    const uint64_t da0 = desc_sw128(sb, 16, 1024), db0 = desc_sw128(sb + G_W, 65536, 1024);
    bar_sync(3 + wg, 256);
#pragma unroll
    for (int k = 0; k < 4; k++) {
        const int slot = k % NSLOT;
        if ((k & 1) == 0 && first) mbar_wait_u(bar + 8 * (GB_W0 + (k >> 1)), wpar);
        mbar_wait_u(bar + 8 * (GB_FULL + slot), NSLOT == 4 ? (tile & 1) : ((k >> 1) & 1));
        if (k == 3 && pass) bar_arrive(3 + (wg ^ 1), 256);
        asm volatile("wgmma.fence.sync.aligned;" ::: "memory");
#pragma unroll
        for (int kk = 0; kk < 4; kk++) wgmma_n128(acc, da0 + (slot_off(slot, MODE) >> 4) + kk * 2, db0 + k * 1024 + kk * 128, (k | kk) != 0);
        asm volatile("wgmma.commit_group.sync.aligned;" ::: "memory");
        if (k > 0) {
            asm volatile("wgmma.wait_group.sync.aligned 1;" ::: "memory");
            mbar_arrive_if(bar + 8 * (GB_EMPTY + (k - 1) % NSLOT), l0);
        }
#pragma unroll
        for (int kk = 0; kk < 4; kk++) wgmma_n128(acc, da0 + ((slot_off(slot, MODE) + 8192) >> 4) + kk * 2, db0 + k * 1024 + 512 + kk * 128, 1);
        asm volatile("wgmma.commit_group.sync.aligned;" ::: "memory");
    }
    asm volatile("wgmma.wait_group.sync.aligned 0;" ::: "memory");
    mbar_arrive_if(bar + 8 * (GB_EMPTY + 3 % NSLOT), l0);
}
__device__ __forceinline__ void stage_bf16(const float* acc, uint32_t buf, float s0, float s1) {
    const int lane = threadIdx.x & 31, wq = (threadIdx.x >> 5) & 3;
    const int row = wq * 16 + (lane & 7) + ((lane >> 3) & 1) * 8;
    const uint32_t base = buf + row * 128;
#pragma unroll
    for (int j = 0; j < 16; j += 2) {
        const int ch = (j & 7) + (lane >> 4);
        stsm4(base + (j >> 3) * 8192 + ((ch ^ (row & 7)) << 4),
              pack2(acc[4 * j] * s0, acc[4 * j + 1] * s0), pack2(acc[4 * j + 2] * s1, acc[4 * j + 3] * s1),
              pack2(acc[4 * j + 4] * s0, acc[4 * j + 5] * s0), pack2(acc[4 * j + 6] * s1, acc[4 * j + 7] * s1));
    }
}

__device__ __forceinline__ void attention_tile(float* acc, uint32_t buf, int tile, int h, int wg, uint32_t epoch) {
    const int lane = threadIdx.x & 31, wq = (threadIdx.x >> 5) & 3, g = lane >> 2, t = lane & 3;
    const int sg = wq >> 1, hf = wq & 1, seg = tile * 2 + sg;
    uint32_t qf[8][4];
#pragma unroll
    for (int kk = 0; kk < 8; kk++) {
        qf[kk][0] = pack2(acc[8 * kk], acc[8 * kk + 1]); qf[kk][1] = pack2(acc[8 * kk + 2], acc[8 * kk + 3]);
        qf[kk][2] = pack2(acc[8 * kk + 4], acc[8 * kk + 5]); qf[kk][3] = pack2(acc[8 * kk + 6], acc[8 * kk + 7]);
    }
    float sc[5][4];
#pragma unroll
    for (int b = 0; b < 5; b++) { sc[b][0] = sc[b][1] = sc[b][2] = sc[b][3] = 0.f; }
    {
        const int row = sg * 32 + (lane >> 4) * 8 + (lane & 7);
        const uint32_t ka = buf + row * 128;
#pragma unroll
        for (int kk = 0; kk < 8; kk++) {
            uint32_t kb[4];
            const uint32_t off = (kk >> 2) * 8192 + (((2 * (kk & 3) + ((lane >> 3) & 1)) ^ (lane & 7)) << 4);
            ldsm4(kb, ka + off);
            MMA(sc[0], qf[kk], kb[0], kb[1]); MMA(sc[1], qf[kk], kb[2], kb[3]);
            if (hf) {
                ldsm4(kb, ka + off + 2048);
                MMA(sc[2], qf[kk], kb[0], kb[1]); MMA(sc[3], qf[kk], kb[2], kb[3]);
            }
        }
    }
    const float cexp = 0.08838834764831845f * 1.4426950408889634f;
    const int r0 = hf * 16 + g, r1 = r0 + 8;
#pragma unroll
    for (int b = 0; b < 4; b++) {
        const int j = b * 8 + 2 * t;
        if (j > r0) sc[b][0] = -INFINITY;
        if (j + 1 > r0) sc[b][1] = -INFINITY;
        if (j > r1) sc[b][2] = -INFINITY;
        if (j + 1 > r1) sc[b][3] = -INFINITY;
    }
    float m0 = -INFINITY, m1 = -INFINITY;
#pragma unroll
    for (int b = 0; b < 4; b++) { m0 = fmaxf(m0, fmaxf(sc[b][0], sc[b][1])); m1 = fmaxf(m1, fmaxf(sc[b][2], sc[b][3])); }
    m0 = fmaxf(m0, __shfl_xor_sync(0xffffffffu, m0, 1)); m0 = fmaxf(m0, __shfl_xor_sync(0xffffffffu, m0, 2));
    m1 = fmaxf(m1, __shfl_xor_sync(0xffffffffu, m1, 1)); m1 = fmaxf(m1, __shfl_xor_sync(0xffffffffu, m1, 2));
    float l0 = 0.f, l1 = 0.f;
    {
        const float c0 = -m0 * cexp, c1 = -m1 * cexp;
        uint32_t pf[4][2];
#pragma unroll
        for (int b = 0; b < 4; b++) {
            pf[b][0] = pack2(ex2(fmaf(sc[b][0], cexp, c0)), ex2(fmaf(sc[b][1], cexp, c0)));
            pf[b][1] = pack2(ex2(fmaf(sc[b][2], cexp, c1)), ex2(fmaf(sc[b][3], cexp, c1)));
            l0 += bf_lo(pf[b][0]) + bf_hi(pf[b][0]); l1 += bf_lo(pf[b][1]) + bf_hi(pf[b][1]);
        }
        const int row = sg * 32 + ((lane >> 3) & 1) * 8 + (lane & 7);
        const uint32_t va = buf + 16384 + row * 128;
#pragma unroll
        for (int j = 0; j < 16; j += 2) {
            float* o0 = acc + 4 * j; float* o1 = acc + 4 * j + 4;
            uint32_t vb[4];
            const uint32_t off = (j >> 3) * 8192 + ((((j & 7) + (lane >> 4)) ^ (lane & 7)) << 4);
            ldsm4t(vb, va + off);
            mma16816z(o0, pf[0][0], pf[0][1], pf[1][0], pf[1][1], vb[0], vb[1]);
            mma16816z(o1, pf[0][0], pf[0][1], pf[1][0], pf[1][1], vb[2], vb[3]);
            if (hf) {
                ldsm4t(vb, va + off + 2048);
                mma16816(o0, pf[2][0], pf[2][1], pf[3][0], pf[3][1], vb[0], vb[1]);
                mma16816(o1, pf[2][0], pf[2][1], pf[3][0], pf[3][1], vb[2], vb[3]);
            }
        }
    }
    bar_sync(1 + wg, 128);
    wait_rec(&g_f.rec[2 * h], epoch, seg + 1);
    if (seg == 63 && (threadIdx.x & 63) == 0) GT(1570 + h);
    __syncwarp();
    {
        const uint4* kvf = (const uint4*)&g_KVf[seg][h][0] + lane;
        uint4 km[4], vm[4];
#pragma unroll
        for (int i = 0; i < 4; i++) km[i] = __ldcg(kvf + i * 32);
#pragma unroll
        for (int i = 0; i < 4; i++) vm[i] = __ldcg(kvf + 128 + i * 32);
        float sb_[4] = {0.f, 0.f, 0.f, 0.f};
#pragma unroll
        for (int i = 0; i < 4; i++) { MMA(sc[4], qf[2 * i], km[i].x, km[i].y); MMA(sb_, qf[2 * i + 1], km[i].z, km[i].w); }
#pragma unroll
        for (int i = 0; i < 4; i++) sc[4][i] += sb_[i];
        float n0 = fmaxf(sc[4][0], sc[4][1]), n1 = fmaxf(sc[4][2], sc[4][3]);
        n0 = fmaxf(n0, __shfl_xor_sync(0xffffffffu, n0, 1)); n1 = fmaxf(n1, __shfl_xor_sync(0xffffffffu, n1, 1));
        n0 = fmaxf(n0, __shfl_xor_sync(0xffffffffu, n0, 2)); n1 = fmaxf(n1, __shfl_xor_sync(0xffffffffu, n1, 2));
        n0 = fmaxf(n0, m0); n1 = fmaxf(n1, m1);
        const float a0 = ex2((m0 - n0) * cexp), a1 = ex2((m1 - n1) * cexp);
        const float c0 = -n0 * cexp, c1 = -n1 * cexp;
        const uint32_t p0 = pack2(ex2(fmaf(sc[4][0], cexp, c0)), ex2(fmaf(sc[4][1], cexp, c0)));
        const uint32_t p1 = pack2(ex2(fmaf(sc[4][2], cexp, c1)), ex2(fmaf(sc[4][3], cexp, c1)));
        l0 = fmaf(l0, a0, bf_lo(p0) + bf_hi(p0)); l1 = fmaf(l1, a1, bf_lo(p1) + bf_hi(p1));
        const uint32_t* vmw = (const uint32_t*)vm;
#pragma unroll
        for (int j = 0; j < 16; j++) {
            float* o = acc + 4 * j;
            o[0] *= a0; o[1] *= a0; o[2] *= a1; o[3] *= a1;
            mma1688(o, p0, p1, vmw[j]);
        }
        l0 += __shfl_xor_sync(0xffffffffu, l0, 1); l1 += __shfl_xor_sync(0xffffffffu, l1, 1);
        l0 += __shfl_xor_sync(0xffffffffu, l0, 2); l1 += __shfl_xor_sync(0xffffffffu, l1, 2);
    }
    stage_bf16(acc, buf, __frcp_rn(l0), __frcp_rn(l1));
}

__device__ __forceinline__ void g_consumer(uint32_t sb_, int g, int wg, uint32_t epoch) {
    const uint32_t sb = uni(sb_);
    const uint32_t l0 = opaque((threadIdx.x & 31) == 0);
    const uint32_t bar = sb + G_BAR, buf = sb + G_BUF + wg * 32768;
    const int lane = threadIdx.x & 31;
    float acc[64];
    if (wg == 1) bar_arrive(3, 256);
    const int n1 = g < 32 ? HSPLIT / 2 : NT - HSPLIT / 2;
#pragma unroll 1
    for (int i = 0; i < n1; i++) {
        gemm_tile<4>(acc, sb, wg, i == 0 || i == NT / 2, i >= NT / 2, wg, true, l0);
        if ((i == n1 - 1 || i == NT / 2 - 1) && lane == 0) mbar_arrive(bar + 8 * GB_WFREE);
        if (threadIdx.x == 0 && i == 0) GT((64 + g) * 8 + 1);
        if (threadIdx.x == 128 && i == 3) GT((64 + g) * 8 + 2);
        if (i > 0) mbar_wait(bar + 8 * (GB_FREE + wg), (i - 1) & 1);
        stage_bf16(acc, buf, 1.f, 1.f);
        asm volatile("fence.proxy.async.shared::cta;" ::: "memory");
        mbar_arrive(bar + 8 * (GB_STG + wg));
    }
    if (threadIdx.x == 128) GT((64 + g) * 8 + 3);
    if (g < 32) {
#pragma unroll 1
        for (int i = 0; i < NT / 2; i++) {
            const int tile = 2 * i + wg;
            gemm_tile<2>(acc, sb, tile, i == 0, 1, wg, tile != NT - 1, l0);
            if (threadIdx.x == 0 && i == 0) GT((64 + g) * 8 + 4);
            if (threadIdx.x == 128 && i == 3) GT((64 + g) * 8 + 5);
            mbar_wait(bar + 8 * (GB_KV + wg), i & 1);
            attention_tile(acc, buf, tile, g, wg, epoch);
            asm volatile("fence.proxy.async.shared::cta;" ::: "memory");
            mbar_arrive(bar + 8 * (GB_STG + wg));
        }
    } else {
        const int wq = (threadIdx.x >> 5) & 3, gq = lane >> 2, t = lane & 3;
#pragma unroll 1
        for (int i = 0; i < NT / 2; i++) {
            const int tile = 2 * i + wg;
            gemm_tile<4, 1>(acc, sb, tile, i == 0, 0, wg, tile != NT - 1, l0);
            if (threadIdx.x == 0 && i == 0) GT((64 + g) * 8 + 4);
            if (threadIdx.x == 128 && i == 3) GT((64 + g) * 8 + 5);
            if (tile == 0) mbar_wait(bar + 8 * GB_FREE, 1);
            else mbar_wait(bar + 8 * (GB_FREE + (wg ^ 1)), ((tile - 1) >> 1) & 1);
            const uint32_t base = sb + G_BUF + (wq * 16 + gq) * 128 + (t & 1) * 8;
#pragma unroll
            for (int j = 0; j < 16; j++) {
                const uint32_t a = base + (j >> 2) * 8192 + ((((j & 3) * 2 + (t >> 1)) ^ gq) << 4);
                sts64(a, acc[4 * j], acc[4 * j + 1]);
                sts64(a + 1024, acc[4 * j + 2], acc[4 * j + 3]);
            }
            asm volatile("fence.proxy.async.shared::cta;" ::: "memory");
            mbar_arrive(bar + 8 * (GB_STG + wg));
        }
    }
}

__device__ __forceinline__ void load_w(uint32_t sb, const CUtensorMap* tm, int col, int row, int k0 = 0, int k1 = 2) {
    const uint32_t bar = sb + G_BAR;
#pragma unroll
    for (int kh = k0; kh < k1; kh++) {
        mbar_expect_tx(bar + 8 * (GB_W0 + kh), 65536);
        tma2d(sb + G_W + kh * 32768, tm, col, row + kh * 256, bar + 8 * (GB_W0 + kh));
        tma2d(sb + G_W + 65536 + kh * 32768, tm, col + 64, row + kh * 256, bar + 8 * (GB_W0 + kh));
    }
}

__device__ __forceinline__ void g_producer(uint32_t sb, int g, const Maps& maps, uint32_t epoch) {
    const uint32_t bar = sb + G_BAR;
    const int warp = (threadIdx.x >> 5) - 8;
    if (threadIdx.x == 256 && g == 5) GT(1410);
    if (threadIdx.x == 256 && g == 5) GT(1411);
    if (warp == 3) {
        wait_eq4(&g_f.xn[(threadIdx.x & 31) * 4], epoch, 13);
        __syncwarp();
        if ((threadIdx.x & 31) == 0) mbar_arrive(bar + 8 * GB_XN);
        wait_eq2(&g_f.rload[(threadIdx.x & 31) * 2], epoch, 13);
        __syncwarp();
        if ((threadIdx.x & 31) == 0) mbar_arrive(bar + 8 * GB_XN);
    }
    if ((threadIdx.x & 31) != 0) return;
    if (threadIdx.x == 256 && g == 5) GT(1412);
    if (warp == 0) {
        wait_eq4(&g_f.xn[0], epoch, 13);
        const int m1 = g < 32 ? HSPLIT : 2 * NT - HSPLIT;
#pragma unroll 1
        for (int it = 0; it < m1; it++) {
            const int tile = it < NT ? it : it - NT + HSPLIT;
            if (it == HOLD) mbar_wait(bar + 8 * GB_XN, 1);
            if (it == 1) mbar_wait(bar + 8 * GB_XN, 0);
            if (it == NT) {
                mbar_wait(bar + 8 * GB_WFREE, 0);
                load_w(sb, (g & 1) ? &maps.wv : &maps.wk, ((g - 32) >> 1) * 128, 0);
            }
#pragma unroll
            for (int k = 0; k < 4; k++) {
                if (k == 2 && it == 0) load_w(sb, (g & 1) ? &maps.wv : &maps.wk, (g >> 1) * 128, 0, 1, 2);
                mbar_wait(bar + 8 * (GB_EMPTY + k), (it & 1) ^ 1);
                mbar_expect_tx(bar + 8 * (GB_FULL + k), 16384);
                tma3d(sb + slot_off(k), &maps.xn3, tile * 64, k * 2, bar + 8 * (GB_FULL + k));
            }
        }
        mbar_wait(bar + 8 * GB_WFREE, g >= 32);
        const int u = g - 32, ks = u >> 2, ns = u & 3;
        if (g < 32) load_w(sb, &maps.wq, g * 128, 0); else load_w(sb, &maps.wo2, ns * 128, ks * 512);
        if (g < 32) {
#pragma unroll 1
            for (int tile = 0; tile < NT; tile++) {
#pragma unroll
                for (int k = 0; k < 4; k++) {
                    mbar_wait(bar + 8 * (GB_EMPTY + (k & 1)), ((k >> 1) & 1) ^ 1);
                    mbar_expect_tx(bar + 8 * (GB_FULL + (k & 1)), 16384);
                    tma3d(sb + slot_off(k & 1), &maps.xn3, tile * 64, k * 2, bar + 8 * (GB_FULL + (k & 1)));
                }
            }
        } else {
            mbar_wait(bar + 8 * (GB_FREE + 1), 1);
#pragma unroll 1
            for (int tile = 0; tile < NT; tile++) {
                wait_eq4(&g_f.o[tile][ks][0], epoch, 9);
                if (g == 40 && tile == NT - 1) GT(1437);
                if (tile == NT - 1) GT(1690 + g - 32);
#pragma unroll
                for (int k = 0; k < 4; k++) {
                    mbar_wait(bar + 8 * (GB_EMPTY + k), (tile & 1) ^ 1);
                    mbar_expect_tx(bar + 8 * (GB_FULL + k), 16384);
                    tma3d(sb + slot_off(k, 1), &maps.ox3, tile * 64, ks * 8 + k * 2, bar + 8 * (GB_FULL + k));
                }
            }
        }
    } else if (warp < 3) {
        const int wg = warp - 1;
        const uint32_t buf = sb + G_BUF + wg * 32768;
        const CUtensorMap* tkv = (g & 1) ? &maps.vx3 : &maps.kx3;
        const int n1 = g < 32 ? HSPLIT / 2 : NT - HSPLIT / 2;
#pragma unroll 1
        for (int i = 0; i < n1; i++) {
            const int tile = (i < NT / 2 ? 2 * i : 2 * i - NT + HSPLIT) + wg, hd = (i < NT / 2 ? g : g - 32) >> 1;
            mbar_wait(bar + 8 * (GB_STG + wg), i & 1);
            tma_store3d(tkv, buf, tile * 64, hd * 2);
            asm volatile("cp.async.bulk.commit_group;" ::: "memory");
            asm volatile("cp.async.bulk.wait_group.read 0;" ::: "memory");
            mbar_arrive(bar + 8 * (GB_FREE + wg));
            asm volatile("cp.async.bulk.wait_group 0;" ::: "memory");
            PUBLISH(&g_f.kv[tile][hd][g & 1], epoch);
        }
        if (g < 32) {
            mbar_wait(bar + 8 * GB_WFREE, 0);
            auto load_kv = [&](int tile) {
                wait_eq2(&g_f.kv[tile][g][0], epoch, 10);
                const uint32_t mb = bar + 8 * (GB_KV + wg);
                mbar_expect_tx(mb, 32768);
                tma3d(buf, &maps.kx3, tile * 64, g * 2, mb); tma3d(buf + 16384, &maps.vx3, tile * 64, g * 2, mb);
            };
            load_kv(wg);
#pragma unroll 1
            for (int i = 0; i < NT / 2; i++) {
                const int tile = 2 * i + wg;
                mbar_wait(bar + 8 * (GB_STG + wg), i & 1);
                tma_store3d(&maps.ox3, buf, tile * 64, g * 2);
                asm volatile("cp.async.bulk.commit_group;" ::: "memory");
                asm volatile("cp.async.bulk.wait_group 0;" ::: "memory");
                PUBLISH(&g_f.o[tile][g >> 2][g & 3], epoch);
                if (g == 3 && tile == NT - 1) GT(1436);
                if (tile == NT - 1) GT(1610 + g);
                if (i + 1 < NT / 2) load_kv(tile + 2);
            }
        } else {
            const int ns = (g - 32) & 3;
            wait_eq4(&g_f.zeroed[0], epoch, 11);
            __threadfence();
            asm volatile("fence.proxy.async.global;" ::: "memory");
#pragma unroll 1
            for (int i = 0; i < NT / 2; i++) {
                const int tile = 2 * i + wg;
                mbar_wait(bar + 8 * (GB_STG + wg), i & 1);
#pragma unroll
                for (int j = 0; j < 4; j++)
                    asm volatile("cp.reduce.async.bulk.tensor.2d.global.shared::cta.add.tile.bulk_group [%0, {%2, %3}], [%1];"
                        :: "l"((uint64_t)&maps.acc), "r"(sb + G_BUF + j * 8192), "r"(ns * 128 + j * 32), "r"(tile * 64) : "memory");
                asm volatile("cp.async.bulk.commit_group;" ::: "memory");
                asm volatile("cp.async.bulk.wait_group.read 0;" ::: "memory");
                mbar_arrive(bar + 8 * (GB_FREE + wg));
                asm volatile("cp.async.bulk.wait_group 0;" ::: "memory");
                asm volatile("red.release.gpu.global.add.u32 [%0], 1;" :: "l"(&g_f.acc[tile]) : "memory");
                if (g == 40 && tile == NT - 1) GT(1435);
                if (tile == NT - 1) GT(1650 + g - 32);
            }
        }
    }
}

__device__ __forceinline__ void rbf2(float& a, float& b) { uint32_t w = pack2(a, b); a = bf_lo(w); b = bf_hi(w); }
__device__ __forceinline__ void warp_sum2(float& a, float& b) {
#pragma unroll
    for (int o = 16; o; o >>= 1) { float c = __shfl_xor_sync(0xffffffffu, a, o), d = __shfl_xor_sync(0xffffffffu, b, o); a += c; b += d; }
}
__device__ __forceinline__ float sum16(const float* v) {
    return (((v[0] + v[1]) + (v[2] + v[3])) + ((v[4] + v[5]) + (v[6] + v[7]))) + (((v[8] + v[9]) + (v[10] + v[11])) + ((v[12] + v[13]) + (v[14] + v[15])));
}
__device__ __forceinline__ void ln_row2(float* v, float* u) {
    float sv = sum16(v), su = sum16(u);
    warp_sum2(sv, su);
    const float mv = sv * (1.f / DM), mu = su * (1.f / DM);
    float qv = 0.f, qu = 0.f, qv2 = 0.f, qu2 = 0.f;
#pragma unroll
    for (int i = 0; i < 16; i += 2) {
        float d0 = v[i] - mv, d1 = v[i + 1] - mv, e0 = u[i] - mu, e1 = u[i + 1] - mu;
        qv = fmaf(d0, d0, qv); qv2 = fmaf(d1, d1, qv2); qu = fmaf(e0, e0, qu); qu2 = fmaf(e1, e1, qu2);
    }
    qv += qv2; qu += qu2;
    warp_sum2(qv, qu);
    const float rv = rbf(mv), ru = rbf(mu);
    const float iv = __frcp_rn(rbf(sqrtf(rbf(rbf(qv * (1.f / DM)) + 1e-5f)))), iu = __frcp_rn(rbf(sqrtf(rbf(rbf(qu * (1.f / DM)) + 1e-5f))));
#pragma unroll
    for (int i = 0; i < 16; i += 2) {
        float a = v[i] - rv, b = v[i + 1] - rv, c = u[i] - ru, d = u[i + 1] - ru;
        rbf2(a, b); rbf2(c, d);
        a *= iv; b *= iv; c *= iu; d *= iu;
        rbf2(a, b); rbf2(c, d);
        v[i] = a; v[i + 1] = b; u[i] = c; u[i + 1] = d;
    }
}

__device__ __forceinline__ void finalizer(uint8_t* smem, int fin, const bf16* __restrict__ x, const bf16* __restrict__ wr, bf16* __restrict__ out, uint32_t epoch) {
    const int tid = threadIdx.x, lane = tid & 31, w = tid >> 5;
    __nanosleep(20000);
    for (int i = fin * 384 + tid; i < SQ * DM / 4; i += 4 * 384) ((float4*)g_acc)[i] = make_float4(0.f, 0.f, 0.f, 0.f);
    if (fin == 0) for (int i = tid; i < NT; i += 384) g_f.acc[i] = 0;
    __threadfence();
    __syncthreads();
    if (tid == 0) st_rel(&g_f.zeroed[fin], epoch);
    if (tid == 0) wait_eq4(&g_f.zeroed[0], epoch, 11);
    __syncthreads();
    if (tid == 0) GT((128 + fin) * 8 + 1);
    float b0 = -INFINITY, b1 = -INFINITY; int i0 = 0x7fffffff, i1 = 0x7fffffff;
    float wv[16];
#pragma unroll
    for (int j = 0; j < 2; j++) {
        uint4 u = *(const uint4*)(wr + j * 256 + lane * 8);
        uint32_t ww[4] = {u.x, u.y, u.z, u.w};
#pragma unroll
        for (int i = 0; i < 4; i++) { wv[j * 8 + 2 * i] = bf_lo(ww[i]); wv[j * 8 + 2 * i + 1] = bf_hi(ww[i]); }
    }
    const int gw = w * 4 + fin;
    const uint32_t tag = (epoch & 0xfffffu) << 12;
    uint4 xn_[2][2];
#pragma unroll
    for (int r = 0; r < 2; r++)
#pragma unroll
        for (int j = 0; j < 2; j++) xn_[r][j] = *(const uint4*)(x + (size_t)(gw * 2 + r) * DM + j * 256 + lane * 8);
    int ready = 0;
#pragma unroll 1
    for (int item = gw; item < SQ / 2; item += NFW) {
        const int row0 = item * 2, tile = item >> 5;
        if (tile >= ready) {
            uint32_t n = 0;
#pragma unroll 1
            while (true) {
                const uint32_t m = __ballot_sync(0xffffffffu, ldg_rlx(&g_f.acc[lane]) >= 32);
                ready = m == 0xffffffffu ? 32 : __ffs(~m) - 1;
                if (tile < ready) break;
                __nanosleep(32);
                if (++n > SPIN_LIMIT) { ABORT(12); break; }
            }
        }
        if (item == SQ / 2 - 1 && lane == 0) GT(1438);
        float4 av[2][4];
#pragma unroll
        for (int r = 0; r < 2; r++)
#pragma unroll
            for (int j = 0; j < 4; j++) av[r][j] = __ldcg((const float4*)(g_acc + (size_t)(row0 + r) * DM + (j >> 1) * 256 + lane * 8 + (j & 1) * 4));
        uint4 xu[2][2];
        const int nxt = min(item + NFW, SQ / 2 - 1);
#pragma unroll
        for (int r = 0; r < 2; r++)
#pragma unroll
            for (int j = 0; j < 2; j++) { xu[r][j] = xn_[r][j]; xn_[r][j] = *(const uint4*)(x + (size_t)(nxt * 2 + r) * DM + j * 256 + lane * 8); }
        float hv[2][16], v[2][16];
#pragma unroll
        for (int r = 0; r < 2; r++) {
#pragma unroll
            for (int j = 0; j < 2; j++) {
                uint32_t ww[4] = {xu[r][j].x, xu[r][j].y, xu[r][j].z, xu[r][j].w};
                float a[8] = {av[r][2 * j].x, av[r][2 * j].y, av[r][2 * j].z, av[r][2 * j].w, av[r][2 * j + 1].x, av[r][2 * j + 1].y, av[r][2 * j + 1].z, av[r][2 * j + 1].w};
#pragma unroll
                for (int i = 0; i < 4; i++) {
                    float a0 = a[2 * i], a1 = a[2 * i + 1];
                    rbf2(a0, a1);
                    a0 += bf_lo(ww[i]); a1 += bf_hi(ww[i]);
                    rbf2(a0, a1);
                    hv[r][j * 8 + 2 * i] = a0; hv[r][j * 8 + 2 * i + 1] = a1;
                }
            }
#pragma unroll
            for (int i = 0; i < 16; i++) v[r][i] = hv[r][i];
        }
        ln_row2(v[0], v[1]);
        float r0 = 0.f, r1 = 0.f;
#pragma unroll
        for (int i = 0; i < 16; i++) { r0 = fmaf(v[0][i], wv[i], r0); r1 = fmaf(v[1][i], wv[i], r1); }
        warp_sum2(r0, r1);
        rbf2(r0, r1);
        if (cand_better(r0, row0, b0, i0)) { b1 = b0; i1 = i0; b0 = r0; i0 = row0; }
        else if (cand_better(r0, row0, b1, i1)) { b1 = r0; i1 = row0; }
        if (cand_better(r1, row0 + 1, b0, i0)) { b1 = b0; i1 = i0; b0 = r1; i0 = row0 + 1; }
        else if (cand_better(r1, row0 + 1, b1, i1)) { b1 = r1; i1 = row0 + 1; }
        if (item == SQ / 2 - 1 && lane == 0) GT(1439);
        const bool last = item + NFW >= SQ / 2, spec = item < SPEC_TILES * 32 && item + NFW >= SPEC_TILES * 32;
        const bool pub = (lane == 0 && spec) || (lane == 1 && last);
        if (pub)
            asm volatile("st.relaxed.gpu.global.v4.b32 [%0], {%1,%2,%3,%4};" :: "l"(&g_f.cand[lane][gw]),
                         "r"(FU(b0)), "r"(tag | (uint32_t)min(i0, 4095)), "r"(FU(b1)), "r"(tag | (uint32_t)min(i1, 4095)) : "memory");
#pragma unroll
        for (int r = 0; r < 2; r++)
#pragma unroll
            for (int j = 0; j < 2; j++) {
                const size_t o = (size_t)(row0 + r) * DM + j * 256 + lane * 8;
                const float* hh = hv[r] + j * 8; const float* nn = v[r] + j * 8;
                *(uint4*)(out + o) = make_uint4(pack2(hh[0] + nn[0], hh[1] + nn[1]), pack2(hh[2] + nn[2], hh[3] + nn[3]),
                                                pack2(hh[4] + nn[4], hh[5] + nn[5]), pack2(hh[6] + nn[6], hh[7] + nn[7]));
                *(uint4*)(g_h + o) = make_uint4(pack2(hh[0], hh[1]), pack2(hh[2], hh[3]), pack2(hh[4], hh[5]), pack2(hh[6], hh[7]));
                *(uint4*)(g_hn + o) = make_uint4(pack2(nn[0], nn[1]), pack2(nn[2], nn[3]), pack2(nn[4], nn[5]), pack2(nn[6], nn[7]));
            }
        if (last || spec) {
            __threadfence();
            __syncwarp();
            if (pub) stg_rlx(&g_f.rows[lane][gw], epoch);
        }
    }
    if (fin == 0 && tid == 0) { g_epoch = epoch; if (epoch == 0xffffffu) { g_ticket[0] = 0; g_ticket[32] = 0; } }
}

__device__ __forceinline__ int startup(uint8_t* smem, const bf16* __restrict__ x, const Maps& maps, uint32_t& epoch) {
    const int tid = threadIdx.x, lane = tid & 31, w = tid >> 5, cta = blockIdx.x;
    volatile uint32_t* sh = (volatile uint32_t*)(smem + SH_OFF);
    if (cta == 4 && tid == 0) GT(1399);
    epoch = (ldg_rlx(&g_epoch) + 1) & 0x00ffffffu;
    if (w < 4) {
        if (!(cta & 1)) {
            uint32_t* pp = (uint32_t*)(xpage() + ((XR3 ^ 0x3000u) ^ ((w == 1 || w == 2) ? 0x1000u : 0u) ^ ((w & 2) << 13))) + (cta >> 1) * 8;
            if (lane < 8) stg_rlx(pp + lane, 0u);
            __syncwarp();
            if (lane == 0) {
                uint32_t best = 0xffffffffu, a = 0;
#pragma unroll 1
                for (int r = 0; r < NPROBE; r++) {
                    uint32_t t0 = clk32();
                    asm volatile("atom.relaxed.gpu.global.add.u32 %0, [%1], %2;" : "=r"(a) : "l"(pp), "r"(a + 1) : "memory");
                    if (a == 0x7fffffffu) ABORT(15);
                    uint32_t t1 = clk32();
                    if (r > 0) best = min(best, t1 - t0);
                    else if (w == 0) {
                        asm volatile("red.relaxed.gpu.global.max.u32 [%0], %1;" :: "l"(&g_ticket[0]), "r"(epoch << 8) : "memory");
                        asm volatile("red.relaxed.gpu.global.max.u32 [%0], %1;" :: "l"(&g_ticket[32]), "r"(epoch << 8) : "memory");
                    }
                }
                sh[w] = best;
            }
        }
        if (!(cta & 1)) bar_sync(1, 128);
        if (cta == 4 && tid == 0) GT(1400);
        if (w == 0) {
            if (lane == 0) {
                uint32_t rp;
                if (!(cta & 1)) {
                    uint32_t a = sh[0], b = sh[1], c = sh[2], d = sh[3];
                    uint32_t mid = (min(min(a, b), min(c, d)) + max(max(a, b), max(c, d))) >> 1;
                    const int dd = (int)min(a, d) - (int)min(b, c);
                    uint32_t cls = abs(dd) > 60 ? dd > 0 : a > mid;
                    uint32_t t = atomicAdd(&g_ticket[cls * 32], 1u) & 255;
                    if (t >= (cls ? 34u : 32u)) { cls ^= 1; t = atomicAdd(&g_ticket[cls * 32], 1u) & 255; }
                    rp = min(cls ? 32 + t : t, 65u);
                    stg_rlx(&g_table[(cta >> 1) * 8], (epoch << 8) | rp);
                } else {
                    uint32_t v, n = 0;
#pragma unroll 1
                    while (((v = ldg_rlx(&g_table[(cta >> 1) * 8])) >> 8) != epoch) { if (++n > SPIN_LIMIT) { ABORT(14); break; } }
                    rp = v & 255;
                }
                const int role = rp * 2 + (cta & 1);
                sh[8] = role; sh[9] = epoch;
                while (sh[10] != epoch + 1 && cta < 128) {}
                asm volatile("fence.proxy.async;" ::: "memory");
                if (role < 64) rec_first_loads(smem_u32(smem), role, maps);
                else if (role < 128) load_w(smem_u32(smem), (role & 1) ? &maps.wv : &maps.wk, ((role - 64) >> 1) * 128, 0, 0, 1);
                if (cta == 4) GT(1401);
            }
        }
    } else if (cta < 128) {
        uint4 u[2][2];
        const int row0 = cta * 16 + (w - 4) * 2;
#pragma unroll
        for (int r = 0; r < 2; r++)
#pragma unroll
            for (int j = 0; j < 2; j++) u[r][j] = *(const uint4*)(x + (size_t)(row0 + r) * DM + j * 256 + lane * 8);
        if (cta < 48) {
            const uint32_t b = cta >> 3, off = (b >= 4 ? 0x8000u + (b & 1) * 0x4000u : ((b & 1) ? 0x3000u : 0u) + ((b & 2) << 13)) ^ aslot(cta & 7);
            *(uint4*)(xpage() + off + (tid - 128) * 16) = make_uint4(0, 0, 0, 0);
        }
        float v[2][16];
#pragma unroll
        for (int r = 0; r < 2; r++)
#pragma unroll
            for (int j = 0; j < 2; j++) {
                uint32_t ww[4] = {u[r][j].x, u[r][j].y, u[r][j].z, u[r][j].w};
#pragma unroll
                for (int i = 0; i < 4; i++) { v[r][j * 8 + 2 * i] = bf_lo(ww[i]); v[r][j * 8 + 2 * i + 1] = bf_hi(ww[i]); }
            }
        ln_row2(v[0], v[1]);
#pragma unroll
        for (int r = 0; r < 2; r++)
#pragma unroll
            for (int j = 0; j < 2; j++)
                *(uint4*)(g_xn + (size_t)(row0 + r) * DM + j * 256 + lane * 8) =
                    make_uint4(pack2(v[r][j * 8], v[r][j * 8 + 1]), pack2(v[r][j * 8 + 2], v[r][j * 8 + 3]), pack2(v[r][j * 8 + 4], v[r][j * 8 + 5]), pack2(v[r][j * 8 + 6], v[r][j * 8 + 7]));
        bar_sync(2, 256);
        if (tid == 160) { st_rel(&g_f.xn[cta], epoch); sh[10] = epoch + 1; }
        if (cta == 4 && tid == 160) GT(1403);
        __syncwarp();
    }
    if (cta == 4 && tid == 128) GT(1402);
    __syncthreads();
    const int role = sh[8];
    return role;
}

__global__ void __cluster_dims__(2, 1, 1) __launch_bounds__(384, 1)
main_kernel(const __grid_constant__ Maps maps, const bf16* __restrict__ x, const bf16* __restrict__ mem0, const bf16* __restrict__ wr,
            const bf16* __restrict__ wd, bf16* __restrict__ out) {
    extern __shared__ __align__(1024) uint8_t smem[];
    const uint32_t sb = smem_u32(smem);
    if (threadIdx.x == 0) {
        for (int i = 0; i < MB_N; i++) mbar_init(sb + R_BAR + 8 * i, i == MB_V ? 4 : 1);
        for (int i = 0; i < GB_N; i++)
            mbar_init(sb + G_BAR + 8 * i, i == GB_WFREE ? 8 : (i >= GB_EMPTY && i < GB_KV ? 4 : (i >= GB_STG && i < GB_FREE ? 128 : 1)));
        asm volatile("fence.mbarrier_init.release.cluster;" ::: "memory");
    }
    if (threadIdx.x >= 352 && threadIdx.x < 352 + (int)(sizeof(Maps) / sizeof(CUtensorMap)))
        asm volatile("prefetch.tensormap [%0];" :: "l"((const CUtensorMap*)&maps + (threadIdx.x - 352)) : "memory");
    uint32_t epoch;
    asm volatile("fence.proxy.async.shared::cta;" ::: "memory");
    const int role = uni(startup(smem, x, maps, epoch));
    const int wg = uni(threadIdx.x >> 7);
    if (role < 64) {
#define SETREG(n) do { if ((n) < 168) asm volatile("setmaxnreg.dec.sync.aligned.u32 %0;" :: "n"(n)); if ((n) > 168) asm volatile("setmaxnreg.inc.sync.aligned.u32 %0;" :: "n"(n)); } while (0)
#define RESREG(n) do { if ((n) < 168) asm volatile("setmaxnreg.inc.sync.aligned.u32 168;"); if ((n) > 168) asm volatile("setmaxnreg.dec.sync.aligned.u32 168;"); } while (0)
        if (wg == 0) {
            SETREG(RGA);
            rec_a(sb, role, mem0, epoch);
            RESREG(RGA);
        } else if (wg == 1) {
            SETREG(RGB);
            rec_b(sb, role, epoch);
            RESREG(RGB);
        } else {
            SETREG(RGC);
            rec_c(sb, role, mem0, maps, epoch);
            RESREG(RGC);
        }
        ffn_phase(maps, wd, out);
        if (threadIdx.x == 0) GT(((volatile int*)(smem + SH_OFF))[8] * 8 + 6);
    } else if (role < 128) {
        if (wg < 2) {
            asm volatile("setmaxnreg.inc.sync.aligned.u32 232;");
            g_consumer(sb, role - 64, wg, epoch);
            if (threadIdx.x == 128) GT(role * 8 + 6);
        } else {
            asm volatile("setmaxnreg.dec.sync.aligned.u32 40;");
            g_producer(sb, role - 64, maps, epoch);
        }
    } else {
        finalizer(smem, role - 128, x, wr, out, epoch);
        if (threadIdx.x == 0) GT(((volatile int*)(smem + SH_OFF))[8] * 8 + 6);
    }
}

typedef CUresult (*EncodeFn)(CUtensorMap*, CUtensorMapDataType, cuuint32_t, void*, const cuuint64_t*, const cuuint64_t*, const cuuint32_t*, const cuuint32_t*,
                             CUtensorMapInterleave, CUtensorMapSwizzle, CUtensorMapL2promotion, CUtensorMapFloatOOBfill);
static void make_map3(EncodeFn fn, CUtensorMap* m, const void* ptr, uint64_t cols, uint64_t rows) {
    cuuint64_t dims[3] = {64, rows, cols / 64};
    cuuint64_t strides[2] = {cols * 2, 128};
    cuuint32_t box[3] = {64, 64, 2};
    cuuint32_t es[3] = {1, 1, 1};
    fn(m, CU_TENSOR_MAP_DATA_TYPE_BFLOAT16, 3, (void*)ptr, dims, strides, box, es, CU_TENSOR_MAP_INTERLEAVE_NONE, CU_TENSOR_MAP_SWIZZLE_128B,
       CU_TENSOR_MAP_L2_PROMOTION_L2_256B, CU_TENSOR_MAP_FLOAT_OOB_FILL_NONE);
}
static void make_map(EncodeFn fn, CUtensorMap* m, const void* ptr, uint64_t cols, uint64_t rows, uint32_t bcols, uint32_t brows,
                     bool f32 = false, CUtensorMapSwizzle sw = CU_TENSOR_MAP_SWIZZLE_128B) {
    cuuint64_t dims[2] = {cols, rows};
    cuuint64_t strides[1] = {cols * (f32 ? 4 : 2)};
    cuuint32_t box[2] = {bcols, brows};
    cuuint32_t es[2] = {1, 1};
    fn(m, f32 ? CU_TENSOR_MAP_DATA_TYPE_FLOAT32 : CU_TENSOR_MAP_DATA_TYPE_BFLOAT16, 2, (void*)ptr, dims, strides, box, es, CU_TENSOR_MAP_INTERLEAVE_NONE, sw,
       CU_TENSOR_MAP_L2_PROMOTION_L2_256B, CU_TENSOR_MAP_FLOAT_OOB_FILL_NONE);
}

extern "C" void kernel_launch(void* const* d_in, const int* in_sizes, int n_in, void* d_out, int out_size) {
    const bf16* x = (const bf16*)d_in[0];
    const bf16* mem0 = (const bf16*)d_in[1];
    const bf16* Wq = (const bf16*)d_in[2];
    const bf16* Wk = (const bf16*)d_in[3];
    const bf16* Wv = (const bf16*)d_in[4];
    const bf16* Wo = (const bf16*)d_in[5];
    const bf16* wr = (const bf16*)d_in[8];
    const bf16* wg = (const bf16*)d_in[9];
    const bf16* wu = (const bf16*)d_in[10];
    const bf16* wd = (const bf16*)d_in[11];
    bf16* out = (bf16*)d_out;

    static EncodeFn enc = nullptr;
    static void *pxn, *pK, *pV, *pO, *pacc;
    if (!enc) {
        cudaDriverEntryPointQueryResult qr;
        void* fn = nullptr;
        cudaGetDriverEntryPoint("cuTensorMapEncodeTiled", &fn, cudaEnableDefault, &qr);
        enc = (EncodeFn)fn;
        cudaGetSymbolAddress(&pxn, g_xn); cudaGetSymbolAddress(&pK, g_K); cudaGetSymbolAddress(&pV, g_V);
        cudaGetSymbolAddress(&pO, g_O); cudaGetSymbolAddress(&pacc, g_acc);
        cudaFuncSetAttribute(main_kernel, cudaFuncAttributeMaxDynamicSharedMemorySize, SMEM_TOTAL);
    }
    Maps m;
    make_map(enc, &m.wq, Wq, HD, DM, 64, 256);
    make_map(enc, &m.wk, Wk, HD, DM, 64, 256);
    make_map(enc, &m.wv, Wv, HD, DM, 64, 256);
    make_map(enc, &m.wo, Wo, DM, HD, 64, 128);
    make_map(enc, &m.wo2, Wo, DM, HD, 64, 256);
    make_map(enc, &m.kx, pK, HD, SQ, 64, 64);
    make_map(enc, &m.vx, pV, HD, SQ, 64, 64);
    make_map3(enc, &m.kx3, pK, HD, SQ); make_map3(enc, &m.vx3, pV, HD, SQ); make_map3(enc, &m.ox3, pO, HD, SQ); make_map3(enc, &m.xn3, pxn, DM, SQ);
    make_map(enc, &m.acc, pacc, DM, SQ, 32, 64, true);
    make_map(enc, &m.wg, wg, FF, DM, 32, 256, false, CU_TENSOR_MAP_SWIZZLE_NONE);
    make_map(enc, &m.wu, wu, FF, DM, 32, 256, false, CU_TENSOR_MAP_SWIZZLE_NONE);

    cudaStream_t st = cudaStreamPerThread;
    main_kernel<<<NCTA, 384, SMEM_TOTAL, st>>>(m, x, mem0, wr, wd, out);
}
```

```cpp
#include <cuda_runtime.h>
#include <cuda_bf16.h>
#include <cuda.h>
#include <stdint.h>
#include <stddef.h>

typedef __nv_bfloat16 bf16;

constexpr int SQ = 2048, DM = 512, NH = 32, DH = 128, NSEG = 64, HD = 4096, FF = 1792;

constexpr int NT = 32;
#define SPEC_TILES 30
__device__ __align__(1024) bf16 g_xn[SQ * DM];
__device__ __align__(1024) bf16 g_K[SQ * HD];
__device__ __align__(1024) bf16 g_V[SQ * HD];
__device__ __align__(1024) bf16 g_O[SQ * HD];
__device__ __align__(1024) uint32_t g_KVf[NSEG][NH][1024];
__device__ __align__(1024) bf16 g_P[8 * SQ * DM];
__device__ __align__(1024) bf16 g_h[SQ * DM];
__device__ __align__(1024) bf16 g_hn[SQ * DM];
__device__ uint8_t g_xraw[12 << 20];
#define XPG 0
__device__ __forceinline__ uint64_t xpage() { return (((uint64_t)g_xraw + (2 << 20) - 1) & ~(uint64_t)((2 << 20) - 1)) + ((uint64_t)XPG << 21); }
constexpr uint32_t XR3 = (1u << 20) | (1u << 19) | (1u << 12);
__device__ __forceinline__ uint32_t aslot(uint32_t s) { return ((s & 1) << 18) | ((s & 2) << 19) | ((s & 4) * 0xc000u); }
#define IL 1
constexpr int AC1 = IL ? 48 : 256;
__device__ __forceinline__ uint32_t acc_off(uint32_t W, uint32_t lane) {
    return ((W & 2) ? 0x3000u : 0u) + ((W & 4) << 12) + (W & 1) * 2048 + (IL ? (lane >> 2) * 256 : (lane >> 2) * 128 + (lane & 4) * 16) + (lane & 3) * 16;
}
#define XM 1
__device__ __forceinline__ uint32_t ext_base(uint32_t W) { return 0x8000u + ((W & 4) << 12) + (W & 3) * 1024; }
__device__ __forceinline__ uint32_t ext_lane(uint32_t lane) { return XM == 1 ? (lane >> 3) * 256 + (lane & 7) * 4 : (XM == 2 ? (lane >> 4) * 512 + (lane & 15) * 4 : lane * 4); }
__device__ __forceinline__ uint32_t zero_off(uint32_t c, uint32_t ln) {
    return ln < 16 ? ((c & 16) ? 0x3000u : 0u) + ((c & 32) << 9) + (c & 15) * 256 + ln * 16 : ext_base(c >> 3) + ext_lane((c & 7) * 4);
}
struct Flags {
    uint32_t kv[NT][NH][2];
    uint32_t o[NT][8][32];
    uint32_t rec[64];
    uint32_t xn[128];
    uint32_t rload[64];
    uint32_t p[NT][32];
    uint32_t rows[2][64];
    uint4 cand[2][64];
    uint4 norm[64];
};
__device__ __align__(1024) Flags g_f;
__device__ __align__(1024) uint4 g_yp[2][FF / 32][DM];
__device__ __align__(1024) uint32_t g_table[66 * 8];
__device__ __align__(256) uint32_t g_ticket[64];
__device__ uint32_t g_epoch;
#define HOLD 2
#define HSPLIT 20
#define NPROBE 3
constexpr int NCTA = 132;
constexpr int NFW = 64;
__device__ uint32_t g_abort;
__device__ long long g_dbg[4096];
#define TR(slot, v)

__device__ __forceinline__ uint32_t smem_u32(const void* p) { return (uint32_t)__cvta_generic_to_shared(p); }
__device__ __forceinline__ void mbar_init(uint32_t a, uint32_t c) { asm volatile("mbarrier.init.shared::cta.b64 [%0], %1;" :: "r"(a), "r"(c) : "memory"); }
__device__ __forceinline__ void mbar_expect_tx(uint32_t a, uint32_t tx) { asm volatile("mbarrier.arrive.expect_tx.shared::cta.b64 _, [%0], %1;" :: "r"(a), "r"(tx) : "memory"); }
__device__ __forceinline__ void mbar_arrive(uint32_t a) { asm volatile("mbarrier.arrive.shared::cta.b64 _, [%0];" :: "r"(a) : "memory"); }
__device__ __forceinline__ void mbar_arrive_if(uint32_t a, uint32_t pred) {
    asm volatile("{\n.reg .pred p;\nsetp.ne.u32 p, %1, 0;\n@p mbarrier.arrive.shared::cta.b64 _, [%0];\n}" :: "r"(a), "r"(pred) : "memory");
}
__device__ __forceinline__ bool mbar_try(uint32_t a, uint32_t ph) {
    uint32_t ok;
    asm volatile("{\n.reg .pred p;\nmbarrier.try_wait.parity.shared::cta.b64 p, [%1], %2;\nselp.u32 %0, 1, 0, p;\n}" : "=r"(ok) : "r"(a), "r"(ph) : "memory");
    return ok != 0;
}
#define SPINLOG 20
constexpr uint32_t SPIN_LIMIT = 1u << SPINLOG;
#define ABORT(code_) atomicCAS(&g_abort, 0u, (code_))
__device__ __forceinline__ void mbar_wait(uint32_t a, uint32_t ph) {
    uint32_t n = 0;
#pragma unroll 1
    while (!mbar_try(a, ph)) { if (++n > SPIN_LIMIT) { ABORT(1); break; } }
}
__device__ __forceinline__ void bar_sync(int id, int n) { asm volatile("bar.sync %0, %1;" :: "r"(id), "r"(n) : "memory"); }
__device__ __forceinline__ void bar_arrive(int id, int n) { asm volatile("bar.arrive %0, %1;" :: "r"(id), "r"(n) : "memory"); }

__device__ __forceinline__ void ldsm4(uint32_t* r, uint32_t a) {
    asm volatile("ldmatrix.sync.aligned.m8n8.x4.shared.b16 {%0,%1,%2,%3}, [%4];" : "=r"(r[0]), "=r"(r[1]), "=r"(r[2]), "=r"(r[3]) : "r"(a) : "memory");
}
__device__ __forceinline__ void ldsm4t(uint32_t* r, uint32_t a) {
    asm volatile("ldmatrix.sync.aligned.m8n8.x4.trans.shared.b16 {%0,%1,%2,%3}, [%4];" : "=r"(r[0]), "=r"(r[1]), "=r"(r[2]), "=r"(r[3]) : "r"(a) : "memory");
}
__device__ __forceinline__ void stsm4t(uint32_t a, uint32_t r0, uint32_t r1, uint32_t r2, uint32_t r3) {
    asm volatile("stmatrix.sync.aligned.m8n8.x4.trans.shared.b16 [%0], {%1,%2,%3,%4};" :: "r"(a), "r"(r0), "r"(r1), "r"(r2), "r"(r3) : "memory");
}
__device__ __forceinline__ void stsm4(uint32_t a, uint32_t r0, uint32_t r1, uint32_t r2, uint32_t r3) {
    asm volatile("stmatrix.sync.aligned.m8n8.x4.shared.b16 [%0], {%1,%2,%3,%4};" :: "r"(a), "r"(r0), "r"(r1), "r"(r2), "r"(r3) : "memory");
}
__device__ __forceinline__ uint32_t movm(uint32_t a) { uint32_t d; asm volatile("movmatrix.sync.aligned.m8n8.trans.b16 %0, %1;" : "=r"(d) : "r"(a)); return d; }
__device__ __forceinline__ void mma16816(float* d, uint32_t a0, uint32_t a1, uint32_t a2, uint32_t a3, uint32_t b0, uint32_t b1) {
    asm volatile("mma.sync.aligned.m16n8k16.row.col.f32.bf16.bf16.f32 {%0,%1,%2,%3}, {%4,%5,%6,%7}, {%8,%9}, {%0,%1,%2,%3};"
        : "+f"(d[0]), "+f"(d[1]), "+f"(d[2]), "+f"(d[3]) : "r"(a0), "r"(a1), "r"(a2), "r"(a3), "r"(b0), "r"(b1));
}
__device__ __forceinline__ void mma1688(float* d, uint32_t a0, uint32_t a1, uint32_t b0) {
    asm volatile("mma.sync.aligned.m16n8k8.row.col.f32.bf16.bf16.f32 {%0,%1,%2,%3}, {%4,%5}, {%6}, {%0,%1,%2,%3};"
        : "+f"(d[0]), "+f"(d[1]), "+f"(d[2]), "+f"(d[3]) : "r"(a0), "r"(a1), "r"(b0));
}
__device__ __forceinline__ uint32_t pack2(float a, float b) { uint32_t d; asm("cvt.rn.bf16x2.f32 %0, %1, %2;" : "=r"(d) : "f"(b), "f"(a)); return d; }
__device__ __forceinline__ float bf_lo(uint32_t w) { return __uint_as_float(w << 16); }
__device__ __forceinline__ float bf_hi(uint32_t w) { return __uint_as_float(w & 0xffff0000u); }
__device__ __forceinline__ float rbf(float x) { return __bfloat162float(__float2bfloat16_rn(x)); }

__device__ __forceinline__ void sts128(uint32_t a, float x, float y, float z, float w) { asm volatile("st.shared.v4.f32 [%0], {%1,%2,%3,%4};" :: "r"(a), "f"(x), "f"(y), "f"(z), "f"(w) : "memory"); }
__device__ __forceinline__ void sts128u(uint32_t a, uint32_t x, uint32_t y, uint32_t z, uint32_t w) { asm volatile("st.shared.v4.b32 [%0], {%1,%2,%3,%4};" :: "r"(a), "r"(x), "r"(y), "r"(z), "r"(w) : "memory"); }
__device__ __forceinline__ void sts64(uint32_t a, float x, float y) { asm volatile("st.shared.v2.f32 [%0], {%1,%2};" :: "r"(a), "f"(x), "f"(y) : "memory"); }
__device__ __forceinline__ float4 lds128(uint32_t a) { float4 v; asm volatile("ld.shared.v4.f32 {%0,%1,%2,%3}, [%4];" : "=f"(v.x), "=f"(v.y), "=f"(v.z), "=f"(v.w) : "r"(a) : "memory"); return v; }
__device__ __forceinline__ float2 lds64(uint32_t a) { float2 v; asm volatile("ld.shared.v2.f32 {%0,%1}, [%2];" : "=f"(v.x), "=f"(v.y) : "r"(a) : "memory"); return v; }
__device__ __forceinline__ uint2 lds64u(uint32_t a) { uint2 v; asm volatile("ld.shared.v2.b32 {%0,%1}, [%2];" : "=r"(v.x), "=r"(v.y) : "r"(a) : "memory"); return v; }
__device__ __forceinline__ float4 lds128v(uint32_t a) { float4 v; asm volatile("ld.volatile.shared.v4.f32 {%0,%1,%2,%3}, [%4];" : "=f"(v.x), "=f"(v.y), "=f"(v.z), "=f"(v.w) : "r"(a) : "memory"); return v; }
__device__ __forceinline__ float2 lds64v(uint32_t a) { float2 v; asm volatile("ld.volatile.shared.v2.f32 {%0,%1}, [%2];" : "=f"(v.x), "=f"(v.y) : "r"(a) : "memory"); return v; }
__device__ __forceinline__ uint4 lds128uv(uint32_t a) { uint4 v; asm volatile("ld.volatile.shared.v4.b32 {%0,%1,%2,%3}, [%4];" : "=r"(v.x), "=r"(v.y), "=r"(v.z), "=r"(v.w) : "r"(a) : "memory"); return v; }
__device__ __forceinline__ void st_async4(uint32_t a, float x, float y, float z, float w, uint32_t mb) {
    asm volatile("st.async.weak.shared::cluster.mbarrier::complete_tx::bytes.v4.f32 [%0], {%1,%2,%3,%4}, [%5];" :: "r"(a), "f"(x), "f"(y), "f"(z), "f"(w), "r"(mb) : "memory");
}
__device__ __forceinline__ void st_async2(uint32_t a, uint32_t x, uint32_t y, uint32_t mb) {
    asm volatile("st.async.weak.shared::cluster.mbarrier::complete_tx::bytes.v2.b32 [%0], {%1,%2}, [%3];" :: "r"(a), "r"(x), "r"(y), "r"(mb) : "memory");
}
__device__ __forceinline__ uint32_t ldg_rlx(const uint32_t* p) { uint32_t v; asm volatile("ld.relaxed.gpu.global.b32 %0, [%1];" : "=r"(v) : "l"(p) : "memory"); return v; }
__device__ __forceinline__ uint4 ldg_rlx4(const uint32_t* p) { uint4 v; asm volatile("ld.relaxed.gpu.global.v4.b32 {%0,%1,%2,%3}, [%4];" : "=r"(v.x), "=r"(v.y), "=r"(v.z), "=r"(v.w) : "l"(p) : "memory"); return v; }
__device__ __forceinline__ void stg_rlx(uint32_t* p, uint32_t v) { asm volatile("st.relaxed.gpu.global.b32 [%0], %1;" :: "l"(p), "r"(v) : "memory"); }
__device__ __forceinline__ void tma2d(uint32_t dst, const CUtensorMap* tm, int c0, int c1, uint32_t mb) {
    asm volatile("cp.async.bulk.tensor.2d.shared::cluster.global.mbarrier::complete_tx::bytes [%0], [%1, {%3, %4}], [%2];"
        :: "r"(dst), "l"((uint64_t)tm), "r"(mb), "r"(c0), "r"(c1) : "memory");
}

__device__ __forceinline__ void tma3d(uint32_t dst, const CUtensorMap* tm, int row, int chunk, uint32_t mb) {
    asm volatile("cp.async.bulk.tensor.3d.shared::cluster.global.mbarrier::complete_tx::bytes [%0], [%1, {%3, %4, %5}], [%2];"
        :: "r"(dst), "l"((uint64_t)tm), "r"(mb), "r"(0), "r"(row), "r"(chunk) : "memory");
}
__device__ __forceinline__ void tma_store3d(const CUtensorMap* tm, uint32_t src, int row, int chunk) {
    asm volatile("cp.async.bulk.tensor.3d.global.shared::cta.bulk_group [%0, {%2, %3, %4}], [%1];" :: "l"((uint64_t)tm), "r"(src), "r"(0), "r"(row), "r"(chunk) : "memory");
}
__device__ __forceinline__ void bulk_store(void* dst, uint32_t src, uint32_t bytes) {
    asm volatile("cp.async.bulk.global.shared::cta.bulk_group [%0], [%1], %2;" :: "l"(dst), "r"(src), "r"(bytes) : "memory");
}
#define GT(slot)
#define CNT(k)
#define CNT2(k, c)
#define PS0 20
#define TS(i)
#define TSDECL
struct Maps { CUtensorMap wq, wk, wv, wo, wo2, kx, vx, kx3, vx3, ox3, xn3, p3, wg, wu; };
typedef Maps RecMaps;
__device__ __forceinline__ void st_rel(uint32_t* p, uint32_t v) { asm volatile("st.release.gpu.global.u32 [%0], %1;" :: "l"(p), "r"(v) : "memory"); }
#define PUBLISH(p, v) st_rel(p, v)
__device__ __forceinline__ uint2 ldg_rlx2(const uint32_t* p) { uint2 v; asm volatile("ld.relaxed.gpu.global.v2.b32 {%0,%1}, [%2];" : "=r"(v.x), "=r"(v.y) : "l"(p) : "memory"); return v; }
__device__ __forceinline__ void wait_eq2(const uint32_t* p, uint32_t e, int code) {
    uint32_t n = 0;
#pragma unroll 1
    while (true) { uint2 v = ldg_rlx2(p); if (v.x == e && v.y == e) break; __nanosleep(64); if (++n > SPIN_LIMIT) { ABORT(code); break; } }
}
__device__ __forceinline__ void wait_eq4(const uint32_t* p, uint32_t e, int code) {
    uint32_t n = 0;
#pragma unroll 1
    while (true) { uint4 v = ldg_rlx4(p); if (v.x == e && v.y == e && v.z == e && v.w == e) break; __nanosleep(64); if (++n > SPIN_LIMIT) { ABORT(code); break; } }
}
__device__ __forceinline__ void wait_rec(const uint32_t* p, uint32_t e, uint32_t steps) {
    uint32_t n = 0;
#pragma unroll 1
    while (true) {
        uint2 v = ldg_rlx2(p);
        if ((v.x >> 8) == e && (v.y >> 8) == e && (v.x & 255) >= steps && (v.y & 255) >= steps) break;
        __nanosleep(64); if (++n > SPIN_LIMIT) { ABORT(8); break; }
    }
}

constexpr int R_QK1 = 0;
constexpr int R_WO = 65536;
constexpr int R_T = 131072;
constexpr int R_SLOT1 = R_T;
constexpr int R_MEMB = R_T + 24576;
constexpr int R_QP = R_MEMB + 8192;
constexpr int R_VRED = R_QP + 4096;
constexpr int R_STG = R_VRED + 2048;
constexpr int R_AX = R_STG + 2048;
constexpr int R_SLOT0 = 196608;
constexpr int R_SLOC = R_SLOT0 + 24576;
constexpr int R_SREM = R_SLOC + 1536;
constexpr int R_VB = R_SREM + 1536;
constexpr int R_MISC = R_VB + 2048;
constexpr int R_LT = R_MISC + 128;
constexpr int R_BAR = 229888;
constexpr int R_TS = 229888 + 128;
static_assert(R_AX + 24576 <= R_SLOT0 && R_LT + 2560 <= 229376, "smem map");
enum { MB_W0 = 0, MB_W1, MB_WV, MB_WO, MB_S, MB_FULL0, MB_FULL1, MB_V, MB_N };

__device__ __forceinline__ float ex2(float x) { float y; asm("ex2.approx.ftz.f32 %0, %1;" : "=f"(y) : "f"(x)); return y; }
__device__ __forceinline__ float rcpf(float x) { float y; asm("rcp.approx.ftz.f32 %0, %1;" : "=f"(y) : "f"(x)); return y; }
__device__ __forceinline__ void mma16816z(float* d, uint32_t a0, uint32_t a1, uint32_t a2, uint32_t a3, uint32_t b0, uint32_t b1) {
    asm volatile("mma.sync.aligned.m16n8k16.row.col.f32.bf16.bf16.f32 {%0,%1,%2,%3}, {%4,%5,%6,%7}, {%8,%9}, {%10,%10,%10,%10};"
        : "=f"(d[0]), "=f"(d[1]), "=f"(d[2]), "=f"(d[3]) : "r"(a0), "r"(a1), "r"(a2), "r"(a3), "r"(b0), "r"(b1), "f"(0.f));
}
__device__ __forceinline__ void mma1688hz(float* d, uint32_t a0, uint32_t a1, uint32_t b0) {
    asm volatile("mma.sync.aligned.m16n8k8.row.col.f32.f16.f16.f32 {%0,%1,%2,%3}, {%4,%5}, {%6}, {%7,%7,%7,%7};"
        : "=f"(d[0]), "=f"(d[1]), "=f"(d[2]), "=f"(d[3]) : "r"(a0), "r"(a1), "r"(b0), "f"(0.f));
}
#define MMA(d, a, b0, b1) mma16816(d, a[0], a[1], a[2], a[3], b0, b1)
#define MMAZ(d, a, b0, b1) mma16816z(d, a[0], a[1], a[2], a[3], b0, b1)
#define MMAF(first, d, a, b0, b1) do { if (first) MMAZ(d, a, b0, b1); else MMA(d, a, b0, b1); } while (0)

__device__ __forceinline__ uint32_t uni(uint32_t x) { return __reduce_max_sync(0xffffffffu, x); }
__device__ __forceinline__ void mbar_wait_u(uint32_t a, uint32_t ph) {
    uint32_t n = 0;
#pragma unroll 1
    while (!__all_sync(0xffffffffu, mbar_try(a, ph))) { if (++n > SPIN_LIMIT) { ABORT(1); break; } }
}
__device__ __forceinline__ void mbar_wait_p(uint32_t a, uint32_t ph) {
    asm volatile("{\n.reg .pred p, q;\n.reg .u32 n;\nmov.u32 n, 0;\nWL: mbarrier.try_wait.parity.shared::cta.b64 p, [%0], %1;\nadd.u32 n, n, 1;\n"
                 "setp.lt.and.u32 q, n, %2, !p;\n@q bra.uni WL;\n}" :: "r"(a), "r"(ph), "n"(SPIN_LIMIT) : "memory");
}
__device__ __forceinline__ uint32_t mbar_test(uint32_t a, uint32_t ph) {
    uint32_t ok;
    asm volatile("{\n.reg .pred p;\nmbarrier.test_wait.parity.shared::cta.b64 p, [%1], %2;\nselp.u32 %0, 1, 0, p;\n}" : "=r"(ok) : "r"(a), "r"(ph) : "memory");
    return ok;
}
__device__ __forceinline__ uint32_t opaque(uint32_t x) { return __shfl_sync(0xffffffffu, x, threadIdx.x & 31); }
__device__ __forceinline__ const uint32_t* mkptr(uint32_t lo, uint32_t hi) { uint64_t r; asm("mov.b64 %0, {%1, %2};" : "=l"(r) : "r"(lo), "r"(hi)); return (const uint32_t*)r; }
__device__ __forceinline__ uint32_t prmt(uint32_t a, uint32_t b, uint32_t s) { uint32_t d; asm("prmt.b32 %0, %1, %2, %3;" : "=r"(d) : "r"(a), "r"(b), "r"(s)); return d; }
__device__ __forceinline__ uint32_t packh2(float a, float b) { uint32_t d; asm("cvt.rn.f16x2.f32 %0, %1, %2;" : "=r"(d) : "f"(b), "f"(a)); return d; }
__device__ __forceinline__ uint32_t hadd2b(uint32_t a, uint32_t b) { uint32_t d; asm("add.rn.bf16x2 %0, %1, %2;" : "=r"(d) : "r"(a), "r"(b)); return d; }
__device__ __forceinline__ uint32_t hmul2b(uint32_t a, uint32_t b) { uint32_t d; asm("mul.rn.bf16x2 %0, %1, %2;" : "=r"(d) : "r"(a), "r"(b)); return d; }
__device__ __forceinline__ uint32_t amax2b(uint32_t a, uint32_t b) { uint32_t d; asm("max.xorsign.abs.bf16x2 %0, %1, %2;" : "=r"(d) : "r"(a), "r"(b)); return d; }
__device__ __forceinline__ uint32_t amax2h(uint32_t a, uint32_t b) { uint32_t d; asm("max.xorsign.abs.f16x2 %0, %1, %2;" : "=r"(d) : "r"(a), "r"(b)); return d; }
__device__ __forceinline__ void sts32(uint32_t a, uint32_t x) { asm volatile("st.shared.b32 [%0], %1;" :: "r"(a), "r"(x) : "memory"); }
__device__ __forceinline__ uint32_t lds32v_(uint32_t a) { uint32_t v; asm volatile("ld.volatile.shared.b32 %0, [%1];" : "=r"(v) : "r"(a) : "memory"); return v; }
__device__ __forceinline__ void stg4(void* p, uint4 v) { asm volatile("st.relaxed.gpu.global.v4.b32 [%0], {%1,%2,%3,%4};" :: "l"(p), "r"(v.x), "r"(v.y), "r"(v.z), "r"(v.w) : "memory"); }
__device__ __forceinline__ void lds_frag(uint32_t* r, uint32_t a) {
    asm volatile("ld.shared.v4.b32 {%0,%1,%2,%3}, [%4];" : "=r"(r[0]), "=r"(r[1]), "=r"(r[2]), "=r"(r[3]) : "r"(a) : "memory");
}
__device__ __forceinline__ void lds_fragv(uint32_t* r, uint32_t a) {
    asm volatile("ld.volatile.shared.v4.b32 {%0,%1,%2,%3}, [%4];" : "=r"(r[0]), "=r"(r[1]), "=r"(r[2]), "=r"(r[3]) : "r"(a) : "memory");
}
__device__ __forceinline__ uint32_t xorv(uint32_t a, uint32_t b) { uint32_t d; asm volatile("xor.b32 %0, %1, %2;" : "=r"(d) : "r"(a), "r"(b)); return d; }
#define SCHED(k) asm volatile("{\n.reg .pred p;\nsetp.ne.u32 p, %0, %1;\n@p bra.uni SD;\nSL: nanosleep.u32 64;\nbra.uni SL;\nSD:\n}" :: "r"(sbu - s), "n"(k) : "memory")
__device__ __forceinline__ uint32_t pack2v(float a, float b) { uint32_t d; asm volatile("cvt.rn.bf16x2.f32 %0, %1, %2;" : "=r"(d) : "f"(b), "f"(a)); return d; }
#define FU(x) __float_as_uint(x)
__device__ __forceinline__ uint32_t clk32() { uint32_t t; asm volatile("mov.u32 %0, %%clock;" : "=r"(t) :: "memory"); return t; }
__device__ __forceinline__ void spin_until(uint32_t t0, uint32_t d) {
    if (d) {
#pragma unroll 1
        while (__any_sync(0xffffffffu, clk32() - t0 < d)) {}
    }
}
constexpr int SH_OFF = 229376 + 384;
constexpr uint32_t HONE2 = 0x3c003c00u, HCNT2 = 0x50005000u;

__device__ __forceinline__ uint64_t desc_sw128(uint32_t addr, uint32_t lbo, uint32_t sbo) {
    return (uint64_t)((addr & 0x3FFFF) >> 4) | ((uint64_t)(lbo >> 4) << 16) | ((uint64_t)(sbo >> 4) << 32) | (1ull << 62);
}
#define DP 480
#define NAX 4
#define NXL 2
#define NCX 2
#define NCL 2
#define DC 100
#define DEC 0
#define KXI 5
#define ANB 3
#define BNB 3
#define CNB 3
#define SMA 0x40
#define SMB 0
#define SMC 0x01
#define IVA 0
#define RGA 160
#define RGC 160
#define RGB (504 - RGA - RGC)
#define NRW 8
#define NBR 16
#define E0 0
#define E1 6
#define E2 4
#define E3 8
#define IV 2
#define DEX 0
#define STAG 1
#define VDEP 0
#define NB1 10
#define DB2 40
#define DITHER 0
#define DA 40
#define DB 40
#define DS 200

template <int K> __device__ __forceinline__ void sched(uint32_t key) {
    asm volatile("{\n.reg .pred p;\nsetp.ne.u32 p, %0, %1;\n@p bra.uni SD;\nSL: nanosleep.u32 64;\nbra.uni SL;\nSD:\n}" :: "r"(key), "n"(K) : "memory");
}
__device__ __forceinline__ void sched_i(int i, uint32_t key) {
    if (i == -1) sched<20>(key); if (i == 0) sched<21>(key); if (i == 1) sched<22>(key); if (i == 2) sched<23>(key);
    if (i == 3) sched<24>(key); if (i == 4) sched<25>(key); if (i == 5) sched<26>(key); if (i == 6) sched<27>(key);
}
template <int NB, int SM, class F>
__device__ __forceinline__ void g1(float* q0, float* k0, uint32_t (*wq)[4], uint32_t (*wk)[4], uint32_t ga, uint32_t key, F&& hook) {
    float q1[4], k1[4];
    uint32_t b[NB][4];
#pragma unroll
    for (int i = 0; i < NB; i++) ldsm4(b[i], ga + i * 512);
    hook(-1, b[0]);
    if (SM & 1) sched_i(-1, key);
#pragma unroll
    for (int i = 0; i < 8; i++) {
        uint32_t* c = b[i % NB];
        MMAF(i == 0, q0, wq[2 * i], c[0], c[1]); MMAF(i == 0, k0, wk[2 * i], c[0], c[1]);
        MMAF(i == 0, q1, wq[2 * i + 1], c[2], c[3]); MMAF(i == 0, k1, wk[2 * i + 1], c[2], c[3]);
        const uint32_t cc_[4] = {c[0], c[1], c[2], c[3]};
        if (i + NB < 8) ldsm4(b[i % NB], ga + (i + NB) * 512);
        hook(i, cc_);
        if ((SM >> (i + 1)) & 1) sched_i(i, key);
    }
#pragma unroll
    for (int i = 0; i < 4; i++) { q0[i] += q1[i]; k0[i] += k1[i]; }
}
__device__ __forceinline__ float frag_norm2(uint32_t (*w)[4]) {
    float d0[4], d1[4];
#pragma unroll
    for (int i = 0; i < 32; i++) { MMAF(i == 0, d0, w[i], w[i][0], w[i][2]); MMAF(i == 0, d1, w[i], w[i][1], w[i][3]); }
    const int lane = threadIdx.x & 31, g = lane >> 2, t = lane & 3;
    float v = g == 2 * t ? d0[0] + d1[2] : (g == 2 * t + 1 ? d0[1] + d1[3] : 0.f);
#pragma unroll
    for (int o = 16; o; o >>= 1) v += __shfl_xor_sync(0xffffffffu, v, o);
    return v;
}
__device__ __forceinline__ void load_slot(uint32_t sb, int c, int tile, const Maps& maps) {
    const uint32_t dst = sb + ((tile & 1) ? R_SLOT1 : R_SLOT0), mb = sb + R_BAR + 8 * (MB_FULL0 + (tile & 1));
    mbar_expect_tx(mb, 24576);
    tma2d(dst + 16384, &maps.kx, c * 64, tile * 64, mb);
    tma3d(dst, &maps.vx3, tile * 64, (c >> 1) * 2, mb);
}
__device__ __forceinline__ void put_mem0(uint32_t sb, int W, const bf16* __restrict__ mem0) {
    const int lane = threadIdx.x & 31;
    const uint4 m0 = *(const uint4*)(mem0 + (lane & 7) * DM + (W * 8 + (lane >> 3)) * 8), m1 = *(const uint4*)(mem0 + (lane & 7) * DM + (W * 8 + 4 + (lane >> 3)) * 8);
    bar_sync(3, 256);
    sts128u(sb + R_MEMB + W * 1024 + lane * 16, m0.x, m0.y, m0.z, m0.w);
    sts128u(sb + R_MEMB + W * 1024 + 512 + lane * 16, m1.x, m1.y, m1.z, m1.w);
}
#define GATHER1(HALF)                                                                                           \
        {                                                                                                       \
            float d0[4], d1[4], d2[4], d3[4];                                                                   \
            const uint4 x0 = ldg_rlx4(pm), x1 = ldg_rlx4(pm + AC1); const uint32_t y = ldg_rlx(px);               \
            mma1688hz(d0, x0.x, x0.y, lt.z); mma1688hz(d1, x1.x, x1.y, lt.z);                                   \
            cw = (lt.w & 0x4000u) ? prmt(x0.w, x1.w, 0x7632u) : y;                                              \
            mma1688hz(d2, x0.z, prmt(x0.w, y, lt.w), lt.z); mma1688hz(d3, x1.z, prmt(x1.w, y, lt.w | 0x2200u), lt.z);          \
            stsm4t(rG + R_MEMB + HALF * 4096, pack2(d0[0], d0[1]), pack2(d0[2], d0[3]), pack2(d2[0], d2[1]), pack2(d2[2], d2[3]));       \
            stsm4t(rG + R_MEMB + HALF * 4096 + 512, pack2(d1[0], d1[1]), pack2(d1[2], d1[3]), pack2(d3[0], d3[1]), pack2(d3[2], d3[3])); \
        }
__device__ __forceinline__ uint32_t h2b(uint32_t w) {
    uint32_t d;
    asm("{\n.reg .f16 l, h;\n.reg .f32 a, b;\nmov.b32 {l, h}, %1;\ncvt.f32.f16 a, l;\ncvt.f32.f16 b, h;\ncvt.rn.bf16x2.f32 %0, b, a;\n}" : "=r"(d) : "r"(w));
    return d;
}
#define GATHER2(HALF)                                                                                           \
        {                                                                                                       \
            const uint4 x0 = ldg_rlx4(pm), x1 = ldg_rlx4(pm + AC1); const uint32_t y = ldg_rlx(px);               \
            cw = (lt.w & 0x4000u) ? prmt(x0.w, x1.w, 0x7632u) : y;                                              \
            stsm4t(rG + R_MEMB + HALF * 4096, h2b(x0.x), h2b(x0.y), h2b(x0.z), h2b(prmt(x0.w, y, lt.w)));       \
            stsm4t(rG + R_MEMB + HALF * 4096 + 512, h2b(x1.x), h2b(x1.y), h2b(x1.z), h2b(prmt(x1.w, y, lt.w | 0x2200u))); \
        }
#define GATHER(HALF, PRE, SYNC, AFTER)                                                                                      \
        {                                                                                                       \
            const uint32_t so = aslot(s);                                                                       \
            const uint32_t ua = (glo + acc_off(HALF * 4 + fo, 0)) ^ so, ux = (glo + ext_base(HALF * 4 + fo)) ^ so; \
            uint4 lt;                                                                                           \
            lt.x = lds32v_(rL + R_LT); lt.y = lds32v_(rL + R_LT + 4); lt.z = DEC ? 0 : lds32v_(rL + R_LT + 8); lt.w = lds32v_(rL + R_LT + 12); \
            const uint32_t* pm = mkptr(ua + lt.x, ghi);                                                         \
            const uint32_t* px = mkptr(ux + lt.y, ghi);                                                         \
            PRE                                                                                                 \
            bar_sync(5, 384);                                                                                   \
            const uint32_t t0 = clk32();                                                                        \
            SYNC                                                                                                \
            spin_until(t0, DP + DITHER);                                                                                 \
            TS(11);                                                                                             \
            uint32_t cw, nr = 0;                                                                                \
            _Pragma("unroll 1") do {                                                                            \
                if (DEC) GATHER2(HALF) else GATHER1(HALF)                                                       \
                nr++;                                                                                           \
            } while (__any_sync(0xffffffffu, cw != HCNT2 && nr < SPIN_LIMIT));                                  \
            AFTER                                                                                               \
            CNT2(HALF * 4 + (s & 1) * 2 + (nr > 2), nr > 1);                                                    \
            TS(12);                                                                                             \
        }
#define GOBAR (fo == 3 ? 14 : 10 + fo)

__device__ __forceinline__ void rec_a(uint32_t sb, int c, const bf16* __restrict__ mem0, uint32_t epoch) {
    const int tid = threadIdx.x, lane = tid & 31, f = tid >> 5;
    uint32_t wq[16][4], wk[16][4];
    const int lrow = ((lane >> 4) << 3) + (lane & 7), lsel = (lane >> 3) & 1;
    {
        mbar_wait(sb + R_BAR + 8 * MB_W0, 0);
        if (c == 7 && tid == 0) GT(1421);
        const uint32_t a = sb + R_T + lrow * 128 + (((2 * f + lsel) ^ (lane & 7)) << 4);
#pragma unroll
        for (int kk = 0; kk < 16; kk++) { ldsm4t(wq[kk], a + kk * 2048); ldsm4t(wk[kk], a + 32768 + kk * 2048); }
        if (f == 3) wait_eq4(&g_f.xn[lane * 4], epoch, 13);
        __syncwarp();
        put_mem0(sb, f, mem0);
    }
    const uint32_t rL = opaque(sb + lane * 16), rG = opaque(sb + lane * 16 + f * 1024);
    const uint32_t sbu = uni(sb), fo = uni(f), cc = uni(c);
    const uint64_t gx = xpage();
    const uint32_t ghi = uni((uint32_t)(gx >> 32)), glo = uni((uint32_t)gx);
#pragma unroll
    for (int i = 0; i < NAX; i++) {
        sts128u(rG + R_AX + 4096 * i, wq[i][0], wq[i][1], wq[i][2], wq[i][3]);
        sts128u(rG + R_AX + 4096 * i + 512, wk[i][0], wk[i][1], wk[i][2], wk[i][3]);
    }
    sts128u(rL + R_LT + 512 + f * 512, (sb + R_SREM + (f >= 2 ? lane * 8 + f * 256 : lane * 16 + f * 1024)) ^ 0x01000000u, (sb + R_BAR + 8 * MB_S) ^ 0x01000000u,
            sb + R_QP + (lane >> 4) * 128 + lsel * 512 + (lane & 7) * 16 + (f == 3 ? 2048 : 0), sb + lrow * 128 + ((lsel ^ (lane & 7)) << 4));
    __syncwarp();
    if (tid == 0) GT(c * 8 + 1);
    TSDECL;
    const float cexp = 0.08838834764831845f * 1.4426950408889634f;
    float cs = cexp;
    mbar_wait_u(sbu + R_BAR + 8 * MB_FULL0, 0);
    auto step = [&](int s) -> bool {
        bar_sync(1, 128);
        TS(3);
        float q0[4], k0[4];
        uint32_t kx[4][4];
        uint4 ta;
        const uint32_t ro = ((s & 2) ? R_SLOT1 : R_SLOT0) + (s & 1) * 4096;
        g1<ANB, SMA>(q0, k0, wq, wk, rL + R_MEMB, sbu - s, [&](int i, const uint32_t*) {
            if (i == -1) {
#pragma unroll
                for (int n = NAX - NXL; n < NAX; n++) { lds_fragv(wq[n], rG + R_AX + 4096 * n); lds_fragv(wk[n], rG + R_AX + 4096 * n + 512); }
                ta = lds128uv(rL + R_LT + 512 + fo * 512);
            }
            if (i == KXI) {
#pragma unroll
                for (int kk = 0; kk < 4; kk++)
                    asm volatile("{\n.reg .pred p;\nsetp.lt.u32 p, %5, 2;\nmov.b32 %0, 0;\nmov.b32 %1, 0;\nmov.b32 %2, 0;\nmov.b32 %3, 0;\n"
                                 "@p ldmatrix.sync.aligned.m8n8.x4.shared.b16 {%0,%1,%2,%3}, [%4];\n}"
                                 : "=r"(kx[kk][0]), "=r"(kx[kk][1]), "=r"(kx[kk][2]), "=r"(kx[kk][3]) : "r"((ta.w ^ (kk * 32)) + (ro + 16384 + fo * 2048)), "r"(fo) : "memory");
            }
            if (i == IVA) bar_arrive(GOBAR, 96);
        });
        stsm4t(rG + R_QP, pack2(q0[0], q0[1]), pack2(q0[2], q0[3]), pack2(k0[0], k0[1]), pack2(k0[2], k0[3]));
        TS(4);
        if (fo < 2) {
            bar_sync(3, 256);
            TS(5);
            uint32_t qa[4][4];
#pragma unroll
            for (int kk = 0; kk < 4; kk++) { if (kk == 2) bar_arrive(13, 256); ldsm4(qa[kk], ta.z + kk * 1024); }
            float s0[4], s1[4], s2[4], s3[4];
            MMAZ(s0, qa[0], kx[0][0], kx[0][1]); MMAZ(s1, qa[0], kx[0][2], kx[0][3]);
            MMAZ(s2, qa[1], kx[1][0], kx[1][1]); MMAZ(s3, qa[1], kx[1][2], kx[1][3]);
            MMA(s0, qa[2], kx[2][0], kx[2][1]); MMA(s1, qa[2], kx[2][2], kx[2][3]);
            MMA(s2, qa[3], kx[3][0], kx[3][1]); MMA(s3, qa[3], kx[3][2], kx[3][3]);
            const float x = ((s0[0] + s0[2]) + (s2[0] + s2[2])) * cs, y = ((s0[1] + s0[3]) + (s2[1] + s2[3])) * cs;
            const float z = ((s1[0] + s1[2]) + (s3[0] + s3[2])) * cs, w = ((s1[1] + s1[3]) + (s3[1] + s3[3])) * cs;
            st_async4(ta.x, x, y, z, w, ta.y);
            sts128(rG + R_SLOC, x, y, z, w);
        } else {
            bar_sync(3, 256);
            TS(5);
            uint32_t kb[4], kc[4], qa[4], qc[4];
            ldsm4(kb, ta.z + 256); ldsm4(qa, ta.z); bar_arrive(13, 256); ldsm4(kc, ta.z + 1280); ldsm4(qc, ta.z + 1024);
            const uint32_t k0_ = hadd2b(kb[0], kb[1]), k1_ = hadd2b(kb[2], kb[3]), k2_ = hadd2b(kc[0], kc[1]), k3_ = hadd2b(kc[2], kc[3]);
            float s0[4], s2[4];
            MMAZ(s0, qa, k0_, k1_); MMAZ(s2, qc, k2_, k3_);
            const float x = ((s0[0] + s0[2]) + (s2[0] + s2[2])) * cs, y = ((s0[1] + s0[3]) + (s2[1] + s2[3])) * cs;
            st_async2(ta.x, FU(x), FU(y), ta.y);
            sts64((ta.x ^ 0x01000000u) + (R_SLOC - R_SREM), x, y);
            sts128u(rL + R_STG + (fo & 1) * 512, k0_, k1_, k2_, k3_);
            bar_arrive(9, 192);
        }
        TS(6);
        const uint32_t r8 = (rL + sbu) >> 1;
        uint32_t vt00[4], vt01[4], vt10[4], vt11[4];
        {
            const uint32_t rV = ta.w ^ ((fo & 1) * 64), vo = ro + (fo >> 1) * 8192;
            ldsm4t(vt00, rV + vo); ldsm4t(vt10, (rV ^ 32) + vo); ldsm4t(vt01, rV + vo + 2048); ldsm4t(vt11, (rV ^ 32) + vo + 2048);
        }
        bar_sync(4, 128);
        const float4 l0 = lds128v(rL + R_SLOC), l1 = lds128v(rL + R_SLOC + 1024);
        const float2 l2 = lds64v(r8 + R_SLOC + 512), l3 = lds64v(r8 + R_SLOC + 768);
        if (E2) bar_arrive(15, 256);
        TS(7);
        if (s == NSEG - 1) { mbar_wait_u(sbu + R_BAR + 8 * MB_S, 1); mbar_wait_u(sbu + R_BAR + 8 * MB_V, 1); return true; }
        mbar_wait_p(sbu + R_BAR + 8 * MB_S, s & 1);
        TS(8);
        {
            const float4 r0 = lds128v(rL + R_SREM), r1 = lds128v(rL + R_SREM + 1024);
            const float2 r2 = lds64v(r8 + R_SREM + 512), r3 = lds64v(r8 + R_SREM + 768);
            float sv[10];
            sv[0] = l0.x + r0.x; sv[1] = l0.y + r0.y; sv[2] = l0.z + r0.z; sv[3] = l0.w + r0.w;
            sv[4] = l1.x + r1.x; sv[5] = l1.y + r1.y; sv[6] = l1.z + r1.z; sv[7] = l1.w + r1.w;
            sv[8] = ((l2.x + l3.x) + r2.x) + r3.x; sv[9] = ((l2.y + l3.y) + r2.y) + r3.y;
            float m = fmaxf(fmaxf(fmaxf(sv[0], sv[1]), fmaxf(sv[2], sv[3])), fmaxf(fmaxf(sv[4], sv[5]), fmaxf(sv[6], sv[7])));
            m = fmaxf(m, fmaxf(sv[8], sv[9]));
            {
                const float m1 = __shfl_xor_sync(0xffffffffu, m, 1), m2 = __shfl_xor_sync(0xffffffffu, m, 2), m3 = __shfl_xor_sync(0xffffffffu, m, 3);
                m = fmaxf(fmaxf(m, m1), fmaxf(m2, m3));
            }
            const uint32_t ONE2 = 0x3f803f80u;
            float o0[4], o1[4], sm[4];
            const uint32_t pb0 = pack2(ex2(sv[0] - m), ex2(sv[1] - m)), pb1 = pack2(ex2(sv[2] - m), ex2(sv[3] - m));
            mma16816z(sm, ONE2, ONE2, ONE2, ONE2, pb0, pb1);
            MMAZ(o0, vt00, pb0, pb1); MMAZ(o1, vt10, pb0, pb1);
            const uint32_t z = (VDEP == 0 ? FU(m) : pb0) & (sbu & 8);
            const uint32_t vok = mbar_test(sbu + R_BAR + 8 * MB_V + z, s & 1);
            const uint32_t rv = r8 + vok * 8;
            float2 va = lds64v(rv + R_VB - 8 + fo * 512);
            bar_arrive(13, 256);
            float2 vb = lds64v(rv + R_VB - 8 + fo * 512 + 256);
            float sig = __uint_as_float(lds32v_(sbu + R_MISC + 40));
            const uint32_t pb2 = pack2(ex2(sv[4] - m), ex2(sv[5] - m)), pb3 = pack2(ex2(sv[6] - m), ex2(sv[7] - m));
            mma16816(sm, ONE2, ONE2, ONE2, ONE2, pb2, pb3);
            const uint32_t pb4 = pack2(ex2(sv[8] - m), ex2(sv[9] - m));
            MMA(o0, vt01, pb2, pb3); MMA(o1, vt11, pb2, pb3);
            mma1688(sm, ONE2, ONE2, pb4);
            const float z0 = rcpf(sm[0]), z1 = rcpf(sm[1]);
#define PUT_O()                                                                                                   \
            {                                                                                                     \
                float a0[4] = {o0[0], o0[1], o0[2], o0[3]}, a1[4] = {o1[0], o1[1], o1[2], o1[3]};                 \
                mma1688(a0, FU(va.x), FU(va.y), pb4); mma1688(a1, FU(vb.x), FU(vb.y), pb4);                       \
                const float i0 = z0 * sig, i1 = z1 * sig;                                                         \
                stsm4t(rG + R_QP, pack2(a0[0] * i0, a0[1] * i1), pack2(a0[2] * i0, a0[3] * i1), pack2(a1[0] * i0, a1[1] * i1), pack2(a1[2] * i0, a1[3] * i1)); \
            }
            PUT_O()
            asm volatile("{\n.reg .pred p;\nsetp.ne.u32 p, %0, 0;\n@p bar.arrive 8, 256;\n}" :: "r"(vok) : "memory");
            if (__builtin_expect(__any_sync(0xffffffffu, vok == 0), 0)) {
                mbar_wait_p(sbu + R_BAR + 8 * MB_V, s & 1);
                va = lds64v(r8 + R_VB + fo * 512); vb = lds64v(r8 + R_VB + fo * 512 + 256);
                sig = __uint_as_float(lds32v_(sbu + R_MISC + 40));
                PUT_O()
                bar_arrive(8, 256);
                CNT(8);
            }
            const float r = __uint_as_float(0x7f000000u - FU(sig));
            cs = cexp * r * (fo >= 2 ? r : 1.f);
        }
        TS(10);
        return false;
    };
    step(0);
#pragma unroll 1
    for (int s = 0;; s++) {
        if (s & 1) mbar_wait_p(sbu + R_BAR + 8 * (MB_FULL0 + (((s + 1) >> 1) & 1)), ((s + 1) >> 2) & 1);
        auto early = [&]() {
            SCHED(13);
#pragma unroll
            for (int i = 0; i < NAX - NXL; i++) { lds_fragv(wq[i], rG + R_AX + 4096 * i); lds_fragv(wk[i], rG + R_AX + 4096 * i + 512); }
        };
        GATHER(0, asm volatile("" :: "l"(pm), "l"(px)); early();, , )
        if (step(s + 1)) break;
    }
    CNT(9);
    if (rG == sbu) GT(cc * 8 + 4);
}

__device__ __forceinline__ void rec_b(uint32_t sb, int c, uint32_t epoch) {
    const int tid = threadIdx.x - 128, lane = tid & 31, f = tid >> 5;
    uint32_t wq[16][4], wk[16][4], wo[32][4];
    const int lrow = ((lane >> 4) << 3) + (lane & 7), lsel = (lane >> 3) & 1;
    const uint32_t rL = opaque(sb + lane * 16), rW = opaque(sb + lane * 16 + f * 16384);
    const uint32_t sbu = uni(sb), fo = uni(f), cc = uni(c), po = cc & 1, ep = uni(epoch);
    {
        mbar_wait(sb + R_BAR + 8 * MB_WO, 0);
        if (c == 7 && tid == 0) GT(1426);
        const uint32_t aO = sb + R_WO + f * 16384 + lrow * 128 + ((lsel ^ (lane & 7)) << 4);
#pragma unroll
        for (int i = 0; i < 32; i++) {
            const int tile = STAG ? (i >> 4) * 2 + (i & 1) : i & 3, kk = STAG ? (i >> 1) & 7 : i >> 2;
            ldsm4t(wo[i], (aO ^ (32 * tile)) + kk * 2048);
        }
        const float no = frag_norm2(wo);
        if (lane == 0) sts32(sb + R_MISC + 80 + f * 4, FU(no));
        __syncwarp();
        bar_arrive(15, 256);
#pragma unroll
        for (int i = NRW; i < 32; i++) sts128u(rW + R_WO + i * 512, wo[i][0], wo[i][1], wo[i][2], wo[i][3]);
        mbar_wait(sb + R_BAR + 8 * MB_W1, 0);
        if (c == 7 && tid == 0) GT(1422);
        if (tid == 0) stg_rlx(&g_f.rload[c], epoch);
        __syncwarp();
        const uint32_t a = sb + R_QK1 + lrow * 128 + (((2 * f + lsel) ^ (lane & 7)) << 4);
#pragma unroll
        for (int kk = 0; kk < 16; kk++) { ldsm4t(wq[kk], a + kk * 2048); ldsm4t(wk[kk], a + 32768 + kk * 2048); }
        bar_sync(13, 128);
#pragma unroll
        for (int i = 0; i < 16; i++) {
            sts128u(rW + R_QK1 + i * 1024, wq[i][0], wq[i][1], wq[i][2], wq[i][3]);
            sts128u(rW + R_QK1 + i * 1024 + 512, wk[i][0], wk[i][1], wk[i][2], wk[i][3]);
        }
        __syncwarp();
    }
    const uint64_t gx = xpage();
    const uint32_t ghi = uni((uint32_t)(gx >> 32)), glo = uni((uint32_t)gx);
    TSDECL;
#pragma unroll 1
    for (int s = 0;; s++) {
        bar_sync(2, 256);
        TS(3);
        float q0[4], k0[4];
        g1<BNB, SMB>(q0, k0, wq, wk, rL + R_MEMB + 4096, sbu - s, [&](int i, const uint32_t*) {
            if (i >= 2 && i < 6) {
#pragma unroll
                for (int n = NRW + (i - 2) * E0 / 4; n < NRW + (i - 1) * E0 / 4; n++) lds_fragv(wo[n], rW + R_WO + n * 512);
            }
            if (i == IV) bar_arrive(GOBAR, 96);
        });
        stsm4t(rL + fo * 1024 + R_QP + 512, pack2(q0[0], q0[1]), pack2(q0[2], q0[3]), pack2(k0[0], k0[1]), pack2(k0[2], k0[3]));
        bar_arrive(3, 256);
        TS(4);
        const uint32_t so = aslot(s);
        const uint4 lt = lds128uv(rL + R_LT);
        uint32_t* pm = (uint32_t*)mkptr(((glo + acc_off(po * 4 + fo, 0)) ^ so) + lt.x, ghi);
        uint32_t* px = (uint32_t*)mkptr(((glo + ext_base(po * 4 + fo)) ^ so) + lt.y, ghi);
        bar_sync(13, 256);
#pragma unroll
        for (int n = NRW + E0; n < NRW + E0 + E1; n++) lds_fragv(wo[n], rW + R_WO + n * 512);
        if (E2) bar_sync(15, 256);
        if (s == NSEG - 1) break;
        TS(5);
#pragma unroll
        for (int n = NRW + E0 + E1; n < NRW + E0 + E1 + E2; n++) lds_fragv(wo[n], rW + R_WO + n * 512);
        bar_sync(13, 256);
#pragma unroll
        for (int n = NRW + E0 + E1 + E2; n < NRW + E0 + E1 + E2 + E3; n++) lds_fragv(wo[n], rW + R_WO + n * 512);
        SCHED(4);
        TS(6);
        bar_sync(8, 256);
        TS(7);
        {
            float o[4][4];
            uint32_t b[4][4];
#pragma unroll
            for (int i = 0; i < 4; i++) ldsm4(b[i], rL + R_QP + i * 1024);
#pragma unroll
            for (int n = NRW + E0 + E1 + E2 + E3; n < 32; n++) lds_fragv(wo[n], rW + R_WO + n * 512);
            float p[4][4];
#define G2_STEP(o, hf, kk) _Pragma("unroll") for (int i = 0; i < 2; i++) MMAF((kk) < 2, o[((kk) & 1) * 2 + i], wo[(hf) * 16 + (kk) * 2 + i], b[(kk) >> 1][((kk) & 1) * 2], b[(kk) >> 1][((kk) & 1) * 2 + 1])
#define G2_RED(o, wl, ptr) const uint32_t wl = packh2(o[1][2] + o[3][2], o[1][3] + o[3][3]);                          \
                asm volatile("red.relaxed.gpu.global.add.noftz.v4.f16x2 [%0], {%1,%2,%3,%4};" :: "l"(ptr),           \
                    "r"(packh2(o[0][0] + o[2][0], o[0][1] + o[2][1])), "r"(packh2(o[0][2] + o[2][2], o[0][3] + o[2][3])), \
                    "r"(packh2(o[1][0] + o[3][0], o[1][1] + o[3][1])), "r"(prmt(wl, HONE2, lt.w)) : "memory")
#pragma unroll
            for (int kk = 0; kk < 8; kk++) { G2_STEP(o, 0, kk); }
            SCHED(11);
#pragma unroll
            for (int kk = 0; kk < 4; kk++) { G2_STEP(p, 1, kk); }
            G2_RED(o, w3, pm);
            SCHED(12);
#pragma unroll
            for (int kk = 4; kk < 8; kk++) { G2_STEP(p, 1, kk); }
            G2_RED(p, w7, pm + AC1);
            asm volatile("red.relaxed.gpu.global.add.noftz.f16x2 [%0], %1;" :: "l"(px), "r"((lt.w & 0x4000u) ? prmt(w3, w7, 0x7632u) : HONE2) : "memory");
        }
        bar_arrive(5, 384);
        asm volatile("{\n.reg .pred p;\nsetp.eq.u32 p, %0, %1;\n@p mbarrier.arrive.expect_tx.shared::cta.b64 _, [%2], 1536;\n}"
                     :: "r"(rW), "r"(sbu), "r"(sbu + R_BAR + 8 * MB_S) : "memory");
        const uint32_t tb = clk32();
        spin_until(tb, DB);
        TS(8);
#pragma unroll
        for (int i = 0; i < NBR; i++) {
            if (i == NB1) {
                if (fo == 1 && (s & 1)) {
                    bar_sync(0, 64);
                    if (rL == sbu) st_rel(&g_f.rec[cc], (ep << 8) | (s + 1));
                    __syncwarp();
                }
                spin_until(tb, DP + DB2);
            }
            lds_fragv(wq[i], rW + R_QK1 + i * 1024); lds_fragv(wk[i], rW + R_QK1 + i * 1024 + 512);
        }
        TS(9);
    }
}

#undef lds_fragv
__device__ __forceinline__ void rec_first_loads(uint32_t sb, int c, const Maps& maps) {
    const uint32_t bar = sb + R_BAR;
    const int F0 = c * 64;
    mbar_expect_tx(bar + 8 * MB_W0, 65536); mbar_expect_tx(bar + 8 * MB_WO, 65536); mbar_expect_tx(bar + 8 * MB_WV, 65536);
    tma2d(sb + R_QK1, &maps.wv, F0, 0, bar + 8 * MB_WV); tma2d(sb + R_QK1 + 32768, &maps.wv, F0, 256, bar + 8 * MB_WV);
    for (int i = 0; i < 4; i++) tma2d(sb + R_WO + i * 16384, &maps.wo, (c & 1) * 256 + i * 64, (c >> 1) * 128, bar + 8 * MB_WO);
    tma2d(sb + R_T + 32768, &maps.wk, F0, 0, bar + 8 * MB_W0); tma2d(sb + R_T, &maps.wq, F0, 0, bar + 8 * MB_W0);
    mbar_expect_tx(bar + 8 * MB_S, 1536);
}
__device__ __forceinline__ void rec_c(uint32_t sb, int c, const bf16* __restrict__ mem0, const Maps& maps, uint32_t epoch) {
    const int tid = threadIdx.x - 256, lane = tid & 31, u = tid >> 5;
    const uint32_t bar = sb + R_BAR;
    const int lrow = ((lane >> 4) << 3) + (lane & 7), lsel = (lane >> 3) & 1;
    const int kh = u >> 1, j = u & 1;
    uint32_t wv[32][4];
    {
        if (u == 0) {
            sts128u(sb + lane * 16 + R_LT, acc_off(0, lane), ext_lane(lane),
                    ((lane >> 2) == 2 * (lane & 3) ? 0x3c00u : 0u) | ((lane >> 2) == 2 * (lane & 3) + 1 ? 0x3c000000u : 0u), (lane & 1) ? 0x5410u : 0x3210u);
        }
        mbar_wait(bar + 8 * MB_WV, 0);
        if (c == 7 && tid == 0) GT(1425);
        const uint32_t aa = sb + R_QK1 + (kh * 256 + lrow) * 128 + (((4 * j + 2 * kh + lsel) ^ (lane & 7)) << 4);
#pragma unroll
        for (int kk = 0; kk < 16; kk++) { ldsm4t(wv[kk], aa + kk * 2048); ldsm4t(wv[16 + kk], (aa ^ 32) + kk * 2048); }
        bar_sync(9, 128);
        if (tid == 0) {
            asm volatile("fence.proxy.async.shared::cta;" ::: "memory");
            mbar_expect_tx(bar + 8 * MB_W1, 65536);
            tma2d(sb + R_QK1 + 32768, &maps.wk, c * 64, 256, bar + 8 * MB_W1); tma2d(sb + R_QK1, &maps.wq, c * 64, 256, bar + 8 * MB_W1);
        }
        __syncwarp();
        const float nv = frag_norm2(wv);
        if (lane == 0) sts32(sb + R_MISC + 64 + u * 4, FU(nv));
        if (tid == 96) { wait_eq2(&g_f.kv[0][c >> 1][0], epoch, 6); load_slot(sb, c, 0, maps); }
        __syncwarp();
        bar_sync(15, 256);
        if (u == 0) {
            if (lane == 0) {
                const float4 a = lds128(sb + R_MISC + 64), b = lds128(sb + R_MISC + 80);
                stg4(&g_f.norm[c], make_uint4(FU((a.x + a.y) + (a.z + a.w)), epoch, FU((b.x + b.y) + (b.z + b.w)), epoch));
            }
            __syncwarp();
            uint4 r, q; uint32_t n = 0;
#pragma unroll 1
            while (true) {
                r = ldg_rlx4((const uint32_t*)&g_f.norm[lane]); q = ldg_rlx4((const uint32_t*)&g_f.norm[lane + 32]);
                if (__all_sync(0xffffffffu, r.y == epoch && r.w == epoch && q.y == epoch && q.w == epoch)) break;
                __nanosleep(32);
                if (++n > SPIN_LIMIT) { ABORT(5); break; }
            }
            float nv2 = __uint_as_float(r.x) + __uint_as_float(q.x), no = __uint_as_float(r.z) + __uint_as_float(q.z);
#pragma unroll
            for (int o = 16; o; o >>= 1) { nv2 += __shfl_xor_sync(0xffffffffu, nv2, o); no += __shfl_xor_sync(0xffffffffu, no, o); }
            const int lc = ((int)(FU(nv2) >> 23) + (int)(FU(no) >> 23) - 252 + 9 + 1) >> 1;
            if (lane == 0) sts32(sb + R_MISC + 16, 140 - lc);
        }
        __syncwarp();
        put_mem0(sb, 4 + u, mem0);
    }
    const uint32_t rL = opaque(sb + lane * 16), rG = opaque(sb + lane * 16 + u * 1024);
    const uint32_t sbu = uni(sb), fo = uni(u), cc = uni(c), ep = uni(epoch);
    const uint64_t gx = xpage();
    const uint32_t ghi = uni((uint32_t)(gx >> 32)), glo = uni((uint32_t)gx);
    constexpr int CX = R_AX + NAX * 4096;
    static_assert(NAX + NCX <= 6, "AX");
#pragma unroll
    for (int i = 0; i < NCX; i++) {
        sts128u(rG + CX + 4096 * i, wv[i][0], wv[i][1], wv[i][2], wv[i][3]);
        sts128u(rG + CX + 4096 * i + 512, wv[16 + i][0], wv[16 + i][1], wv[16 + i][2], wv[16 + i][3]);
    }
    __syncwarp();
    TSDECL;
    uint32_t rpb = 0x3f800000u;
    bar_arrive(2, 256);
#pragma unroll 1
    for (int s = 0;; s++) {
        spin_until(clk32(), DC);
#pragma unroll
        for (int i = NCX - NCL; i < NCX; i++) { lds_fragv(wv[i], rG + CX + 4096 * i); lds_fragv(wv[16 + i], rG + CX + 4096 * i + 512); }
        bar_sync(GOBAR, 96);
        TS(3);
        float v0[4], v1[4];
        uint32_t mx, my;
        g1<CNB, SMC>(v0, v1, wv, wv + 16, rL + R_MEMB + (fo >> 1) * 4096, sbu - s, [&](int i, const uint32_t* c_) {
            if (i >= 0) {
                mx = amax2b(i == 0 ? c_[0] : amax2b(mx, c_[0]), c_[1]);
                my = amax2b(i == 0 ? c_[2] : amax2b(my, c_[2]), c_[3]);
            }
        });
        TS(4);
        const uint32_t l16 = (rL ^ sbu) | (lds32v_(rL + R_LT + 4) & 1);
        const uint32_t r8 = sbu + (l16 >> 1);
        {
            sts128(rL + R_VRED + fo * 512, v1[0], v1[1], v1[2], v1[3]);
            const uint32_t d = r8 + R_VB + ((cc & 1) * 4 + (fo & 1) * 2 + (fo >> 1)) * 256;
            const uint32_t dr = xorv(d, 0x01000000u), br = xorv(sbu + R_BAR + 8 * MB_V, 0x01000000u);
            bar_sync(6 + (fo & 1), 64);
            const float4 a0 = lds128(rL + R_VRED + (fo ^ 2) * 512);
            const float rp = __uint_as_float(rpb);
            const uint32_t w0 = pack2((v0[0] + a0.x) * rp, (v0[1] + a0.y) * rp), w1 = pack2((v0[2] + a0.z) * rp, (v0[3] + a0.w) * rp);
            st_async2(dr, w0, w1, br);
            sts64(d, __uint_as_float(w0), __uint_as_float(w1));
            mx = amax2b(mx, my);
            mx = __reduce_max_sync(0xffffffffu, amax2b(mx, mx << 16) & 0x7f800000u);
            if (fo == 2) { sts32(sbu + R_MISC + 8, mx); bar_arrive(6, 64); }
            if (fo == 0) {
                bar_sync(6, 64);
                const int em = (int)(max(mx, lds32v_(sbu + R_MISC + 8)) >> 23) + (int)(rpb >> 23) - 127;
                const int es = min(max((int)lds32v_(sbu + R_MISC + 16) - max(em, 127), -60), 60);
                sts32(sbu + R_MISC + 40, (127 + es) << 23);
            }
            __syncwarp();
            asm volatile("{\n.reg .pred p;\nsetp.eq.u32 p, %0, %1;\n@p mbarrier.arrive.expect_tx.shared::cta.b64 _, [%2], 256;\n}"
                         :: "r"(rL), "r"(sbu), "r"(sbu + R_BAR + 8 * MB_V) : "memory");
        }
        TS(5);
        if (fo == 1) {
            bar_sync(9, 192);
            uint8_t* dst = (uint8_t*)&g_KVf[s][cc >> 1][(cc & 1) * 256] + l16;
            const uint32_t r2 = prmt(rpb, 0, 0x3232u);
#pragma unroll
            for (int i = 0; i < 2; i++) {
                const uint4 a = lds128uv(rL + R_STG + i * 512);
                stg4(dst + i * 512, make_uint4(hmul2b(a.x, r2), hmul2b(a.y, r2), hmul2b(a.z, r2), hmul2b(a.w, r2)));
                const float2 b0 = lds64v(r8 + R_VB + (cc & 1) * 1024 + i * 512), b1 = lds64v(r8 + R_VB + (cc & 1) * 1024 + i * 512 + 256);
                stg4(dst + 2048 + i * 512, make_uint4(FU(b0.x), FU(b0.y), FU(b1.x), FU(b1.y)));
            }
            __syncwarp();
            if (s == NSEG - 1) {
                if (l16 == 0) { st_rel(&g_f.rec[cc], (ep << 8) | NSEG); GT(1500 + cc); }
            } else if (s & 1) bar_arrive(0, 64);
            __syncwarp();
        } else {
            bar_arrive(9, 192);
            if (fo == 2) {
                if (l16 < 272) stg4((void*)mkptr((glo + zero_off(cc, l16 >> 4)) ^ aslot(s + 4), ghi), make_uint4(0, 0, 0, 0));
                __syncwarp();
            } else if (fo == 3) {
                if (((s & 1) || s == 0) && s + 3 < NSEG) {
                    const uint32_t* fp = &g_f.kv[(s + 3) >> 1][cc >> 1][0];
                    uint32_t n = 0;
#pragma unroll 1
                    while (true) {
                        const uint2 v = ldg_rlx2(fp);
                        if (__all_sync(0xffffffffu, v.x == ep && v.y == ep)) break;
                        __nanosleep(64);
                        if (++n > SPIN_LIMIT) { ABORT(6); break; }
                    }
                }
                if (!(s & 1) && s + 2 < NSEG) {
                    if (s == 0) asm volatile("fence.proxy.async.shared::cta;" ::: "memory");
                    if (l16 == 0) load_slot(sbu, cc, (s + 2) >> 1, maps);
                    __syncwarp();
                }
            }
        }
        TS(6);
        if (s == NSEG - 1) break;
        auto early = [&]() {
#pragma unroll
            for (int i = 0; i < NCX - NCL; i++) { lds_fragv(wv[i], rG + CX + 4096 * i); lds_fragv(wv[16 + i], rG + CX + 4096 * i + 512); }
        };
        GATHER(1, , early(); rpb = 0x7f000000u - lds32v_(sbu + R_MISC + 40);, bar_arrive(2, 256);)
    }
}

__device__ __forceinline__ bool cand_better(float v, int i, float bv, int bi) { return v > bv || (v == bv && i < bi); }
constexpr int F_WG = 0, F_WU = 32768, F_WD = 65536, F_X = 98304, F_RED = F_X + 4096, F_ACT = F_RED + 8192, F_SEL = F_ACT + 256;

__device__ __noinline__ void ffn_phase(const Maps& maps, const bf16* __restrict__ wd, bf16* __restrict__ out) {
    extern __shared__ __align__(1024) uint8_t smem[];
    const uint32_t sb = smem_u32(smem);
    const int c = ((volatile int*)(smem + SH_OFF))[8];
    const uint32_t epoch = ((volatile uint32_t*)(smem + SH_OFF))[9];
    const int tid = threadIdx.x;
    constexpr int NWK = FF / 32;
    const bool worker = c < NWK;
    bar_sync(0, 384);
    const uint32_t mb = sb + R_BAR + 8 * MB_W0;
    if (tid == 32 && worker) {
        asm volatile("fence.proxy.async.shared::cta;" ::: "memory");
        mbar_expect_tx(mb, 98304);
        tma2d(sb + F_WG, &maps.wg, c * 32, 0, mb); tma2d(sb + F_WG + 16384, &maps.wg, c * 32, 256, mb);
        tma2d(sb + F_WU, &maps.wu, c * 32, 0, mb); tma2d(sb + F_WU + 16384, &maps.wu, c * 32, 256, mb);
        asm volatile("cp.async.bulk.shared::cluster.global.mbarrier::complete_tx::bytes [%0], [%1], %2, [%3];"
            :: "r"(sb + F_WD), "l"(wd + (size_t)c * 32 * DM), "r"(32768), "r"(mb) : "memory");
    }
    int p0 = -1, p1 = -1;
#pragma unroll 1
    for (int pass = 0; pass < 2; pass++) {
        if (tid < 32) {
            const uint32_t tag = epoch & 0xfffffu;
            uint4 r, q; uint32_t n = 0;
            const int t2 = tid + 32 < NFW ? tid + 32 : tid;
#pragma unroll 1
            while (true) {
                r = ldg_rlx4((const uint32_t*)&g_f.cand[pass][tid]); q = ldg_rlx4((const uint32_t*)&g_f.cand[pass][t2]);
                if (__all_sync(0xffffffffu, (r.y >> 12) == tag && (r.w >> 12) == tag && (q.y >> 12) == tag && (q.w >> 12) == tag)) break;
                __nanosleep(32);
                if (++n > SPIN_LIMIT) { ABORT(7); break; }
            }
            float b0 = __uint_as_float(r.x), b1 = __uint_as_float(r.z); int i0 = r.y & 4095, i1 = r.w & 4095;
            if (t2 != tid) {
                float c0 = __uint_as_float(q.x), c1 = __uint_as_float(q.z); int j0 = q.y & 4095, j1 = q.w & 4095;
                if (cand_better(c0, j0, b0, i0)) {
                    if (cand_better(c1, j1, b0, i0)) { b1 = c1; i1 = j1; } else { b1 = b0; i1 = i0; }
                    b0 = c0; i0 = j0;
                } else if (cand_better(c0, j0, b1, i1)) { b1 = c0; i1 = j0; }
            }
#pragma unroll
            for (int o = 16; o; o >>= 1) {
                float c0 = __shfl_xor_sync(0xffffffffu, b0, o), c1 = __shfl_xor_sync(0xffffffffu, b1, o);
                int j0 = __shfl_xor_sync(0xffffffffu, i0, o), j1 = __shfl_xor_sync(0xffffffffu, i1, o);
                if (cand_better(c0, j0, b0, i0)) {
                    if (cand_better(c1, j1, b0, i0)) { b1 = c1; i1 = j1; } else { b1 = b0; i1 = i0; }
                    b0 = c0; i0 = j0;
                } else if (cand_better(c0, j0, b1, i1)) { b1 = c0; i1 = j0; }
            }
            i0 = min(i0, SQ - 1); i1 = min(i1, SQ - 1);
            if (i0 != p0 || i1 != p1) {
                n = 0;
#pragma unroll 1
                while (!__all_sync(0xffffffffu, ldg_rlx(&g_f.rows[pass][tid]) == epoch && ldg_rlx(&g_f.rows[pass][t2]) == epoch)) { __nanosleep(32); if (++n > SPIN_LIMIT) { ABORT(7); break; } }
            }
            int* sel = (int*)(smem + F_SEL);
            if (pass && tid == 0) GT(c * 8 + 5);
            if (tid == 0) { sel[0] = i0; sel[1] = i1; ((float*)sel)[2] = b0; ((float*)sel)[3] = b1; }
        }
        bar_sync(0, 384);
        const int t0 = ((int*)(smem + F_SEL))[0], t1 = ((int*)(smem + F_SEL))[1];
        if (c == 3 && tid == 0 && pass == 0) GT(1430);
        if (t0 == p0 && t1 == p1) break;
        const uint32_t ytag = epoch * 2 + pass + 1;
        if (worker) {
            float2* xs = (float2*)(smem + F_X);
            if (tid < 256) {
                uint32_t a = __ldcg((const uint32_t*)(g_hn + (size_t)t0 * DM) + tid), b = __ldcg((const uint32_t*)(g_hn + (size_t)t1 * DM) + tid);
                *(float4*)(xs + tid * 2) = make_float4(bf_lo(a), bf_lo(b), bf_hi(a), bf_hi(b));
            }
            mbar_wait(mb, 1);
            if (c == 3 && tid == 0 && pass == 0) GT(1431);
            bar_sync(0, 384);
            float4* red = (float4*)(smem + F_RED);
            if (tid < 256) {
                const int cp = tid & 31, kg = tid >> 5;
                const uint32_t* wp = (const uint32_t*)(smem + (cp < 16 ? F_WG : F_WU)) + (cp & 15);
                float a0 = 0.f, a1 = 0.f, b0 = 0.f, b1 = 0.f;
#pragma unroll 16
                for (int k = kg * 64; k < kg * 64 + 64; k++) {
                    uint32_t w = wp[k * 16]; float2 x = xs[k];
                    a0 = fmaf(x.x, bf_lo(w), a0); a1 = fmaf(x.x, bf_hi(w), a1); b0 = fmaf(x.y, bf_lo(w), b0); b1 = fmaf(x.y, bf_hi(w), b1);
                }
                red[kg * 32 + cp] = make_float4(a0, a1, b0, b1);
            }
            bar_sync(0, 384);
            float2* act = (float2*)(smem + F_ACT);
            if (tid < 64) {
                const int f = tid & 31, tk = tid >> 5;
                const float* r = (const float*)red + (f >> 1) * 4 + tk * 2 + (f & 1);
                float gsum = 0.f, usum = 0.f;
#pragma unroll
                for (int kg = 0; kg < 8; kg++) { gsum += r[kg * 128]; usum += r[kg * 128 + 64]; }
                gsum = rbf(gsum); usum = rbf(usum);
                float sg = rbf(gsum / (1.f + __expf(-gsum)));
                ((float*)act)[f * 2 + tk] = rbf(sg * usum);
            }
            bar_sync(0, 384);
            if (tid < 256) {
                const uint32_t* wp = (const uint32_t*)(smem + F_WD) + tid;
                float a0 = 0.f, a1 = 0.f, b0 = 0.f, b1 = 0.f;
#pragma unroll 16
                for (int f = 0; f < 32; f++) {
                    uint32_t w = wp[f * 256]; float2 x = act[f];
                    a0 = fmaf(x.x, bf_lo(w), a0); a1 = fmaf(x.x, bf_hi(w), a1); b0 = fmaf(x.y, bf_lo(w), b0); b1 = fmaf(x.y, bf_hi(w), b1);
                }
                asm volatile("st.relaxed.gpu.global.v4.b32 [%0], {%1,%2,%3,%2};" :: "l"(&g_yp[pass][c][tid]), "r"(FU(a0)), "r"(ytag), "r"(FU(a1)) : "memory");
                asm volatile("st.relaxed.gpu.global.v4.b32 [%0], {%1,%2,%3,%2};" :: "l"(&g_yp[pass][c][256 + tid]), "r"(FU(b0)), "r"(ytag), "r"(FU(b1)) : "memory");
            }
            if (c == 3 && tid == 0 && pass == 0) GT(1432);
        } else {
            const int r = c - NWK, j = tid & 63, part = tid >> 6, tk = r >> 2, dp = (r & 3) * 64 + j;
            const int tok = tk ? t1 : t0, old = tk ? p1 : p0;
            uint32_t hw = 0, nw = 0;
            if (part == 0) {
                hw = __ldcg((const uint32_t*)(g_h + (size_t)tok * DM) + dp); nw = __ldcg((const uint32_t*)(g_hn + (size_t)tok * DM) + dp);
                if (old >= 0 && old != t0 && old != t1) {
                    uint32_t ho = __ldcg((const uint32_t*)(g_h + (size_t)old * DM) + dp), no = __ldcg((const uint32_t*)(g_hn + (size_t)old * DM) + dp);
                    ((uint32_t*)(out + (size_t)old * DM))[dp] = pack2(bf_lo(ho) + bf_lo(no), bf_hi(ho) + bf_hi(no));
                }
            }
            float s0 = 0.f, s1 = 0.f;
            uint4 v[10]; uint32_t n = 0;
            bool ok;
#pragma unroll 1
            do {
                ok = true;
#pragma unroll
                for (int i = 0; i < 10; i++) {
                    const int src = part + 6 * i;
                    v[i] = src < NWK ? ldg_rlx4((const uint32_t*)&g_yp[pass][src][tk * 256 + dp]) : make_uint4(0, ytag, 0, ytag);
                }
#pragma unroll
                for (int i = 0; i < 10; i++) ok = ok && v[i].y == ytag && v[i].w == ytag;
                if (!ok) __nanosleep(100);
                if (++n > SPIN_LIMIT) { ABORT(7); break; }
            } while (!ok);
#pragma unroll
            for (int i = 0; i < 10; i++) { s0 += __uint_as_float(v[i].x); s1 += __uint_as_float(v[i].z); }
            float2* red = (float2*)(smem + F_RED);
            red[part * 64 + j] = make_float2(s0, s1);
            bar_sync(0, 384);
            if (part == 0) {
#pragma unroll
                for (int i = 1; i < 6; i++) { float2 q = red[i * 64 + j]; s0 += q.x; s1 += q.y; }
                const float rs = rbf(1.f / (1.f + __expf(-((float*)(smem + F_SEL))[2 + tk])));
                const float y0 = rbf(rbf(s0) * rs), y1 = rbf(rbf(s1) * rs);
                ((uint32_t*)(out + (size_t)tok * DM))[dp] = pack2(bf_lo(hw) + rbf(bf_lo(nw) + y0), bf_hi(hw) + rbf(bf_hi(nw) + y1));
            }
            if (tid == 0 && pass == 0 && r == 0) GT(1434);
        }
        p0 = t0; p1 = t1;
        if (c == 3 && tid == 0 && pass == 0) GT(1433);
        bar_sync(0, 384);
    }
}

constexpr int G_W = 0;
constexpr int G_RING = 131072;
constexpr int G_BUF = 163840;
constexpr int G_BAR = 229376;
constexpr int G_SMEM = G_BAR + 512;
enum { GB_W0 = 0, GB_W1, GB_WFREE, GB_FULL, GB_EMPTY = GB_FULL + 8, GB_KV = GB_EMPTY + 8, GB_STG = GB_KV + 2, GB_FREE = GB_STG + 2, GB_XN = GB_FREE + 2, GB_RL, GB_KVF, GB_N };
constexpr int SMEM_TOTAL = 232448;

__device__ __forceinline__ void wgmma_n128(float* d, uint64_t da, uint64_t db, int scale_d) {
    asm volatile("{\n.reg .pred p;\nsetp.ne.b32 p, %66, 0;\n"
        "wgmma.mma_async.sync.aligned.m64n128k16.f32.bf16.bf16 "
        "{%0,%1,%2,%3,%4,%5,%6,%7,%8,%9,%10,%11,%12,%13,%14,%15,%16,%17,%18,%19,%20,%21,%22,%23,%24,%25,%26,%27,%28,%29,%30,%31,"
        "%32,%33,%34,%35,%36,%37,%38,%39,%40,%41,%42,%43,%44,%45,%46,%47,%48,%49,%50,%51,%52,%53,%54,%55,%56,%57,%58,%59,%60,%61,%62,%63}, "
        "%64, %65, p, 1, 1, 0, 1;\n}"
        : "+f"(d[0]), "+f"(d[1]), "+f"(d[2]), "+f"(d[3]), "+f"(d[4]), "+f"(d[5]), "+f"(d[6]), "+f"(d[7]), "+f"(d[8]), "+f"(d[9]), "+f"(d[10]), "+f"(d[11]),
          "+f"(d[12]), "+f"(d[13]), "+f"(d[14]), "+f"(d[15]), "+f"(d[16]), "+f"(d[17]), "+f"(d[18]), "+f"(d[19]), "+f"(d[20]), "+f"(d[21]), "+f"(d[22]), "+f"(d[23]),
          "+f"(d[24]), "+f"(d[25]), "+f"(d[26]), "+f"(d[27]), "+f"(d[28]), "+f"(d[29]), "+f"(d[30]), "+f"(d[31]), "+f"(d[32]), "+f"(d[33]), "+f"(d[34]), "+f"(d[35]),
          "+f"(d[36]), "+f"(d[37]), "+f"(d[38]), "+f"(d[39]), "+f"(d[40]), "+f"(d[41]), "+f"(d[42]), "+f"(d[43]), "+f"(d[44]), "+f"(d[45]), "+f"(d[46]), "+f"(d[47]),
          "+f"(d[48]), "+f"(d[49]), "+f"(d[50]), "+f"(d[51]), "+f"(d[52]), "+f"(d[53]), "+f"(d[54]), "+f"(d[55]), "+f"(d[56]), "+f"(d[57]), "+f"(d[58]), "+f"(d[59]),
          "+f"(d[60]), "+f"(d[61]), "+f"(d[62]), "+f"(d[63])
        : "l"(da), "l"(db), "r"(scale_d));
}

__device__ __forceinline__ constexpr uint32_t slot_off(int slot) {
    return slot < 2 ? G_RING + slot * 16384 : G_BUF + (slot - 2) * 32768 + 16384;
}
template <int NSLOT>
__device__ __forceinline__ void gemm_tile(float* acc, uint32_t sb, int tile, int it, bool first, uint32_t wpar, int wg, bool pass, uint32_t l0) {
    const uint32_t bar = sb + G_BAR;
    bar_sync(3 + wg, 256);
    int prev = 0;
#pragma unroll
    for (int k = 0; k < 4; k++) {
        const int n = tile * 4 + k, slot = NSLOT == 4 ? k : n % 3;
        const uint32_t sz = sb + (((it + k) << 4) & sb & 0x3f0);
        const uint64_t da = desc_sw128(sz + slot_off(slot), 16, 1024), db0 = desc_sw128(sz + G_W, 65536, 1024);
        if ((k & 1) == 0 && first) mbar_wait_u(bar + 8 * (GB_W0 + (k >> 1)), wpar);
        mbar_wait_u(bar + 8 * (GB_FULL + slot), NSLOT == 4 ? (tile & 1) : ((n / 3) & 1));
        if (k == 3 && pass) bar_arrive(3 + (wg ^ 1), 256);
        asm volatile("wgmma.fence.sync.aligned;" ::: "memory");
#pragma unroll
        for (int kk = 0; kk < 4; kk++) wgmma_n128(acc, da + kk * 2, db0 + k * 1024 + kk * 128, (k | kk) != 0);
        asm volatile("wgmma.commit_group.sync.aligned;" ::: "memory");
        if (k > 0) {
            asm volatile("wgmma.wait_group.sync.aligned 1;" ::: "memory");
            mbar_arrive_if(bar + 8 * (GB_EMPTY + prev), l0);
        }
#pragma unroll
        for (int kk = 0; kk < 4; kk++) wgmma_n128(acc, da + 512 + kk * 2, db0 + k * 1024 + 512 + kk * 128, 1);
        asm volatile("wgmma.commit_group.sync.aligned;" ::: "memory");
        prev = slot;
    }
    asm volatile("wgmma.wait_group.sync.aligned 0;" ::: "memory");
    mbar_arrive_if(bar + 8 * (GB_EMPTY + prev), l0);
}
__device__ __forceinline__ void stage_bf16(const float* acc, uint32_t buf, float s0, float s1) {
    const int lane = threadIdx.x & 31, wq = (threadIdx.x >> 5) & 3;
    const int row = wq * 16 + (lane & 7) + ((lane >> 3) & 1) * 8;
    const uint32_t base = buf + row * 128;
#pragma unroll
    for (int j = 0; j < 16; j += 2) {
        const int ch = (j & 7) + (lane >> 4);
        stsm4(base + (j >> 3) * 8192 + ((ch ^ (row & 7)) << 4),
              pack2(acc[4 * j] * s0, acc[4 * j + 1] * s0), pack2(acc[4 * j + 2] * s1, acc[4 * j + 3] * s1),
              pack2(acc[4 * j + 4] * s0, acc[4 * j + 5] * s0), pack2(acc[4 * j + 6] * s1, acc[4 * j + 7] * s1));
    }
}

template <int ACC>
__device__ __forceinline__ void wgmma_rs64(float* d, const uint32_t* a, uint64_t db) {
    asm volatile("{\n.reg .pred p;\nsetp.ne.b32 p, %37, 0;\n"
        "wgmma.mma_async.sync.aligned.m64n64k16.f32.bf16.bf16 {%0,%1,%2,%3,%4,%5,%6,%7,%8,%9,%10,%11,%12,%13,%14,%15,%16,%17,%18,%19,%20,%21,%22,%23,%24,%25,%26,%27,%28,%29,%30,%31}, {%32,%33,%34,%35}, %36, p, 1, 1, 0;\n}"
        : "+f"(d[0]), "+f"(d[1]), "+f"(d[2]), "+f"(d[3]), "+f"(d[4]), "+f"(d[5]), "+f"(d[6]), "+f"(d[7]), "+f"(d[8]), "+f"(d[9]), "+f"(d[10]), "+f"(d[11]), "+f"(d[12]), "+f"(d[13]), "+f"(d[14]), "+f"(d[15]), "+f"(d[16]), "+f"(d[17]), "+f"(d[18]), "+f"(d[19]), "+f"(d[20]), "+f"(d[21]), "+f"(d[22]), "+f"(d[23]), "+f"(d[24]), "+f"(d[25]), "+f"(d[26]), "+f"(d[27]), "+f"(d[28]), "+f"(d[29]), "+f"(d[30]), "+f"(d[31])
        : "r"(a[0]), "r"(a[1]), "r"(a[2]), "r"(a[3]), "l"(db), "n"(ACC));
}
template <int ACC>
__device__ __forceinline__ void wgmma_rs128t(float* d, const uint32_t* a, uint64_t db) {
    asm volatile("{\n.reg .pred p;\nsetp.ne.b32 p, %69, 0;\n"
        "wgmma.mma_async.sync.aligned.m64n128k16.f32.bf16.bf16 {%0,%1,%2,%3,%4,%5,%6,%7,%8,%9,%10,%11,%12,%13,%14,%15,%16,%17,%18,%19,%20,%21,%22,%23,%24,%25,%26,%27,%28,%29,%30,%31,%32,%33,%34,%35,%36,%37,%38,%39,%40,%41,%42,%43,%44,%45,%46,%47,%48,%49,%50,%51,%52,%53,%54,%55,%56,%57,%58,%59,%60,%61,%62,%63}, {%64,%65,%66,%67}, %68, p, 1, 1, 1;\n}"
        : "+f"(d[0]), "+f"(d[1]), "+f"(d[2]), "+f"(d[3]), "+f"(d[4]), "+f"(d[5]), "+f"(d[6]), "+f"(d[7]), "+f"(d[8]), "+f"(d[9]), "+f"(d[10]), "+f"(d[11]), "+f"(d[12]), "+f"(d[13]), "+f"(d[14]), "+f"(d[15]), "+f"(d[16]), "+f"(d[17]), "+f"(d[18]), "+f"(d[19]), "+f"(d[20]), "+f"(d[21]), "+f"(d[22]), "+f"(d[23]), "+f"(d[24]), "+f"(d[25]), "+f"(d[26]), "+f"(d[27]), "+f"(d[28]), "+f"(d[29]), "+f"(d[30]), "+f"(d[31]), "+f"(d[32]), "+f"(d[33]), "+f"(d[34]), "+f"(d[35]), "+f"(d[36]), "+f"(d[37]), "+f"(d[38]), "+f"(d[39]), "+f"(d[40]), "+f"(d[41]), "+f"(d[42]), "+f"(d[43]), "+f"(d[44]), "+f"(d[45]), "+f"(d[46]), "+f"(d[47]), "+f"(d[48]), "+f"(d[49]), "+f"(d[50]), "+f"(d[51]), "+f"(d[52]), "+f"(d[53]), "+f"(d[54]), "+f"(d[55]), "+f"(d[56]), "+f"(d[57]), "+f"(d[58]), "+f"(d[59]), "+f"(d[60]), "+f"(d[61]), "+f"(d[62]), "+f"(d[63])
        : "r"(a[0]), "r"(a[1]), "r"(a[2]), "r"(a[3]), "l"(db), "n"(ACC));
}
__device__ __forceinline__ void attention_tile(float* acc, uint32_t sb, int tile, int h, int wg, uint32_t epoch) {
    const uint32_t buf = sb + G_BUF + 32768 + ((tile << 4) & sb & 0x3f0);
    const int lane = threadIdx.x & 31, wq = (threadIdx.x >> 5) & 3, g = lane >> 2, t = lane & 3;
    const int sg = wq >> 1, hf = wq & 1, seg = tile * 2 + sg;
    uint32_t qf[8][4];
#pragma unroll
    for (int kk = 0; kk < 8; kk++) {
        qf[kk][0] = pack2(acc[8 * kk], acc[8 * kk + 1]); qf[kk][1] = pack2(acc[8 * kk + 2], acc[8 * kk + 3]);
        qf[kk][2] = pack2(acc[8 * kk + 4], acc[8 * kk + 5]); qf[kk][3] = pack2(acc[8 * kk + 6], acc[8 * kk + 7]);
    }
    float sc[5][4];
    {
        const uint64_t dk = desc_sw128(buf, 16, 1024);
        asm volatile("wgmma.fence.sync.aligned;" ::: "memory");
#pragma unroll
        for (int kk = 0; kk < 8; kk++) {
            if (kk == 0) wgmma_rs64<0>(acc, qf[kk], dk); else wgmma_rs64<1>(acc, qf[kk], dk + (kk >> 2) * 512 + (kk & 3) * 2);
        }
        asm volatile("wgmma.commit_group.sync.aligned;" ::: "memory");
        asm volatile("wgmma.wait_group.sync.aligned 0;" ::: "memory");
#pragma unroll
        for (int i = 0; i < 32; i++) asm volatile("" : "+f"(acc[i]) :: "memory");
#pragma unroll
        for (int b = 0; b < 4; b++)
#pragma unroll
            for (int i = 0; i < 4; i++) sc[b][i] = sg ? acc[16 + 4 * b + i] : acc[4 * b + i];
        sc[4][0] = sc[4][1] = sc[4][2] = sc[4][3] = 0.f;
    }
    const float cexp = 0.08838834764831845f * 1.4426950408889634f;
    const int r0 = hf * 16 + g, r1 = r0 + 8;
#pragma unroll
    for (int b = 0; b < 4; b++) {
        const int j = b * 8 + 2 * t;
        if (j > r0) sc[b][0] = -INFINITY;
        if (j + 1 > r0) sc[b][1] = -INFINITY;
        if (j > r1) sc[b][2] = -INFINITY;
        if (j + 1 > r1) sc[b][3] = -INFINITY;
    }
    float m0 = -INFINITY, m1 = -INFINITY;
#pragma unroll
    for (int b = 0; b < 4; b++) { m0 = fmaxf(m0, fmaxf(sc[b][0], sc[b][1])); m1 = fmaxf(m1, fmaxf(sc[b][2], sc[b][3])); }
    m0 = fmaxf(m0, __shfl_xor_sync(0xffffffffu, m0, 1)); m0 = fmaxf(m0, __shfl_xor_sync(0xffffffffu, m0, 2));
    m1 = fmaxf(m1, __shfl_xor_sync(0xffffffffu, m1, 1)); m1 = fmaxf(m1, __shfl_xor_sync(0xffffffffu, m1, 2));
    float l0 = 0.f, l1 = 0.f;
    {
        const float c0 = -m0 * cexp, c1 = -m1 * cexp;
        uint32_t pf[4][2];
#pragma unroll
        for (int b = 0; b < 4; b++) {
            pf[b][0] = pack2(ex2(fmaf(sc[b][0], cexp, c0)), ex2(fmaf(sc[b][1], cexp, c0)));
            pf[b][1] = pack2(ex2(fmaf(sc[b][2], cexp, c1)), ex2(fmaf(sc[b][3], cexp, c1)));
            l0 += bf_lo(pf[b][0]) + bf_hi(pf[b][0]); l1 += bf_lo(pf[b][1]) + bf_hi(pf[b][1]);
        }
        uint32_t pa[4][4];
#pragma unroll
        for (int kk = 0; kk < 4; kk++)
#pragma unroll
            for (int i = 0; i < 4; i++) pa[kk][i] = (kk >> 1) == sg ? pf[(kk & 1) * 2 + (i >> 1)][i & 1] : 0u;
        const uint64_t dv = desc_sw128(buf + 16384, 8192, 1024);
        asm volatile("wgmma.fence.sync.aligned;" ::: "memory");
#pragma unroll
        for (int kk = 0; kk < 4; kk++) { if (kk == 0) wgmma_rs128t<0>(acc, pa[kk], dv); else wgmma_rs128t<1>(acc, pa[kk], dv + kk * 128); }
        asm volatile("wgmma.commit_group.sync.aligned;" ::: "memory");
        asm volatile("wgmma.wait_group.sync.aligned 0;" ::: "memory");
#pragma unroll
        for (int i = 0; i < 64; i++) asm volatile("" : "+f"(acc[i]) :: "memory");
    }
    __syncwarp();
    if (lane == 0) mbar_arrive(sb + G_BAR + 8 * GB_KVF);
    if (h == 5 && (threadIdx.x & 127) == 0 && tile < 6) GT(1750 + tile * 8 + 3);
    wait_rec(&g_f.rec[2 * h], epoch, seg + 1);
    if (seg == 63 && (threadIdx.x & 63) == 0) GT(1570 + h);
    if (h == 5 && (threadIdx.x & 127) == 0 && tile < 6) GT(1750 + tile * 8 + 4);
    __syncwarp();
    {
        const uint4* kvf = (const uint4*)&g_KVf[seg][h][0] + lane;
        uint4 km[4], vm[4];
#pragma unroll
        for (int i = 0; i < 4; i++) km[i] = __ldcg(kvf + i * 32);
#pragma unroll
        for (int i = 0; i < 4; i++) vm[i] = __ldcg(kvf + 128 + i * 32);
        float sb_[4] = {0.f, 0.f, 0.f, 0.f};
#pragma unroll
        for (int i = 0; i < 4; i++) { MMA(sc[4], qf[2 * i], km[i].x, km[i].y); MMA(sb_, qf[2 * i + 1], km[i].z, km[i].w); }
#pragma unroll
        for (int i = 0; i < 4; i++) sc[4][i] += sb_[i];
        float n0 = fmaxf(sc[4][0], sc[4][1]), n1 = fmaxf(sc[4][2], sc[4][3]);
        n0 = fmaxf(n0, __shfl_xor_sync(0xffffffffu, n0, 1)); n1 = fmaxf(n1, __shfl_xor_sync(0xffffffffu, n1, 1));
        n0 = fmaxf(n0, __shfl_xor_sync(0xffffffffu, n0, 2)); n1 = fmaxf(n1, __shfl_xor_sync(0xffffffffu, n1, 2));
        n0 = fmaxf(n0, m0); n1 = fmaxf(n1, m1);
        const float a0 = ex2((m0 - n0) * cexp), a1 = ex2((m1 - n1) * cexp);
        const float c0 = -n0 * cexp, c1 = -n1 * cexp;
        const uint32_t p0 = pack2(ex2(fmaf(sc[4][0], cexp, c0)), ex2(fmaf(sc[4][1], cexp, c0)));
        const uint32_t p1 = pack2(ex2(fmaf(sc[4][2], cexp, c1)), ex2(fmaf(sc[4][3], cexp, c1)));
        l0 = fmaf(l0, a0, bf_lo(p0) + bf_hi(p0)); l1 = fmaf(l1, a1, bf_lo(p1) + bf_hi(p1));
        const uint32_t* vmw = (const uint32_t*)vm;
#pragma unroll
        for (int j = 0; j < 16; j++) {
            float* o = acc + 4 * j;
            o[0] *= a0; o[1] *= a0; o[2] *= a1; o[3] *= a1;
            mma1688(o, p0, p1, vmw[j]);
        }
        l0 += __shfl_xor_sync(0xffffffffu, l0, 1); l1 += __shfl_xor_sync(0xffffffffu, l1, 1);
        l0 += __shfl_xor_sync(0xffffffffu, l0, 2); l1 += __shfl_xor_sync(0xffffffffu, l1, 2);
    }
    if (h == 5 && (threadIdx.x & 127) == 0 && tile < 6) GT(1750 + tile * 8 + 5);
    if (tile == 0) mbar_wait(sb + G_BAR + 8 * GB_FREE, 1);
    else mbar_wait(sb + G_BAR + 8 * (GB_FREE + (wg ^ 1)), ((tile - 1) >> 1) & 1);
    stage_bf16(acc, sb + G_BUF, __frcp_rn(l0), __frcp_rn(l1));
}

__device__ __forceinline__ void g_consumer(uint32_t sb_, int g_, int wg_, uint32_t epoch) {
    const uint32_t sb = uni(sb_);
    const int g = uni(g_), wg = uni(wg_);
    const uint32_t l0 = opaque((threadIdx.x & 31) == 0);
    const uint32_t bar = sb + G_BAR, buf = sb + G_BUF + wg * 32768;
    const int lane = threadIdx.x & 31;
    float acc[64];
    if (wg == 1) bar_arrive(3, 256);
    const int n1 = g < 32 ? HSPLIT / 2 : NT - HSPLIT / 2;
#pragma unroll 1
    for (int i = 0; i < n1; i++) {
        gemm_tile<4>(acc, sb, wg, i, i == 0 || i == NT / 2, i >= NT / 2, wg, true, l0);
        if ((i == n1 - 1 || i == NT / 2 - 1) && lane == 0) mbar_arrive(bar + 8 * GB_WFREE);
        if (threadIdx.x == 0 && i == 0) GT((64 + g) * 8 + 1);
        if (threadIdx.x == 128 && i == 3) GT((64 + g) * 8 + 2);
        if (i > 0) mbar_wait(bar + 8 * (GB_FREE + wg), (i - 1) & 1);
        stage_bf16(acc, buf, 1.f, 1.f);
        asm volatile("fence.proxy.async.shared::cta;" ::: "memory");
        mbar_arrive(bar + 8 * (GB_STG + wg));
    }
    if (threadIdx.x == 128) GT((64 + g) * 8 + 3);
    if (g < 32) {
#pragma unroll 1
        for (int i = 0; i < NT / 2; i++) {
            const int tile = 2 * i + wg;
            gemm_tile<3>(acc, sb, tile, i, i == 0, 1, wg, tile != NT - 1, l0);
            if (threadIdx.x == 0 && i == 0) GT((64 + g) * 8 + 4);
            if (threadIdx.x == 128 && i == 3) GT((64 + g) * 8 + 5);
            if (g == 5 && (threadIdx.x & 127) == 0 && tile < 6) GT(1750 + tile * 8 + 1);
            mbar_wait(bar + 8 * (GB_KV + wg), i & 1);
            if (g == 5 && (threadIdx.x & 127) == 0 && tile < 6) GT(1750 + tile * 8 + 2);
            attention_tile(acc, sb, tile, g, wg, epoch);
            if (g == 5 && (threadIdx.x & 127) == 0 && tile < 6) GT(1750 + tile * 8 + 6);
            asm volatile("fence.proxy.async.shared::cta;" ::: "memory");
            mbar_arrive(bar + 8 * (GB_STG + wg));
        }
    } else {
#pragma unroll 1
        for (int i = 0; i < NT / 2; i++) {
            const int tile = 2 * i + wg;
            gemm_tile<4>(acc, sb, tile, i, i == 0, 0, wg, tile != NT - 1, l0);
            if (threadIdx.x == 0 && i == 0) GT((64 + g) * 8 + 4);
            if (threadIdx.x == 128 && i == 3) GT((64 + g) * 8 + 5);
            mbar_wait(bar + 8 * (GB_FREE + wg), (i - 1) & 1);
            stage_bf16(acc, buf, 1.f, 1.f);
            asm volatile("fence.proxy.async.shared::cta;" ::: "memory");
            mbar_arrive(bar + 8 * (GB_STG + wg));
        }
    }
}

__device__ __forceinline__ void load_w(uint32_t sb, const CUtensorMap* tm, int col, int row, int k0 = 0, int k1 = 2) {
    const uint32_t bar = sb + G_BAR;
#pragma unroll
    for (int kh = k0; kh < k1; kh++) {
        mbar_expect_tx(bar + 8 * (GB_W0 + kh), 65536);
        tma2d(sb + G_W + kh * 32768, tm, col, row + kh * 256, bar + 8 * (GB_W0 + kh));
        tma2d(sb + G_W + 65536 + kh * 32768, tm, col + 64, row + kh * 256, bar + 8 * (GB_W0 + kh));
    }
}

__device__ __forceinline__ void rbf2(float& a, float& b) { uint32_t w = pack2(a, b); a = bf_lo(w); b = bf_hi(w); }
__device__ __forceinline__ void warp_sum2(float& a, float& b) {
#pragma unroll
    for (int o = 16; o; o >>= 1) { float c = __shfl_xor_sync(0xffffffffu, a, o), d = __shfl_xor_sync(0xffffffffu, b, o); a += c; b += d; }
}
__device__ __forceinline__ float sum16(const float* v) {
    return (((v[0] + v[1]) + (v[2] + v[3])) + ((v[4] + v[5]) + (v[6] + v[7]))) + (((v[8] + v[9]) + (v[10] + v[11])) + ((v[12] + v[13]) + (v[14] + v[15])));
}
__device__ __forceinline__ void ln_row2(float* v, float* u) {
    float sv = sum16(v), su = sum16(u);
    warp_sum2(sv, su);
    const float mv = sv * (1.f / DM), mu = su * (1.f / DM);
    float qv = 0.f, qu = 0.f, qv2 = 0.f, qu2 = 0.f;
#pragma unroll
    for (int i = 0; i < 16; i += 2) {
        float d0 = v[i] - mv, d1 = v[i + 1] - mv, e0 = u[i] - mu, e1 = u[i + 1] - mu;
        qv = fmaf(d0, d0, qv); qv2 = fmaf(d1, d1, qv2); qu = fmaf(e0, e0, qu); qu2 = fmaf(e1, e1, qu2);
    }
    qv += qv2; qu += qu2;
    warp_sum2(qv, qu);
    const float rv = rbf(mv), ru = rbf(mu);
    const float iv = __frcp_rn(rbf(sqrtf(rbf(rbf(qv * (1.f / DM)) + 1e-5f)))), iu = __frcp_rn(rbf(sqrtf(rbf(rbf(qu * (1.f / DM)) + 1e-5f))));
#pragma unroll
    for (int i = 0; i < 16; i += 2) {
        float a = v[i] - rv, b = v[i + 1] - rv, c = u[i] - ru, d = u[i + 1] - ru;
        rbf2(a, b); rbf2(c, d);
        a *= iv; b *= iv; c *= iu; d *= iu;
        rbf2(a, b); rbf2(c, d);
        v[i] = a; v[i + 1] = b; u[i] = c; u[i + 1] = d;
    }
}

__device__ __forceinline__ void ln_row1(float* v) {
    float sv = sum16(v);
#pragma unroll
    for (int o = 16; o; o >>= 1) sv += __shfl_xor_sync(0xffffffffu, sv, o);
    const float mv = sv * (1.f / DM);
    float qv = 0.f, qv2 = 0.f;
#pragma unroll
    for (int i = 0; i < 16; i += 2) { float d0 = v[i] - mv, d1 = v[i + 1] - mv; qv = fmaf(d0, d0, qv); qv2 = fmaf(d1, d1, qv2); }
    qv += qv2;
#pragma unroll
    for (int o = 16; o; o >>= 1) qv += __shfl_xor_sync(0xffffffffu, qv, o);
    const float rv = rbf(mv);
    const float iv = __frcp_rn(rbf(sqrtf(rbf(rbf(qv * (1.f / DM)) + 1e-5f))));
#pragma unroll
    for (int i = 0; i < 16; i += 2) {
        float a = v[i] - rv, b = v[i + 1] - rv;
        rbf2(a, b);
        a *= iv; b *= iv;
        rbf2(a, b);
        v[i] = a; v[i + 1] = b;
    }
}
__device__ __forceinline__ void finalizer(int g, const bf16* __restrict__ x, const bf16* __restrict__ wr, bf16* __restrict__ out, uint32_t epoch) {
    const int lane = threadIdx.x & 31;
    float b0 = -INFINITY, b1 = -INFINITY; int i0 = 0x7fffffff, i1 = 0x7fffffff;
    const uint32_t tag = (epoch & 0xfffffu) << 12;
    uint32_t fl = ~epoch;
    uint4 xa = *(const uint4*)(x + (size_t)g * DM + lane * 8), xb = *(const uint4*)(x + (size_t)g * DM + lane * 8 + 256);
#pragma unroll 1
    for (int tile = 0; tile < NT; tile++) {
        const int row = tile * 64 + g;
        const size_t o0 = (size_t)row * DM + lane * 8;
        uint32_t n = 0;
#pragma unroll 1
        while (!__all_sync(0xffffffffu, fl == epoch)) {
            if (n) __nanosleep(tile ? 100 : 1000);
            fl = ldg_rlx(&g_f.p[tile][lane]);
            if (++n > SPIN_LIMIT) { ABORT(12); break; }
        }
        if (tile == NT - 1 && g == 63 && lane == 0) GT(1438);
        float v[16];
        {
            uint4 pa[8][2];
#pragma unroll
            for (int k = 0; k < 8; k++) {
                pa[k][0] = ldg_rlx4((const uint32_t*)(g_P + (size_t)k * SQ * DM + o0));
                pa[k][1] = ldg_rlx4((const uint32_t*)(g_P + (size_t)k * SQ * DM + o0 + 256));
            }
            fl = ldg_rlx(&g_f.p[min(tile + 1, NT - 1)][lane]);
#pragma unroll
            for (int j = 0; j < 2; j++) {
#pragma unroll
                for (int i = 0; i < 4; i++) {
                    uint32_t w[8];
#pragma unroll
                    for (int k = 0; k < 8; k++) w[k] = i == 0 ? pa[k][j].x : (i == 1 ? pa[k][j].y : (i == 2 ? pa[k][j].z : pa[k][j].w));
                    v[j * 8 + 2 * i] = ((bf_lo(w[0]) + bf_lo(w[1])) + (bf_lo(w[2]) + bf_lo(w[3]))) + ((bf_lo(w[4]) + bf_lo(w[5])) + (bf_lo(w[6]) + bf_lo(w[7])));
                    v[j * 8 + 2 * i + 1] = ((bf_hi(w[0]) + bf_hi(w[1])) + (bf_hi(w[2]) + bf_hi(w[3]))) + ((bf_hi(w[4]) + bf_hi(w[5])) + (bf_hi(w[6]) + bf_hi(w[7])));
                }
            }
        }
        const uint4 ra = *(const uint4*)(wr + lane * 8), rb = *(const uint4*)(wr + 256 + lane * 8);
        uint32_t hw[8];
        {
            const uint32_t xw[8] = {xa.x, xa.y, xa.z, xa.w, xb.x, xb.y, xb.z, xb.w};
#pragma unroll
            for (int i = 0; i < 8; i++) {
                float a0 = v[2 * i], a1 = v[2 * i + 1];
                rbf2(a0, a1);
                hw[i] = pack2(a0 + bf_lo(xw[i]), a1 + bf_hi(xw[i]));
                v[2 * i] = bf_lo(hw[i]); v[2 * i + 1] = bf_hi(hw[i]);
            }
        }
        if (tile + 1 < NT) { xa = *(const uint4*)(x + o0 + 64 * DM); xb = *(const uint4*)(x + o0 + 64 * DM + 256); }
        ln_row1(v);
        float r0 = 0.f, r1 = 0.f;
        {
            const uint32_t ww[8] = {ra.x, ra.y, ra.z, ra.w, rb.x, rb.y, rb.z, rb.w};
#pragma unroll
            for (int i = 0; i < 8; i++) { r0 = fmaf(v[2 * i], bf_lo(ww[i]), r0); r1 = fmaf(v[2 * i + 1], bf_hi(ww[i]), r1); }
        }
        r0 += r1;
#pragma unroll
        for (int o = 16; o; o >>= 1) r0 += __shfl_xor_sync(0xffffffffu, r0, o);
        r0 = rbf(r0);
        if (cand_better(r0, row, b0, i0)) { b1 = b0; i1 = i0; b0 = r0; i0 = row; }
        else if (cand_better(r0, row, b1, i1)) { b1 = r0; i1 = row; }
        if (tile == NT - 1 && g == 63 && lane == 0) GT(1439);
        const bool last = tile == NT - 1, spec = tile == SPEC_TILES - 1;
        const bool pub = (lane == 0 && spec) || (lane == 1 && last);
        if (pub)
            asm volatile("st.relaxed.gpu.global.v4.b32 [%0], {%1,%2,%3,%4};" :: "l"(&g_f.cand[lane][g]),
                         "r"(FU(b0)), "r"(tag | (uint32_t)min(i0, 4095)), "r"(FU(b1)), "r"(tag | (uint32_t)min(i1, 4095)) : "memory");
#pragma unroll
        for (int j = 0; j < 2; j++) {
            const uint32_t* hh = hw + j * 4; const float* nn = v + j * 8;
            *(uint4*)(out + o0 + j * 256) = make_uint4(pack2(bf_lo(hh[0]) + nn[0], bf_hi(hh[0]) + nn[1]), pack2(bf_lo(hh[1]) + nn[2], bf_hi(hh[1]) + nn[3]),
                                                       pack2(bf_lo(hh[2]) + nn[4], bf_hi(hh[2]) + nn[5]), pack2(bf_lo(hh[3]) + nn[6], bf_hi(hh[3]) + nn[7]));
            *(uint4*)(g_h + o0 + j * 256) = make_uint4(hh[0], hh[1], hh[2], hh[3]);
            *(uint4*)(g_hn + o0 + j * 256) = make_uint4(pack2(nn[0], nn[1]), pack2(nn[2], nn[3]), pack2(nn[4], nn[5]), pack2(nn[6], nn[7]));
        }
        if (last || spec) {
            __threadfence();
            __syncwarp();
            if (pub) stg_rlx(&g_f.rows[lane][g], epoch);
        }
    }
    if (g == 0 && lane == 0) { g_epoch = epoch; if (epoch == 0xffffffu) { g_ticket[0] = 0; g_ticket[32] = 0; } }
}

__device__ __noinline__ void g_producer(uint32_t sb, int g, const Maps& maps, uint32_t epoch, const bf16* __restrict__ x, const bf16* __restrict__ wr, bf16* __restrict__ out) {
    const uint32_t bar = sb + G_BAR;
    const int warp = (threadIdx.x >> 5) - 8;
    if (threadIdx.x == 256 && g == 5) GT(1410);
    if (threadIdx.x == 256 && g == 5) GT(1411);
    if (warp == 3) {
        wait_eq4(&g_f.xn[(threadIdx.x & 31) * 4], epoch, 13);
        __syncwarp();
        if ((threadIdx.x & 31) == 0) mbar_arrive(bar + 8 * GB_XN);
        wait_eq2(&g_f.rload[(threadIdx.x & 31) * 2], epoch, 13);
        __syncwarp();
        if ((threadIdx.x & 31) == 0) mbar_arrive(bar + 8 * GB_RL);
        finalizer(g, x, wr, out, epoch);
        if (g == 63 && (threadIdx.x & 31) == 0) GT(128 * 8 + 6);
    }
    if ((threadIdx.x & 31) != 0) return;
    if (threadIdx.x == 256 && g == 5) GT(1412);
    if (warp == 0) {
        wait_eq4(&g_f.xn[0], epoch, 13);
        const int m1 = g < 32 ? HSPLIT : 2 * NT - HSPLIT;
#pragma unroll 1
        for (int it = 0; it < m1; it++) {
            const int tile = it < NT ? it : it - NT + HSPLIT;
            if (it == HOLD) mbar_wait(bar + 8 * GB_RL, 0);
            if (it == 1) mbar_wait(bar + 8 * GB_XN, 0);
            if (it == NT) {
                mbar_wait(bar + 8 * GB_WFREE, 0);
                load_w(sb, (g & 1) ? &maps.wv : &maps.wk, ((g - 32) >> 1) * 128, 0);
            }
#pragma unroll
            for (int k = 0; k < 4; k++) {
                if (k == 2 && it == 0) load_w(sb, (g & 1) ? &maps.wv : &maps.wk, (g >> 1) * 128, 0, 1, 2);
                mbar_wait(bar + 8 * (GB_EMPTY + k), (it & 1) ^ 1);
                mbar_expect_tx(bar + 8 * (GB_FULL + k), 16384);
                tma3d(sb + slot_off(k), &maps.xn3, tile * 64, k * 2, bar + 8 * (GB_FULL + k));
            }
        }
        mbar_wait(bar + 8 * GB_WFREE, g >= 32);
        const int u = g - 32, ks = u >> 2, ns = u & 3;
        if (g < 32) load_w(sb, &maps.wq, g * 128, 0); else load_w(sb, &maps.wo2, ns * 128, ks * 512);
        if (g < 32) {
#pragma unroll 1
            for (int n = 0; n < NT * 4; n++) {
                const int slot = n % 3;
                mbar_wait(bar + 8 * (GB_EMPTY + slot), ((n / 3) & 1) ^ 1);
                mbar_expect_tx(bar + 8 * (GB_FULL + slot), 16384);
                tma3d(sb + slot_off(slot), &maps.xn3, (n >> 2) * 64, (n & 3) * 2, bar + 8 * (GB_FULL + slot));
            }
        } else {
#pragma unroll 1
            for (int tile = 0; tile < NT; tile++) {
                wait_eq4(&g_f.o[tile][ks][0], epoch, 9);
                if (g == 40 && tile == NT - 1) GT(1437);
                if (tile == NT - 1) GT(1690 + g - 32);
#pragma unroll
                for (int k = 0; k < 4; k++) {
                    mbar_wait(bar + 8 * (GB_EMPTY + k), (tile & 1) ^ 1);
                    mbar_expect_tx(bar + 8 * (GB_FULL + k), 16384);
                    tma3d(sb + slot_off(k), &maps.ox3, tile * 64, ks * 8 + k * 2, bar + 8 * (GB_FULL + k));
                }
            }
        }
    } else if (warp < 3) {
        const int wg = warp - 1;
        const uint32_t buf = sb + G_BUF + wg * 32768;
        const CUtensorMap* tkv = (g & 1) ? &maps.vx3 : &maps.kx3;
        const int n1 = g < 32 ? HSPLIT / 2 : NT - HSPLIT / 2;
#pragma unroll 1
        for (int i = 0; i < n1; i++) {
            const int tile = (i < NT / 2 ? 2 * i : 2 * i - NT + HSPLIT) + wg, hd = (i < NT / 2 ? g : g - 32) >> 1;
            mbar_wait(bar + 8 * (GB_STG + wg), i & 1);
            tma_store3d(tkv, buf, tile * 64, hd * 2);
            asm volatile("cp.async.bulk.commit_group;" ::: "memory");
            asm volatile("cp.async.bulk.wait_group.read 0;" ::: "memory");
            mbar_arrive(bar + 8 * (GB_FREE + wg));
            asm volatile("cp.async.bulk.wait_group 0;" ::: "memory");
            PUBLISH(&g_f.kv[tile][hd][g & 1], epoch);
        }
        if (g < 32) {
            if (wg == 1) {
                mbar_wait(bar + 8 * GB_WFREE, 0);
#pragma unroll 1
                for (int tile = 0; tile < NT; tile++) {
                    wait_eq2(&g_f.kv[tile][g][0], epoch, 10);
                    if (tile > 0) mbar_wait(bar + 8 * GB_KVF, (tile - 1) & 1);
                    const uint32_t mb = bar + 8 * (GB_KV + (tile & 1));
                    mbar_expect_tx(mb, 32768);
                    tma3d(buf, &maps.kx3, tile * 64, g * 2, mb); tma3d(buf + 16384, &maps.vx3, tile * 64, g * 2, mb);
                }
            } else {
#pragma unroll 1
                for (int tile = 0; tile < NT; tile++) {
                    mbar_wait(bar + 8 * (GB_STG + (tile & 1)), (tile >> 1) & 1);
                    tma_store3d(&maps.ox3, buf, tile * 64, g * 2);
                    asm volatile("cp.async.bulk.commit_group;" ::: "memory");
                    asm volatile("cp.async.bulk.wait_group.read 0;" ::: "memory");
                    mbar_arrive(bar + 8 * (GB_FREE + (tile & 1)));
                    asm volatile("cp.async.bulk.wait_group 0;" ::: "memory");
                    PUBLISH(&g_f.o[tile][g >> 2][g & 3], epoch);
                    if (g == 3 && tile == NT - 1) GT(1436);
                    if (tile == NT - 1) GT(1610 + g);
                }
            }
        } else {
            const int u = g - 32;
#pragma unroll 1
            for (int i = 0; i < NT / 2; i++) {
                const int tile = 2 * i + wg;
                mbar_wait(bar + 8 * (GB_STG + wg), i & 1);
                tma_store3d(&maps.p3, buf, (u >> 2) * SQ + tile * 64, (u & 3) * 2);
                asm volatile("cp.async.bulk.commit_group;" ::: "memory");
                asm volatile("cp.async.bulk.wait_group.read 0;" ::: "memory");
                mbar_arrive(bar + 8 * (GB_FREE + wg));
                asm volatile("cp.async.bulk.wait_group 0;" ::: "memory");
                PUBLISH(&g_f.p[tile][u], epoch);
                if (g == 40 && tile == NT - 1) GT(1435);
                if (tile == NT - 1) GT(1650 + u);
            }
        }
    }
}

__device__ __forceinline__ int startup(uint8_t* smem, const bf16* __restrict__ x, const Maps& maps, uint32_t& epoch) {
    const int tid = threadIdx.x, lane = tid & 31, w = tid >> 5, cta = blockIdx.x;
    volatile uint32_t* sh = (volatile uint32_t*)(smem + SH_OFF);
    if (cta == 4 && tid == 0) GT(1399);
    epoch = (ldg_rlx(&g_epoch) + 1) & 0x00ffffffu;
    if (w < 4) {
        if (!(cta & 1)) {
            uint32_t* pp = (uint32_t*)(xpage() + ((XR3 ^ 0x3000u) ^ ((w == 1 || w == 2) ? 0x1000u : 0u) ^ ((w & 2) << 13))) + (cta >> 1) * 8;
            if (lane < 8) stg_rlx(pp + lane, 0u);
            __syncwarp();
            if (lane == 0) {
                uint32_t best = 0xffffffffu, a = 0;
#pragma unroll 1
                for (int r = 0; r < NPROBE; r++) {
                    uint32_t t0 = clk32();
                    asm volatile("atom.relaxed.gpu.global.add.u32 %0, [%1], %2;" : "=r"(a) : "l"(pp), "r"(a + 1) : "memory");
                    if (a == 0x7fffffffu) ABORT(15);
                    uint32_t t1 = clk32();
                    if (r > 0) best = min(best, t1 - t0);
                    else if (w == 0) {
                        asm volatile("red.relaxed.gpu.global.max.u32 [%0], %1;" :: "l"(&g_ticket[0]), "r"(epoch << 8) : "memory");
                        asm volatile("red.relaxed.gpu.global.max.u32 [%0], %1;" :: "l"(&g_ticket[32]), "r"(epoch << 8) : "memory");
                    }
                }
                sh[w] = best;
            }
        }
        if (!(cta & 1)) bar_sync(1, 128);
        if (cta == 4 && tid == 0) GT(1400);
        if (w == 0) {
            if (lane == 0) {
                uint32_t rp;
                if (!(cta & 1)) {
                    uint32_t a = sh[0], b = sh[1], c = sh[2], d = sh[3];
                    uint32_t mid = (min(min(a, b), min(c, d)) + max(max(a, b), max(c, d))) >> 1;
                    const int dd = (int)min(a, d) - (int)min(b, c);
                    uint32_t cls = abs(dd) > 60 ? dd > 0 : a > mid;
                    uint32_t t = atomicAdd(&g_ticket[cls * 32], 1u) & 255;
                    if (t >= (cls ? 34u : 32u)) { cls ^= 1; t = atomicAdd(&g_ticket[cls * 32], 1u) & 255; }
                    rp = min(cls ? 32 + t : t, 65u);
                    stg_rlx(&g_table[(cta >> 1) * 8], (epoch << 8) | rp);
                } else {
                    uint32_t v, n = 0;
#pragma unroll 1
                    while (((v = ldg_rlx(&g_table[(cta >> 1) * 8])) >> 8) != epoch) { if (++n > SPIN_LIMIT) { ABORT(14); break; } }
                    rp = v & 255;
                }
                const int role = rp * 2 + (cta & 1);
                sh[8] = role; sh[9] = epoch;
                while (sh[10] != epoch + 1 && cta < 128) {}
                asm volatile("fence.proxy.async;" ::: "memory");
                if (role < 64) rec_first_loads(smem_u32(smem), role, maps);
                else if (role < 128) load_w(smem_u32(smem), (role & 1) ? &maps.wv : &maps.wk, ((role - 64) >> 1) * 128, 0, 0, 1);
                if (cta == 4) GT(1401);
            }
        }
    } else if (cta < 128) {
        uint4 u[2][2];
        const int row0 = cta * 16 + (w - 4) * 2;
#pragma unroll
        for (int r = 0; r < 2; r++)
#pragma unroll
            for (int j = 0; j < 2; j++) u[r][j] = *(const uint4*)(x + (size_t)(row0 + r) * DM + j * 256 + lane * 8);
        if (cta < 48) {
            const uint32_t b = cta >> 3, off = (b >= 4 ? 0x8000u + (b & 1) * 0x4000u : ((b & 1) ? 0x3000u : 0u) + ((b & 2) << 13)) ^ aslot(cta & 7);
            *(uint4*)(xpage() + off + (tid - 128) * 16) = make_uint4(0, 0, 0, 0);
        }
        float v[2][16];
#pragma unroll
        for (int r = 0; r < 2; r++)
#pragma unroll
            for (int j = 0; j < 2; j++) {
                uint32_t ww[4] = {u[r][j].x, u[r][j].y, u[r][j].z, u[r][j].w};
#pragma unroll
                for (int i = 0; i < 4; i++) { v[r][j * 8 + 2 * i] = bf_lo(ww[i]); v[r][j * 8 + 2 * i + 1] = bf_hi(ww[i]); }
            }
        ln_row2(v[0], v[1]);
#pragma unroll
        for (int r = 0; r < 2; r++)
#pragma unroll
            for (int j = 0; j < 2; j++)
                *(uint4*)(g_xn + (size_t)(row0 + r) * DM + j * 256 + lane * 8) =
                    make_uint4(pack2(v[r][j * 8], v[r][j * 8 + 1]), pack2(v[r][j * 8 + 2], v[r][j * 8 + 3]), pack2(v[r][j * 8 + 4], v[r][j * 8 + 5]), pack2(v[r][j * 8 + 6], v[r][j * 8 + 7]));
        bar_sync(2, 256);
        if (tid == 160) { st_rel(&g_f.xn[cta], epoch); sh[10] = epoch + 1; }
        if (cta == 4 && tid == 160) GT(1403);
        __syncwarp();
    }
    if (cta == 4 && tid == 128) GT(1402);
    __syncthreads();
    const int role = sh[8];
    return role;
}

__global__ void __cluster_dims__(2, 1, 1) __launch_bounds__(384, 1)
main_kernel(const __grid_constant__ Maps maps, const bf16* __restrict__ x, const bf16* __restrict__ mem0, const bf16* __restrict__ wr,
            const bf16* __restrict__ wd, bf16* __restrict__ out) {
    extern __shared__ __align__(1024) uint8_t smem[];
    const uint32_t sb = smem_u32(smem);
    if (threadIdx.x == 0) {
        for (int i = 0; i < MB_N; i++) mbar_init(sb + R_BAR + 8 * i, i == MB_V ? 4 : 1);
        for (int i = 0; i < GB_N; i++)
            mbar_init(sb + G_BAR + 8 * i, i == GB_WFREE ? 8 : ((i >= GB_EMPTY && i < GB_KV) || i == GB_KVF ? 4 : (i >= GB_STG && i < GB_FREE ? 128 : 1)));
        asm volatile("fence.mbarrier_init.release.cluster;" ::: "memory");
    }
    if (threadIdx.x >= 352 && threadIdx.x < 352 + (int)(sizeof(Maps) / sizeof(CUtensorMap)))
        asm volatile("prefetch.tensormap [%0];" :: "l"((const CUtensorMap*)&maps + (threadIdx.x - 352)) : "memory");
    uint32_t epoch;
    asm volatile("fence.proxy.async.shared::cta;" ::: "memory");
    const int role = uni(startup(smem, x, maps, epoch));
    const int wg = uni(threadIdx.x >> 7);
    if (role < 64) {
#define SETREG(n) do { if ((n) < 168) asm volatile("setmaxnreg.dec.sync.aligned.u32 %0;" :: "n"(n)); if ((n) > 168) asm volatile("setmaxnreg.inc.sync.aligned.u32 %0;" :: "n"(n)); } while (0)
#define RESREG(n) do { if ((n) < 168) asm volatile("setmaxnreg.inc.sync.aligned.u32 168;"); if ((n) > 168) asm volatile("setmaxnreg.dec.sync.aligned.u32 168;"); } while (0)
        if (wg == 0) {
            SETREG(RGA);
            rec_a(sb, role, mem0, epoch);
            RESREG(RGA);
        } else if (wg == 1) {
            SETREG(RGB);
            rec_b(sb, role, epoch);
            RESREG(RGB);
        } else {
            SETREG(RGC);
            rec_c(sb, role, mem0, maps, epoch);
            RESREG(RGC);
        }
        ffn_phase(maps, wd, out);
        if (threadIdx.x == 0) GT(((volatile int*)(smem + SH_OFF))[8] * 8 + 6);
    } else if (role < 128) {
        if (wg < 2) {
            g_consumer(sb, role - 64, wg, epoch);
            if (threadIdx.x == 128) GT(role * 8 + 6);
        } else {
            g_producer(sb, role - 64, maps, epoch, x, wr, out);
        }
    }
}

typedef CUresult (*EncodeFn)(CUtensorMap*, CUtensorMapDataType, cuuint32_t, void*, const cuuint64_t*, const cuuint64_t*, const cuuint32_t*, const cuuint32_t*,
                             CUtensorMapInterleave, CUtensorMapSwizzle, CUtensorMapL2promotion, CUtensorMapFloatOOBfill);
static void make_map3(EncodeFn fn, CUtensorMap* m, const void* ptr, uint64_t cols, uint64_t rows) {
    cuuint64_t dims[3] = {64, rows, cols / 64};
    cuuint64_t strides[2] = {cols * 2, 128};
    cuuint32_t box[3] = {64, 64, 2};
    cuuint32_t es[3] = {1, 1, 1};
    fn(m, CU_TENSOR_MAP_DATA_TYPE_BFLOAT16, 3, (void*)ptr, dims, strides, box, es, CU_TENSOR_MAP_INTERLEAVE_NONE, CU_TENSOR_MAP_SWIZZLE_128B,
       CU_TENSOR_MAP_L2_PROMOTION_L2_256B, CU_TENSOR_MAP_FLOAT_OOB_FILL_NONE);
}
static void make_map(EncodeFn fn, CUtensorMap* m, const void* ptr, uint64_t cols, uint64_t rows, uint32_t bcols, uint32_t brows,
                     bool f32 = false, CUtensorMapSwizzle sw = CU_TENSOR_MAP_SWIZZLE_128B) {
    cuuint64_t dims[2] = {cols, rows};
    cuuint64_t strides[1] = {cols * (f32 ? 4 : 2)};
    cuuint32_t box[2] = {bcols, brows};
    cuuint32_t es[2] = {1, 1};
    fn(m, f32 ? CU_TENSOR_MAP_DATA_TYPE_FLOAT32 : CU_TENSOR_MAP_DATA_TYPE_BFLOAT16, 2, (void*)ptr, dims, strides, box, es, CU_TENSOR_MAP_INTERLEAVE_NONE, sw,
       CU_TENSOR_MAP_L2_PROMOTION_L2_256B, CU_TENSOR_MAP_FLOAT_OOB_FILL_NONE);
}

extern "C" void kernel_launch(void* const* d_in, const int* in_sizes, int n_in, void* d_out, int out_size) {
    const bf16* x = (const bf16*)d_in[0];
    const bf16* mem0 = (const bf16*)d_in[1];
    const bf16* Wq = (const bf16*)d_in[2];
    const bf16* Wk = (const bf16*)d_in[3];
    const bf16* Wv = (const bf16*)d_in[4];
    const bf16* Wo = (const bf16*)d_in[5];
    const bf16* wr = (const bf16*)d_in[8];
    const bf16* wg = (const bf16*)d_in[9];
    const bf16* wu = (const bf16*)d_in[10];
    const bf16* wd = (const bf16*)d_in[11];
    bf16* out = (bf16*)d_out;

    static EncodeFn enc = nullptr;
    static void *pxn, *pK, *pV, *pO, *pacc;
    if (!enc) {
        cudaDriverEntryPointQueryResult qr;
        void* fn = nullptr;
        cudaGetDriverEntryPoint("cuTensorMapEncodeTiled", &fn, cudaEnableDefault, &qr);
        enc = (EncodeFn)fn;
        cudaGetSymbolAddress(&pxn, g_xn); cudaGetSymbolAddress(&pK, g_K); cudaGetSymbolAddress(&pV, g_V);
        cudaGetSymbolAddress(&pO, g_O); cudaGetSymbolAddress(&pacc, g_P);
        cudaFuncSetAttribute(main_kernel, cudaFuncAttributeMaxDynamicSharedMemorySize, SMEM_TOTAL);
    }
    Maps m;
    make_map(enc, &m.wq, Wq, HD, DM, 64, 256);
    make_map(enc, &m.wk, Wk, HD, DM, 64, 256);
    make_map(enc, &m.wv, Wv, HD, DM, 64, 256);
    make_map(enc, &m.wo, Wo, DM, HD, 64, 128);
    make_map(enc, &m.wo2, Wo, DM, HD, 64, 256);
    make_map(enc, &m.kx, pK, HD, SQ, 64, 64);
    make_map(enc, &m.vx, pV, HD, SQ, 64, 64);
    make_map3(enc, &m.kx3, pK, HD, SQ); make_map3(enc, &m.vx3, pV, HD, SQ); make_map3(enc, &m.ox3, pO, HD, SQ); make_map3(enc, &m.xn3, pxn, DM, SQ);
    make_map3(enc, &m.p3, pacc, DM, 8 * SQ);
    make_map(enc, &m.wg, wg, FF, DM, 32, 256, false, CU_TENSOR_MAP_SWIZZLE_NONE);
    make_map(enc, &m.wu, wu, FF, DM, 32, 256, false, CU_TENSOR_MAP_SWIZZLE_NONE);

    cudaStream_t st = cudaStreamPerThread;
    main_kernel<<<NCTA, 384, SMEM_TOTAL, st>>>(m, x, mem0, wr, wd, out);
}
```

```cpp
#include <cuda_runtime.h>
#include <cuda_bf16.h>
#include <cuda.h>
#include <stdint.h>
#include <stddef.h>

typedef __nv_bfloat16 bf16;

constexpr int SQ = 2048, DM = 512, NH = 32, DH = 128, NSEG = 64, HD = 4096, FF = 1792;

constexpr int NT = 32;
#define SPEC_TILES 30
__device__ __align__(1024) bf16 g_xn[SQ * DM];
__device__ __align__(1024) bf16 g_K[SQ * HD];
__device__ __align__(1024) bf16 g_V[SQ * HD];
__device__ __align__(1024) bf16 g_O[SQ * HD];
__device__ __align__(1024) uint32_t g_KVf[NSEG][NH][1024];
__device__ __align__(1024) bf16 g_P[8 * SQ * DM];
__device__ __align__(1024) bf16 g_h[SQ * DM];
__device__ __align__(1024) bf16 g_hn[SQ * DM];
__device__ uint8_t g_xraw[12 << 20];
#define XPG 0
__device__ __forceinline__ uint64_t xpage() { return (((uint64_t)g_xraw + (2 << 20) - 1) & ~(uint64_t)((2 << 20) - 1)) + ((uint64_t)XPG << 21); }
constexpr uint32_t XR3 = (1u << 20) | (1u << 19) | (1u << 12);
__device__ __forceinline__ uint32_t aslot(uint32_t s) { return ((s & 1) << 18) | ((s & 2) << 19) | ((s & 4) * 0xc000u); }
#define IL 1
constexpr int AC1 = IL ? 48 : 256;
__device__ __forceinline__ uint32_t acc_off(uint32_t W, uint32_t lane) {
    return ((W & 2) ? 0x3000u : 0u) + ((W & 4) << 12) + (W & 1) * 2048 + (IL ? (lane >> 2) * 256 : (lane >> 2) * 128 + (lane & 4) * 16) + (lane & 3) * 16;
}
#define XM 4
__device__ __forceinline__ uint32_t ext_base(uint32_t W) { return 0x8000u + ((W & 4) << 12) + (W & 3) * 1024; }
__device__ __forceinline__ uint32_t ext_lane(uint32_t lane) { return XM == 1 ? (lane >> 3) * 256 + (lane & 7) * 4 : (XM == 2 ? (lane >> 4) * 512 + (lane & 15) * 4 : lane * 4); }
__device__ __forceinline__ uint32_t zero_off(uint32_t c, uint32_t ln) {
    return ln < 16 ? ((c & 16) ? 0x3000u : 0u) + ((c & 32) << 9) + (c & 15) * 256 + ln * 16 : ext_base(c >> 3) + ext_lane((c & 7) * 4);
}
struct Flags {
    uint32_t kv[NT][NH][2];
    uint32_t o[NT][8][32];
    uint32_t rec[64];
    uint32_t xn[128];
    uint32_t rload[64];
    uint32_t p[NT][32];
    uint32_t rows[2][128];
    uint4 cand[2][128];
    uint4 norm[64];
};
__device__ __align__(1024) Flags g_f;
__device__ __align__(1024) uint4 g_yp[2][FF / 32][DM];
__device__ __align__(1024) uint32_t g_table[66 * 8];
__device__ __align__(256) uint32_t g_ticket[64];
__device__ uint32_t g_epoch;
#define HOLD 2
#define HSPLIT 24
#define EREL 0
#define PFK 2
#define PFO 0
#define PFS 0
#define NPROBE 3
constexpr int NCTA = 132;
constexpr int NFW = 112;
__device__ uint32_t g_abort;
__device__ long long g_dbg[4096];
#define TR(slot, v)

__device__ __forceinline__ uint32_t smem_u32(const void* p) { return (uint32_t)__cvta_generic_to_shared(p); }
__device__ __forceinline__ void mbar_init(uint32_t a, uint32_t c) { asm volatile("mbarrier.init.shared::cta.b64 [%0], %1;" :: "r"(a), "r"(c) : "memory"); }
__device__ __forceinline__ void mbar_expect_tx(uint32_t a, uint32_t tx) { asm volatile("mbarrier.arrive.expect_tx.shared::cta.b64 _, [%0], %1;" :: "r"(a), "r"(tx) : "memory"); }
__device__ __forceinline__ void mbar_arrive(uint32_t a) { asm volatile("mbarrier.arrive.shared::cta.b64 _, [%0];" :: "r"(a) : "memory"); }
__device__ __forceinline__ void mbar_arrive_if(uint32_t a, uint32_t pred) {
    asm volatile("{\n.reg .pred p;\nsetp.ne.u32 p, %1, 0;\n@p mbarrier.arrive.shared::cta.b64 _, [%0];\n}" :: "r"(a), "r"(pred) : "memory");
}
__device__ __forceinline__ bool mbar_try(uint32_t a, uint32_t ph) {
    uint32_t ok;
    asm volatile("{\n.reg .pred p;\nmbarrier.try_wait.parity.shared::cta.b64 p, [%1], %2;\nselp.u32 %0, 1, 0, p;\n}" : "=r"(ok) : "r"(a), "r"(ph) : "memory");
    return ok != 0;
}
#define SPINLOG 20
constexpr uint32_t SPIN_LIMIT = 1u << SPINLOG;
#define ABORT(code_) atomicCAS(&g_abort, 0u, (code_))
__device__ __forceinline__ void mbar_wait(uint32_t a, uint32_t ph) {
    uint32_t n = 0;
#pragma unroll 1
    while (!mbar_try(a, ph)) { if (++n > SPIN_LIMIT) { ABORT(1); break; } }
}
__device__ __forceinline__ void bar_sync(int id, int n) { asm volatile("bar.sync %0, %1;" :: "r"(id), "r"(n) : "memory"); }
__device__ __forceinline__ void bar_arrive(int id, int n) { asm volatile("bar.arrive %0, %1;" :: "r"(id), "r"(n) : "memory"); }

__device__ __forceinline__ void ldsm4(uint32_t* r, uint32_t a) {
    asm volatile("ldmatrix.sync.aligned.m8n8.x4.shared.b16 {%0,%1,%2,%3}, [%4];" : "=r"(r[0]), "=r"(r[1]), "=r"(r[2]), "=r"(r[3]) : "r"(a) : "memory");
}
__device__ __forceinline__ void ldsm4t(uint32_t* r, uint32_t a) {
    asm volatile("ldmatrix.sync.aligned.m8n8.x4.trans.shared.b16 {%0,%1,%2,%3}, [%4];" : "=r"(r[0]), "=r"(r[1]), "=r"(r[2]), "=r"(r[3]) : "r"(a) : "memory");
}
__device__ __forceinline__ void stsm4t(uint32_t a, uint32_t r0, uint32_t r1, uint32_t r2, uint32_t r3) {
    asm volatile("stmatrix.sync.aligned.m8n8.x4.trans.shared.b16 [%0], {%1,%2,%3,%4};" :: "r"(a), "r"(r0), "r"(r1), "r"(r2), "r"(r3) : "memory");
}
__device__ __forceinline__ void stsm4(uint32_t a, uint32_t r0, uint32_t r1, uint32_t r2, uint32_t r3) {
    asm volatile("stmatrix.sync.aligned.m8n8.x4.shared.b16 [%0], {%1,%2,%3,%4};" :: "r"(a), "r"(r0), "r"(r1), "r"(r2), "r"(r3) : "memory");
}
__device__ __forceinline__ uint32_t movm(uint32_t a) { uint32_t d; asm volatile("movmatrix.sync.aligned.m8n8.trans.b16 %0, %1;" : "=r"(d) : "r"(a)); return d; }
__device__ __forceinline__ void mma16816(float* d, uint32_t a0, uint32_t a1, uint32_t a2, uint32_t a3, uint32_t b0, uint32_t b1) {
    asm volatile("mma.sync.aligned.m16n8k16.row.col.f32.bf16.bf16.f32 {%0,%1,%2,%3}, {%4,%5,%6,%7}, {%8,%9}, {%0,%1,%2,%3};"
        : "+f"(d[0]), "+f"(d[1]), "+f"(d[2]), "+f"(d[3]) : "r"(a0), "r"(a1), "r"(a2), "r"(a3), "r"(b0), "r"(b1));
}
__device__ __forceinline__ void mma1688(float* d, uint32_t a0, uint32_t a1, uint32_t b0) {
    asm volatile("mma.sync.aligned.m16n8k8.row.col.f32.bf16.bf16.f32 {%0,%1,%2,%3}, {%4,%5}, {%6}, {%0,%1,%2,%3};"
        : "+f"(d[0]), "+f"(d[1]), "+f"(d[2]), "+f"(d[3]) : "r"(a0), "r"(a1), "r"(b0));
}
__device__ __forceinline__ uint32_t pack2(float a, float b) { uint32_t d; asm("cvt.rn.bf16x2.f32 %0, %1, %2;" : "=r"(d) : "f"(b), "f"(a)); return d; }
__device__ __forceinline__ float bf_lo(uint32_t w) { return __uint_as_float(w << 16); }
__device__ __forceinline__ float bf_hi(uint32_t w) { return __uint_as_float(w & 0xffff0000u); }
__device__ __forceinline__ float rbf(float x) { return __bfloat162float(__float2bfloat16_rn(x)); }

__device__ __forceinline__ void sts128(uint32_t a, float x, float y, float z, float w) { asm volatile("st.shared.v4.f32 [%0], {%1,%2,%3,%4};" :: "r"(a), "f"(x), "f"(y), "f"(z), "f"(w) : "memory"); }
__device__ __forceinline__ void sts128u(uint32_t a, uint32_t x, uint32_t y, uint32_t z, uint32_t w) { asm volatile("st.shared.v4.b32 [%0], {%1,%2,%3,%4};" :: "r"(a), "r"(x), "r"(y), "r"(z), "r"(w) : "memory"); }
__device__ __forceinline__ void sts64(uint32_t a, float x, float y) { asm volatile("st.shared.v2.f32 [%0], {%1,%2};" :: "r"(a), "f"(x), "f"(y) : "memory"); }
__device__ __forceinline__ float4 lds128(uint32_t a) { float4 v; asm volatile("ld.shared.v4.f32 {%0,%1,%2,%3}, [%4];" : "=f"(v.x), "=f"(v.y), "=f"(v.z), "=f"(v.w) : "r"(a) : "memory"); return v; }
__device__ __forceinline__ float2 lds64(uint32_t a) { float2 v; asm volatile("ld.shared.v2.f32 {%0,%1}, [%2];" : "=f"(v.x), "=f"(v.y) : "r"(a) : "memory"); return v; }
__device__ __forceinline__ uint2 lds64u(uint32_t a) { uint2 v; asm volatile("ld.shared.v2.b32 {%0,%1}, [%2];" : "=r"(v.x), "=r"(v.y) : "r"(a) : "memory"); return v; }
__device__ __forceinline__ float4 lds128v(uint32_t a) { float4 v; asm volatile("ld.volatile.shared.v4.f32 {%0,%1,%2,%3}, [%4];" : "=f"(v.x), "=f"(v.y), "=f"(v.z), "=f"(v.w) : "r"(a) : "memory"); return v; }
__device__ __forceinline__ float2 lds64v(uint32_t a) { float2 v; asm volatile("ld.volatile.shared.v2.f32 {%0,%1}, [%2];" : "=f"(v.x), "=f"(v.y) : "r"(a) : "memory"); return v; }
__device__ __forceinline__ uint4 lds128uv(uint32_t a) { uint4 v; asm volatile("ld.volatile.shared.v4.b32 {%0,%1,%2,%3}, [%4];" : "=r"(v.x), "=r"(v.y), "=r"(v.z), "=r"(v.w) : "r"(a) : "memory"); return v; }
__device__ __forceinline__ void st_async4(uint32_t a, float x, float y, float z, float w, uint32_t mb) {
    asm volatile("st.async.weak.shared::cluster.mbarrier::complete_tx::bytes.v4.f32 [%0], {%1,%2,%3,%4}, [%5];" :: "r"(a), "f"(x), "f"(y), "f"(z), "f"(w), "r"(mb) : "memory");
}
__device__ __forceinline__ void st_async2(uint32_t a, uint32_t x, uint32_t y, uint32_t mb) {
    asm volatile("st.async.weak.shared::cluster.mbarrier::complete_tx::bytes.v2.b32 [%0], {%1,%2}, [%3];" :: "r"(a), "r"(x), "r"(y), "r"(mb) : "memory");
}
__device__ __forceinline__ uint32_t ldg_rlx(const uint32_t* p) { uint32_t v; asm volatile("ld.relaxed.gpu.global.b32 %0, [%1];" : "=r"(v) : "l"(p) : "memory"); return v; }
__device__ __forceinline__ uint4 ldg_rlx4(const uint32_t* p) { uint4 v; asm volatile("ld.relaxed.gpu.global.v4.b32 {%0,%1,%2,%3}, [%4];" : "=r"(v.x), "=r"(v.y), "=r"(v.z), "=r"(v.w) : "l"(p) : "memory"); return v; }
__device__ __forceinline__ uint4 ldg_rlx4_if(const uint32_t* p, bool c) {
    uint4 v;
    asm volatile("{\n.reg .pred p;\nsetp.ne.u32 p, %5, 0;\nmov.b32 %0, 0;\nmov.b32 %1, 0;\nmov.b32 %2, 0;\nmov.b32 %3, 0;\n@p ld.relaxed.gpu.global.v4.b32 {%0,%1,%2,%3}, [%4];\n}"
                 : "=r"(v.x), "=r"(v.y), "=r"(v.z), "=r"(v.w) : "l"(p), "r"((uint32_t)c) : "memory");
    return v;
}
__device__ __forceinline__ void stg_rlx(uint32_t* p, uint32_t v) { asm volatile("st.relaxed.gpu.global.b32 [%0], %1;" :: "l"(p), "r"(v) : "memory"); }
__device__ __forceinline__ void tma2d(uint32_t dst, const CUtensorMap* tm, int c0, int c1, uint32_t mb) {
    asm volatile("cp.async.bulk.tensor.2d.shared::cluster.global.mbarrier::complete_tx::bytes [%0], [%1, {%3, %4}], [%2];"
        :: "r"(dst), "l"((uint64_t)tm), "r"(mb), "r"(c0), "r"(c1) : "memory");
}

__device__ __forceinline__ void tma3d(uint32_t dst, const CUtensorMap* tm, int row, int chunk, uint32_t mb) {
    asm volatile("cp.async.bulk.tensor.3d.shared::cluster.global.mbarrier::complete_tx::bytes [%0], [%1, {%3, %4, %5}], [%2];"
        :: "r"(dst), "l"((uint64_t)tm), "r"(mb), "r"(0), "r"(row), "r"(chunk) : "memory");
}
__device__ __forceinline__ void tma2d_mc(uint32_t dst, const CUtensorMap* tm, int c0, int c1, uint32_t mb) {
    asm volatile("cp.async.bulk.tensor.2d.shared::cluster.global.mbarrier::complete_tx::bytes.multicast::cluster [%0], [%1, {%3, %4}], [%2], %5;"
        :: "r"(dst), "l"((uint64_t)tm), "r"(mb), "r"(c0), "r"(c1), "h"((uint16_t)3) : "memory");
}
__device__ __forceinline__ void mbar_arrive2_if(uint32_t a, uint32_t pred) {
    asm volatile("{\n.reg .pred p;\nsetp.ne.u32 p, %1, 0;\n@p mbarrier.arrive.shared::cta.b64 _, [%0];\n@p mbarrier.arrive.shared::cluster.b64 _, [%2];\n}"
                 :: "r"(a), "r"(pred), "r"(a ^ 0x01000000u) : "memory");
}
__device__ __forceinline__ void tma_pf3d(const CUtensorMap* tm, int row, int chunk) {
    asm volatile("cp.async.bulk.prefetch.tensor.3d.L2.global.tile [%0, {%1, %2, %3}];" :: "l"((uint64_t)tm), "r"(0), "r"(row), "r"(chunk) : "memory");
}
__device__ __forceinline__ void tma_pf2d(const CUtensorMap* tm, int c0, int c1) {
    asm volatile("cp.async.bulk.prefetch.tensor.2d.L2.global.tile [%0, {%1, %2}];" :: "l"((uint64_t)tm), "r"(c0), "r"(c1) : "memory");
}
__device__ __forceinline__ void tma_store3d(const CUtensorMap* tm, uint32_t src, int row, int chunk) {
    asm volatile("cp.async.bulk.tensor.3d.global.shared::cta.bulk_group [%0, {%2, %3, %4}], [%1];" :: "l"((uint64_t)tm), "r"(src), "r"(0), "r"(row), "r"(chunk) : "memory");
}
__device__ __forceinline__ void bulk_store(void* dst, uint32_t src, uint32_t bytes) {
    asm volatile("cp.async.bulk.global.shared::cta.bulk_group [%0], [%1], %2;" :: "l"(dst), "r"(src), "r"(bytes) : "memory");
}
#define GT(slot)
#define CNT(k)
#define CNT2(k, c)
#define PS0 20
#define TS(i)
#define TSDECL
struct Maps { CUtensorMap wq, wk, wv, wo, wo2, kx, ox2, kx3, vx3, xn2, wg, wu; };
typedef Maps RecMaps;
__device__ __forceinline__ void st_rel(uint32_t* p, uint32_t v) { asm volatile("st.release.gpu.global.u32 [%0], %1;" :: "l"(p), "r"(v) : "memory"); }
#define PUBLISH(p, v) st_rel(p, v)
__device__ __forceinline__ uint2 ldg_rlx2(const uint32_t* p) { uint2 v; asm volatile("ld.relaxed.gpu.global.v2.b32 {%0,%1}, [%2];" : "=r"(v.x), "=r"(v.y) : "l"(p) : "memory"); return v; }
__device__ __forceinline__ void wait_eq2(const uint32_t* p, uint32_t e, int code) {
    uint32_t n = 0;
#pragma unroll 1
    while (true) { uint2 v = ldg_rlx2(p); if (v.x == e && v.y == e) break; __nanosleep(64); if (++n > SPIN_LIMIT) { ABORT(code); break; } }
}
__device__ __forceinline__ void wait_eq4(const uint32_t* p, uint32_t e, int code) {
    uint32_t n = 0;
#pragma unroll 1
    while (true) { uint4 v = ldg_rlx4(p); if (v.x == e && v.y == e && v.z == e && v.w == e) break; __nanosleep(64); if (++n > SPIN_LIMIT) { ABORT(code); break; } }
}
__device__ __forceinline__ void wait_rec(const uint32_t* p, uint32_t e, uint32_t steps) {
    uint32_t n = 0;
#pragma unroll 1
    while (true) {
        uint2 v = ldg_rlx2(p);
        if (__all_sync(0xffffffffu, (v.x >> 8) == e && (v.y >> 8) == e && (v.x & 255) >= steps && (v.y & 255) >= steps)) break;
        __nanosleep(64); if (++n > SPIN_LIMIT) { ABORT(8); break; }
    }
}

constexpr int R_QK1 = 0;
constexpr int R_WO = 65536;
constexpr int R_T = 131072;
constexpr int R_SLOT1 = R_T;
constexpr int R_MEMB = R_T + 24576;
constexpr int R_QP = R_MEMB + 8192;
constexpr int R_VRED = R_QP + 4096;
constexpr int R_STG = R_VRED + 2048;
constexpr int R_AX = R_STG + 2048;
constexpr int R_SLOT0 = 196608;
constexpr int R_SLOC = R_SLOT0 + 24576;
constexpr int R_SREM = R_SLOC + 1536;
constexpr int R_VB = R_SREM + 1536;
constexpr int R_MISC = R_VB + 2048;
constexpr int R_LT = R_MISC + 128;
constexpr int R_BAR = 229888;
constexpr int R_TS = 229888 + 128;
static_assert(R_AX + 24576 <= R_SLOT0 && R_LT + 2560 <= 229376, "smem map");
enum { MB_W0 = 0, MB_W1, MB_WV, MB_WO, MB_S, MB_FULL0, MB_FULL1, MB_V, MB_N };

__device__ __forceinline__ float ex2(float x) { float y; asm("ex2.approx.ftz.f32 %0, %1;" : "=f"(y) : "f"(x)); return y; }
__device__ __forceinline__ float rcpf(float x) { float y; asm("rcp.approx.ftz.f32 %0, %1;" : "=f"(y) : "f"(x)); return y; }
__device__ __forceinline__ void mma16816z(float* d, uint32_t a0, uint32_t a1, uint32_t a2, uint32_t a3, uint32_t b0, uint32_t b1) {
    asm volatile("mma.sync.aligned.m16n8k16.row.col.f32.bf16.bf16.f32 {%0,%1,%2,%3}, {%4,%5,%6,%7}, {%8,%9}, {%10,%10,%10,%10};"
        : "=f"(d[0]), "=f"(d[1]), "=f"(d[2]), "=f"(d[3]) : "r"(a0), "r"(a1), "r"(a2), "r"(a3), "r"(b0), "r"(b1), "f"(0.f));
}
__device__ __forceinline__ void mma1688hz(float* d, uint32_t a0, uint32_t a1, uint32_t b0) {
    asm volatile("mma.sync.aligned.m16n8k8.row.col.f32.f16.f16.f32 {%0,%1,%2,%3}, {%4,%5}, {%6}, {%7,%7,%7,%7};"
        : "=f"(d[0]), "=f"(d[1]), "=f"(d[2]), "=f"(d[3]) : "r"(a0), "r"(a1), "r"(b0), "f"(0.f));
}
#define MMA(d, a, b0, b1) mma16816(d, a[0], a[1], a[2], a[3], b0, b1)
#define MMAZ(d, a, b0, b1) mma16816z(d, a[0], a[1], a[2], a[3], b0, b1)
#define MMAF(first, d, a, b0, b1) do { if (first) MMAZ(d, a, b0, b1); else MMA(d, a, b0, b1); } while (0)

__device__ __forceinline__ uint32_t uni(uint32_t x) { return __reduce_max_sync(0xffffffffu, x); }
__device__ __forceinline__ void mbar_wait_u(uint32_t a, uint32_t ph) {
    uint32_t n = 0;
#pragma unroll 1
    while (!__all_sync(0xffffffffu, mbar_try(a, ph))) { if (++n > SPIN_LIMIT) { ABORT(1); break; } }
}
__device__ __forceinline__ void mbar_wait_p(uint32_t a, uint32_t ph) {
    asm volatile("{\n.reg .pred p, q;\n.reg .u32 n;\nmov.u32 n, 0;\nWL: mbarrier.try_wait.parity.shared::cta.b64 p, [%0], %1;\nadd.u32 n, n, 1;\n"
                 "setp.lt.and.u32 q, n, %2, !p;\n@q bra.uni WL;\n}" :: "r"(a), "r"(ph), "n"(SPIN_LIMIT) : "memory");
}
__device__ __forceinline__ uint32_t mbar_test(uint32_t a, uint32_t ph) {
    uint32_t ok;
    asm volatile("{\n.reg .pred p;\nmbarrier.test_wait.parity.shared::cta.b64 p, [%1], %2;\nselp.u32 %0, 1, 0, p;\n}" : "=r"(ok) : "r"(a), "r"(ph) : "memory");
    return ok;
}
__device__ __forceinline__ uint32_t opaque(uint32_t x) { return __shfl_sync(0xffffffffu, x, threadIdx.x & 31); }
__device__ __forceinline__ const uint32_t* mkptr(uint32_t lo, uint32_t hi) { uint64_t r; asm("mov.b64 %0, {%1, %2};" : "=l"(r) : "r"(lo), "r"(hi)); return (const uint32_t*)r; }
__device__ __forceinline__ uint32_t prmt(uint32_t a, uint32_t b, uint32_t s) { uint32_t d; asm("prmt.b32 %0, %1, %2, %3;" : "=r"(d) : "r"(a), "r"(b), "r"(s)); return d; }
__device__ __forceinline__ uint32_t packh2(float a, float b) { uint32_t d; asm("cvt.rn.f16x2.f32 %0, %1, %2;" : "=r"(d) : "f"(b), "f"(a)); return d; }
__device__ __forceinline__ uint32_t hadd2b(uint32_t a, uint32_t b) { uint32_t d; asm("add.rn.bf16x2 %0, %1, %2;" : "=r"(d) : "r"(a), "r"(b)); return d; }
__device__ __forceinline__ uint32_t hmul2b(uint32_t a, uint32_t b) { uint32_t d; asm("mul.rn.bf16x2 %0, %1, %2;" : "=r"(d) : "r"(a), "r"(b)); return d; }
__device__ __forceinline__ uint32_t amax2b(uint32_t a, uint32_t b) { uint32_t d; asm("max.xorsign.abs.bf16x2 %0, %1, %2;" : "=r"(d) : "r"(a), "r"(b)); return d; }
__device__ __forceinline__ uint32_t amax2h(uint32_t a, uint32_t b) { uint32_t d; asm("max.xorsign.abs.f16x2 %0, %1, %2;" : "=r"(d) : "r"(a), "r"(b)); return d; }
__device__ __forceinline__ void sts32(uint32_t a, uint32_t x) { asm volatile("st.shared.b32 [%0], %1;" :: "r"(a), "r"(x) : "memory"); }
__device__ __forceinline__ uint32_t lds32v_(uint32_t a) { uint32_t v; asm volatile("ld.volatile.shared.b32 %0, [%1];" : "=r"(v) : "r"(a) : "memory"); return v; }
__device__ __forceinline__ void stg4(void* p, uint4 v) { asm volatile("st.relaxed.gpu.global.v4.b32 [%0], {%1,%2,%3,%4};" :: "l"(p), "r"(v.x), "r"(v.y), "r"(v.z), "r"(v.w) : "memory"); }
__device__ __forceinline__ void lds_frag(uint32_t* r, uint32_t a) {
    asm volatile("ld.shared.v4.b32 {%0,%1,%2,%3}, [%4];" : "=r"(r[0]), "=r"(r[1]), "=r"(r[2]), "=r"(r[3]) : "r"(a) : "memory");
}
__device__ __forceinline__ void lds_fragv(uint32_t* r, uint32_t a) {
    asm volatile("ld.volatile.shared.v4.b32 {%0,%1,%2,%3}, [%4];" : "=r"(r[0]), "=r"(r[1]), "=r"(r[2]), "=r"(r[3]) : "r"(a) : "memory");
}
__device__ __forceinline__ uint32_t xorv(uint32_t a, uint32_t b) { uint32_t d; asm volatile("xor.b32 %0, %1, %2;" : "=r"(d) : "r"(a), "r"(b)); return d; }
#define SCHED(k) asm volatile("{\n.reg .pred p;\nsetp.ne.u32 p, %0, %1;\n@p bra.uni SD;\nSL: nanosleep.u32 64;\nbra.uni SL;\nSD:\n}" :: "r"(sbu - s), "n"(k) : "memory")
#define PINM() asm volatile("{\n.reg .pred p;\nsetp.eq.u32 p, %0, 1;\n@p st.shared.u32 [%0], %0;\n}" :: "r"(sbu) : "memory")
__device__ __forceinline__ uint32_t pack2v(float a, float b) { uint32_t d; asm volatile("cvt.rn.bf16x2.f32 %0, %1, %2;" : "=r"(d) : "f"(b), "f"(a)); return d; }
#define FU(x) __float_as_uint(x)
__device__ __forceinline__ uint32_t clk32() { uint32_t t; asm volatile("mov.u32 %0, %%clock;" : "=r"(t) :: "memory"); return t; }
__device__ __forceinline__ void spin_until(uint32_t t0, uint32_t d) {
    if (d) {
#pragma unroll 1
        while (__any_sync(0xffffffffu, clk32() - t0 < d)) {}
    }
}
constexpr int SH_OFF = 229376 + 384;
constexpr uint32_t HONE2 = 0x3c003c00u, HCNT2 = 0x50005000u;

__device__ __forceinline__ uint64_t desc_sw128(uint32_t addr, uint32_t lbo, uint32_t sbo) {
    return (uint64_t)((addr & 0x3FFFF) >> 4) | ((uint64_t)(lbo >> 4) << 16) | ((uint64_t)(sbo >> 4) << 32) | (1ull << 62);
}
#define DP 440
#define NAX 4
#define NXL 0
#define NCX 2
#define NCL 1
#define DC 100
#define DEC 0
#define KXI 5
#define ANB 3
#define BNB 3
#define CNB 3
#define SMA 0x40
#define SMB 0
#define SMC 0x01
#define IVA 0
#define RGA 168
#define RGC 160
#define RGB (504 - RGA - RGC)
#define NRW 6
#define NBR 16
#define E0 0
#define E1 6
#define E2 4
#define E3 8
#define IV 2
#define DEX 0
#define STAG 1
#define VDEP 0
#define AEARLY 0
#define VTP 1
#define TEARLY 1
#define DT 0
#define NB1 10
#define DB2 40
#define DITHER 0
#define DA 40
#define DB 40
#define DS 200

template <int K> __device__ __forceinline__ void sched(uint32_t key) {
    asm volatile("{\n.reg .pred p;\nsetp.ne.u32 p, %0, %1;\n@p bra.uni SD;\nSL: nanosleep.u32 64;\nbra.uni SL;\nSD:\n}" :: "r"(key), "n"(K) : "memory");
}
__device__ __forceinline__ void sched_i(int i, uint32_t key) {
    if (i == -1) sched<20>(key); if (i == 0) sched<21>(key); if (i == 1) sched<22>(key); if (i == 2) sched<23>(key);
    if (i == 3) sched<24>(key); if (i == 4) sched<25>(key); if (i == 5) sched<26>(key); if (i == 6) sched<27>(key);
}
template <int NB, int SM, class F>
__device__ __forceinline__ void g1(float* q0, float* k0, uint32_t (*wq)[4], uint32_t (*wk)[4], uint32_t ga, uint32_t key, F&& hook) {
    float q1[4], k1[4];
    uint32_t b[NB][4];
#pragma unroll
    for (int i = 0; i < NB; i++) ldsm4(b[i], ga + i * 512);
    hook(-1, b[0]);
    if (SM & 1) sched_i(-1, key);
#pragma unroll
    for (int i = 0; i < 8; i++) {
        uint32_t* c = b[i % NB];
        MMAF(i == 0, q0, wq[2 * i], c[0], c[1]); MMAF(i == 0, k0, wk[2 * i], c[0], c[1]);
        MMAF(i == 0, q1, wq[2 * i + 1], c[2], c[3]); MMAF(i == 0, k1, wk[2 * i + 1], c[2], c[3]);
        const uint32_t cc_[4] = {c[0], c[1], c[2], c[3]};
        if (i + NB < 8) ldsm4(b[i % NB], ga + (i + NB) * 512);
        hook(i, cc_);
        if ((SM >> (i + 1)) & 1) sched_i(i, key);
    }
#pragma unroll
    for (int i = 0; i < 4; i++) { q0[i] += q1[i]; k0[i] += k1[i]; }
}
__device__ __forceinline__ float frag_norm2(uint32_t (*w)[4]) {
    float d0[4], d1[4];
#pragma unroll
    for (int i = 0; i < 32; i++) { MMAF(i == 0, d0, w[i], w[i][0], w[i][2]); MMAF(i == 0, d1, w[i], w[i][1], w[i][3]); }
    const int lane = threadIdx.x & 31, g = lane >> 2, t = lane & 3;
    float v = g == 2 * t ? d0[0] + d1[2] : (g == 2 * t + 1 ? d0[1] + d1[3] : 0.f);
#pragma unroll
    for (int o = 16; o; o >>= 1) v += __shfl_xor_sync(0xffffffffu, v, o);
    return v;
}
__device__ __forceinline__ void load_slot(uint32_t sb, int c, int tile, const Maps& maps) {
    const uint32_t dst = sb + ((tile & 1) ? R_SLOT1 : R_SLOT0), mb = sb + R_BAR + 8 * (MB_FULL0 + (tile & 1));
    mbar_expect_tx(mb, 24576);
    tma2d(dst + 16384, &maps.kx, c * 64, tile * 64, mb);
    tma3d(dst, &maps.vx3, tile * 64, (c >> 1) * 2, mb);
}
__device__ __forceinline__ void put_mem0(uint32_t sb, int W, const bf16* __restrict__ mem0) {
    const int lane = threadIdx.x & 31;
    const uint4 m0 = *(const uint4*)(mem0 + (lane & 7) * DM + (W * 8 + (lane >> 3)) * 8), m1 = *(const uint4*)(mem0 + (lane & 7) * DM + (W * 8 + 4 + (lane >> 3)) * 8);
    bar_sync(3, 256);
    sts128u(sb + R_MEMB + W * 1024 + lane * 16, m0.x, m0.y, m0.z, m0.w);
    sts128u(sb + R_MEMB + W * 1024 + 512 + lane * 16, m1.x, m1.y, m1.z, m1.w);
}
#define GATHER1(HALF)                                                                                           \
        {                                                                                                       \
            float d0[4], d1[4], d2[4], d3[4];                                                                   \
            const uint4 x0 = ldg_rlx4(pm), x1 = ldg_rlx4(pm + AC1); const uint32_t y = ldg_rlx(px);               \
            mma1688hz(d0, x0.x, x0.y, lt.z); mma1688hz(d1, x1.x, x1.y, lt.z);                                   \
            cw = (lt.w & 0x4000u) ? prmt(x0.w, x1.w, 0x7632u) : y;                                              \
            mma1688hz(d2, x0.z, prmt(x0.w, y, lt.w), lt.z); mma1688hz(d3, x1.z, prmt(x1.w, y, lt.w | 0x2200u), lt.z);          \
            stsm4t(rG + R_MEMB + HALF * 4096, pack2(d0[0], d0[1]), pack2(d0[2], d0[3]), pack2(d2[0], d2[1]), pack2(d2[2], d2[3]));       \
            stsm4t(rG + R_MEMB + HALF * 4096 + 512, pack2(d1[0], d1[1]), pack2(d1[2], d1[3]), pack2(d3[0], d3[1]), pack2(d3[2], d3[3])); \
        }
__device__ __forceinline__ uint32_t h2b(uint32_t w) {
    uint32_t d;
    asm("{\n.reg .f16 l, h;\n.reg .f32 a, b;\nmov.b32 {l, h}, %1;\ncvt.f32.f16 a, l;\ncvt.f32.f16 b, h;\ncvt.rn.bf16x2.f32 %0, b, a;\n}" : "=r"(d) : "r"(w));
    return d;
}
#define GATHER2(HALF)                                                                                           \
        {                                                                                                       \
            const uint4 x0 = ldg_rlx4(pm), x1 = ldg_rlx4(pm + AC1); const uint32_t y = ldg_rlx(px);               \
            cw = (lt.w & 0x4000u) ? prmt(x0.w, x1.w, 0x7632u) : y;                                              \
            stsm4t(rG + R_MEMB + HALF * 4096, h2b(x0.x), h2b(x0.y), h2b(x0.z), h2b(prmt(x0.w, y, lt.w)));       \
            stsm4t(rG + R_MEMB + HALF * 4096 + 512, h2b(x1.x), h2b(x1.y), h2b(x1.z), h2b(prmt(x1.w, y, lt.w | 0x2200u))); \
        }
#define GATHER(HALF, PRE, SYNC, AFTER)                                                                                      \
        {                                                                                                       \
            const uint32_t so = aslot(s);                                                                       \
            const uint32_t ua = (glo + acc_off(HALF * 4 + fo, 0)) ^ so, ux = (glo + ext_base(HALF * 4 + fo)) ^ so; \
            uint4 lt;                                                                                           \
            lt.x = lds32v_(rL + R_LT); lt.y = lds32v_(rL + R_LT + 4); lt.z = DEC ? 0 : lds32v_(rL + R_LT + 8); lt.w = lds32v_(rL + R_LT + 12); \
            const uint32_t* pm = mkptr(ua + lt.x, ghi);                                                         \
            const uint32_t* px = mkptr(ux + lt.y, ghi);                                                         \
            PRE                                                                                                 \
            bar_sync(5, 384);                                                                                   \
            const uint32_t t0 = clk32();                                                                        \
            SYNC                                                                                                \
            spin_until(t0, DP + DITHER);                                                                                 \
            TS(11);                                                                                             \
            uint32_t cw, nr = 0;                                                                                \
            _Pragma("unroll 1") do {                                                                            \
                if (DEC) GATHER2(HALF) else GATHER1(HALF)                                                       \
                nr++;                                                                                           \
            } while (__any_sync(0xffffffffu, cw != HCNT2 && nr < SPIN_LIMIT));                                  \
            AFTER                                                                                               \
            CNT2(HALF * 4 + (s & 1) * 2 + (nr > 2), nr > 1);                                                    \
            TS(12);                                                                                             \
        }
#define GOBAR (fo == 3 ? 14 : 10 + fo)

__device__ __forceinline__ void rec_a(uint32_t sb, int c, const bf16* __restrict__ mem0, uint32_t epoch) {
    const int tid = threadIdx.x, lane = tid & 31, f = tid >> 5;
    uint32_t wq[16][4], wk[16][4];
    const int lrow = ((lane >> 4) << 3) + (lane & 7), lsel = (lane >> 3) & 1;
    {
        mbar_wait(sb + R_BAR + 8 * MB_W0, 0);
        if (c == 7 && tid == 0) GT(1421);
        const uint32_t a = sb + R_T + lrow * 128 + (((2 * f + lsel) ^ (lane & 7)) << 4);
#pragma unroll
        for (int kk = 0; kk < 16; kk++) { ldsm4t(wq[kk], a + kk * 2048); ldsm4t(wk[kk], a + 32768 + kk * 2048); }
        if (f == 3) wait_eq4(&g_f.xn[lane * 4], epoch, 13);
        __syncwarp();
        put_mem0(sb, f, mem0);
    }
    const uint32_t rL = opaque(sb + lane * 16), rG = opaque(sb + lane * 16 + f * 1024);
    const uint32_t sbu = uni(sb), fo = uni(f), cc = uni(c);
    const uint64_t gx = xpage();
    const uint32_t ghi = uni((uint32_t)(gx >> 32)), glo = uni((uint32_t)gx);
#pragma unroll
    for (int i = 0; i < NAX; i++) {
        sts128u(rG + R_AX + 4096 * i, wq[i][0], wq[i][1], wq[i][2], wq[i][3]);
        sts128u(rG + R_AX + 4096 * i + 512, wk[i][0], wk[i][1], wk[i][2], wk[i][3]);
    }
    sts128u(rL + R_LT + 512 + f * 512, (sb + R_SREM + (f >= 2 ? lane * 8 + f * 256 : lane * 16 + f * 1024)) ^ 0x01000000u, (sb + R_BAR + 8 * MB_S) ^ 0x01000000u,
            sb + R_QP + (lane >> 4) * 128 + lsel * 512 + (lane & 7) * 16 + (f == 3 ? 2048 : 0), sb + lrow * 128 + ((lsel ^ (lane & 7)) << 4));
    __syncwarp();
    if (tid == 0) GT(c * 8 + 1);
    TSDECL;
    const float cexp = 0.08838834764831845f * 1.4426950408889634f;
    float cs = cexp;
    mbar_wait_u(sbu + R_BAR + 8 * MB_FULL0, 0);
    auto step = [&](int s) -> bool {
        bar_sync(1, 128);
        TS(3);
        float q0[4], k0[4];
        uint32_t kx[4][4];
        uint4 ta;
        const uint32_t ro = ((s & 2) ? R_SLOT1 : R_SLOT0) + (s & 1) * 4096;
        g1<ANB, SMA>(q0, k0, wq, wk, rL + R_MEMB, sbu - s, [&](int i, const uint32_t*) {
            if (i == -1) {
#pragma unroll
                for (int n = NAX - NXL; n < NAX; n++) { lds_fragv(wq[n], rG + R_AX + 4096 * n); lds_fragv(wk[n], rG + R_AX + 4096 * n + 512); }
                ta = lds128uv(rL + R_LT + 512 + fo * 512);
            }
            if (i == KXI) {
#pragma unroll
                for (int kk = 0; kk < 4; kk++)
                    asm volatile("{\n.reg .pred p;\nsetp.lt.u32 p, %5, 2;\nmov.b32 %0, 0;\nmov.b32 %1, 0;\nmov.b32 %2, 0;\nmov.b32 %3, 0;\n"
                                 "@p ldmatrix.sync.aligned.m8n8.x4.shared.b16 {%0,%1,%2,%3}, [%4];\n}"
                                 : "=r"(kx[kk][0]), "=r"(kx[kk][1]), "=r"(kx[kk][2]), "=r"(kx[kk][3]) : "r"((ta.w ^ (kk * 32)) + (ro + 16384 + fo * 2048)), "r"(fo) : "memory");
            }
            if (i == IVA) bar_arrive(GOBAR, 96);
        });
        stsm4t(rG + R_QP, pack2(q0[0], q0[1]), pack2(q0[2], q0[3]), pack2(k0[0], k0[1]), pack2(k0[2], k0[3]));
        TS(4);
        if (fo < 2) {
            bar_sync(3, 256);
            TS(5);
            uint32_t qa[4][4];
#pragma unroll
            for (int kk = 0; kk < 4; kk++) { if (kk == 2) bar_arrive(13, 256); ldsm4(qa[kk], ta.z + kk * 1024); }
            float s0[4], s1[4], s2[4], s3[4];
            MMAZ(s0, qa[0], kx[0][0], kx[0][1]); MMAZ(s1, qa[0], kx[0][2], kx[0][3]);
            MMAZ(s2, qa[1], kx[1][0], kx[1][1]); MMAZ(s3, qa[1], kx[1][2], kx[1][3]);
            MMA(s0, qa[2], kx[2][0], kx[2][1]); MMA(s1, qa[2], kx[2][2], kx[2][3]);
            MMA(s2, qa[3], kx[3][0], kx[3][1]); MMA(s3, qa[3], kx[3][2], kx[3][3]);
            const float x = ((s0[0] + s0[2]) + (s2[0] + s2[2])) * cs, y = ((s0[1] + s0[3]) + (s2[1] + s2[3])) * cs;
            const float z = ((s1[0] + s1[2]) + (s3[0] + s3[2])) * cs, w = ((s1[1] + s1[3]) + (s3[1] + s3[3])) * cs;
            st_async4(ta.x, x, y, z, w, ta.y);
            sts128(rG + R_SLOC, x, y, z, w);
        } else {
            bar_sync(3, 256);
            TS(5);
            uint32_t kb[4], kc[4], qa[4], qc[4];
            ldsm4(kb, ta.z + 256); ldsm4(qa, ta.z); bar_arrive(13, 256); ldsm4(kc, ta.z + 1280); ldsm4(qc, ta.z + 1024);
            const uint32_t k0_ = hadd2b(kb[0], kb[1]), k1_ = hadd2b(kb[2], kb[3]), k2_ = hadd2b(kc[0], kc[1]), k3_ = hadd2b(kc[2], kc[3]);
            float s0[4], s2[4];
            MMAZ(s0, qa, k0_, k1_); MMAZ(s2, qc, k2_, k3_);
            const float x = ((s0[0] + s0[2]) + (s2[0] + s2[2])) * cs, y = ((s0[1] + s0[3]) + (s2[1] + s2[3])) * cs;
            st_async2(ta.x, FU(x), FU(y), ta.y);
            sts64((ta.x ^ 0x01000000u) + (R_SLOC - R_SREM), x, y);
            sts128u(rL + R_STG + (fo & 1) * 512, k0_, k1_, k2_, k3_);
            bar_arrive(9, 192);
        }
        TS(6);
        const uint32_t r8 = (rL + sbu) >> 1;
        uint32_t vt00[4], vt01[4], vt10[4], vt11[4];
        const uint32_t rV = ta.w ^ ((fo & 1) * 64), vo = ro + (fo >> 1) * 8192;
        if (VTP < 2) { ldsm4t(vt00, rV + vo); ldsm4t(vt10, (rV ^ 32) + vo); }
        if (VTP < 1) { ldsm4t(vt01, rV + vo + 2048); ldsm4t(vt11, (rV ^ 32) + vo + 2048); }
        bar_sync(4, 128);
        const float4 l0 = lds128v(rL + R_SLOC), l1 = lds128v(rL + R_SLOC + 1024);
        const float2 l2 = lds64v(r8 + R_SLOC + 512), l3 = lds64v(r8 + R_SLOC + 768);
        if (E2) bar_arrive(15, 256);
        TS(7);
        if (s == NSEG - 1) { mbar_wait_u(sbu + R_BAR + 8 * MB_S, 1); mbar_wait_u(sbu + R_BAR + 8 * MB_V, 1); return true; }
        mbar_wait_p(sbu + R_BAR + 8 * MB_S, s & 1);
        TS(8);
        {
            const float4 r0 = lds128v(rL + R_SREM), r1 = lds128v(rL + R_SREM + 1024);
            const float2 r2 = lds64v(r8 + R_SREM + 512), r3 = lds64v(r8 + R_SREM + 768);
            if (VTP >= 1) PINM();
            if (VTP >= 2) { ldsm4t(vt00, rV + vo); ldsm4t(vt10, (rV ^ 32) + vo); }
            if (VTP >= 1) { ldsm4t(vt01, rV + vo + 2048); ldsm4t(vt11, (rV ^ 32) + vo + 2048); }
            float sv[10];
            sv[0] = l0.x + r0.x; sv[1] = l0.y + r0.y; sv[2] = l0.z + r0.z; sv[3] = l0.w + r0.w;
            sv[4] = l1.x + r1.x; sv[5] = l1.y + r1.y; sv[6] = l1.z + r1.z; sv[7] = l1.w + r1.w;
            sv[8] = ((l2.x + l3.x) + r2.x) + r3.x; sv[9] = ((l2.y + l3.y) + r2.y) + r3.y;
            float m = fmaxf(fmaxf(fmaxf(sv[0], sv[1]), fmaxf(sv[2], sv[3])), fmaxf(fmaxf(sv[4], sv[5]), fmaxf(sv[6], sv[7])));
            m = fmaxf(m, fmaxf(sv[8], sv[9]));
            {
                const float m1 = __shfl_xor_sync(0xffffffffu, m, 1), m2 = __shfl_xor_sync(0xffffffffu, m, 2), m3 = __shfl_xor_sync(0xffffffffu, m, 3);
                m = fmaxf(fmaxf(m, m1), fmaxf(m2, m3));
            }
            const uint32_t ONE2 = 0x3f803f80u;
            float o0[4], o1[4], sm[4];
            const uint32_t pb0 = pack2(ex2(sv[0] - m), ex2(sv[1] - m)), pb1 = pack2(ex2(sv[2] - m), ex2(sv[3] - m));
            mma16816z(sm, ONE2, ONE2, ONE2, ONE2, pb0, pb1);
            MMAZ(o0, vt00, pb0, pb1); MMAZ(o1, vt10, pb0, pb1);
            const uint32_t z = (VDEP == 0 ? FU(m) : pb0) & (sbu & 8);
            const uint32_t vok = mbar_test(sbu + R_BAR + 8 * MB_V + z, s & 1);
            const uint32_t rv = r8 + vok * 8;
            float2 va = lds64v(rv + R_VB - 8 + fo * 512);
            bar_arrive(13, 256);
            float2 vb = lds64v(rv + R_VB - 8 + fo * 512 + 256);
            float sig = __uint_as_float(lds32v_(sbu + R_MISC + 40));
            const uint32_t pb2 = pack2(ex2(sv[4] - m), ex2(sv[5] - m)), pb3 = pack2(ex2(sv[6] - m), ex2(sv[7] - m));
            mma16816(sm, ONE2, ONE2, ONE2, ONE2, pb2, pb3);
            const uint32_t pb4 = pack2(ex2(sv[8] - m), ex2(sv[9] - m));
            MMA(o0, vt01, pb2, pb3); MMA(o1, vt11, pb2, pb3);
            mma1688(sm, ONE2, ONE2, pb4);
            const float z0 = rcpf(sm[0]), z1 = rcpf(sm[1]);
#define PUT_O()                                                                                                   \
            {                                                                                                     \
                float a0[4] = {o0[0], o0[1], o0[2], o0[3]}, a1[4] = {o1[0], o1[1], o1[2], o1[3]};                 \
                mma1688(a0, FU(va.x), FU(va.y), pb4); mma1688(a1, FU(vb.x), FU(vb.y), pb4);                       \
                const float i0 = z0 * sig, i1 = z1 * sig;                                                         \
                stsm4t(rG + R_QP, pack2(a0[0] * i0, a0[1] * i1), pack2(a0[2] * i0, a0[3] * i1), pack2(a1[0] * i0, a1[1] * i1), pack2(a1[2] * i0, a1[3] * i1)); \
            }
            PUT_O()
            asm volatile("{\n.reg .pred p;\nsetp.ne.u32 p, %0, 0;\n@p bar.arrive 8, 256;\n}" :: "r"(vok) : "memory");
            if (__builtin_expect(__any_sync(0xffffffffu, vok == 0), 0)) {
                mbar_wait_p(sbu + R_BAR + 8 * MB_V, s & 1);
                va = lds64v(r8 + R_VB + fo * 512); vb = lds64v(r8 + R_VB + fo * 512 + 256);
                sig = __uint_as_float(lds32v_(sbu + R_MISC + 40));
                PUT_O()
                bar_arrive(8, 256);
                CNT(8);
            }
            const float r = __uint_as_float(0x7f000000u - FU(sig));
            cs = cexp * r * (fo >= 2 ? r : 1.f);
        }
        TS(10);
        return false;
    };
    step(0);
#pragma unroll 1
    for (int s = 0;; s++) {
        if (s & 1) mbar_wait_p(sbu + R_BAR + 8 * (MB_FULL0 + (((s + 1) >> 1) & 1)), ((s + 1) >> 2) & 1);
        auto early = [&]() {
            SCHED(13);
#pragma unroll
            for (int i = 0; i < NAX - NXL; i++) { lds_fragv(wq[i], rG + R_AX + 4096 * i); lds_fragv(wk[i], rG + R_AX + 4096 * i + 512); }
        };
        GATHER(0, , early();, )
        if (step(s + 1)) break;
    }
    CNT(9);
    if (rG == sbu) GT(cc * 8 + 4);
}

__device__ __forceinline__ void rec_b(uint32_t sb, int c, uint32_t epoch) {
    const int tid = threadIdx.x - 128, lane = tid & 31, f = tid >> 5;
    uint32_t wq[16][4], wk[16][4], wo[32][4];
    const int lrow = ((lane >> 4) << 3) + (lane & 7), lsel = (lane >> 3) & 1;
    const uint32_t rL = opaque(sb + lane * 16), rW = opaque(sb + lane * 16 + f * 16384);
    const uint32_t sbu = uni(sb), fo = uni(f), cc = uni(c), po = cc & 1, ep = uni(epoch);
    {
        mbar_wait(sb + R_BAR + 8 * MB_WO, 0);
        if (c == 7 && tid == 0) GT(1426);
        const uint32_t aO = sb + R_WO + f * 16384 + lrow * 128 + ((lsel ^ (lane & 7)) << 4);
#pragma unroll
        for (int i = 0; i < 32; i++) {
            const int tile = STAG ? (i >> 4) * 2 + (i & 1) : i & 3, kk = STAG ? (i >> 1) & 7 : i >> 2;
            ldsm4t(wo[i], (aO ^ (32 * tile)) + kk * 2048);
        }
        const float no = frag_norm2(wo);
        if (lane == 0) sts32(sb + R_MISC + 80 + f * 4, FU(no));
        __syncwarp();
        bar_arrive(15, 256);
#pragma unroll
        for (int i = NRW; i < 32; i++) sts128u(rW + R_WO + i * 512, wo[i][0], wo[i][1], wo[i][2], wo[i][3]);
        mbar_wait(sb + R_BAR + 8 * MB_W1, 0);
        if (c == 7 && tid == 0) GT(1422);
        if (tid == 0) stg_rlx(&g_f.rload[c], epoch);
        __syncwarp();
        const uint32_t a = sb + R_QK1 + lrow * 128 + (((2 * f + lsel) ^ (lane & 7)) << 4);
#pragma unroll
        for (int kk = 0; kk < 16; kk++) { ldsm4t(wq[kk], a + kk * 2048); ldsm4t(wk[kk], a + 32768 + kk * 2048); }
        bar_sync(13, 128);
#pragma unroll
        for (int i = 0; i < 16; i++) {
            sts128u(rW + R_QK1 + i * 1024, wq[i][0], wq[i][1], wq[i][2], wq[i][3]);
            sts128u(rW + R_QK1 + i * 1024 + 512, wk[i][0], wk[i][1], wk[i][2], wk[i][3]);
        }
        __syncwarp();
    }
    const uint64_t gx = xpage();
    const uint32_t ghi = uni((uint32_t)(gx >> 32)), glo = uni((uint32_t)gx);
    TSDECL;
#pragma unroll 1
    for (int s = 0;; s++) {
        bar_sync(2, 256);
        TS(3);
        float q0[4], k0[4];
        g1<BNB, SMB>(q0, k0, wq, wk, rL + R_MEMB + 4096, sbu - s, [&](int i, const uint32_t*) {
            if (i >= 2 && i < 6) {
#pragma unroll
                for (int n = NRW + (i - 2) * E0 / 4; n < NRW + (i - 1) * E0 / 4; n++) lds_fragv(wo[n], rW + R_WO + n * 512);
            }
            if (i == IV) bar_arrive(GOBAR, 96);
        });
        stsm4t(rL + fo * 1024 + R_QP + 512, pack2(q0[0], q0[1]), pack2(q0[2], q0[3]), pack2(k0[0], k0[1]), pack2(k0[2], k0[3]));
        bar_arrive(3, 256);
        TS(4);
        const uint32_t so = aslot(s);
        const uint4 lt = lds128uv(rL + R_LT);
        uint32_t* pm = (uint32_t*)mkptr(((glo + acc_off(po * 4 + fo, 0)) ^ so) + lt.x, ghi);
        uint32_t* px = (uint32_t*)mkptr(((glo + ext_base(po * 4 + fo)) ^ so) + lt.y, ghi);
        bar_sync(13, 256);
#pragma unroll
        for (int n = NRW + E0; n < NRW + E0 + E1; n++) lds_fragv(wo[n], rW + R_WO + n * 512);
        if (E2) bar_sync(15, 256);
        if (s == NSEG - 1) break;
        TS(5);
#pragma unroll
        for (int n = NRW + E0 + E1; n < NRW + E0 + E1 + E2; n++) lds_fragv(wo[n], rW + R_WO + n * 512);
        bar_sync(13, 256);
#pragma unroll
        for (int n = NRW + E0 + E1 + E2; n < NRW + E0 + E1 + E2 + E3; n++) lds_fragv(wo[n], rW + R_WO + n * 512);
        SCHED(4);
        TS(6);
        bar_sync(8, 256);
        TS(7);
        {
            float o[4][4];
            uint32_t b[4][4];
#pragma unroll
            for (int i = 0; i < 4; i++) ldsm4(b[i], rL + R_QP + i * 1024);
            PINM();
#pragma unroll
            for (int n = NRW + E0 + E1 + E2 + E3; n < 32; n++) lds_fragv(wo[n], rW + R_WO + n * 512);
            float p[4][4];
#define G2_STEP(o, hf, kk) _Pragma("unroll") for (int i = 0; i < 2; i++) MMAF((kk) < 2, o[((kk) & 1) * 2 + i], wo[(hf) * 16 + (kk) * 2 + i], b[(kk) >> 1][((kk) & 1) * 2], b[(kk) >> 1][((kk) & 1) * 2 + 1])
#define G2_RED(o, wl, ptr) const uint32_t wl = packh2(o[1][2] + o[3][2], o[1][3] + o[3][3]);                          \
                asm volatile("red.relaxed.gpu.global.add.noftz.v4.f16x2 [%0], {%1,%2,%3,%4};" :: "l"(ptr),           \
                    "r"(packh2(o[0][0] + o[2][0], o[0][1] + o[2][1])), "r"(packh2(o[0][2] + o[2][2], o[0][3] + o[2][3])), \
                    "r"(packh2(o[1][0] + o[3][0], o[1][1] + o[3][1])), "r"(prmt(wl, HONE2, lt.w)) : "memory")
#pragma unroll
            for (int kk = 0; kk < 8; kk++) { G2_STEP(o, 0, kk); }
            SCHED(11);
#pragma unroll
            for (int kk = 0; kk < 4; kk++) { G2_STEP(p, 1, kk); }
            G2_RED(o, w3, pm);
            SCHED(12);
#pragma unroll
            for (int kk = 4; kk < 8; kk++) { G2_STEP(p, 1, kk); }
            G2_RED(p, w7, pm + AC1);
            asm volatile("red.relaxed.gpu.global.add.noftz.f16x2 [%0], %1;" :: "l"(px), "r"((lt.w & 0x4000u) ? prmt(w3, w7, 0x7632u) : HONE2) : "memory");
        }
        bar_arrive(5, 384);
        asm volatile("{\n.reg .pred p;\nsetp.eq.u32 p, %0, %1;\n@p mbarrier.arrive.expect_tx.shared::cta.b64 _, [%2], 1536;\n}"
                     :: "r"(rW), "r"(sbu), "r"(sbu + R_BAR + 8 * MB_S) : "memory");
        const uint32_t tb = clk32();
        spin_until(tb, DB);
        TS(8);
#pragma unroll
        for (int i = 0; i < NBR; i++) {
            if (i == NB1) spin_until(tb, DP + DB2);
            lds_fragv(wq[i], rW + R_QK1 + i * 1024); lds_fragv(wk[i], rW + R_QK1 + i * 1024 + 512);
        }
        TS(9);
    }
}

#undef lds_fragv
__device__ __forceinline__ void rec_first_loads(uint32_t sb, int c, const Maps& maps) {
    const uint32_t bar = sb + R_BAR;
    const int F0 = c * 64;
    mbar_expect_tx(bar + 8 * MB_W0, 65536); mbar_expect_tx(bar + 8 * MB_WO, 65536); mbar_expect_tx(bar + 8 * MB_WV, 65536);
    tma2d(sb + R_QK1, &maps.wv, F0, 0, bar + 8 * MB_WV); tma2d(sb + R_QK1 + 32768, &maps.wv, F0, 256, bar + 8 * MB_WV);
    for (int i = 0; i < 4; i++) tma2d(sb + R_WO + i * 16384, &maps.wo, (c & 1) * 256 + i * 64, (c >> 1) * 128, bar + 8 * MB_WO);
    tma2d(sb + R_T + 32768, &maps.wk, F0, 0, bar + 8 * MB_W0); tma2d(sb + R_T, &maps.wq, F0, 0, bar + 8 * MB_W0);
    mbar_expect_tx(bar + 8 * MB_S, 1536);
}
__device__ __forceinline__ void rec_c(uint32_t sb, int c, const bf16* __restrict__ mem0, const Maps& maps, uint32_t epoch) {
    const int tid = threadIdx.x - 256, lane = tid & 31, u = tid >> 5;
    const uint32_t bar = sb + R_BAR;
    const int lrow = ((lane >> 4) << 3) + (lane & 7), lsel = (lane >> 3) & 1;
    const int kh = u >> 1, j = u & 1;
    uint32_t wv[32][4];
    {
        if (u == 0) {
            sts128u(sb + lane * 16 + R_LT, acc_off(0, lane), ext_lane(lane),
                    ((lane >> 2) == 2 * (lane & 3) ? 0x3c00u : 0u) | ((lane >> 2) == 2 * (lane & 3) + 1 ? 0x3c000000u : 0u), (lane & 1) ? 0x5410u : 0x3210u);
        }
        mbar_wait(bar + 8 * MB_WV, 0);
        if (c == 7 && tid == 0) GT(1425);
        const uint32_t aa = sb + R_QK1 + (kh * 256 + lrow) * 128 + (((4 * j + 2 * kh + lsel) ^ (lane & 7)) << 4);
#pragma unroll
        for (int kk = 0; kk < 16; kk++) { ldsm4t(wv[kk], aa + kk * 2048); ldsm4t(wv[16 + kk], (aa ^ 32) + kk * 2048); }
        bar_sync(9, 128);
        if (tid == 0) {
            asm volatile("fence.proxy.async.shared::cta;" ::: "memory");
            mbar_expect_tx(bar + 8 * MB_W1, 65536);
            tma2d(sb + R_QK1 + 32768, &maps.wk, c * 64, 256, bar + 8 * MB_W1); tma2d(sb + R_QK1, &maps.wq, c * 64, 256, bar + 8 * MB_W1);
        }
        __syncwarp();
        const float nv = frag_norm2(wv);
        if (lane == 0) sts32(sb + R_MISC + 64 + u * 4, FU(nv));
        if (tid == 96) { wait_eq2(&g_f.kv[0][c >> 1][0], epoch, 6); load_slot(sb, c, 0, maps); }
        __syncwarp();
        bar_sync(15, 256);
        if (u == 0) {
            if (lane == 0) {
                const float4 a = lds128(sb + R_MISC + 64), b = lds128(sb + R_MISC + 80);
                stg4(&g_f.norm[c], make_uint4(FU((a.x + a.y) + (a.z + a.w)), epoch, FU((b.x + b.y) + (b.z + b.w)), epoch));
            }
            __syncwarp();
            uint4 r, q; uint32_t n = 0;
#pragma unroll 1
            while (true) {
                r = ldg_rlx4((const uint32_t*)&g_f.norm[lane]); q = ldg_rlx4((const uint32_t*)&g_f.norm[lane + 32]);
                if (__all_sync(0xffffffffu, r.y == epoch && r.w == epoch && q.y == epoch && q.w == epoch)) break;
                __nanosleep(32);
                if (++n > SPIN_LIMIT) { ABORT(5); break; }
            }
            float nv2 = __uint_as_float(r.x) + __uint_as_float(q.x), no = __uint_as_float(r.z) + __uint_as_float(q.z);
#pragma unroll
            for (int o = 16; o; o >>= 1) { nv2 += __shfl_xor_sync(0xffffffffu, nv2, o); no += __shfl_xor_sync(0xffffffffu, no, o); }
            const int lc = ((int)(FU(nv2) >> 23) + (int)(FU(no) >> 23) - 252 + 9 + 1) >> 1;
            if (lane == 0) sts32(sb + R_MISC + 16, 140 - lc);
        }
        __syncwarp();
        put_mem0(sb, 4 + u, mem0);
    }
    const uint32_t rL = opaque(sb + lane * 16), rG = opaque(sb + lane * 16 + u * 1024);
    const uint32_t sbu = uni(sb), fo = uni(u), cc = uni(c), ep = uni(epoch);
    const uint64_t gx = xpage();
    const uint32_t ghi = uni((uint32_t)(gx >> 32)), glo = uni((uint32_t)gx);
    constexpr int CX = R_AX + NAX * 4096;
    static_assert(NAX + NCX <= 6, "AX");
#pragma unroll
    for (int i = 0; i < NCX; i++) {
        sts128u(rG + CX + 4096 * i, wv[i][0], wv[i][1], wv[i][2], wv[i][3]);
        sts128u(rG + CX + 4096 * i + 512, wv[16 + i][0], wv[16 + i][1], wv[16 + i][2], wv[16 + i][3]);
    }
    __syncwarp();
    TSDECL;
    uint32_t rpb = 0x3f800000u;
    bar_arrive(2, 256);
#pragma unroll 1
    for (int s = 0;; s++) {
        if (TEARLY && fo == 3 && !(s & 1) && s > 0 && s + 2 < NSEG) {
            if (rL == sbu) load_slot(sbu, cc, (s + 2) >> 1, maps);
            __syncwarp();
        } else spin_until(clk32(), DC);
#pragma unroll
        for (int i = NCX - NCL; i < NCX; i++) { lds_fragv(wv[i], rG + CX + 4096 * i); lds_fragv(wv[16 + i], rG + CX + 4096 * i + 512); }
        bar_sync(GOBAR, 96);
        TS(3);
        float v0[4], v1[4];
        uint32_t mx, my;
        g1<CNB, SMC>(v0, v1, wv, wv + 16, rL + R_MEMB + (fo >> 1) * 4096, sbu - s, [&](int i, const uint32_t* c_) {
            if (i >= 0) {
                mx = amax2b(i == 0 ? c_[0] : amax2b(mx, c_[0]), c_[1]);
                my = amax2b(i == 0 ? c_[2] : amax2b(my, c_[2]), c_[3]);
            }
        });
        TS(4);
        const uint32_t l16 = (rL ^ sbu) | (lds32v_(rL + R_LT + 4) & 1);
        const uint32_t r8 = sbu + (l16 >> 1);
        {
            sts128(rL + R_VRED + fo * 512, v1[0], v1[1], v1[2], v1[3]);
            const uint32_t d = r8 + R_VB + ((cc & 1) * 4 + (fo & 1) * 2 + (fo >> 1)) * 256;
            const uint32_t dr = xorv(d, 0x01000000u), br = xorv(sbu + R_BAR + 8 * MB_V, 0x01000000u);
            bar_sync(6 + (fo & 1), 64);
            const float4 a0 = lds128(rL + R_VRED + (fo ^ 2) * 512);
            const float rp = __uint_as_float(rpb);
            const uint32_t w0 = pack2((v0[0] + a0.x) * rp, (v0[1] + a0.y) * rp), w1 = pack2((v0[2] + a0.z) * rp, (v0[3] + a0.w) * rp);
            st_async2(dr, w0, w1, br);
            sts64(d, __uint_as_float(w0), __uint_as_float(w1));
            mx = amax2b(mx, my);
            mx = __reduce_max_sync(0xffffffffu, amax2b(mx, mx << 16) & 0x7f800000u);
            if (fo == 2) { sts32(sbu + R_MISC + 8, mx); bar_arrive(6, 64); }
            if (fo == 0) {
                bar_sync(6, 64);
                const int em = (int)(max(mx, lds32v_(sbu + R_MISC + 8)) >> 23) + (int)(rpb >> 23) - 127;
                const int es = min(max((int)lds32v_(sbu + R_MISC + 16) - max(em, 127), -60), 60);
                sts32(sbu + R_MISC + 40, (127 + es) << 23);
            }
            __syncwarp();
            asm volatile("{\n.reg .pred p;\nsetp.eq.u32 p, %0, %1;\n@p mbarrier.arrive.expect_tx.shared::cta.b64 _, [%2], 256;\n}"
                         :: "r"(rL), "r"(sbu), "r"(sbu + R_BAR + 8 * MB_V) : "memory");
        }
        TS(5);
        if (fo == 1) {
            bar_sync(9, 192);
            uint8_t* dst = (uint8_t*)&g_KVf[s][cc >> 1][(cc & 1) * 256] + l16;
            const uint32_t r2 = prmt(rpb, 0, 0x3232u);
#pragma unroll
            for (int i = 0; i < 2; i++) {
                const uint4 a = lds128uv(rL + R_STG + i * 512);
                stg4(dst + i * 512, make_uint4(~hmul2b(a.x, r2), ~hmul2b(a.y, r2), ~hmul2b(a.z, r2), ~hmul2b(a.w, r2)));
                const float2 b0 = lds64v(r8 + R_VB + (cc & 1) * 1024 + i * 512), b1 = lds64v(r8 + R_VB + (cc & 1) * 1024 + i * 512 + 256);
                stg4(dst + 2048 + i * 512, make_uint4(~FU(b0.x), ~FU(b0.y), ~FU(b1.x), ~FU(b1.y)));
            }
            __syncwarp();
            if (l16 == 0) { stg_rlx(&g_f.rec[cc], (ep << 8) | (s + 1)); if (s == NSEG - 1) GT(1500 + cc); }
            __syncwarp();
        } else {
            bar_arrive(9, 192);
            if (fo == 2) {
                if (l16 < 272) stg4((void*)mkptr((glo + zero_off(cc, l16 >> 4)) ^ aslot(s + 4), ghi), make_uint4(0, 0, 0, 0));
                __syncwarp();
            } else if (fo == 3) {
                if (((s & 1) || s == 0) && s + 3 < NSEG) {
                    const uint32_t* fp = &g_f.kv[(s + 3) >> 1][cc >> 1][0];
                    uint32_t n = 0;
#pragma unroll 1
                    while (true) {
                        const uint2 v = ldg_rlx2(fp);
                        if (__all_sync(0xffffffffu, v.x == ep && v.y == ep)) break;
                        __nanosleep(64);
                        if (++n > SPIN_LIMIT) { ABORT(6); break; }
                    }
                }
                if (!(s & 1) && s + 2 < NSEG && (!TEARLY || s == 0)) {
                    if (s == 0) asm volatile("fence.proxy.async.shared::cta;" ::: "memory");
                    spin_until(clk32(), DT);
                    if (l16 == 0) load_slot(sbu, cc, (s + 2) >> 1, maps);
                    __syncwarp();
                }
            }
        }
        TS(6);
        if (s == NSEG - 1) break;
        auto early = [&]() {
#pragma unroll
            for (int i = 0; i < NCX - NCL; i++) { lds_fragv(wv[i], rG + CX + 4096 * i); lds_fragv(wv[16 + i], rG + CX + 4096 * i + 512); }
        };
        GATHER(1, , early(); rpb = 0x7f000000u - lds32v_(sbu + R_MISC + 40);, bar_arrive(2, 256);)
    }
}

__device__ __forceinline__ bool cand_better(float v, int i, float bv, int bi) { return v > bv || (v == bv && i < bi); }
constexpr int F_WG = 0, F_WU = 32768, F_WD = 65536, F_X = 98304, F_RED = F_X + 4096, F_ACT = F_RED + 8192, F_SEL = F_ACT + 256;

__device__ __noinline__ void ffn_phase(const Maps& maps, const bf16* __restrict__ wd, bf16* __restrict__ out) {
    extern __shared__ __align__(1024) uint8_t smem[];
    const uint32_t sb = smem_u32(smem);
    const int c = ((volatile int*)(smem + SH_OFF))[8];
    const uint32_t epoch = ((volatile uint32_t*)(smem + SH_OFF))[9];
    const int tid = threadIdx.x;
    constexpr int NWK = FF / 32;
    const bool worker = c < NWK;
    bar_sync(0, 384);
    const uint32_t mb = sb + R_BAR + 8 * MB_W0;
    if (tid == 32 && worker) {
        asm volatile("fence.proxy.async.shared::cta;" ::: "memory");
        mbar_expect_tx(mb, 98304);
        tma2d(sb + F_WG, &maps.wg, c * 32, 0, mb); tma2d(sb + F_WG + 16384, &maps.wg, c * 32, 256, mb);
        tma2d(sb + F_WU, &maps.wu, c * 32, 0, mb); tma2d(sb + F_WU + 16384, &maps.wu, c * 32, 256, mb);
        asm volatile("cp.async.bulk.shared::cluster.global.mbarrier::complete_tx::bytes [%0], [%1], %2, [%3];"
            :: "r"(sb + F_WD), "l"(wd + (size_t)c * 32 * DM), "r"(32768), "r"(mb) : "memory");
    }
    int p0 = -1, p1 = -1;
#pragma unroll 1
    for (int pass = 0; pass < 2; pass++) {
        if (tid < 32) {
            const uint32_t tag = epoch & 0xfffffu;
            uint4 r[4]; uint32_t n = 0;
            const int t3 = tid + 96 < NFW ? tid + 96 : tid;
#pragma unroll 1
            while (true) {
                bool ok = true;
#pragma unroll
                for (int i = 0; i < 4; i++) r[i] = ldg_rlx4((const uint32_t*)&g_f.cand[pass][i < 3 ? tid + 32 * i : t3]);
#pragma unroll
                for (int i = 0; i < 4; i++) ok = ok && (r[i].y >> 12) == tag && (r[i].w >> 12) == tag;
                if (__all_sync(0xffffffffu, ok)) break;
                __nanosleep(32);
                if (++n > SPIN_LIMIT) { ABORT(7); break; }
            }
            float b0 = __uint_as_float(r[0].x), b1 = __uint_as_float(r[0].z); int i0 = r[0].y & 4095, i1 = r[0].w & 4095;
#pragma unroll
            for (int i = 1; i < 4; i++) {
                if (i < 3 || t3 != tid) {
                    float c0 = __uint_as_float(r[i].x), c1 = __uint_as_float(r[i].z); int j0 = r[i].y & 4095, j1 = r[i].w & 4095;
                    if (cand_better(c0, j0, b0, i0)) {
                        if (cand_better(c1, j1, b0, i0)) { b1 = c1; i1 = j1; } else { b1 = b0; i1 = i0; }
                        b0 = c0; i0 = j0;
                    } else if (cand_better(c0, j0, b1, i1)) { b1 = c0; i1 = j0; }
                }
            }
#pragma unroll
            for (int o = 16; o; o >>= 1) {
                float c0 = __shfl_xor_sync(0xffffffffu, b0, o), c1 = __shfl_xor_sync(0xffffffffu, b1, o);
                int j0 = __shfl_xor_sync(0xffffffffu, i0, o), j1 = __shfl_xor_sync(0xffffffffu, i1, o);
                if (cand_better(c0, j0, b0, i0)) {
                    if (cand_better(c1, j1, b0, i0)) { b1 = c1; i1 = j1; } else { b1 = b0; i1 = i0; }
                    b0 = c0; i0 = j0;
                } else if (cand_better(c0, j0, b1, i1)) { b1 = c0; i1 = j0; }
            }
            i0 = min(i0, SQ - 1); i1 = min(i1, SQ - 1);
            if (i0 != p0 || i1 != p1) {
                n = 0;
#pragma unroll 1
                while (!__all_sync(0xffffffffu, (ldg_rlx(&g_f.rows[pass][tid]) == epoch) & (ldg_rlx(&g_f.rows[pass][tid + 32]) == epoch) &
                                                   (ldg_rlx(&g_f.rows[pass][tid + 64]) == epoch) & (ldg_rlx(&g_f.rows[pass][t3]) == epoch))) { __nanosleep(32); if (++n > SPIN_LIMIT) { ABORT(7); break; } }
            }
            int* sel = (int*)(smem + F_SEL);
            if (pass && tid == 0) GT(c * 8 + 5);
            if (tid == 0) { sel[0] = i0; sel[1] = i1; ((float*)sel)[2] = b0; ((float*)sel)[3] = b1; }
        }
        bar_sync(0, 384);
        const int t0 = ((int*)(smem + F_SEL))[0], t1 = ((int*)(smem + F_SEL))[1];
        if (c == 3 && tid == 0 && pass == 0) GT(1430);
        if (t0 == p0 && t1 == p1) break;
        const uint32_t ytag = epoch * 2 + pass + 1;
        if (worker) {
            float2* xs = (float2*)(smem + F_X);
            if (tid < 256) {
                uint32_t a = __ldcg((const uint32_t*)(g_hn + (size_t)t0 * DM) + tid), b = __ldcg((const uint32_t*)(g_hn + (size_t)t1 * DM) + tid);
                *(float4*)(xs + tid * 2) = make_float4(bf_lo(a), bf_lo(b), bf_hi(a), bf_hi(b));
            }
            mbar_wait(mb, 1);
            if (c == 3 && tid == 0 && pass == 0) GT(1431);
            bar_sync(0, 384);
            float4* red = (float4*)(smem + F_RED);
            if (tid < 256) {
                const int cp = tid & 31, kg = tid >> 5;
                const uint32_t* wp = (const uint32_t*)(smem + (cp < 16 ? F_WG : F_WU)) + (cp & 15);
                float a0 = 0.f, a1 = 0.f, b0 = 0.f, b1 = 0.f;
#pragma unroll 16
                for (int k = kg * 64; k < kg * 64 + 64; k++) {
                    uint32_t w = wp[k * 16]; float2 x = xs[k];
                    a0 = fmaf(x.x, bf_lo(w), a0); a1 = fmaf(x.x, bf_hi(w), a1); b0 = fmaf(x.y, bf_lo(w), b0); b1 = fmaf(x.y, bf_hi(w), b1);
                }
                red[kg * 32 + cp] = make_float4(a0, a1, b0, b1);
            }
            bar_sync(0, 384);
            float2* act = (float2*)(smem + F_ACT);
            if (tid < 64) {
                const int f = tid & 31, tk = tid >> 5;
                const float* r = (const float*)red + (f >> 1) * 4 + tk * 2 + (f & 1);
                float gsum = 0.f, usum = 0.f;
#pragma unroll
                for (int kg = 0; kg < 8; kg++) { gsum += r[kg * 128]; usum += r[kg * 128 + 64]; }
                gsum = rbf(gsum); usum = rbf(usum);
                float sg = rbf(gsum / (1.f + __expf(-gsum)));
                ((float*)act)[f * 2 + tk] = rbf(sg * usum);
            }
            bar_sync(0, 384);
            if (tid < 256) {
                const uint32_t* wp = (const uint32_t*)(smem + F_WD) + tid;
                float a0 = 0.f, a1 = 0.f, b0 = 0.f, b1 = 0.f;
#pragma unroll 16
                for (int f = 0; f < 32; f++) {
                    uint32_t w = wp[f * 256]; float2 x = act[f];
                    a0 = fmaf(x.x, bf_lo(w), a0); a1 = fmaf(x.x, bf_hi(w), a1); b0 = fmaf(x.y, bf_lo(w), b0); b1 = fmaf(x.y, bf_hi(w), b1);
                }
                asm volatile("st.relaxed.gpu.global.v4.b32 [%0], {%1,%2,%3,%2};" :: "l"(&g_yp[pass][c][tid]), "r"(FU(a0)), "r"(ytag), "r"(FU(a1)) : "memory");
                asm volatile("st.relaxed.gpu.global.v4.b32 [%0], {%1,%2,%3,%2};" :: "l"(&g_yp[pass][c][256 + tid]), "r"(FU(b0)), "r"(ytag), "r"(FU(b1)) : "memory");
            }
            if (c == 3 && tid == 0 && pass == 0) GT(1432);
        } else {
            const int r = c - NWK, j = tid & 63, part = tid >> 6, tk = r >> 2, dp = (r & 3) * 64 + j;
            const int tok = tk ? t1 : t0, old = tk ? p1 : p0;
            uint32_t hw = 0, nw = 0;
            if (part == 0) {
                hw = __ldcg((const uint32_t*)(g_h + (size_t)tok * DM) + dp); nw = __ldcg((const uint32_t*)(g_hn + (size_t)tok * DM) + dp);
                if (old >= 0 && old != t0 && old != t1) {
                    uint32_t ho = __ldcg((const uint32_t*)(g_h + (size_t)old * DM) + dp), no = __ldcg((const uint32_t*)(g_hn + (size_t)old * DM) + dp);
                    ((uint32_t*)(out + (size_t)old * DM))[dp] = pack2(bf_lo(ho) + bf_lo(no), bf_hi(ho) + bf_hi(no));
                }
            }
            float s0 = 0.f, s1 = 0.f;
            uint4 v[10]; uint32_t n = 0;
            bool ok;
#pragma unroll 1
            do {
                ok = true;
#pragma unroll
                for (int i = 0; i < 10; i++) {
                    const int src = part + 6 * i;
                    v[i] = src < NWK ? ldg_rlx4((const uint32_t*)&g_yp[pass][src][tk * 256 + dp]) : make_uint4(0, ytag, 0, ytag);
                }
#pragma unroll
                for (int i = 0; i < 10; i++) ok = ok && v[i].y == ytag && v[i].w == ytag;
                if (!ok) __nanosleep(100);
                if (++n > SPIN_LIMIT) { ABORT(7); break; }
            } while (!ok);
#pragma unroll
            for (int i = 0; i < 10; i++) { s0 += __uint_as_float(v[i].x); s1 += __uint_as_float(v[i].z); }
            float2* red = (float2*)(smem + F_RED);
            red[part * 64 + j] = make_float2(s0, s1);
            bar_sync(0, 384);
            if (part == 0) {
#pragma unroll
                for (int i = 1; i < 6; i++) { float2 q = red[i * 64 + j]; s0 += q.x; s1 += q.y; }
                const float rs = rbf(1.f / (1.f + __expf(-((float*)(smem + F_SEL))[2 + tk])));
                const float y0 = rbf(rbf(s0) * rs), y1 = rbf(rbf(s1) * rs);
                ((uint32_t*)(out + (size_t)tok * DM))[dp] = pack2(bf_lo(hw) + rbf(bf_lo(nw) + y0), bf_hi(hw) + rbf(bf_hi(nw) + y1));
            }
            if (tid == 0 && pass == 0 && r == 0) GT(1434);
        }
        p0 = t0; p1 = t1;
        if (c == 3 && tid == 0 && pass == 0) GT(1433);
        bar_sync(0, 384);
    }
}

constexpr int G_W = 0;
constexpr int G_RING = 131072;
constexpr int G_BUF = 163840;
constexpr int G_BAR = 229376;
constexpr int G_SMEM = G_BAR + 512;
enum { GB_W0 = 0, GB_W1, GB_WFREE, GB_FULL, GB_EMPTY = GB_FULL + 8, GB_KV = GB_EMPTY + 8, GB_STG = GB_KV + 2, GB_FREE = GB_STG + 2, GB_XN = GB_FREE + 2, GB_RL, GB_T1D, GB_VV, GB_KVF = GB_VV + 2, GB_VF, GB_N };
constexpr int SMEM_TOTAL = 232448;

__device__ __forceinline__ void wgmma_n128(float* d, uint64_t da, uint64_t db, int scale_d) {
    asm volatile("{\n.reg .pred p;\nsetp.ne.b32 p, %66, 0;\n"
        "wgmma.mma_async.sync.aligned.m64n128k16.f32.bf16.bf16 "
        "{%0,%1,%2,%3,%4,%5,%6,%7,%8,%9,%10,%11,%12,%13,%14,%15,%16,%17,%18,%19,%20,%21,%22,%23,%24,%25,%26,%27,%28,%29,%30,%31,"
        "%32,%33,%34,%35,%36,%37,%38,%39,%40,%41,%42,%43,%44,%45,%46,%47,%48,%49,%50,%51,%52,%53,%54,%55,%56,%57,%58,%59,%60,%61,%62,%63}, "
        "%64, %65, p, 1, 1, 0, 1;\n}"
        : "+f"(d[0]), "+f"(d[1]), "+f"(d[2]), "+f"(d[3]), "+f"(d[4]), "+f"(d[5]), "+f"(d[6]), "+f"(d[7]), "+f"(d[8]), "+f"(d[9]), "+f"(d[10]), "+f"(d[11]),
          "+f"(d[12]), "+f"(d[13]), "+f"(d[14]), "+f"(d[15]), "+f"(d[16]), "+f"(d[17]), "+f"(d[18]), "+f"(d[19]), "+f"(d[20]), "+f"(d[21]), "+f"(d[22]), "+f"(d[23]),
          "+f"(d[24]), "+f"(d[25]), "+f"(d[26]), "+f"(d[27]), "+f"(d[28]), "+f"(d[29]), "+f"(d[30]), "+f"(d[31]), "+f"(d[32]), "+f"(d[33]), "+f"(d[34]), "+f"(d[35]),
          "+f"(d[36]), "+f"(d[37]), "+f"(d[38]), "+f"(d[39]), "+f"(d[40]), "+f"(d[41]), "+f"(d[42]), "+f"(d[43]), "+f"(d[44]), "+f"(d[45]), "+f"(d[46]), "+f"(d[47]),
          "+f"(d[48]), "+f"(d[49]), "+f"(d[50]), "+f"(d[51]), "+f"(d[52]), "+f"(d[53]), "+f"(d[54]), "+f"(d[55]), "+f"(d[56]), "+f"(d[57]), "+f"(d[58]), "+f"(d[59]),
          "+f"(d[60]), "+f"(d[61]), "+f"(d[62]), "+f"(d[63])
        : "l"(da), "l"(db), "r"(scale_d));
}

__device__ __forceinline__ constexpr uint32_t slot_off(int slot) {
    return slot < 2 ? G_RING + slot * 16384 : G_BUF + (slot - 2) * 32768 + 16384;
}
template <int NSLOT>
__device__ __forceinline__ void gemm_tile(float* acc, uint32_t sb, int tile, int it, bool first, uint32_t wpar, int wg, bool pass, uint32_t l0) {
    const uint32_t bar = sb + G_BAR;
    bar_sync(3 + wg, 256);
    int prev = 0;
#pragma unroll
    for (int k = 0; k < 4; k++) {
        const int n = tile * 4 + k, slot = NSLOT == 4 ? k : n % 3;
        const uint32_t sz = sb + (((it + k) << 4) & sb & 0x3f0);
        const uint64_t da = desc_sw128(sz + slot_off(slot), 16, 1024), db0 = desc_sw128(sz + G_W, 65536, 1024);
        if ((k & 1) == 0 && first) mbar_wait_p(bar + 8 * (GB_W0 + (k >> 1)), wpar);
        bool rel = false;
        if (EREL && k > 0 && !__all_sync(0xffffffffu, mbar_test(bar + 8 * (GB_FULL + slot), tile & 1))) {
            asm volatile("wgmma.wait_group.sync.aligned 0;" ::: "memory");
            mbar_arrive2_if(bar + 8 * (GB_EMPTY + prev), l0);
            rel = true;
        }
        mbar_wait_p(bar + 8 * (GB_FULL + slot), NSLOT == 4 ? (tile & 1) : ((n / 3) & 1));
        if (k == 3 && pass) bar_arrive(3 + (wg ^ 1), 256);
        asm volatile("wgmma.fence.sync.aligned;" ::: "memory");
#pragma unroll
        for (int kk = 0; kk < 4; kk++) wgmma_n128(acc, da + kk * 2, db0 + k * 1024 + kk * 128, (k | kk) != 0);
        asm volatile("wgmma.commit_group.sync.aligned;" ::: "memory");
        if (k > 0) {
            asm volatile("wgmma.wait_group.sync.aligned 1;" ::: "memory");
            mbar_arrive2_if(bar + 8 * (GB_EMPTY + prev), rel ? 0 : l0);
        }
#pragma unroll
        for (int kk = 0; kk < 4; kk++) wgmma_n128(acc, da + 512 + kk * 2, db0 + k * 1024 + 512 + kk * 128, 1);
        asm volatile("wgmma.commit_group.sync.aligned;" ::: "memory");
        prev = slot;
    }
    asm volatile("wgmma.wait_group.sync.aligned 0;" ::: "memory");
    mbar_arrive2_if(bar + 8 * (GB_EMPTY + prev), l0);
}
__device__ __forceinline__ void stage_bf16(const float* acc, uint32_t buf, float s0, float s1) {
    const int lane = threadIdx.x & 31, wq = (threadIdx.x >> 5) & 3;
    const int row = wq * 16 + (lane & 7) + ((lane >> 3) & 1) * 8;
    const uint32_t base = buf + row * 128;
#pragma unroll
    for (int j = 0; j < 16; j += 2) {
        const int ch = (j & 7) + (lane >> 4);
        stsm4(base + (j >> 3) * 8192 + ((ch ^ (row & 7)) << 4),
              pack2(acc[4 * j] * s0, acc[4 * j + 1] * s0), pack2(acc[4 * j + 2] * s1, acc[4 * j + 3] * s1),
              pack2(acc[4 * j + 4] * s0, acc[4 * j + 5] * s0), pack2(acc[4 * j + 6] * s1, acc[4 * j + 7] * s1));
    }
}

__device__ __forceinline__ void store_perm(const float* acc, bf16* dst, int ld, float s0, float s1) {
#pragma unroll
    for (int i = 0; i < 4; i++) {
        const float* a = acc + 16 * i;
        *(uint4*)(dst + i * 32) = make_uint4(pack2(a[0] * s0, a[1] * s0), pack2(a[4] * s0, a[5] * s0), pack2(a[8] * s0, a[9] * s0), pack2(a[12] * s0, a[13] * s0));
        *(uint4*)(dst + 8 * ld + i * 32) = make_uint4(pack2(a[2] * s1, a[3] * s1), pack2(a[6] * s1, a[7] * s1), pack2(a[10] * s1, a[11] * s1), pack2(a[14] * s1, a[15] * s1));
    }
}
template <int ACC>
__device__ __forceinline__ void wgmma_rs64(float* d, const uint32_t* a, uint64_t db) {
    asm volatile("{\n.reg .pred p;\nsetp.ne.b32 p, %37, 0;\n"
        "wgmma.mma_async.sync.aligned.m64n64k16.f32.bf16.bf16 {%0,%1,%2,%3,%4,%5,%6,%7,%8,%9,%10,%11,%12,%13,%14,%15,%16,%17,%18,%19,%20,%21,%22,%23,%24,%25,%26,%27,%28,%29,%30,%31}, {%32,%33,%34,%35}, %36, p, 1, 1, 0;\n}"
        : "+f"(d[0]), "+f"(d[1]), "+f"(d[2]), "+f"(d[3]), "+f"(d[4]), "+f"(d[5]), "+f"(d[6]), "+f"(d[7]), "+f"(d[8]), "+f"(d[9]), "+f"(d[10]), "+f"(d[11]), "+f"(d[12]), "+f"(d[13]), "+f"(d[14]), "+f"(d[15]), "+f"(d[16]), "+f"(d[17]), "+f"(d[18]), "+f"(d[19]), "+f"(d[20]), "+f"(d[21]), "+f"(d[22]), "+f"(d[23]), "+f"(d[24]), "+f"(d[25]), "+f"(d[26]), "+f"(d[27]), "+f"(d[28]), "+f"(d[29]), "+f"(d[30]), "+f"(d[31])
        : "r"(a[0]), "r"(a[1]), "r"(a[2]), "r"(a[3]), "l"(db), "n"(ACC));
}
template <int ACC>
__device__ __forceinline__ void wgmma_rs128t(float* d, const uint32_t* a, uint64_t db) {
    asm volatile("{\n.reg .pred p;\nsetp.ne.b32 p, %69, 0;\n"
        "wgmma.mma_async.sync.aligned.m64n128k16.f32.bf16.bf16 {%0,%1,%2,%3,%4,%5,%6,%7,%8,%9,%10,%11,%12,%13,%14,%15,%16,%17,%18,%19,%20,%21,%22,%23,%24,%25,%26,%27,%28,%29,%30,%31,%32,%33,%34,%35,%36,%37,%38,%39,%40,%41,%42,%43,%44,%45,%46,%47,%48,%49,%50,%51,%52,%53,%54,%55,%56,%57,%58,%59,%60,%61,%62,%63}, {%64,%65,%66,%67}, %68, p, 1, 1, 1;\n}"
        : "+f"(d[0]), "+f"(d[1]), "+f"(d[2]), "+f"(d[3]), "+f"(d[4]), "+f"(d[5]), "+f"(d[6]), "+f"(d[7]), "+f"(d[8]), "+f"(d[9]), "+f"(d[10]), "+f"(d[11]), "+f"(d[12]), "+f"(d[13]), "+f"(d[14]), "+f"(d[15]), "+f"(d[16]), "+f"(d[17]), "+f"(d[18]), "+f"(d[19]), "+f"(d[20]), "+f"(d[21]), "+f"(d[22]), "+f"(d[23]), "+f"(d[24]), "+f"(d[25]), "+f"(d[26]), "+f"(d[27]), "+f"(d[28]), "+f"(d[29]), "+f"(d[30]), "+f"(d[31]), "+f"(d[32]), "+f"(d[33]), "+f"(d[34]), "+f"(d[35]), "+f"(d[36]), "+f"(d[37]), "+f"(d[38]), "+f"(d[39]), "+f"(d[40]), "+f"(d[41]), "+f"(d[42]), "+f"(d[43]), "+f"(d[44]), "+f"(d[45]), "+f"(d[46]), "+f"(d[47]), "+f"(d[48]), "+f"(d[49]), "+f"(d[50]), "+f"(d[51]), "+f"(d[52]), "+f"(d[53]), "+f"(d[54]), "+f"(d[55]), "+f"(d[56]), "+f"(d[57]), "+f"(d[58]), "+f"(d[59]), "+f"(d[60]), "+f"(d[61]), "+f"(d[62]), "+f"(d[63])
        : "r"(a[0]), "r"(a[1]), "r"(a[2]), "r"(a[3]), "l"(db), "n"(ACC));
}
__device__ __forceinline__ void attention_tile(float* acc, uint32_t sb, int tile, int h, int wg, int wq, uint32_t l0, uint32_t epoch, uint2 rec) {
    const uint32_t buf = sb + G_BUF + ((tile << 4) & sb & 0x3f0);
    const int lane = threadIdx.x & 31, g = lane >> 2, t = lane & 3;
    const int sg = wq >> 1, hf = wq & 1, seg = tile * 2 + sg;
    uint32_t qf[8][4];
#pragma unroll
    for (int kk = 0; kk < 8; kk++) {
        qf[kk][0] = pack2(acc[8 * kk], acc[8 * kk + 1]); qf[kk][1] = pack2(acc[8 * kk + 2], acc[8 * kk + 3]);
        qf[kk][2] = pack2(acc[8 * kk + 4], acc[8 * kk + 5]); qf[kk][3] = pack2(acc[8 * kk + 6], acc[8 * kk + 7]);
    }
    uint32_t* kvf = &g_KVf[seg][h][lane * 4];
    uint4 km[4], vm[4];
    const bool early = __all_sync(0xffffffffu, (rec.x >> 8) == epoch && (rec.y >> 8) == epoch && (rec.x & 255) > seg && (rec.y & 255) > seg);
#pragma unroll
    for (int i = 0; i < 4; i++) { km[i] = ldg_rlx4_if(kvf + i * 128, early); vm[i] = ldg_rlx4_if(kvf + 512 + i * 128, early); }
    mbar_wait_p(sb + G_BAR + 8 * (GB_KV + wg), (tile >> 1) & 1);
    if (h == 5 && (threadIdx.x & 127) == 0 && tile < 6) GT(1750 + tile * 8 + 2);
    float sc[5][4];
    {
        const uint64_t dk = desc_sw128(buf, 16, 1024);
        asm volatile("wgmma.fence.sync.aligned;" ::: "memory");
#pragma unroll
        for (int kk = 0; kk < 8; kk++) {
            if (kk == 0) wgmma_rs64<0>(acc, qf[kk], dk); else wgmma_rs64<1>(acc, qf[kk], dk + (kk >> 2) * 512 + (kk & 3) * 2);
        }
        asm volatile("wgmma.commit_group.sync.aligned;" ::: "memory");
        asm volatile("wgmma.wait_group.sync.aligned 0;" ::: "memory");
        mbar_arrive_if(sb + G_BAR + 8 * GB_KVF, l0);
#pragma unroll
        for (int i = 0; i < 32; i++) asm volatile("" : "+f"(acc[i]) :: "memory");
#pragma unroll
        for (int b = 0; b < 4; b++)
#pragma unroll
            for (int i = 0; i < 4; i++) sc[b][i] = sg ? acc[16 + 4 * b + i] : acc[4 * b + i];
        sc[4][0] = sc[4][1] = sc[4][2] = sc[4][3] = 0.f;
    }
    const float cexp = 0.08838834764831845f * 1.4426950408889634f;
    const int r0 = hf * 16 + g, r1 = r0 + 8;
#pragma unroll
    for (int b = 0; b < 4; b++) {
        const int j = b * 8 + 2 * t;
        if (j > r0) sc[b][0] = -INFINITY;
        if (j + 1 > r0) sc[b][1] = -INFINITY;
        if (j > r1) sc[b][2] = -INFINITY;
        if (j + 1 > r1) sc[b][3] = -INFINITY;
    }
    float m0 = -INFINITY, m1 = -INFINITY;
#pragma unroll
    for (int b = 0; b < 4; b++) { m0 = fmaxf(m0, fmaxf(sc[b][0], sc[b][1])); m1 = fmaxf(m1, fmaxf(sc[b][2], sc[b][3])); }
    m0 = fmaxf(m0, __shfl_xor_sync(0xffffffffu, m0, 1)); m0 = fmaxf(m0, __shfl_xor_sync(0xffffffffu, m0, 2));
    m1 = fmaxf(m1, __shfl_xor_sync(0xffffffffu, m1, 1)); m1 = fmaxf(m1, __shfl_xor_sync(0xffffffffu, m1, 2));
    float z0 = 0.f, z1 = 0.f;
    {
        const float c0 = -m0 * cexp, c1 = -m1 * cexp;
        uint32_t pf[4][2];
#pragma unroll
        for (int b = 0; b < 4; b++) {
            pf[b][0] = pack2(ex2(fmaf(sc[b][0], cexp, c0)), ex2(fmaf(sc[b][1], cexp, c0)));
            pf[b][1] = pack2(ex2(fmaf(sc[b][2], cexp, c1)), ex2(fmaf(sc[b][3], cexp, c1)));
            z0 += bf_lo(pf[b][0]) + bf_hi(pf[b][0]); z1 += bf_lo(pf[b][1]) + bf_hi(pf[b][1]);
        }
        uint32_t pa[4][4];
#pragma unroll
        for (int kk = 0; kk < 4; kk++)
#pragma unroll
            for (int i = 0; i < 4; i++) pa[kk][i] = (kk >> 1) == sg ? pf[(kk & 1) * 2 + (i >> 1)][i & 1] : 0u;
        const uint64_t dv = desc_sw128(buf + 32768, 8192, 1024);
        mbar_wait_p(sb + G_BAR + 8 * (GB_VV + wg), (tile >> 1) & 1);
        asm volatile("wgmma.fence.sync.aligned;" ::: "memory");
#pragma unroll
        for (int kk = 0; kk < 4; kk++) { if (kk == 0) wgmma_rs128t<0>(acc, pa[kk], dv); else wgmma_rs128t<1>(acc, pa[kk], dv + kk * 128); }
        asm volatile("wgmma.commit_group.sync.aligned;" ::: "memory");
        asm volatile("wgmma.wait_group.sync.aligned 0;" ::: "memory");
#pragma unroll
        for (int i = 0; i < 64; i++) asm volatile("" : "+f"(acc[i]) :: "memory");
    }
    mbar_arrive_if(sb + G_BAR + 8 * GB_VF, l0);
    if (h == 5 && (threadIdx.x & 127) == 0 && tile < 6) GT(1750 + tile * 8 + 3);
    if (!early) wait_rec(&g_f.rec[2 * h], epoch, seg + 1);
    if (seg == 63 && (threadIdx.x & 63) == 0) GT(1570 + h);
    if (h == 5 && (threadIdx.x & 127) == 0 && tile < 6) GT(1750 + tile * 8 + 4);
    __syncwarp();
    {
        uint32_t n = 0;
#pragma unroll 1
        while (true) {
            uint32_t mn = 0xffffffffu;
#pragma unroll
            for (int i = 0; i < 4; i++) mn = min(min(min(mn, min(km[i].x, km[i].y)), min(km[i].z, km[i].w)), min(min(vm[i].x, vm[i].y), min(vm[i].z, vm[i].w)));
            if (__all_sync(0xffffffffu, mn != 0)) break;
            if (++n > SPIN_LIMIT) { ABORT(4); break; }
#pragma unroll
            for (int i = 0; i < 4; i++) { km[i] = ldg_rlx4(kvf + i * 128); vm[i] = ldg_rlx4(kvf + 512 + i * 128); }
        }
#pragma unroll
        for (int i = 0; i < 4; i++) {
            km[i] = make_uint4(~km[i].x, ~km[i].y, ~km[i].z, ~km[i].w); vm[i] = make_uint4(~vm[i].x, ~vm[i].y, ~vm[i].z, ~vm[i].w);
        }
        if (hf) bar_arrive(5 + wg * 2 + sg, 64);
        float sb_[4] = {0.f, 0.f, 0.f, 0.f};
#pragma unroll
        for (int i = 0; i < 4; i++) { MMA(sc[4], qf[2 * i], km[i].x, km[i].y); MMA(sb_, qf[2 * i + 1], km[i].z, km[i].w); }
#pragma unroll
        for (int i = 0; i < 4; i++) sc[4][i] += sb_[i];
        float n0 = fmaxf(sc[4][0], sc[4][1]), n1 = fmaxf(sc[4][2], sc[4][3]);
        n0 = fmaxf(n0, __shfl_xor_sync(0xffffffffu, n0, 1)); n1 = fmaxf(n1, __shfl_xor_sync(0xffffffffu, n1, 1));
        n0 = fmaxf(n0, __shfl_xor_sync(0xffffffffu, n0, 2)); n1 = fmaxf(n1, __shfl_xor_sync(0xffffffffu, n1, 2));
        n0 = fmaxf(n0, m0); n1 = fmaxf(n1, m1);
        const float a0 = ex2((m0 - n0) * cexp), a1 = ex2((m1 - n1) * cexp);
        const float c0 = -n0 * cexp, c1 = -n1 * cexp;
        const uint32_t p0 = pack2(ex2(fmaf(sc[4][0], cexp, c0)), ex2(fmaf(sc[4][1], cexp, c0)));
        const uint32_t p1 = pack2(ex2(fmaf(sc[4][2], cexp, c1)), ex2(fmaf(sc[4][3], cexp, c1)));
        z0 = fmaf(z0, a0, bf_lo(p0) + bf_hi(p0)); z1 = fmaf(z1, a1, bf_lo(p1) + bf_hi(p1));
        const uint32_t* vmw = (const uint32_t*)vm;
#pragma unroll
        for (int j = 0; j < 16; j++) {
            float* o = acc + 4 * j;
            o[0] *= a0; o[1] *= a0; o[2] *= a1; o[3] *= a1;
            mma1688(o, p0, p1, vmw[j]);
        }
        z0 += __shfl_xor_sync(0xffffffffu, z0, 1); z1 += __shfl_xor_sync(0xffffffffu, z1, 1);
        z0 += __shfl_xor_sync(0xffffffffu, z0, 2); z1 += __shfl_xor_sync(0xffffffffu, z1, 2);
    }
    if (h == 5 && (threadIdx.x & 127) == 0 && tile < 6) GT(1750 + tile * 8 + 5);
    store_perm(acc, g_O + (size_t)(tile * 64 + wq * 16 + g) * HD + h * 128 + t * 8, HD, rcpf(z0), rcpf(z1));
    if (tile >= 2) mbar_wait_p(sb + G_BAR + 8 * (GB_FREE + wg), ((tile >> 1) - 1) & 1);
    mbar_arrive(sb + G_BAR + 8 * (GB_STG + wg));
    if (!hf) {
        bar_sync(5 + wg * 2 + sg, 64);
#pragma unroll
        for (int i = 0; i < 8; i++) stg4(kvf + i * 128, make_uint4(0, 0, 0, 0));
    }
}

__device__ __forceinline__ void g_consumer(uint32_t sb_, int g_, int wg_, uint32_t epoch) {
    const uint32_t sb = uni(sb_);
    const int g = uni(g_), wg = uni(wg_), wq = uni((threadIdx.x >> 5) & 3);
    const uint32_t l0 = opaque((threadIdx.x & 31) == 0);
    const uint32_t bar = sb + G_BAR, buf = sb + G_BUF + wg * 32768;
    const int lane = threadIdx.x & 31;
    float acc[64];
    if (wg == 1) bar_arrive(3, 256);
    const int n1 = g < 32 ? HSPLIT / 2 : NT - HSPLIT / 2;
#pragma unroll 1
    for (int i = 0; i < n1; i++) {
        gemm_tile<4>(acc, sb, wg, i, i == 0 || i == NT / 2, i >= NT / 2, wg, true, l0);
        if (i == n1 - 1 || i == NT / 2 - 1) mbar_arrive_if(bar + 8 * GB_WFREE, l0);
        if (threadIdx.x == 0 && i == 0) GT((64 + g) * 8 + 1);
        if (threadIdx.x == 128 && i == 3) GT((64 + g) * 8 + 2);
        if (i > 0) mbar_wait_p(bar + 8 * (GB_FREE + wg), (i - 1) & 1);
        stage_bf16(acc, buf, 1.f, 1.f);
        asm volatile("fence.proxy.async.shared::cta;" ::: "memory");
        mbar_arrive(bar + 8 * (GB_STG + wg));
    }
    if (threadIdx.x == 128) GT((64 + g) * 8 + 3);
    if (g < 32) {
#pragma unroll 1
        for (int i = 0; i < NT / 2; i++) {
            const int tile = 2 * i + wg;
            const uint2 rec = ldg_rlx2(&g_f.rec[2 * g]);
            gemm_tile<4>(acc, sb, tile, i, i == 0, 1, wg, tile != NT - 1, l0);
            if (threadIdx.x == 0 && i == 0) GT((64 + g) * 8 + 4);
            if (threadIdx.x == 128 && i == 3) GT((64 + g) * 8 + 5);
            if (g == 5 && (threadIdx.x & 127) == 0 && tile < 6) GT(1750 + tile * 8 + 1);
            attention_tile(acc, sb, tile, g, wg, wq, l0, epoch, rec);
            if (g == 5 && (threadIdx.x & 127) == 0 && tile < 6) GT(1750 + tile * 8 + 6);
        }
    } else {
#pragma unroll 1
        for (int i = 0; i < NT / 2; i++) {
            const int tile = 2 * i + wg;
            gemm_tile<4>(acc, sb, tile, i, i == 0, 0, wg, tile != NT - 1, l0);
            if (threadIdx.x == 0 && i == 0) GT((64 + g) * 8 + 4);
            if (threadIdx.x == 128 && i == 3) GT((64 + g) * 8 + 5);
            store_perm(acc, g_P + (size_t)(((g - 32) >> 2) * SQ + tile * 64 + wq * 16 + (lane >> 2)) * DM + ((g - 32) & 3) * 128 + (lane & 3) * 8, DM, 1.f, 1.f);
            mbar_wait_p(bar + 8 * (GB_FREE + wg), (i - 1) & 1);
            mbar_arrive(bar + 8 * (GB_STG + wg));
        }
    }
}

__device__ __forceinline__ void load_w(uint32_t sb, const CUtensorMap* tm, int col, int row, int k0 = 0, int k1 = 2) {
    const uint32_t bar = sb + G_BAR;
#pragma unroll
    for (int kh = k0; kh < k1; kh++) {
        mbar_expect_tx(bar + 8 * (GB_W0 + kh), 65536);
        tma2d(sb + G_W + kh * 32768, tm, col, row + kh * 256, bar + 8 * (GB_W0 + kh));
        tma2d(sb + G_W + 65536 + kh * 32768, tm, col + 64, row + kh * 256, bar + 8 * (GB_W0 + kh));
    }
}

__device__ __forceinline__ void rbf2(float& a, float& b) { uint32_t w = pack2(a, b); a = bf_lo(w); b = bf_hi(w); }
__device__ __forceinline__ void warp_sum2(float& a, float& b) {
#pragma unroll
    for (int o = 16; o; o >>= 1) { float c = __shfl_xor_sync(0xffffffffu, a, o), d = __shfl_xor_sync(0xffffffffu, b, o); a += c; b += d; }
}
__device__ __forceinline__ float sum16(const float* v) {
    return (((v[0] + v[1]) + (v[2] + v[3])) + ((v[4] + v[5]) + (v[6] + v[7]))) + (((v[8] + v[9]) + (v[10] + v[11])) + ((v[12] + v[13]) + (v[14] + v[15])));
}
__device__ __forceinline__ void ln_row2(float* v, float* u) {
    float sv = sum16(v), su = sum16(u);
    warp_sum2(sv, su);
    const float mv = sv * (1.f / DM), mu = su * (1.f / DM);
    float qv = 0.f, qu = 0.f, qv2 = 0.f, qu2 = 0.f;
#pragma unroll
    for (int i = 0; i < 16; i += 2) {
        float d0 = v[i] - mv, d1 = v[i + 1] - mv, e0 = u[i] - mu, e1 = u[i + 1] - mu;
        qv = fmaf(d0, d0, qv); qv2 = fmaf(d1, d1, qv2); qu = fmaf(e0, e0, qu); qu2 = fmaf(e1, e1, qu2);
    }
    qv += qv2; qu += qu2;
    warp_sum2(qv, qu);
    const float rv = rbf(mv), ru = rbf(mu);
    const float iv = __frcp_rn(rbf(sqrtf(rbf(rbf(qv * (1.f / DM)) + 1e-5f)))), iu = __frcp_rn(rbf(sqrtf(rbf(rbf(qu * (1.f / DM)) + 1e-5f))));
#pragma unroll
    for (int i = 0; i < 16; i += 2) {
        float a = v[i] - rv, b = v[i + 1] - rv, c = u[i] - ru, d = u[i + 1] - ru;
        rbf2(a, b); rbf2(c, d);
        a *= iv; b *= iv; c *= iu; d *= iu;
        rbf2(a, b); rbf2(c, d);
        v[i] = a; v[i + 1] = b; u[i] = c; u[i + 1] = d;
    }
}

__device__ __forceinline__ void ln_row1(float* v) {
    float sv = sum16(v);
#pragma unroll
    for (int o = 16; o; o >>= 1) sv += __shfl_xor_sync(0xffffffffu, sv, o);
    const float mv = sv * (1.f / DM);
    float qv = 0.f, qv2 = 0.f;
#pragma unroll
    for (int i = 0; i < 16; i += 2) { float d0 = v[i] - mv, d1 = v[i + 1] - mv; qv = fmaf(d0, d0, qv); qv2 = fmaf(d1, d1, qv2); }
    qv += qv2;
#pragma unroll
    for (int o = 16; o; o >>= 1) qv += __shfl_xor_sync(0xffffffffu, qv, o);
    const float rv = rbf(mv);
    float sq, iv;
    asm("sqrt.approx.f32 %0, %1;" : "=f"(sq) : "f"(rbf(rbf(qv * (1.f / DM)) + 1e-5f)));
    asm("rcp.approx.f32 %0, %1;" : "=f"(iv) : "f"(rbf(sq)));
#pragma unroll
    for (int i = 0; i < 16; i += 2) {
        float a = v[i] - rv, b = v[i + 1] - rv;
        rbf2(a, b);
        a *= iv; b *= iv;
        rbf2(a, b);
        v[i] = a; v[i + 1] = b;
    }
}
constexpr int FSPLIT = 28;
__device__ __forceinline__ int fin_row(int id, int i) {
    if (id < 64) { const int tile = i < FSPLIT / 2 ? 2 * i : i + FSPLIT / 2; return tile < NT ? tile * 64 + id : -1; }
    const int j = id - 64 + i * 48;
    return j < FSPLIT * 32 ? (j >> 6) * 128 + 64 + (j & 63) : -1;
}
__device__ __forceinline__ void finalizer(int id, const bf16* __restrict__ x, const bf16* __restrict__ wr, bf16* __restrict__ out, uint32_t epoch) {
    const int lane = threadIdx.x & 31;
    float b0 = -INFINITY, b1 = -INFINITY; int i0 = 0x7fffffff, i1 = 0x7fffffff;
    const uint32_t tag = (epoch & 0xfffffu) << 12;
    uint32_t fl = ~epoch;
    int row = fin_row(id, 0);
    const uint4 ra = *(const uint4*)(wr + lane * 8), rb = *(const uint4*)(wr + 256 + lane * 8);
    uint4 xa = *(const uint4*)(x + (size_t)row * DM + lane * 8), xb = *(const uint4*)(x + (size_t)row * DM + lane * 8 + 256);
#pragma unroll 1
    for (int it = 0; row >= 0; it++) {
        const int tile = row >> 6, nxt = fin_row(id, it + 1);
        const size_t o0 = (size_t)row * DM + lane * 8;
        uint32_t n = 0;
#pragma unroll 1
        while (!__all_sync(0xffffffffu, fl == epoch)) {
            if (n) __nanosleep(it ? 64 : 1000);
            fl = ldg_rlx(&g_f.p[tile][lane]);
            if (++n > SPIN_LIMIT) { ABORT(12); break; }
        }
        if (tile == NT - 1 && id == 63 && lane == 0) GT(1438);
        if ((id == 63 || id == 3 || id == 70) && lane == 0) GT(1800 + (id == 3) * 32 + tile);
        float v[16];
        {
            uint4 pa[8][2];
#pragma unroll
            for (int k = 0; k < 8; k++) {
                pa[k][0] = ldg_rlx4((const uint32_t*)(g_P + (size_t)k * SQ * DM + o0));
                pa[k][1] = ldg_rlx4((const uint32_t*)(g_P + (size_t)k * SQ * DM + o0 + 256));
            }
            fl = ldg_rlx(&g_f.p[max(nxt, 0) >> 6][lane]);
#pragma unroll
            for (int j = 0; j < 2; j++) {
#pragma unroll
                for (int i = 0; i < 4; i++) {
                    uint32_t w[8];
#pragma unroll
                    for (int k = 0; k < 8; k++) w[k] = i == 0 ? pa[k][j].x : (i == 1 ? pa[k][j].y : (i == 2 ? pa[k][j].z : pa[k][j].w));
                    v[j * 8 + 2 * i] = ((bf_lo(w[0]) + bf_lo(w[1])) + (bf_lo(w[2]) + bf_lo(w[3]))) + ((bf_lo(w[4]) + bf_lo(w[5])) + (bf_lo(w[6]) + bf_lo(w[7])));
                    v[j * 8 + 2 * i + 1] = ((bf_hi(w[0]) + bf_hi(w[1])) + (bf_hi(w[2]) + bf_hi(w[3]))) + ((bf_hi(w[4]) + bf_hi(w[5])) + (bf_hi(w[6]) + bf_hi(w[7])));
                }
            }
        }
        uint32_t hw[8];
        {
            const uint32_t xw[8] = {xa.x, xa.y, xa.z, xa.w, xb.x, xb.y, xb.z, xb.w};
            uint32_t aw[8];
#pragma unroll
            for (int i = 0; i < 8; i++) aw[i] = pack2(v[2 * i], v[2 * i + 1]);
#pragma unroll
            for (int d = 1; d <= 2; d++) {
                const bool up = lane & d;
#pragma unroll
                for (int i = 0; i < 8; i++) {
                    if (!(i & d)) {
                        const uint32_t r = __shfl_xor_sync(0xffffffffu, up ? aw[i] : aw[i | d], d);
                        if (up) aw[i] = r; else aw[i | d] = r;
                    }
                }
            }
#pragma unroll
            for (int i = 0; i < 8; i++) {
                hw[i] = pack2(bf_lo(aw[i]) + bf_lo(xw[i]), bf_hi(aw[i]) + bf_hi(xw[i]));
                v[2 * i] = bf_lo(hw[i]); v[2 * i + 1] = bf_hi(hw[i]);
            }
        }
        xa = *(const uint4*)(x + (size_t)max(nxt, 0) * DM + lane * 8); xb = *(const uint4*)(x + (size_t)max(nxt, 0) * DM + lane * 8 + 256);
        ln_row1(v);
        float r0 = 0.f, r1 = 0.f;
        {
            const uint32_t ww[8] = {ra.x, ra.y, ra.z, ra.w, rb.x, rb.y, rb.z, rb.w};
#pragma unroll
            for (int i = 0; i < 8; i++) { r0 = fmaf(v[2 * i], bf_lo(ww[i]), r0); r1 = fmaf(v[2 * i + 1], bf_hi(ww[i]), r1); }
        }
        r0 += r1;
#pragma unroll
        for (int o = 16; o; o >>= 1) r0 += __shfl_xor_sync(0xffffffffu, r0, o);
        r0 = rbf(r0);
        if (cand_better(r0, row, b0, i0)) { b1 = b0; i1 = i0; b0 = r0; i0 = row; }
        else if (cand_better(r0, row, b1, i1)) { b1 = r0; i1 = row; }
        if (tile == NT - 1 && id == 63 && lane == 0) GT(1439);
        const bool last = nxt < 0, spec = tile < SPEC_TILES && (last || (nxt >> 6) >= SPEC_TILES);
        const bool pub = (lane == 0 && spec) || (lane == 1 && last);
        if (pub)
            asm volatile("st.relaxed.gpu.global.v4.b32 [%0], {%1,%2,%3,%4};" :: "l"(&g_f.cand[lane][id]),
                         "r"(FU(b0)), "r"(tag | (uint32_t)min(i0, 4095)), "r"(FU(b1)), "r"(tag | (uint32_t)min(i1, 4095)) : "memory");
#pragma unroll
        for (int j = 0; j < 2; j++) {
            const uint32_t* hh = hw + j * 4; const float* nn = v + j * 8;
            *(uint4*)(out + o0 + j * 256) = make_uint4(pack2(bf_lo(hh[0]) + nn[0], bf_hi(hh[0]) + nn[1]), pack2(bf_lo(hh[1]) + nn[2], bf_hi(hh[1]) + nn[3]),
                                                       pack2(bf_lo(hh[2]) + nn[4], bf_hi(hh[2]) + nn[5]), pack2(bf_lo(hh[3]) + nn[6], bf_hi(hh[3]) + nn[7]));
            *(uint4*)(g_h + o0 + j * 256) = make_uint4(hh[0], hh[1], hh[2], hh[3]);
            *(uint4*)(g_hn + o0 + j * 256) = make_uint4(pack2(nn[0], nn[1]), pack2(nn[2], nn[3]), pack2(nn[4], nn[5]), pack2(nn[6], nn[7]));
        }
        if (last || spec) {
            __threadfence();
            __syncwarp();
            if (pub) stg_rlx(&g_f.rows[lane][id], epoch);
        }
        row = nxt;
    }
    if (id == 0 && lane == 0) { g_epoch = epoch; if (epoch == 0xffffffu) { g_ticket[0] = 0; g_ticket[32] = 0; } }
}

__device__ __forceinline__ void g_producer(uint32_t sb, int g, const Maps& maps, uint32_t epoch, const bf16* __restrict__ x, const bf16* __restrict__ wr, bf16* __restrict__ out) {
    const uint32_t bar = sb + G_BAR;
    const int warp = (threadIdx.x >> 5) - 8;
    if (threadIdx.x == 256 && g == 5) GT(1410);
    if (threadIdx.x == 256 && g == 5) GT(1411);
    if (warp == 3) {
        wait_eq4(&g_f.xn[(threadIdx.x & 31) * 4], epoch, 13);
        __syncwarp();
        if ((threadIdx.x & 31) == 0) mbar_arrive(bar + 8 * GB_XN);
        wait_eq2(&g_f.rload[(threadIdx.x & 31) * 2], epoch, 13);
        __syncwarp();
        if ((threadIdx.x & 31) == 0) mbar_arrive(bar + 8 * GB_RL);
        finalizer(g, x, wr, out, epoch);
        if (g == 63 && (threadIdx.x & 31) == 0) GT(128 * 8 + 6);
    }
    if ((threadIdx.x & 31) != 0) return;
    if (threadIdx.x == 256 && g == 5) GT(1412);
    if (warp == 0) {
        wait_eq4(&g_f.xn[0], epoch, 13);
        const int rk = g & 1;
        const int m1 = g < 32 ? HSPLIT : 2 * NT - HSPLIT;
#pragma unroll 1
        for (int it = 0; it < m1; it++) {
            const int tile = it < NT ? it : it - NT + HSPLIT;
            if (it == HOLD) mbar_wait(bar + 8 * GB_RL, 0);
            if (it == 1) mbar_wait(bar + 8 * GB_XN, 0);
            if (it == NT) {
                mbar_wait(bar + 8 * GB_WFREE, 0);
                load_w(sb, (g & 1) ? &maps.wv : &maps.wk, ((g - 32) >> 1) * 128, 0);
            }
#pragma unroll
            for (int k = 0; k < 4; k++) {
                if (k == 2 && it == 0) load_w(sb, (g & 1) ? &maps.wv : &maps.wk, (g >> 1) * 128, 0, 1, 2);
                mbar_wait(bar + 8 * (GB_EMPTY + k), (it & 1) ^ 1);
                mbar_expect_tx(bar + 8 * (GB_FULL + k), 16384);
                tma2d_mc(sb + slot_off(k) + rk * 8192, &maps.xn2, (k * 2 + rk) * 64, tile * 64, bar + 8 * (GB_FULL + k));
            }
        }
        mbar_wait(bar + 8 * GB_WFREE, g >= 32);
        const int u = g - 32, ks = u >> 2, ns = u & 3;
        if (g < 32) load_w(sb, &maps.wq, g * 128, 0);
        else {
#pragma unroll
            for (int kh = 0; kh < 2; kh++) {
                mbar_expect_tx(bar + 8 * (GB_W0 + kh), 65536);
#pragma unroll
                for (int nh = 0; nh < 2; nh++)
                    asm volatile("cp.async.bulk.tensor.5d.shared::cluster.global.mbarrier::complete_tx::bytes [%0], [%1, {%3, %4, %4, %4, %5}], [%2];"
                        :: "r"(sb + G_W + nh * 65536 + kh * 32768), "l"((uint64_t)&maps.wo2), "r"(bar + 8 * (GB_W0 + kh)), "r"(ns * 128 + nh * 64), "r"(0), "r"(ks * 16 + kh * 8) : "memory");
            }
        }
        if (g < 32) {
#pragma unroll 1
            for (int n = 0; n < NT * 4; n++) {
                const int slot = n & 3;
                mbar_wait(bar + 8 * (GB_EMPTY + slot), ((n >> 2) & 1) ^ 1);
                mbar_expect_tx(bar + 8 * (GB_FULL + slot), 16384);
                tma2d_mc(sb + slot_off(slot) + rk * 8192, &maps.xn2, (slot * 2 + rk) * 64, (n >> 2) * 64, bar + 8 * (GB_FULL + slot));
            }
        } else {
#pragma unroll 1
            for (int tile = 0; tile < NT; tile++) {
                wait_eq4(&g_f.o[tile][ks][0], epoch, 9);
                if (g == 40 && tile == NT - 1) GT(1437);
                if (tile == NT - 1) GT(1690 + g - 32);
#pragma unroll
                for (int k = 0; k < 4; k++) {
                    mbar_wait(bar + 8 * (GB_EMPTY + k), (tile & 1) ^ 1);
                    mbar_expect_tx(bar + 8 * (GB_FULL + k), 16384);
                    tma2d_mc(sb + slot_off(k) + rk * 8192, &maps.ox2, (ks * 8 + k * 2 + rk) * 64, tile * 64, bar + 8 * (GB_FULL + k));
                }
            }
        }
    } else if (warp < 3) {
        const int wg = warp - 1;
        const uint32_t buf = sb + G_BUF + wg * 32768;
        const CUtensorMap* tkv = (g & 1) ? &maps.vx3 : &maps.kx3;
        const int n1 = g < 32 ? HSPLIT / 2 : NT - HSPLIT / 2;
#pragma unroll 1
        for (int i = 0; i < n1; i++) {
            const int tile = (i < NT / 2 ? 2 * i : 2 * i - NT + HSPLIT) + wg, hd = (i < NT / 2 ? g : g - 32) >> 1;
            mbar_wait(bar + 8 * (GB_STG + wg), i & 1);
            tma_store3d(tkv, buf, tile * 64, hd * 2);
            asm volatile("cp.async.bulk.commit_group;" ::: "memory");
            asm volatile("cp.async.bulk.wait_group.read 0;" ::: "memory");
            mbar_arrive(bar + 8 * (GB_FREE + wg));
            asm volatile("cp.async.bulk.wait_group 0;" ::: "memory");
            PUBLISH(&g_f.kv[tile][hd][g & 1], epoch);
        }
        if (wg == 0) mbar_arrive(bar + 8 * GB_T1D);
        if (g < 32 && wg == 1) {
            mbar_wait(bar + 8 * GB_T1D, 0);
#pragma unroll 1
            for (int tile = 0; tile < NT; tile++) {
                wait_eq2(&g_f.kv[tile][g][0], epoch, 10);
                if (tile > 0) mbar_wait(bar + 8 * GB_KVF, (tile - 1) & 1);
                mbar_expect_tx(bar + 8 * (GB_KV + (tile & 1)), 16384);
                tma3d(sb + G_BUF, &maps.kx3, tile * 64, g * 2, bar + 8 * (GB_KV + (tile & 1)));
                if (tile > 0) mbar_wait(bar + 8 * GB_VF, (tile - 1) & 1);
                mbar_expect_tx(bar + 8 * (GB_VV + (tile & 1)), 16384);
                tma3d(sb + G_BUF + 32768, &maps.vx3, tile * 64, g * 2, bar + 8 * (GB_VV + (tile & 1)));
                if (PFK && tile + PFK < NT) {
                    const uint2 v = ldg_rlx2(&g_f.kv[tile + PFK][g][0]);
                    if (v.x == epoch && v.y == epoch) { tma_pf3d(&maps.kx3, (tile + PFK) * 64, g * 2); tma_pf3d(&maps.vx3, (tile + PFK) * 64, g * 2); }
                }
            }
        } else {
#pragma unroll 1
            for (int tile = g < 32 ? 0 : wg; tile < NT; tile += g < 32 ? 1 : 2) {
                mbar_wait(bar + 8 * (GB_STG + (tile & 1)), (tile >> 1) & 1);
                mbar_arrive(bar + 8 * (GB_FREE + (tile & 1)));
                PUBLISH(g < 32 ? &g_f.o[tile][g >> 2][g & 3] : &g_f.p[tile][g - 32], epoch);
                if (g == 3 && tile == NT - 1) GT(1436);
                if (g == 3) GT(1896 + tile);
                if (g < 32 && tile == NT - 1) GT(1610 + g);
                if (g == 40 && tile == NT - 1) GT(1435);
                if (g == 40) GT(1864 + tile);
                if (g >= 32 && tile == NT - 1) GT(1650 + g - 32);
            }
        }
    }
}

__device__ __forceinline__ int startup(uint8_t* smem, const bf16* __restrict__ x, const Maps& maps, uint32_t& epoch) {
    const int tid = threadIdx.x, lane = tid & 31, w = tid >> 5, cta = blockIdx.x;
    volatile uint32_t* sh = (volatile uint32_t*)(smem + SH_OFF);
    if (cta == 4 && tid == 0) GT(1399);
    epoch = (ldg_rlx(&g_epoch) + 1) & 0x00ffffffu;
    if (w < 4) {
        if (!(cta & 1)) {
            uint32_t* pp = (uint32_t*)(xpage() + ((XR3 ^ 0x3000u) ^ ((w == 1 || w == 2) ? 0x1000u : 0u) ^ ((w & 2) << 13))) + (cta >> 1) * 8;
            if (lane < 8) stg_rlx(pp + lane, 0u);
            __syncwarp();
            if (lane == 0) {
                uint32_t best = 0xffffffffu, a = 0;
#pragma unroll 1
                for (int r = 0; r < NPROBE; r++) {
                    uint32_t t0 = clk32();
                    asm volatile("atom.relaxed.gpu.global.add.u32 %0, [%1], %2;" : "=r"(a) : "l"(pp), "r"(a + 1) : "memory");
                    if (a == 0x7fffffffu) ABORT(15);
                    uint32_t t1 = clk32();
                    if (r > 0) best = min(best, t1 - t0);
                    else if (w == 0) {
                        asm volatile("red.relaxed.gpu.global.max.u32 [%0], %1;" :: "l"(&g_ticket[0]), "r"(epoch << 8) : "memory");
                        asm volatile("red.relaxed.gpu.global.max.u32 [%0], %1;" :: "l"(&g_ticket[32]), "r"(epoch << 8) : "memory");
                    }
                }
                sh[w] = best;
            }
        }
        if (!(cta & 1)) bar_sync(1, 128);
        if (cta == 4 && tid == 0) GT(1400);
        if (w == 0) {
            if (lane == 0) {
                uint32_t rp;
                if (!(cta & 1)) {
                    uint32_t a = sh[0], b = sh[1], c = sh[2], d = sh[3];
                    uint32_t mid = (min(min(a, b), min(c, d)) + max(max(a, b), max(c, d))) >> 1;
                    const int dd = (int)min(a, d) - (int)min(b, c);
                    uint32_t cls = abs(dd) > 60 ? dd > 0 : a > mid;
                    uint32_t t = atomicAdd(&g_ticket[cls * 32], 1u) & 255;
                    if (t >= (cls ? 34u : 32u)) { cls ^= 1; t = atomicAdd(&g_ticket[cls * 32], 1u) & 255; }
                    rp = min(cls ? 32 + t : t, 65u);
                    stg_rlx(&g_table[(cta >> 1) * 8], (epoch << 8) | rp);
                } else {
                    uint32_t v, n = 0;
#pragma unroll 1
                    while (((v = ldg_rlx(&g_table[(cta >> 1) * 8])) >> 8) != epoch) { if (++n > SPIN_LIMIT) { ABORT(14); break; } }
                    rp = v & 255;
                }
                const int role = rp * 2 + (cta & 1);
                sh[8] = role; sh[9] = epoch;
                while (sh[10] != epoch + 1 && cta < 128) {}
                asm volatile("fence.proxy.async;" ::: "memory");
                if (role < 64) rec_first_loads(smem_u32(smem), role, maps);
                else if (role < 128) load_w(smem_u32(smem), (role & 1) ? &maps.wv : &maps.wk, ((role - 64) >> 1) * 128, 0, 0, 1);
                if (cta == 4) GT(1401);
            }
        }
    } else if (cta < 128) {
        uint4 u[2][2];
        const int row0 = cta * 16 + (w - 4) * 2;
#pragma unroll
        for (int r = 0; r < 2; r++)
#pragma unroll
            for (int j = 0; j < 2; j++) u[r][j] = *(const uint4*)(x + (size_t)(row0 + r) * DM + j * 256 + lane * 8);
        if (cta < 48) {
            const uint32_t b = cta >> 3, off = (b >= 4 ? 0x8000u + (b & 1) * 0x4000u : ((b & 1) ? 0x3000u : 0u) + ((b & 2) << 13)) ^ aslot(cta & 7);
            *(uint4*)(xpage() + off + (tid - 128) * 16) = make_uint4(0, 0, 0, 0);
        }
        float v[2][16];
#pragma unroll
        for (int r = 0; r < 2; r++)
#pragma unroll
            for (int j = 0; j < 2; j++) {
                uint32_t ww[4] = {u[r][j].x, u[r][j].y, u[r][j].z, u[r][j].w};
#pragma unroll
                for (int i = 0; i < 4; i++) { v[r][j * 8 + 2 * i] = bf_lo(ww[i]); v[r][j * 8 + 2 * i + 1] = bf_hi(ww[i]); }
            }
        ln_row2(v[0], v[1]);
#pragma unroll
        for (int r = 0; r < 2; r++)
#pragma unroll
            for (int j = 0; j < 2; j++)
                *(uint4*)(g_xn + (size_t)(row0 + r) * DM + j * 256 + lane * 8) =
                    make_uint4(pack2(v[r][j * 8], v[r][j * 8 + 1]), pack2(v[r][j * 8 + 2], v[r][j * 8 + 3]), pack2(v[r][j * 8 + 4], v[r][j * 8 + 5]), pack2(v[r][j * 8 + 6], v[r][j * 8 + 7]));
        bar_sync(2, 256);
        if (tid == 160) { st_rel(&g_f.xn[cta], epoch); sh[10] = epoch + 1; }
        if (cta == 4 && tid == 160) GT(1403);
        __syncwarp();
    }
    if (cta == 4 && tid == 128) GT(1402);
    __syncthreads();
    const int role = sh[8];
    return role;
}

struct WPtr { const bf16 *q, *k, *v, *o; };
__global__ void __cluster_dims__(2, 1, 1) __launch_bounds__(384, 1)
main_kernel(const __grid_constant__ Maps maps, const bf16* __restrict__ x, const bf16* __restrict__ mem0, const bf16* __restrict__ wr,
            const bf16* __restrict__ wd, bf16* __restrict__ out, const WPtr pw) {
    extern __shared__ __align__(1024) uint8_t smem[];
    const uint32_t sb = smem_u32(smem);
    if (threadIdx.x == 0) {
        for (int i = 0; i < MB_N; i++) mbar_init(sb + R_BAR + 8 * i, i == MB_V ? 4 : 1);
        for (int i = 0; i < GB_N; i++)
            mbar_init(sb + G_BAR + 8 * i, i == GB_WFREE || (i >= GB_EMPTY && i < GB_KV) ? 8 : (i >= GB_KVF ? 4 : (i >= GB_STG && i < GB_FREE ? 128 : 1)));
        asm volatile("fence.mbarrier_init.release.cluster;" ::: "memory");
    }
    __syncwarp();
    asm volatile("barrier.cluster.arrive.relaxed.aligned;" ::: "memory");
    if (threadIdx.x >= 352 && threadIdx.x < 352 + (int)(sizeof(Maps) / sizeof(CUtensorMap)))
        asm volatile("prefetch.tensormap [%0];" :: "l"((const CUtensorMap*)&maps + (threadIdx.x - 352)) : "memory");
    uint32_t epoch;
    asm volatile("fence.proxy.async.shared::cta;" ::: "memory");
    const int role = uni(startup(smem, x, maps, epoch));
    asm volatile("barrier.cluster.wait.aligned;" ::: "memory");
    const int wg = uni(threadIdx.x >> 7);
    if (role < 64) {
#define SETREG(n) do { if ((n) < 168) asm volatile("setmaxnreg.dec.sync.aligned.u32 %0;" :: "n"(n)); if ((n) > 168) asm volatile("setmaxnreg.inc.sync.aligned.u32 %0;" :: "n"(n)); } while (0)
#define RESREG(n) do { if ((n) < 168) asm volatile("setmaxnreg.inc.sync.aligned.u32 168;"); if ((n) > 168) asm volatile("setmaxnreg.dec.sync.aligned.u32 168;"); } while (0)
        if (wg == 0) {
            SETREG(RGA);
            rec_a(sb, role, mem0, epoch);
            RESREG(RGA);
        } else if (wg == 1) {
            SETREG(RGB);
            rec_b(sb, role, epoch);
            RESREG(RGB);
        } else {
            SETREG(RGC);
            rec_c(sb, role, mem0, maps, epoch);
            RESREG(RGC);
        }
        ffn_phase(maps, wd, out);
        if (threadIdx.x == 0) GT(((volatile int*)(smem + SH_OFF))[8] * 8 + 6);
    } else if (role < 128) {
        if (wg < 2) {
            asm volatile("setmaxnreg.inc.sync.aligned.u32 192;");
            g_consumer(sb, role - 64, wg, epoch);
            if (threadIdx.x == 128) GT(role * 8 + 6);
        } else {
            asm volatile("setmaxnreg.dec.sync.aligned.u32 120;");
            g_producer(sb, role - 64, maps, epoch, x, wr, out);
        }
    } else {
        finalizer(64 + (threadIdx.x >> 5) * 4 + role - 128, x, wr, out, epoch);
    }
}

typedef CUresult (*EncodeFn)(CUtensorMap*, CUtensorMapDataType, cuuint32_t, void*, const cuuint64_t*, const cuuint64_t*, const cuuint32_t*, const cuuint32_t*,
                             CUtensorMapInterleave, CUtensorMapSwizzle, CUtensorMapL2promotion, CUtensorMapFloatOOBfill);
static void make_map3(EncodeFn fn, CUtensorMap* m, const void* ptr, uint64_t cols, uint64_t rows) {
    cuuint64_t dims[3] = {64, rows, cols / 64};
    cuuint64_t strides[2] = {cols * 2, 128};
    cuuint32_t box[3] = {64, 64, 2};
    cuuint32_t es[3] = {1, 1, 1};
    fn(m, CU_TENSOR_MAP_DATA_TYPE_BFLOAT16, 3, (void*)ptr, dims, strides, box, es, CU_TENSOR_MAP_INTERLEAVE_NONE, CU_TENSOR_MAP_SWIZZLE_128B,
       CU_TENSOR_MAP_L2_PROMOTION_L2_256B, CU_TENSOR_MAP_FLOAT_OOB_FILL_NONE);
}
static void make_map(EncodeFn fn, CUtensorMap* m, const void* ptr, uint64_t cols, uint64_t rows, uint32_t bcols, uint32_t brows,
                     bool f32 = false, CUtensorMapSwizzle sw = CU_TENSOR_MAP_SWIZZLE_128B) {
    cuuint64_t dims[2] = {cols, rows};
    cuuint64_t strides[1] = {cols * (f32 ? 4 : 2)};
    cuuint32_t box[2] = {bcols, brows};
    cuuint32_t es[2] = {1, 1};
    fn(m, f32 ? CU_TENSOR_MAP_DATA_TYPE_FLOAT32 : CU_TENSOR_MAP_DATA_TYPE_BFLOAT16, 2, (void*)ptr, dims, strides, box, es, CU_TENSOR_MAP_INTERLEAVE_NONE, sw,
       CU_TENSOR_MAP_L2_PROMOTION_L2_256B, CU_TENSOR_MAP_FLOAT_OOB_FILL_NONE);
}

extern "C" void kernel_launch(void* const* d_in, const int* in_sizes, int n_in, void* d_out, int out_size) {
    const bf16* x = (const bf16*)d_in[0];
    const bf16* mem0 = (const bf16*)d_in[1];
    const bf16* Wq = (const bf16*)d_in[2];
    const bf16* Wk = (const bf16*)d_in[3];
    const bf16* Wv = (const bf16*)d_in[4];
    const bf16* Wo = (const bf16*)d_in[5];
    const bf16* wr = (const bf16*)d_in[8];
    const bf16* wg = (const bf16*)d_in[9];
    const bf16* wu = (const bf16*)d_in[10];
    const bf16* wd = (const bf16*)d_in[11];
    bf16* out = (bf16*)d_out;

    static EncodeFn enc = nullptr;
    static void *pxn, *pK, *pV, *pO, *pacc;
    if (!enc) {
        cudaDriverEntryPointQueryResult qr;
        void* fn = nullptr;
        cudaGetDriverEntryPoint("cuTensorMapEncodeTiled", &fn, cudaEnableDefault, &qr);
        enc = (EncodeFn)fn;
        cudaGetSymbolAddress(&pxn, g_xn); cudaGetSymbolAddress(&pK, g_K); cudaGetSymbolAddress(&pV, g_V);
        cudaGetSymbolAddress(&pO, g_O); cudaGetSymbolAddress(&pacc, g_P);
        cudaFuncSetAttribute(main_kernel, cudaFuncAttributeMaxDynamicSharedMemorySize, SMEM_TOTAL);
    }
    Maps m;
    make_map(enc, &m.wq, Wq, HD, DM, 64, 256);
    make_map(enc, &m.wk, Wk, HD, DM, 64, 256);
    make_map(enc, &m.wv, Wv, HD, DM, 64, 256);
    make_map(enc, &m.wo, Wo, DM, HD, 64, 128);
    {
        cuuint64_t dims[5] = {DM, 2, 4, 4, HD / 32};
        cuuint64_t strides[4] = {DM * 2, 8 * DM * 2, 2 * DM * 2, 32 * DM * 2};
        cuuint32_t box[5] = {64, 2, 4, 4, 8};
        cuuint32_t es[5] = {1, 1, 1, 1, 1};
        enc(&m.wo2, CU_TENSOR_MAP_DATA_TYPE_BFLOAT16, 5, (void*)Wo, dims, strides, box, es, CU_TENSOR_MAP_INTERLEAVE_NONE, CU_TENSOR_MAP_SWIZZLE_128B,
            CU_TENSOR_MAP_L2_PROMOTION_L2_256B, CU_TENSOR_MAP_FLOAT_OOB_FILL_NONE);
    }
    make_map(enc, &m.kx, pK, HD, SQ, 64, 64);
    make_map(enc, &m.ox2, pO, HD, SQ, 64, 64);
    make_map(enc, &m.xn2, pxn, DM, SQ, 64, 64);
    make_map3(enc, &m.kx3, pK, HD, SQ); make_map3(enc, &m.vx3, pV, HD, SQ);
    make_map(enc, &m.wg, wg, FF, DM, 32, 256, false, CU_TENSOR_MAP_SWIZZLE_NONE);
    make_map(enc, &m.wu, wu, FF, DM, 32, 256, false, CU_TENSOR_MAP_SWIZZLE_NONE);

    cudaStream_t st = cudaStreamPerThread;
    main_kernel<<<NCTA, 384, SMEM_TOTAL, st>>>(m, x, mem0, wr, wd, out, WPtr{Wq, Wk, Wv, Wo});
}
```

```cpp
#include <cuda_runtime.h>
#include <cuda_bf16.h>
#include <cuda.h>
#include <stdint.h>
#include <stddef.h>

typedef __nv_bfloat16 bf16;

constexpr int SQ = 2048, DM = 512, NH = 32, DH = 128, NSEG = 64, HD = 4096, FF = 1792;

constexpr int NT = 32;
#define SPEC_TILES 30
__device__ __align__(1024) bf16 g_xn[SQ * DM];
__device__ __align__(1024) bf16 g_K[SQ * HD];
__device__ __align__(1024) bf16 g_V[SQ * HD];
__device__ __align__(1024) bf16 g_O[SQ * HD];
__device__ __align__(1024) uint32_t g_KVf[NSEG][NH][1024];
__device__ __align__(1024) bf16 g_P[8 * SQ * DM];
__device__ __align__(1024) bf16 g_h[SQ * DM];
__device__ __align__(1024) bf16 g_hn[SQ * DM];
__device__ uint8_t g_xraw[12 << 20];
#define XPG 0
__device__ __forceinline__ uint64_t xpage() { return (((uint64_t)g_xraw + (2 << 20) - 1) & ~(uint64_t)((2 << 20) - 1)) + ((uint64_t)XPG << 21); }
constexpr uint32_t XR3 = (1u << 20) | (1u << 19) | (1u << 12);
__device__ __forceinline__ uint32_t aslot(uint32_t s) { return ((s & 1) << 18) | ((s & 2) << 19) | ((s & 4) * 0xc000u); }
#define IL 1
constexpr int AC1 = IL ? 48 : 256;
__device__ __forceinline__ uint32_t acc_off(uint32_t W, uint32_t lane) {
    return ((W & 2) ? 0x3000u : 0u) + ((W & 4) << 12) + (W & 1) * 2048 + (IL ? (lane >> 2) * 256 : (lane >> 2) * 128 + (lane & 4) * 16) + (lane & 3) * 16;
}
#define XM 4
__device__ __forceinline__ uint32_t ext_base(uint32_t W) { return 0x8000u + ((W & 4) << 12) + (W & 3) * 1024; }
__device__ __forceinline__ uint32_t ext_lane(uint32_t lane) { return XM == 1 ? (lane >> 3) * 256 + (lane & 7) * 4 : (XM == 2 ? (lane >> 4) * 512 + (lane & 15) * 4 : lane * 4); }
__device__ __forceinline__ uint32_t zero_off(uint32_t c, uint32_t ln) {
    return ln < 16 ? ((c & 16) ? 0x3000u : 0u) + ((c & 32) << 9) + (c & 15) * 256 + ln * 16 : ext_base(c >> 3) + ext_lane((c & 7) * 4);
}
struct Flags {
    uint32_t kv[NT][NH][2];
    uint32_t o[NT][8][32];
    uint32_t rec[64];
    uint32_t xn[128];
    uint32_t rload[64];
    uint32_t p[NT][32];
    uint32_t rows[2][128];
    uint4 cand[2][128];
    uint4 norm[64];
};
__device__ __align__(1024) Flags g_f;
__device__ __align__(1024) uint4 g_yp[2][FF / 32][DM];
__device__ __align__(1024) uint32_t g_table[66 * 8];
__device__ __align__(256) uint32_t g_ticket[64];
__device__ uint32_t g_epoch;
#define HOLD 6
#define HSPLIT 24
#define EREL 0
#define PFK 2
#define PFO 0
#define PFS 0
#define NWAITLN 8
#define NPROBE 3
constexpr int NCTA = 132;
constexpr int NFW = 112;
__device__ uint32_t g_abort;
__device__ long long g_dbg[4096];
#define TR(slot, v)

__device__ __forceinline__ uint32_t smem_u32(const void* p) { return (uint32_t)__cvta_generic_to_shared(p); }
__device__ __forceinline__ void mbar_init(uint32_t a, uint32_t c) { asm volatile("mbarrier.init.shared::cta.b64 [%0], %1;" :: "r"(a), "r"(c) : "memory"); }
__device__ __forceinline__ void mbar_expect_tx(uint32_t a, uint32_t tx) { asm volatile("mbarrier.arrive.expect_tx.shared::cta.b64 _, [%0], %1;" :: "r"(a), "r"(tx) : "memory"); }
__device__ __forceinline__ void mbar_arrive(uint32_t a) { asm volatile("mbarrier.arrive.shared::cta.b64 _, [%0];" :: "r"(a) : "memory"); }
__device__ __forceinline__ void mbar_arrive_if(uint32_t a, uint32_t pred) {
    asm volatile("{\n.reg .pred p;\nsetp.ne.u32 p, %1, 0;\n@p mbarrier.arrive.shared::cta.b64 _, [%0];\n}" :: "r"(a), "r"(pred) : "memory");
}
__device__ __forceinline__ bool mbar_try(uint32_t a, uint32_t ph) {
    uint32_t ok;
    asm volatile("{\n.reg .pred p;\nmbarrier.try_wait.parity.shared::cta.b64 p, [%1], %2;\nselp.u32 %0, 1, 0, p;\n}" : "=r"(ok) : "r"(a), "r"(ph) : "memory");
    return ok != 0;
}
#define SPINLOG 20
constexpr uint32_t SPIN_LIMIT = 1u << SPINLOG;
#define ABORT(code_) atomicCAS(&g_abort, 0u, (code_))
__device__ __forceinline__ void mbar_wait(uint32_t a, uint32_t ph) {
    uint32_t n = 0;
#pragma unroll 1
    while (!mbar_try(a, ph)) { if (++n > SPIN_LIMIT) { ABORT(1); break; } }
}
__device__ __forceinline__ void bar_sync(int id, int n) { asm volatile("bar.sync %0, %1;" :: "r"(id), "r"(n) : "memory"); }
__device__ __forceinline__ void bar_arrive(int id, int n) { asm volatile("bar.arrive %0, %1;" :: "r"(id), "r"(n) : "memory"); }

__device__ __forceinline__ void ldsm4(uint32_t* r, uint32_t a) {
    asm volatile("ldmatrix.sync.aligned.m8n8.x4.shared.b16 {%0,%1,%2,%3}, [%4];" : "=r"(r[0]), "=r"(r[1]), "=r"(r[2]), "=r"(r[3]) : "r"(a) : "memory");
}
__device__ __forceinline__ void ldsm4t(uint32_t* r, uint32_t a) {
    asm volatile("ldmatrix.sync.aligned.m8n8.x4.trans.shared.b16 {%0,%1,%2,%3}, [%4];" : "=r"(r[0]), "=r"(r[1]), "=r"(r[2]), "=r"(r[3]) : "r"(a) : "memory");
}
__device__ __forceinline__ void stsm4t(uint32_t a, uint32_t r0, uint32_t r1, uint32_t r2, uint32_t r3) {
    asm volatile("stmatrix.sync.aligned.m8n8.x4.trans.shared.b16 [%0], {%1,%2,%3,%4};" :: "r"(a), "r"(r0), "r"(r1), "r"(r2), "r"(r3) : "memory");
}
__device__ __forceinline__ void stsm4(uint32_t a, uint32_t r0, uint32_t r1, uint32_t r2, uint32_t r3) {
    asm volatile("stmatrix.sync.aligned.m8n8.x4.shared.b16 [%0], {%1,%2,%3,%4};" :: "r"(a), "r"(r0), "r"(r1), "r"(r2), "r"(r3) : "memory");
}
__device__ __forceinline__ uint32_t movm(uint32_t a) { uint32_t d; asm volatile("movmatrix.sync.aligned.m8n8.trans.b16 %0, %1;" : "=r"(d) : "r"(a)); return d; }
__device__ __forceinline__ void mma16816(float* d, uint32_t a0, uint32_t a1, uint32_t a2, uint32_t a3, uint32_t b0, uint32_t b1) {
    asm volatile("mma.sync.aligned.m16n8k16.row.col.f32.bf16.bf16.f32 {%0,%1,%2,%3}, {%4,%5,%6,%7}, {%8,%9}, {%0,%1,%2,%3};"
        : "+f"(d[0]), "+f"(d[1]), "+f"(d[2]), "+f"(d[3]) : "r"(a0), "r"(a1), "r"(a2), "r"(a3), "r"(b0), "r"(b1));
}
__device__ __forceinline__ void mma1688(float* d, uint32_t a0, uint32_t a1, uint32_t b0) {
    asm volatile("mma.sync.aligned.m16n8k8.row.col.f32.bf16.bf16.f32 {%0,%1,%2,%3}, {%4,%5}, {%6}, {%0,%1,%2,%3};"
        : "+f"(d[0]), "+f"(d[1]), "+f"(d[2]), "+f"(d[3]) : "r"(a0), "r"(a1), "r"(b0));
}
__device__ __forceinline__ uint32_t pack2(float a, float b) { uint32_t d; asm("cvt.rn.bf16x2.f32 %0, %1, %2;" : "=r"(d) : "f"(b), "f"(a)); return d; }
__device__ __forceinline__ float bf_lo(uint32_t w) { return __uint_as_float(w << 16); }
__device__ __forceinline__ float bf_hi(uint32_t w) { return __uint_as_float(w & 0xffff0000u); }
__device__ __forceinline__ float rbf(float x) { return __bfloat162float(__float2bfloat16_rn(x)); }

__device__ __forceinline__ void sts128(uint32_t a, float x, float y, float z, float w) { asm volatile("st.shared.v4.f32 [%0], {%1,%2,%3,%4};" :: "r"(a), "f"(x), "f"(y), "f"(z), "f"(w) : "memory"); }
__device__ __forceinline__ void sts128u(uint32_t a, uint32_t x, uint32_t y, uint32_t z, uint32_t w) { asm volatile("st.shared.v4.b32 [%0], {%1,%2,%3,%4};" :: "r"(a), "r"(x), "r"(y), "r"(z), "r"(w) : "memory"); }
__device__ __forceinline__ void sts64(uint32_t a, float x, float y) { asm volatile("st.shared.v2.f32 [%0], {%1,%2};" :: "r"(a), "f"(x), "f"(y) : "memory"); }
__device__ __forceinline__ float4 lds128(uint32_t a) { float4 v; asm volatile("ld.shared.v4.f32 {%0,%1,%2,%3}, [%4];" : "=f"(v.x), "=f"(v.y), "=f"(v.z), "=f"(v.w) : "r"(a) : "memory"); return v; }
__device__ __forceinline__ float2 lds64(uint32_t a) { float2 v; asm volatile("ld.shared.v2.f32 {%0,%1}, [%2];" : "=f"(v.x), "=f"(v.y) : "r"(a) : "memory"); return v; }
__device__ __forceinline__ uint2 lds64u(uint32_t a) { uint2 v; asm volatile("ld.shared.v2.b32 {%0,%1}, [%2];" : "=r"(v.x), "=r"(v.y) : "r"(a) : "memory"); return v; }
__device__ __forceinline__ float4 lds128v(uint32_t a) { float4 v; asm volatile("ld.volatile.shared.v4.f32 {%0,%1,%2,%3}, [%4];" : "=f"(v.x), "=f"(v.y), "=f"(v.z), "=f"(v.w) : "r"(a) : "memory"); return v; }
__device__ __forceinline__ float2 lds64v(uint32_t a) { float2 v; asm volatile("ld.volatile.shared.v2.f32 {%0,%1}, [%2];" : "=f"(v.x), "=f"(v.y) : "r"(a) : "memory"); return v; }
__device__ __forceinline__ uint4 lds128uv(uint32_t a) { uint4 v; asm volatile("ld.volatile.shared.v4.b32 {%0,%1,%2,%3}, [%4];" : "=r"(v.x), "=r"(v.y), "=r"(v.z), "=r"(v.w) : "r"(a) : "memory"); return v; }
__device__ __forceinline__ void st_async4(uint32_t a, float x, float y, float z, float w, uint32_t mb) {
    asm volatile("st.async.weak.shared::cluster.mbarrier::complete_tx::bytes.v4.f32 [%0], {%1,%2,%3,%4}, [%5];" :: "r"(a), "f"(x), "f"(y), "f"(z), "f"(w), "r"(mb) : "memory");
}
__device__ __forceinline__ void st_async2(uint32_t a, uint32_t x, uint32_t y, uint32_t mb) {
    asm volatile("st.async.weak.shared::cluster.mbarrier::complete_tx::bytes.v2.b32 [%0], {%1,%2}, [%3];" :: "r"(a), "r"(x), "r"(y), "r"(mb) : "memory");
}
__device__ __forceinline__ uint32_t ldg_rlx(const uint32_t* p) { uint32_t v; asm volatile("ld.relaxed.gpu.global.b32 %0, [%1];" : "=r"(v) : "l"(p) : "memory"); return v; }
__device__ __forceinline__ uint4 ldg_rlx4(const uint32_t* p) { uint4 v; asm volatile("ld.relaxed.gpu.global.v4.b32 {%0,%1,%2,%3}, [%4];" : "=r"(v.x), "=r"(v.y), "=r"(v.z), "=r"(v.w) : "l"(p) : "memory"); return v; }
__device__ __forceinline__ uint4 ldg_rlx4_if(const uint32_t* p, bool c) {
    uint4 v;
    asm volatile("{\n.reg .pred p;\nsetp.ne.u32 p, %5, 0;\nmov.b32 %0, 0;\nmov.b32 %1, 0;\nmov.b32 %2, 0;\nmov.b32 %3, 0;\n@p ld.relaxed.gpu.global.v4.b32 {%0,%1,%2,%3}, [%4];\n}"
                 : "=r"(v.x), "=r"(v.y), "=r"(v.z), "=r"(v.w) : "l"(p), "r"((uint32_t)c) : "memory");
    return v;
}
__device__ __forceinline__ void stg_rlx(uint32_t* p, uint32_t v) { asm volatile("st.relaxed.gpu.global.b32 [%0], %1;" :: "l"(p), "r"(v) : "memory"); }
__device__ __forceinline__ void tma2d(uint32_t dst, const CUtensorMap* tm, int c0, int c1, uint32_t mb) {
    asm volatile("cp.async.bulk.tensor.2d.shared::cluster.global.mbarrier::complete_tx::bytes [%0], [%1, {%3, %4}], [%2];"
        :: "r"(dst), "l"((uint64_t)tm), "r"(mb), "r"(c0), "r"(c1) : "memory");
}

__device__ __forceinline__ void tma3d(uint32_t dst, const CUtensorMap* tm, int row, int chunk, uint32_t mb) {
    asm volatile("cp.async.bulk.tensor.3d.shared::cluster.global.mbarrier::complete_tx::bytes [%0], [%1, {%3, %4, %5}], [%2];"
        :: "r"(dst), "l"((uint64_t)tm), "r"(mb), "r"(0), "r"(row), "r"(chunk) : "memory");
}
__device__ __forceinline__ void tma2d_mc(uint32_t dst, const CUtensorMap* tm, int c0, int c1, uint32_t mb) {
    asm volatile("cp.async.bulk.tensor.2d.shared::cluster.global.mbarrier::complete_tx::bytes.multicast::cluster [%0], [%1, {%3, %4}], [%2], %5;"
        :: "r"(dst), "l"((uint64_t)tm), "r"(mb), "r"(c0), "r"(c1), "h"((uint16_t)3) : "memory");
}
__device__ __forceinline__ void mbar_arrive2_if(uint32_t a, uint32_t pred) {
    asm volatile("{\n.reg .pred p;\nsetp.ne.u32 p, %1, 0;\n@p mbarrier.arrive.shared::cta.b64 _, [%0];\n@p mbarrier.arrive.shared::cluster.b64 _, [%2];\n}"
                 :: "r"(a), "r"(pred), "r"(a ^ 0x01000000u) : "memory");
}
__device__ __forceinline__ void tma_pf3d(const CUtensorMap* tm, int row, int chunk) {
    asm volatile("cp.async.bulk.prefetch.tensor.3d.L2.global.tile [%0, {%1, %2, %3}];" :: "l"((uint64_t)tm), "r"(0), "r"(row), "r"(chunk) : "memory");
}
__device__ __forceinline__ void tma_pf2d(const CUtensorMap* tm, int c0, int c1) {
    asm volatile("cp.async.bulk.prefetch.tensor.2d.L2.global.tile [%0, {%1, %2}];" :: "l"((uint64_t)tm), "r"(c0), "r"(c1) : "memory");
}
__device__ __forceinline__ void tma_store3d(const CUtensorMap* tm, uint32_t src, int row, int chunk) {
    asm volatile("cp.async.bulk.tensor.3d.global.shared::cta.bulk_group [%0, {%2, %3, %4}], [%1];" :: "l"((uint64_t)tm), "r"(src), "r"(0), "r"(row), "r"(chunk) : "memory");
}
__device__ __forceinline__ void bulk_store(void* dst, uint32_t src, uint32_t bytes) {
    asm volatile("cp.async.bulk.global.shared::cta.bulk_group [%0], [%1], %2;" :: "l"(dst), "r"(src), "r"(bytes) : "memory");
}
#define GT(slot)
#define CNT(k)
#define CNT2(k, c)
#define PS0 20
#define TS(i)
#define TSDECL
struct Maps { CUtensorMap wq, wk, wv, wo, wo2, kx, ox2, kx3, vx3, xn2, wg, wu; };
typedef Maps RecMaps;
__device__ __forceinline__ void st_rel(uint32_t* p, uint32_t v) { asm volatile("st.release.gpu.global.u32 [%0], %1;" :: "l"(p), "r"(v) : "memory"); }
#define PUBLISH(p, v) st_rel(p, v)
__device__ __forceinline__ uint2 ldg_rlx2(const uint32_t* p) { uint2 v; asm volatile("ld.relaxed.gpu.global.v2.b32 {%0,%1}, [%2];" : "=r"(v.x), "=r"(v.y) : "l"(p) : "memory"); return v; }
__device__ __forceinline__ void wait_eq2(const uint32_t* p, uint32_t e, int code) {
    uint32_t n = 0;
#pragma unroll 1
    while (true) { uint2 v = ldg_rlx2(p); if (v.x == e && v.y == e) break; __nanosleep(64); if (++n > SPIN_LIMIT) { ABORT(code); break; } }
}
__device__ __forceinline__ void wait_eq4(const uint32_t* p, uint32_t e, int code) {
    uint32_t n = 0;
#pragma unroll 1
    while (true) { uint4 v = ldg_rlx4(p); if (v.x == e && v.y == e && v.z == e && v.w == e) break; __nanosleep(64); if (++n > SPIN_LIMIT) { ABORT(code); break; } }
}
__device__ __forceinline__ void wait_rec(const uint32_t* p, uint32_t e, uint32_t steps) {
    uint32_t n = 0;
#pragma unroll 1
    while (true) {
        uint2 v = ldg_rlx2(p);
        if (__all_sync(0xffffffffu, (v.x >> 8) == e && (v.y >> 8) == e && (v.x & 255) >= steps && (v.y & 255) >= steps)) break;
        __nanosleep(64); if (++n > SPIN_LIMIT) { ABORT(8); break; }
    }
}

constexpr int R_QK1 = 0;
constexpr int R_WO = 65536;
constexpr int R_T = 131072;
constexpr int R_SLOT1 = R_T;
constexpr int R_MEMB = R_T + 24576;
constexpr int R_QP = R_MEMB + 8192;
constexpr int R_VRED = R_QP + 4096;
constexpr int R_STG = R_VRED + 2048;
constexpr int R_AX = R_STG + 2048;
constexpr int R_SLOT0 = 196608;
constexpr int R_SLOC = R_SLOT0 + 24576;
constexpr int R_SREM = R_SLOC + 1536;
constexpr int R_VB = R_SREM + 1536;
constexpr int R_MISC = R_VB + 2048;
constexpr int R_LT = R_MISC + 128;
constexpr int R_BAR = 229888;
constexpr int R_TS = 229888 + 128;
static_assert(R_AX + 24576 <= R_SLOT0 && R_LT + 2560 <= 229376, "smem map");
enum { MB_W0 = 0, MB_W1, MB_WV, MB_WO, MB_S, MB_FULL0, MB_FULL1, MB_V, MB_N };

__device__ __forceinline__ float ex2(float x) { float y; asm("ex2.approx.ftz.f32 %0, %1;" : "=f"(y) : "f"(x)); return y; }
__device__ __forceinline__ float rcpf(float x) { float y; asm("rcp.approx.ftz.f32 %0, %1;" : "=f"(y) : "f"(x)); return y; }
__device__ __forceinline__ void mma16816z(float* d, uint32_t a0, uint32_t a1, uint32_t a2, uint32_t a3, uint32_t b0, uint32_t b1) {
    asm volatile("mma.sync.aligned.m16n8k16.row.col.f32.bf16.bf16.f32 {%0,%1,%2,%3}, {%4,%5,%6,%7}, {%8,%9}, {%10,%10,%10,%10};"
        : "=f"(d[0]), "=f"(d[1]), "=f"(d[2]), "=f"(d[3]) : "r"(a0), "r"(a1), "r"(a2), "r"(a3), "r"(b0), "r"(b1), "f"(0.f));
}
__device__ __forceinline__ void mma1688hz(float* d, uint32_t a0, uint32_t a1, uint32_t b0) {
    asm volatile("mma.sync.aligned.m16n8k8.row.col.f32.f16.f16.f32 {%0,%1,%2,%3}, {%4,%5}, {%6}, {%7,%7,%7,%7};"
        : "=f"(d[0]), "=f"(d[1]), "=f"(d[2]), "=f"(d[3]) : "r"(a0), "r"(a1), "r"(b0), "f"(0.f));
}
#define MMA(d, a, b0, b1) mma16816(d, a[0], a[1], a[2], a[3], b0, b1)
#define MMAZ(d, a, b0, b1) mma16816z(d, a[0], a[1], a[2], a[3], b0, b1)
#define MMAF(first, d, a, b0, b1) do { if (first) MMAZ(d, a, b0, b1); else MMA(d, a, b0, b1); } while (0)

__device__ __forceinline__ uint32_t uni(uint32_t x) { return __reduce_max_sync(0xffffffffu, x); }
__device__ __forceinline__ void mbar_wait_u(uint32_t a, uint32_t ph) {
    uint32_t n = 0;
#pragma unroll 1
    while (!__all_sync(0xffffffffu, mbar_try(a, ph))) { if (++n > SPIN_LIMIT) { ABORT(1); break; } }
}
__device__ __forceinline__ void mbar_wait_p(uint32_t a, uint32_t ph) {
    asm volatile("{\n.reg .pred p, q;\n.reg .u32 n;\nmov.u32 n, 0;\nWL: mbarrier.try_wait.parity.shared::cta.b64 p, [%0], %1;\nadd.u32 n, n, 1;\n"
                 "setp.lt.and.u32 q, n, %2, !p;\n@q bra.uni WL;\n}" :: "r"(a), "r"(ph), "n"(SPIN_LIMIT) : "memory");
}
__device__ __forceinline__ uint32_t mbar_test(uint32_t a, uint32_t ph) {
    uint32_t ok;
    asm volatile("{\n.reg .pred p;\nmbarrier.test_wait.parity.shared::cta.b64 p, [%1], %2;\nselp.u32 %0, 1, 0, p;\n}" : "=r"(ok) : "r"(a), "r"(ph) : "memory");
    return ok;
}
__device__ __forceinline__ uint32_t opaque(uint32_t x) { return __shfl_sync(0xffffffffu, x, threadIdx.x & 31); }
__device__ __forceinline__ const uint32_t* mkptr(uint32_t lo, uint32_t hi) { uint64_t r; asm("mov.b64 %0, {%1, %2};" : "=l"(r) : "r"(lo), "r"(hi)); return (const uint32_t*)r; }
__device__ __forceinline__ uint32_t prmt(uint32_t a, uint32_t b, uint32_t s) { uint32_t d; asm("prmt.b32 %0, %1, %2, %3;" : "=r"(d) : "r"(a), "r"(b), "r"(s)); return d; }
__device__ __forceinline__ uint32_t packh2(float a, float b) { uint32_t d; asm("cvt.rn.f16x2.f32 %0, %1, %2;" : "=r"(d) : "f"(b), "f"(a)); return d; }
__device__ __forceinline__ uint32_t hadd2b(uint32_t a, uint32_t b) { uint32_t d; asm("add.rn.bf16x2 %0, %1, %2;" : "=r"(d) : "r"(a), "r"(b)); return d; }
__device__ __forceinline__ uint32_t hmul2b(uint32_t a, uint32_t b) { uint32_t d; asm("mul.rn.bf16x2 %0, %1, %2;" : "=r"(d) : "r"(a), "r"(b)); return d; }
__device__ __forceinline__ uint32_t amax2b(uint32_t a, uint32_t b) { uint32_t d; asm("max.xorsign.abs.bf16x2 %0, %1, %2;" : "=r"(d) : "r"(a), "r"(b)); return d; }
__device__ __forceinline__ uint32_t amax2h(uint32_t a, uint32_t b) { uint32_t d; asm("max.xorsign.abs.f16x2 %0, %1, %2;" : "=r"(d) : "r"(a), "r"(b)); return d; }
__device__ __forceinline__ void sts32(uint32_t a, uint32_t x) { asm volatile("st.shared.b32 [%0], %1;" :: "r"(a), "r"(x) : "memory"); }
__device__ __forceinline__ uint32_t lds32v_(uint32_t a) { uint32_t v; asm volatile("ld.volatile.shared.b32 %0, [%1];" : "=r"(v) : "r"(a) : "memory"); return v; }
__device__ __forceinline__ void stg4(void* p, uint4 v) { asm volatile("st.relaxed.gpu.global.v4.b32 [%0], {%1,%2,%3,%4};" :: "l"(p), "r"(v.x), "r"(v.y), "r"(v.z), "r"(v.w) : "memory"); }
__device__ __forceinline__ void lds_frag(uint32_t* r, uint32_t a) {
    asm volatile("ld.shared.v4.b32 {%0,%1,%2,%3}, [%4];" : "=r"(r[0]), "=r"(r[1]), "=r"(r[2]), "=r"(r[3]) : "r"(a) : "memory");
}
__device__ __forceinline__ void lds_fragv(uint32_t* r, uint32_t a) {
    asm volatile("ld.volatile.shared.v4.b32 {%0,%1,%2,%3}, [%4];" : "=r"(r[0]), "=r"(r[1]), "=r"(r[2]), "=r"(r[3]) : "r"(a) : "memory");
}
__device__ __forceinline__ uint32_t xorv(uint32_t a, uint32_t b) { uint32_t d; asm volatile("xor.b32 %0, %1, %2;" : "=r"(d) : "r"(a), "r"(b)); return d; }
#define SCHED(k) asm volatile("{\n.reg .pred p;\nsetp.ne.u32 p, %0, %1;\n@p bra.uni SD;\nSL: nanosleep.u32 64;\nbra.uni SL;\nSD:\n}" :: "r"(sbu - s), "n"(k) : "memory")
#define PINM() asm volatile("{\n.reg .pred p;\nsetp.eq.u32 p, %0, 1;\n@p st.shared.u32 [%0], %0;\n}" :: "r"(sbu) : "memory")
__device__ __forceinline__ uint32_t pack2v(float a, float b) { uint32_t d; asm volatile("cvt.rn.bf16x2.f32 %0, %1, %2;" : "=r"(d) : "f"(b), "f"(a)); return d; }
#define FU(x) __float_as_uint(x)
__device__ __forceinline__ uint32_t clk32() { uint32_t t; asm volatile("mov.u32 %0, %%clock;" : "=r"(t) :: "memory"); return t; }
__device__ __forceinline__ void spin_until(uint32_t t0, uint32_t d) {
    if (d) {
#pragma unroll 1
        while (__any_sync(0xffffffffu, clk32() - t0 < d)) {}
    }
}
constexpr int SH_OFF = 229376 + 384;
constexpr uint32_t HONE2 = 0x3c003c00u, HCNT2 = 0x50005000u;

__device__ __forceinline__ uint64_t desc_sw128(uint32_t addr, uint32_t lbo, uint32_t sbo) {
    return (uint64_t)((addr & 0x3FFFF) >> 4) | ((uint64_t)(lbo >> 4) << 16) | ((uint64_t)(sbo >> 4) << 32) | (1ull << 62);
}
#define DP 440
#define NAX 4
#define NXL 0
#define NCX 2
#define NCL 1
#define DC 100
#define DEC 0
#define KXI 5
#define ANB 3
#define BNB 3
#define CNB 3
#define SMA 0x40
#define SMB 0
#define SMC 0x01
#define IVA 0
#define RGA 168
#define RGC 160
#define RGB (504 - RGA - RGC)
#define NRW 6
#define NBR 16
#define E0 0
#define E1 6
#define E2 4
#define E3 8
#define IV 2
#define DEX 0
#define STAG 1
#define VDEP 0
#define AEARLY 0
#define VTP 1
#define LORD 1
#define TEARLY 1
#define DT 0
#define NB1 10
#define DB2 40
#define DITHER 0
#define DA 40
#define DB 40
#define DS 200

template <int K> __device__ __forceinline__ void sched(uint32_t key) {
    asm volatile("{\n.reg .pred p;\nsetp.ne.u32 p, %0, %1;\n@p bra.uni SD;\nSL: nanosleep.u32 64;\nbra.uni SL;\nSD:\n}" :: "r"(key), "n"(K) : "memory");
}
__device__ __forceinline__ void sched_i(int i, uint32_t key) {
    if (i == -1) sched<20>(key); if (i == 0) sched<21>(key); if (i == 1) sched<22>(key); if (i == 2) sched<23>(key);
    if (i == 3) sched<24>(key); if (i == 4) sched<25>(key); if (i == 5) sched<26>(key); if (i == 6) sched<27>(key);
}
template <int NB, int SM, class F>
__device__ __forceinline__ void g1(float* q0, float* k0, uint32_t (*wq)[4], uint32_t (*wk)[4], uint32_t ga, uint32_t key, F&& hook) {
    float q1[4], k1[4];
    uint32_t b[NB][4];
#pragma unroll
    for (int i = 0; i < NB; i++) ldsm4(b[i], ga + i * 512);
    hook(-1, b[0]);
    if (SM & 1) sched_i(-1, key);
#pragma unroll
    for (int i = 0; i < 8; i++) {
        uint32_t* c = b[i % NB];
        MMAF(i == 0, q0, wq[2 * i], c[0], c[1]); MMAF(i == 0, k0, wk[2 * i], c[0], c[1]);
        MMAF(i == 0, q1, wq[2 * i + 1], c[2], c[3]); MMAF(i == 0, k1, wk[2 * i + 1], c[2], c[3]);
        const uint32_t cc_[4] = {c[0], c[1], c[2], c[3]};
        if (i + NB < 8) ldsm4(b[i % NB], ga + (i + NB) * 512);
        hook(i, cc_);
        if ((SM >> (i + 1)) & 1) sched_i(i, key);
    }
#pragma unroll
    for (int i = 0; i < 4; i++) { q0[i] += q1[i]; k0[i] += k1[i]; }
}
__device__ __forceinline__ float frag_norm2(uint32_t (*w)[4]) {
    float d0[4], d1[4];
#pragma unroll
    for (int i = 0; i < 32; i++) { MMAF(i == 0, d0, w[i], w[i][0], w[i][2]); MMAF(i == 0, d1, w[i], w[i][1], w[i][3]); }
    const int lane = threadIdx.x & 31, g = lane >> 2, t = lane & 3;
    float v = g == 2 * t ? d0[0] + d1[2] : (g == 2 * t + 1 ? d0[1] + d1[3] : 0.f);
#pragma unroll
    for (int o = 16; o; o >>= 1) v += __shfl_xor_sync(0xffffffffu, v, o);
    return v;
}
__device__ __forceinline__ void load_slot(uint32_t sb, int c, int tile, const Maps& maps) {
    const uint32_t dst = sb + ((tile & 1) ? R_SLOT1 : R_SLOT0), mb = sb + R_BAR + 8 * (MB_FULL0 + (tile & 1));
    mbar_expect_tx(mb, 24576);
    tma2d(dst + 16384, &maps.kx, c * 64, tile * 64, mb);
    tma3d(dst, &maps.vx3, tile * 64, (c >> 1) * 2, mb);
}
__device__ __forceinline__ void put_mem0(uint32_t sb, int W, const bf16* __restrict__ mem0) {
    const int lane = threadIdx.x & 31;
    const uint4 m0 = *(const uint4*)(mem0 + (lane & 7) * DM + (W * 8 + (lane >> 3)) * 8), m1 = *(const uint4*)(mem0 + (lane & 7) * DM + (W * 8 + 4 + (lane >> 3)) * 8);
    bar_sync(3, 256);
    sts128u(sb + R_MEMB + W * 1024 + lane * 16, m0.x, m0.y, m0.z, m0.w);
    sts128u(sb + R_MEMB + W * 1024 + 512 + lane * 16, m1.x, m1.y, m1.z, m1.w);
}
#define GATHER1(HALF)                                                                                           \
        {                                                                                                       \
            float d0[4], d1[4], d2[4], d3[4];                                                                   \
            const uint4 x0 = ldg_rlx4(pm), x1 = ldg_rlx4(pm + AC1); const uint32_t y = ldg_rlx(px);               \
            mma1688hz(d0, x0.x, x0.y, lt.z); mma1688hz(d1, x1.x, x1.y, lt.z);                                   \
            cw = (lt.w & 0x4000u) ? prmt(x0.w, x1.w, 0x7632u) : y;                                              \
            mma1688hz(d2, x0.z, prmt(x0.w, y, lt.w), lt.z); mma1688hz(d3, x1.z, prmt(x1.w, y, lt.w | 0x2200u), lt.z);          \
            stsm4t(rG + R_MEMB + HALF * 4096, pack2(d0[0], d0[1]), pack2(d0[2], d0[3]), pack2(d2[0], d2[1]), pack2(d2[2], d2[3]));       \
            stsm4t(rG + R_MEMB + HALF * 4096 + 512, pack2(d1[0], d1[1]), pack2(d1[2], d1[3]), pack2(d3[0], d3[1]), pack2(d3[2], d3[3])); \
        }
__device__ __forceinline__ uint32_t h2b(uint32_t w) {
    uint32_t d;
    asm("{\n.reg .f16 l, h;\n.reg .f32 a, b;\nmov.b32 {l, h}, %1;\ncvt.f32.f16 a, l;\ncvt.f32.f16 b, h;\ncvt.rn.bf16x2.f32 %0, b, a;\n}" : "=r"(d) : "r"(w));
    return d;
}
#define GATHER2(HALF)                                                                                           \
        {                                                                                                       \
            const uint4 x0 = ldg_rlx4(pm), x1 = ldg_rlx4(pm + AC1); const uint32_t y = ldg_rlx(px);               \
            cw = (lt.w & 0x4000u) ? prmt(x0.w, x1.w, 0x7632u) : y;                                              \
            stsm4t(rG + R_MEMB + HALF * 4096, h2b(x0.x), h2b(x0.y), h2b(x0.z), h2b(prmt(x0.w, y, lt.w)));       \
            stsm4t(rG + R_MEMB + HALF * 4096 + 512, h2b(x1.x), h2b(x1.y), h2b(x1.z), h2b(prmt(x1.w, y, lt.w | 0x2200u))); \
        }
#define GATHER(HALF, PRE, SYNC, AFTER)                                                                                      \
        {                                                                                                       \
            const uint32_t so = aslot(s);                                                                       \
            const uint32_t ua = (glo + acc_off(HALF * 4 + fo, 0)) ^ so, ux = (glo + ext_base(HALF * 4 + fo)) ^ so; \
            uint4 lt;                                                                                           \
            lt.x = lds32v_(rL + R_LT); lt.y = lds32v_(rL + R_LT + 4); lt.z = DEC ? 0 : lds32v_(rL + R_LT + 8); lt.w = lds32v_(rL + R_LT + 12); \
            const uint32_t* pm = mkptr(ua + lt.x, ghi);                                                         \
            const uint32_t* px = mkptr(ux + lt.y, ghi);                                                         \
            PRE                                                                                                 \
            bar_sync(5, 384);                                                                                   \
            const uint32_t t0 = clk32();                                                                        \
            SYNC                                                                                                \
            spin_until(t0, DP + DITHER);                                                                                 \
            TS(11);                                                                                             \
            uint32_t cw, nr = 0;                                                                                \
            _Pragma("unroll 1") do {                                                                            \
                if (DEC) GATHER2(HALF) else GATHER1(HALF)                                                       \
                nr++;                                                                                           \
            } while (__any_sync(0xffffffffu, cw != HCNT2 && nr < SPIN_LIMIT));                                  \
            AFTER                                                                                               \
            CNT2(HALF * 4 + (s & 1) * 2 + (nr > 2), nr > 1);                                                    \
            TS(12);                                                                                             \
        }
#define GOBAR (fo == 3 ? 14 : 10 + fo)

__device__ __forceinline__ void rec_a(uint32_t sb, int c, const bf16* __restrict__ mem0, uint32_t epoch) {
    const int tid = threadIdx.x, lane = tid & 31, f = tid >> 5;
    uint32_t wq[16][4], wk[16][4];
    const int lrow = ((lane >> 4) << 3) + (lane & 7), lsel = (lane >> 3) & 1;
    {
        mbar_wait(sb + R_BAR + 8 * MB_W0, 0);
        if (c == 7 && tid == 0) GT(1421);
        const uint32_t a = sb + R_T + lrow * 128 + (((2 * f + lsel) ^ (lane & 7)) << 4);
#pragma unroll
        for (int kk = 0; kk < 16; kk++) { ldsm4t(wq[kk], a + kk * 2048); ldsm4t(wk[kk], a + 32768 + kk * 2048); }
        __syncwarp();
        put_mem0(sb, f, mem0);
    }
    const uint32_t rL = opaque(sb + lane * 16), rG = opaque(sb + lane * 16 + f * 1024);
    const uint32_t sbu = uni(sb), fo = uni(f), cc = uni(c);
    const uint64_t gx = xpage();
    const uint32_t ghi = uni((uint32_t)(gx >> 32)), glo = uni((uint32_t)gx);
#pragma unroll
    for (int i = 0; i < NAX; i++) {
        sts128u(rG + R_AX + 4096 * i, wq[i][0], wq[i][1], wq[i][2], wq[i][3]);
        sts128u(rG + R_AX + 4096 * i + 512, wk[i][0], wk[i][1], wk[i][2], wk[i][3]);
    }
    sts128u(rL + R_LT + 512 + f * 512, (sb + R_SREM + (f >= 2 ? lane * 8 + f * 256 : lane * 16 + f * 1024)) ^ 0x01000000u, (sb + R_BAR + 8 * MB_S) ^ 0x01000000u,
            sb + R_QP + (lane >> 4) * 128 + lsel * 512 + (lane & 7) * 16 + (f == 3 ? 2048 : 0), sb + lrow * 128 + ((lsel ^ (lane & 7)) << 4));
    __syncwarp();
    if (tid == 0) GT(c * 8 + 1);
    TSDECL;
    const float cexp = 0.08838834764831845f * 1.4426950408889634f;
    float cs = cexp;
    auto step = [&](int s, bool first) -> bool {
        bar_sync(1, 128);
        TS(3);
        float q0[4], k0[4];
        uint32_t kx[4][4];
        uint4 ta;
        const uint32_t ro = ((s & 2) ? R_SLOT1 : R_SLOT0) + (s & 1) * 4096;
        g1<ANB, SMA>(q0, k0, wq, wk, rL + R_MEMB, sbu - s, [&](int i, const uint32_t*) {
            if (i == -1) {
#pragma unroll
                for (int n = NAX - NXL; n < NAX; n++) { lds_fragv(wq[n], rG + R_AX + 4096 * n); lds_fragv(wk[n], rG + R_AX + 4096 * n + 512); }
                ta = lds128uv(rL + R_LT + 512 + fo * 512);
            }
            if (i == KXI) {
                if (first) mbar_wait_p(sbu + R_BAR + 8 * MB_FULL0, 0);
#pragma unroll
                for (int kk = 0; kk < 4; kk++)
                    asm volatile("{\n.reg .pred p;\nsetp.lt.u32 p, %5, 2;\nmov.b32 %0, 0;\nmov.b32 %1, 0;\nmov.b32 %2, 0;\nmov.b32 %3, 0;\n"
                                 "@p ldmatrix.sync.aligned.m8n8.x4.shared.b16 {%0,%1,%2,%3}, [%4];\n}"
                                 : "=r"(kx[kk][0]), "=r"(kx[kk][1]), "=r"(kx[kk][2]), "=r"(kx[kk][3]) : "r"((ta.w ^ (kk * 32)) + (ro + 16384 + fo * 2048)), "r"(fo) : "memory");
            }
            if (i == IVA) bar_arrive(GOBAR, 96);
        });
        stsm4t(rG + R_QP, pack2(q0[0], q0[1]), pack2(q0[2], q0[3]), pack2(k0[0], k0[1]), pack2(k0[2], k0[3]));
        TS(4);
        if (fo < 2) {
            bar_sync(3, 256);
            TS(5);
            uint32_t qa[4][4];
#pragma unroll
            for (int kk = 0; kk < 4; kk++) { if (kk == 2) bar_arrive(13, 256); ldsm4(qa[kk], ta.z + kk * 1024); }
            float s0[4], s1[4], s2[4], s3[4];
            MMAZ(s0, qa[0], kx[0][0], kx[0][1]); MMAZ(s1, qa[0], kx[0][2], kx[0][3]);
            MMAZ(s2, qa[1], kx[1][0], kx[1][1]); MMAZ(s3, qa[1], kx[1][2], kx[1][3]);
            MMA(s0, qa[2], kx[2][0], kx[2][1]); MMA(s1, qa[2], kx[2][2], kx[2][3]);
            MMA(s2, qa[3], kx[3][0], kx[3][1]); MMA(s3, qa[3], kx[3][2], kx[3][3]);
            const float x = ((s0[0] + s0[2]) + (s2[0] + s2[2])) * cs, y = ((s0[1] + s0[3]) + (s2[1] + s2[3])) * cs;
            const float z = ((s1[0] + s1[2]) + (s3[0] + s3[2])) * cs, w = ((s1[1] + s1[3]) + (s3[1] + s3[3])) * cs;
            st_async4(ta.x, x, y, z, w, ta.y);
            sts128(rG + R_SLOC, x, y, z, w);
        } else {
            bar_sync(3, 256);
            TS(5);
            uint32_t kb[4], kc[4], qa[4], qc[4];
            ldsm4(kb, ta.z + 256); ldsm4(qa, ta.z); bar_arrive(13, 256); ldsm4(kc, ta.z + 1280); ldsm4(qc, ta.z + 1024);
            const uint32_t k0_ = hadd2b(kb[0], kb[1]), k1_ = hadd2b(kb[2], kb[3]), k2_ = hadd2b(kc[0], kc[1]), k3_ = hadd2b(kc[2], kc[3]);
            float s0[4], s2[4];
            MMAZ(s0, qa, k0_, k1_); MMAZ(s2, qc, k2_, k3_);
            const float x = ((s0[0] + s0[2]) + (s2[0] + s2[2])) * cs, y = ((s0[1] + s0[3]) + (s2[1] + s2[3])) * cs;
            st_async2(ta.x, FU(x), FU(y), ta.y);
            sts64((ta.x ^ 0x01000000u) + (R_SLOC - R_SREM), x, y);
            sts128u(rL + R_STG + (fo & 1) * 512, k0_, k1_, k2_, k3_);
            bar_arrive(9, 192);
        }
        TS(6);
        const uint32_t r8 = (rL + sbu) >> 1;
        uint32_t vt00[4], vt01[4], vt10[4], vt11[4];
        const uint32_t rV = ta.w ^ ((fo & 1) * 64), vo = ro + (fo >> 1) * 8192;
        if (VTP < 2) { ldsm4t(vt00, rV + vo); ldsm4t(vt10, (rV ^ 32) + vo); }
        if (VTP < 1) { ldsm4t(vt01, rV + vo + 2048); ldsm4t(vt11, (rV ^ 32) + vo + 2048); }
        bar_sync(4, 128);
        const float4 l0 = lds128v(rL + R_SLOC), l1 = lds128v(rL + R_SLOC + 1024);
        const float2 l2 = lds64v(r8 + R_SLOC + 512), l3 = lds64v(r8 + R_SLOC + 768);
        if (E2) bar_arrive(15, 256);
        TS(7);
        if (s == NSEG - 1) { mbar_wait_u(sbu + R_BAR + 8 * MB_S, 1); mbar_wait_u(sbu + R_BAR + 8 * MB_V, 1); return true; }
        mbar_wait_p(sbu + R_BAR + 8 * MB_S, s & 1);
        TS(8);
        {
            const float4 r0 = lds128v(rL + R_SREM), r1 = lds128v(rL + R_SREM + 1024);
            const float2 r2 = lds64v(r8 + R_SREM + 512), r3 = lds64v(r8 + R_SREM + 768);
            if (VTP >= 1) PINM();
            if (VTP >= 2) { ldsm4t(vt00, rV + vo); ldsm4t(vt10, (rV ^ 32) + vo); }
            if (VTP >= 1) { ldsm4t(vt01, rV + vo + 2048); ldsm4t(vt11, (rV ^ 32) + vo + 2048); }
            float sv[10];
            sv[0] = l0.x + r0.x; sv[1] = l0.y + r0.y; sv[2] = l0.z + r0.z; sv[3] = l0.w + r0.w;
            sv[4] = l1.x + r1.x; sv[5] = l1.y + r1.y; sv[6] = l1.z + r1.z; sv[7] = l1.w + r1.w;
            sv[8] = ((l2.x + l3.x) + r2.x) + r3.x; sv[9] = ((l2.y + l3.y) + r2.y) + r3.y;
            float m = fmaxf(fmaxf(fmaxf(sv[0], sv[1]), fmaxf(sv[2], sv[3])), fmaxf(fmaxf(sv[4], sv[5]), fmaxf(sv[6], sv[7])));
            m = fmaxf(m, fmaxf(sv[8], sv[9]));
            {
                const float m1 = __shfl_xor_sync(0xffffffffu, m, 1), m2 = __shfl_xor_sync(0xffffffffu, m, 2), m3 = __shfl_xor_sync(0xffffffffu, m, 3);
                m = fmaxf(fmaxf(m, m1), fmaxf(m2, m3));
            }
            const uint32_t ONE2 = 0x3f803f80u;
            float o0[4], o1[4], sm[4];
            const uint32_t pb0 = pack2(ex2(sv[0] - m), ex2(sv[1] - m)), pb1 = pack2(ex2(sv[2] - m), ex2(sv[3] - m));
            mma16816z(sm, ONE2, ONE2, ONE2, ONE2, pb0, pb1);
            MMAZ(o0, vt00, pb0, pb1); MMAZ(o1, vt10, pb0, pb1);
            const uint32_t z = (VDEP == 0 ? FU(m) : pb0) & (sbu & 8);
            const uint32_t vok = mbar_test(sbu + R_BAR + 8 * MB_V + z, s & 1);
            const uint32_t rv = r8 + vok * 8;
            float2 va = lds64v(rv + R_VB - 8 + fo * 512);
            bar_arrive(13, 256);
            float2 vb = lds64v(rv + R_VB - 8 + fo * 512 + 256);
            float sig = __uint_as_float(lds32v_(sbu + R_MISC + 40));
            const uint32_t pb2 = pack2(ex2(sv[4] - m), ex2(sv[5] - m)), pb3 = pack2(ex2(sv[6] - m), ex2(sv[7] - m));
            mma16816(sm, ONE2, ONE2, ONE2, ONE2, pb2, pb3);
            const uint32_t pb4 = pack2(ex2(sv[8] - m), ex2(sv[9] - m));
            MMA(o0, vt01, pb2, pb3); MMA(o1, vt11, pb2, pb3);
            mma1688(sm, ONE2, ONE2, pb4);
            const float z0 = rcpf(sm[0]), z1 = rcpf(sm[1]);
#define PUT_O()                                                                                                   \
            {                                                                                                     \
                float a0[4] = {o0[0], o0[1], o0[2], o0[3]}, a1[4] = {o1[0], o1[1], o1[2], o1[3]};                 \
                mma1688(a0, FU(va.x), FU(va.y), pb4); mma1688(a1, FU(vb.x), FU(vb.y), pb4);                       \
                const float i0 = z0 * sig, i1 = z1 * sig;                                                         \
                stsm4t(rG + R_QP, pack2(a0[0] * i0, a0[1] * i1), pack2(a0[2] * i0, a0[3] * i1), pack2(a1[0] * i0, a1[1] * i1), pack2(a1[2] * i0, a1[3] * i1)); \
            }
            PUT_O()
            asm volatile("{\n.reg .pred p;\nsetp.ne.u32 p, %0, 0;\n@p bar.arrive 8, 256;\n}" :: "r"(vok) : "memory");
            if (__builtin_expect(__any_sync(0xffffffffu, vok == 0), 0)) {
                mbar_wait_p(sbu + R_BAR + 8 * MB_V, s & 1);
                va = lds64v(r8 + R_VB + fo * 512); vb = lds64v(r8 + R_VB + fo * 512 + 256);
                sig = __uint_as_float(lds32v_(sbu + R_MISC + 40));
                PUT_O()
                bar_arrive(8, 256);
                CNT(8);
            }
            const float r = __uint_as_float(0x7f000000u - FU(sig));
            cs = cexp * r * (fo >= 2 ? r : 1.f);
        }
        TS(10);
        return false;
    };
    step(0, true);
#pragma unroll 1
    for (int s = 0;; s++) {
        if (s & 1) mbar_wait_p(sbu + R_BAR + 8 * (MB_FULL0 + (((s + 1) >> 1) & 1)), ((s + 1) >> 2) & 1);
        auto early = [&]() {
            SCHED(13);
#pragma unroll
            for (int i = 0; i < NAX - NXL; i++) { lds_fragv(wq[i], rG + R_AX + 4096 * i); lds_fragv(wk[i], rG + R_AX + 4096 * i + 512); }
        };
        GATHER(0, , early();, )
        if (step(s + 1, false)) break;
    }
    CNT(9);
    if (rG == sbu) GT(cc * 8 + 4);
}

__device__ __forceinline__ void rec_b(uint32_t sb, int c, uint32_t epoch) {
    const int tid = threadIdx.x - 128, lane = tid & 31, f = tid >> 5;
    uint32_t wq[16][4], wk[16][4], wo[32][4];
    const int lrow = ((lane >> 4) << 3) + (lane & 7), lsel = (lane >> 3) & 1;
    const uint32_t rL = opaque(sb + lane * 16), rW = opaque(sb + lane * 16 + f * 16384);
    const uint32_t sbu = uni(sb), fo = uni(f), cc = uni(c), po = cc & 1, ep = uni(epoch);
    {
        mbar_wait(sb + R_BAR + 8 * MB_WO, 0);
        if (c == 7 && tid == 0) GT(1426);
        const uint32_t aO = sb + R_WO + f * 16384 + lrow * 128 + ((lsel ^ (lane & 7)) << 4);
#pragma unroll
        for (int i = 0; i < 32; i++) {
            const int tile = STAG ? (i >> 4) * 2 + (i & 1) : i & 3, kk = STAG ? (i >> 1) & 7 : i >> 2;
            ldsm4t(wo[i], (aO ^ (32 * tile)) + kk * 2048);
        }
        const float no = frag_norm2(wo);
        if (lane == 0) sts32(sb + R_MISC + 80 + f * 4, FU(no));
        __syncwarp();
        bar_sync(15, 256);
        if (tid == 0) {
            const float4 a = lds128(sb + R_MISC + 64), b = lds128(sb + R_MISC + 80);
            stg4(&g_f.norm[c], make_uint4(FU((a.x + a.y) + (a.z + a.w)), epoch, FU((b.x + b.y) + (b.z + b.w)), epoch));
        }
        __syncwarp();
#pragma unroll
        for (int i = NRW; i < 32; i++) sts128u(rW + R_WO + i * 512, wo[i][0], wo[i][1], wo[i][2], wo[i][3]);
        mbar_wait(sb + R_BAR + 8 * MB_W1, 0);
        if (c == 7 && tid == 0) GT(1422);
        if (tid == 0) stg_rlx(&g_f.rload[c], epoch);
        __syncwarp();
        const uint32_t a = sb + R_QK1 + lrow * 128 + (((2 * f + lsel) ^ (lane & 7)) << 4);
#pragma unroll
        for (int kk = 0; kk < 16; kk++) { ldsm4t(wq[kk], a + kk * 2048); ldsm4t(wk[kk], a + 32768 + kk * 2048); }
        bar_sync(13, 128);
#pragma unroll
        for (int i = 0; i < 16; i++) {
            sts128u(rW + R_QK1 + i * 1024, wq[i][0], wq[i][1], wq[i][2], wq[i][3]);
            sts128u(rW + R_QK1 + i * 1024 + 512, wk[i][0], wk[i][1], wk[i][2], wk[i][3]);
        }
        __syncwarp();
    }
    const uint64_t gx = xpage();
    const uint32_t ghi = uni((uint32_t)(gx >> 32)), glo = uni((uint32_t)gx);
    TSDECL;
#pragma unroll 1
    for (int s = 0;; s++) {
        bar_sync(2, 256);
        TS(3);
        float q0[4], k0[4];
        g1<BNB, SMB>(q0, k0, wq, wk, rL + R_MEMB + 4096, sbu - s, [&](int i, const uint32_t*) {
            if (i >= 2 && i < 6) {
#pragma unroll
                for (int n = NRW + (i - 2) * E0 / 4; n < NRW + (i - 1) * E0 / 4; n++) lds_fragv(wo[n], rW + R_WO + n * 512);
            }
            if (i == IV) bar_arrive(GOBAR, 96);
        });
        stsm4t(rL + fo * 1024 + R_QP + 512, pack2(q0[0], q0[1]), pack2(q0[2], q0[3]), pack2(k0[0], k0[1]), pack2(k0[2], k0[3]));
        bar_arrive(3, 256);
        TS(4);
        const uint32_t so = aslot(s);
        const uint4 lt = lds128uv(rL + R_LT);
        uint32_t* pm = (uint32_t*)mkptr(((glo + acc_off(po * 4 + fo, 0)) ^ so) + lt.x, ghi);
        uint32_t* px = (uint32_t*)mkptr(((glo + ext_base(po * 4 + fo)) ^ so) + lt.y, ghi);
        bar_sync(13, 256);
#pragma unroll
        for (int n = NRW + E0; n < NRW + E0 + E1; n++) lds_fragv(wo[n], rW + R_WO + n * 512);
        if (E2) bar_sync(15, 256);
        if (s == NSEG - 1) break;
        TS(5);
#pragma unroll
        for (int n = NRW + E0 + E1; n < NRW + E0 + E1 + E2; n++) lds_fragv(wo[n], rW + R_WO + n * 512);
        bar_sync(13, 256);
#pragma unroll
        for (int n = NRW + E0 + E1 + E2; n < NRW + E0 + E1 + E2 + E3; n++) lds_fragv(wo[n], rW + R_WO + n * 512);
        SCHED(4);
        TS(6);
        bar_sync(8, 256);
        TS(7);
        {
            float o[4][4];
            uint32_t b[4][4];
#pragma unroll
            for (int i = 0; i < 4; i++) ldsm4(b[i], rL + R_QP + i * 1024);
            PINM();
#pragma unroll
            for (int n = NRW + E0 + E1 + E2 + E3; n < 32; n++) lds_fragv(wo[n], rW + R_WO + n * 512);
            float p[4][4];
#define G2_STEP(o, hf, kk) _Pragma("unroll") for (int i = 0; i < 2; i++) MMAF((kk) < 2, o[((kk) & 1) * 2 + i], wo[(hf) * 16 + (kk) * 2 + i], b[(kk) >> 1][((kk) & 1) * 2], b[(kk) >> 1][((kk) & 1) * 2 + 1])
#define G2_RED(o, wl, ptr) const uint32_t wl = packh2(o[1][2] + o[3][2], o[1][3] + o[3][3]);                          \
                asm volatile("red.relaxed.gpu.global.add.noftz.v4.f16x2 [%0], {%1,%2,%3,%4};" :: "l"(ptr),           \
                    "r"(packh2(o[0][0] + o[2][0], o[0][1] + o[2][1])), "r"(packh2(o[0][2] + o[2][2], o[0][3] + o[2][3])), \
                    "r"(packh2(o[1][0] + o[3][0], o[1][1] + o[3][1])), "r"(prmt(wl, HONE2, lt.w)) : "memory")
#pragma unroll
            for (int kk = 0; kk < 8; kk++) { G2_STEP(o, 0, kk); }
            SCHED(11);
#pragma unroll
            for (int kk = 0; kk < 4; kk++) { G2_STEP(p, 1, kk); }
            G2_RED(o, w3, pm);
            SCHED(12);
#pragma unroll
            for (int kk = 4; kk < 8; kk++) { G2_STEP(p, 1, kk); }
            G2_RED(p, w7, pm + AC1);
            asm volatile("red.relaxed.gpu.global.add.noftz.f16x2 [%0], %1;" :: "l"(px), "r"((lt.w & 0x4000u) ? prmt(w3, w7, 0x7632u) : HONE2) : "memory");
        }
        bar_arrive(5, 384);
        asm volatile("{\n.reg .pred p;\nsetp.eq.u32 p, %0, %1;\n@p mbarrier.arrive.expect_tx.shared::cta.b64 _, [%2], 1536;\n}"
                     :: "r"(rW), "r"(sbu), "r"(sbu + R_BAR + 8 * MB_S) : "memory");
        const uint32_t tb = clk32();
        spin_until(tb, DB);
        TS(8);
#pragma unroll
        for (int i = 0; i < NBR; i++) {
            if (i == NB1) spin_until(tb, DP + DB2);
            lds_fragv(wq[i], rW + R_QK1 + i * 1024); lds_fragv(wk[i], rW + R_QK1 + i * 1024 + 512);
        }
        TS(9);
    }
}

#undef lds_fragv
__device__ __forceinline__ void rec_first_loads(uint32_t sb, int c, const Maps& maps) {
    const uint32_t bar = sb + R_BAR;
    const int F0 = c * 64;
    mbar_expect_tx(bar + 8 * MB_W0, 65536); mbar_expect_tx(bar + 8 * MB_WO, 65536); mbar_expect_tx(bar + 8 * MB_WV, 65536);
    tma2d(sb + R_QK1, &maps.wv, F0, 0, bar + 8 * MB_WV); tma2d(sb + R_QK1 + 32768, &maps.wv, F0, 256, bar + 8 * MB_WV);
    tma2d(sb + R_T + 32768, &maps.wk, F0, 0, bar + 8 * MB_W0);
    if (!LORD) {
        for (int i = 0; i < 4; i++) tma2d(sb + R_WO + i * 16384, &maps.wo, (c & 1) * 256 + i * 64, (c >> 1) * 128, bar + 8 * MB_WO);
        tma2d(sb + R_T, &maps.wq, F0, 0, bar + 8 * MB_W0);
    }
    mbar_expect_tx(bar + 8 * MB_S, 1536);
}
__device__ __forceinline__ void rec_c(uint32_t sb, int c, const bf16* __restrict__ mem0, const Maps& maps, uint32_t epoch) {
    const int tid = threadIdx.x - 256, lane = tid & 31, u = tid >> 5;
    const uint32_t bar = sb + R_BAR;
    const int lrow = ((lane >> 4) << 3) + (lane & 7), lsel = (lane >> 3) & 1;
    const int kh = u >> 1, j = u & 1;
    uint32_t wv[32][4];
    {
        if (u == 0) {
            sts128u(sb + lane * 16 + R_LT, acc_off(0, lane), ext_lane(lane),
                    ((lane >> 2) == 2 * (lane & 3) ? 0x3c00u : 0u) | ((lane >> 2) == 2 * (lane & 3) + 1 ? 0x3c000000u : 0u), (lane & 1) ? 0x5410u : 0x3210u);
        }
        mbar_wait(bar + 8 * MB_WV, 0);
        if (c == 7 && tid == 0) GT(1425);
        if (LORD && tid == 32) {
            for (int i = 0; i < 4; i++) tma2d(sb + R_WO + i * 16384, &maps.wo, (c & 1) * 256 + i * 64, (c >> 1) * 128, bar + 8 * MB_WO);
            tma2d(sb + R_T, &maps.wq, c * 64, 0, bar + 8 * MB_W0);
        }
        __syncwarp();
        const uint32_t aa = sb + R_QK1 + (kh * 256 + lrow) * 128 + (((4 * j + 2 * kh + lsel) ^ (lane & 7)) << 4);
#pragma unroll
        for (int kk = 0; kk < 16; kk++) { ldsm4t(wv[kk], aa + kk * 2048); ldsm4t(wv[16 + kk], (aa ^ 32) + kk * 2048); }
        bar_sync(9, 128);
        if (c == 7 && tid == 0) GT(1423);
        if (tid == 0) {
            mbar_expect_tx(bar + 8 * MB_W1, 65536);
            tma2d(sb + R_QK1 + 32768, &maps.wk, c * 64, 256, bar + 8 * MB_W1); tma2d(sb + R_QK1, &maps.wq, c * 64, 256, bar + 8 * MB_W1);
        }
        __syncwarp();
        const float nv = frag_norm2(wv);
        if (lane == 0) sts32(sb + R_MISC + 64 + u * 4, FU(nv));
        __syncwarp();
        bar_arrive(15, 256);
        put_mem0(sb, 4 + u, mem0);
    }
    const uint32_t rL = opaque(sb + lane * 16), rG = opaque(sb + lane * 16 + u * 1024);
    const uint32_t sbu = uni(sb), fo = uni(u), cc = uni(c), ep = uni(epoch);
    const uint64_t gx = xpage();
    const uint32_t ghi = uni((uint32_t)(gx >> 32)), glo = uni((uint32_t)gx);
    constexpr int CX = R_AX + NAX * 4096;
    static_assert(NAX + NCX <= 6, "AX");
#pragma unroll
    for (int i = 0; i < NCX; i++) {
        sts128u(rG + CX + 4096 * i, wv[i][0], wv[i][1], wv[i][2], wv[i][3]);
        sts128u(rG + CX + 4096 * i + 512, wv[16 + i][0], wv[16 + i][1], wv[16 + i][2], wv[16 + i][3]);
    }
    __syncwarp();
    TSDECL;
    uint32_t rpb = 0x3f800000u;
    bar_arrive(2, 256);
    if (fo == 3) {
        uint32_t n = 0;
#pragma unroll 1
        while (true) {
            const uint2 v = ldg_rlx2(&g_f.kv[0][cc >> 1][0]);
            if (__all_sync(0xffffffffu, v.x == ep && v.y == ep)) break;
            __nanosleep(32);
            if (++n > SPIN_LIMIT) { ABORT(6); break; }
        }
        if (rL == sbu) load_slot(sbu, cc, 0, maps);
        __syncwarp();
        if (cc == 7 && rL == sbu) GT(1427);
    }
#pragma unroll 1
    for (int s = 0;; s++) {
        if (TEARLY && fo == 3 && !(s & 1) && s > 0 && s + 2 < NSEG) {
            if (rL == sbu) load_slot(sbu, cc, (s + 2) >> 1, maps);
            __syncwarp();
        } else spin_until(clk32(), DC);
#pragma unroll
        for (int i = NCX - NCL; i < NCX; i++) { lds_fragv(wv[i], rG + CX + 4096 * i); lds_fragv(wv[16 + i], rG + CX + 4096 * i + 512); }
        bar_sync(GOBAR, 96);
        TS(3);
        float v0[4], v1[4];
        uint32_t mx, my;
        g1<CNB, SMC>(v0, v1, wv, wv + 16, rL + R_MEMB + (fo >> 1) * 4096, sbu - s, [&](int i, const uint32_t* c_) {
            if (i >= 0) {
                mx = amax2b(i == 0 ? c_[0] : amax2b(mx, c_[0]), c_[1]);
                my = amax2b(i == 0 ? c_[2] : amax2b(my, c_[2]), c_[3]);
            }
        });
        TS(4);
        const uint32_t l16 = (rL ^ sbu) | (lds32v_(rL + R_LT + 4) & 1);
        const uint32_t r8 = sbu + (l16 >> 1);
        {
            sts128(rL + R_VRED + fo * 512, v1[0], v1[1], v1[2], v1[3]);
            const uint32_t d = r8 + R_VB + ((cc & 1) * 4 + (fo & 1) * 2 + (fo >> 1)) * 256;
            const uint32_t dr = xorv(d, 0x01000000u), br = xorv(sbu + R_BAR + 8 * MB_V, 0x01000000u);
            bar_sync(6 + (fo & 1), 64);
            const float4 a0 = lds128(rL + R_VRED + (fo ^ 2) * 512);
            const float rp = __uint_as_float(rpb);
            const uint32_t w0 = pack2((v0[0] + a0.x) * rp, (v0[1] + a0.y) * rp), w1 = pack2((v0[2] + a0.z) * rp, (v0[3] + a0.w) * rp);
            st_async2(dr, w0, w1, br);
            sts64(d, __uint_as_float(w0), __uint_as_float(w1));
            mx = amax2b(mx, my);
            mx = __reduce_max_sync(0xffffffffu, amax2b(mx, mx << 16) & 0x7f800000u);
            if (fo == 2) { sts32(sbu + R_MISC + 8, mx); bar_arrive(6, 64); }
            if (fo == 0) {
                bar_sync(6, 64);
                if (s == 0) {
                    const uint32_t* np = (const uint32_t*)&g_f.norm[0] + (l16 >> 2);
                    uint4 r, q; uint32_t n = 0;
#pragma unroll 1
                    while (true) {
                        r = ldg_rlx4(np); q = ldg_rlx4(np + 128);
                        const uint2 z = ldg_rlx2(&g_f.xn[l16 >> 3]);
                        if (__all_sync(0xffffffffu, r.y == ep && r.w == ep && q.y == ep && q.w == ep && z.x == ep && z.y == ep)) break;
                        if (++n > SPIN_LIMIT) { ABORT(5); break; }
                    }
                    float nv = __uint_as_float(r.x) + __uint_as_float(q.x), no = __uint_as_float(r.z) + __uint_as_float(q.z);
#pragma unroll
                    for (int o = 16; o; o >>= 1) { nv += __shfl_xor_sync(0xffffffffu, nv, o); no += __shfl_xor_sync(0xffffffffu, no, o); }
                    const int lc = ((int)(FU(nv) >> 23) + (int)(FU(no) >> 23) - 252 + 9 + 1) >> 1;
                    sts32(sbu + R_MISC + 16, 140 - lc);
                    __syncwarp();
                }
                const int em = (int)(max(mx, lds32v_(sbu + R_MISC + 8)) >> 23) + (int)(rpb >> 23) - 127;
                const int es = min(max((int)lds32v_(sbu + R_MISC + 16) - max(em, 127), -60), 60);
                sts32(sbu + R_MISC + 40, (127 + es) << 23);
            }
            __syncwarp();
            asm volatile("{\n.reg .pred p;\nsetp.eq.u32 p, %0, %1;\n@p mbarrier.arrive.expect_tx.shared::cta.b64 _, [%2], 256;\n}"
                         :: "r"(rL), "r"(sbu), "r"(sbu + R_BAR + 8 * MB_V) : "memory");
        }
        TS(5);
        if (fo == 1) {
            bar_sync(9, 192);
            uint8_t* dst = (uint8_t*)&g_KVf[s][cc >> 1][(cc & 1) * 256] + l16;
            const uint32_t r2 = prmt(rpb, 0, 0x3232u);
#pragma unroll
            for (int i = 0; i < 2; i++) {
                const uint4 a = lds128uv(rL + R_STG + i * 512);
                stg4(dst + i * 512, make_uint4(~hmul2b(a.x, r2), ~hmul2b(a.y, r2), ~hmul2b(a.z, r2), ~hmul2b(a.w, r2)));
                const float2 b0 = lds64v(r8 + R_VB + (cc & 1) * 1024 + i * 512), b1 = lds64v(r8 + R_VB + (cc & 1) * 1024 + i * 512 + 256);
                stg4(dst + 2048 + i * 512, make_uint4(~FU(b0.x), ~FU(b0.y), ~FU(b1.x), ~FU(b1.y)));
            }
            __syncwarp();
            if (l16 == 0) { stg_rlx(&g_f.rec[cc], (ep << 8) | (s + 1)); if (s == NSEG - 1) GT(1500 + cc); }
            __syncwarp();
        } else {
            bar_arrive(9, 192);
            if (fo == 2) {
                if (l16 < 272) stg4((void*)mkptr((glo + zero_off(cc, l16 >> 4)) ^ aslot(s + 4), ghi), make_uint4(0, 0, 0, 0));
                __syncwarp();
            } else if (fo == 3) {
                if (((s & 1) || s == 0) && s + 3 < NSEG) {
                    const uint32_t* fp = &g_f.kv[(s + 3) >> 1][cc >> 1][0];
                    uint32_t n = 0;
#pragma unroll 1
                    while (true) {
                        const uint2 v = ldg_rlx2(fp);
                        if (__all_sync(0xffffffffu, v.x == ep && v.y == ep)) break;
                        __nanosleep(64);
                        if (++n > SPIN_LIMIT) { ABORT(6); break; }
                    }
                }
                if (!(s & 1) && s + 2 < NSEG && (!TEARLY || s == 0)) {
                    spin_until(clk32(), DT);
                    if (l16 == 0) load_slot(sbu, cc, (s + 2) >> 1, maps);
                    __syncwarp();
                }
            }
        }
        TS(6);
        if (s == NSEG - 1) break;
        auto early = [&]() {
#pragma unroll
            for (int i = 0; i < NCX - NCL; i++) { lds_fragv(wv[i], rG + CX + 4096 * i); lds_fragv(wv[16 + i], rG + CX + 4096 * i + 512); }
        };
        GATHER(1, , early(); rpb = 0x7f000000u - lds32v_(sbu + R_MISC + 40);, bar_arrive(2, 256);)
    }
}

__device__ __forceinline__ bool cand_better(float v, int i, float bv, int bi) { return v > bv || (v == bv && i < bi); }
constexpr int F_WG = 0, F_WU = 32768, F_WD = 65536, F_X = 98304, F_RED = F_X + 4096, F_ACT = F_RED + 8192, F_SEL = F_ACT + 256;

__device__ __noinline__ void ffn_phase(const Maps& maps, const bf16* __restrict__ wd, bf16* __restrict__ out) {
    extern __shared__ __align__(1024) uint8_t smem[];
    const uint32_t sb = smem_u32(smem);
    const int c = ((volatile int*)(smem + SH_OFF))[8];
    const uint32_t epoch = ((volatile uint32_t*)(smem + SH_OFF))[9];
    const int tid = threadIdx.x;
    constexpr int NWK = FF / 32;
    const bool worker = c < NWK;
    bar_sync(0, 384);
    const uint32_t mb = sb + R_BAR + 8 * MB_W0;
    if (tid == 32 && worker) {
        asm volatile("fence.proxy.async.shared::cta;" ::: "memory");
        mbar_expect_tx(mb, 98304);
        tma2d(sb + F_WG, &maps.wg, c * 32, 0, mb); tma2d(sb + F_WG + 16384, &maps.wg, c * 32, 256, mb);
        tma2d(sb + F_WU, &maps.wu, c * 32, 0, mb); tma2d(sb + F_WU + 16384, &maps.wu, c * 32, 256, mb);
        asm volatile("cp.async.bulk.shared::cluster.global.mbarrier::complete_tx::bytes [%0], [%1], %2, [%3];"
            :: "r"(sb + F_WD), "l"(wd + (size_t)c * 32 * DM), "r"(32768), "r"(mb) : "memory");
    }
    int p0 = -1, p1 = -1;
#pragma unroll 1
    for (int pass = 0; pass < 2; pass++) {
        if (tid < 32) {
            const uint32_t tag = epoch & 0xfffffu;
            uint4 r[4]; uint32_t n = 0;
            const int t3 = tid + 96 < NFW ? tid + 96 : tid;
#pragma unroll 1
            while (true) {
                bool ok = true;
#pragma unroll
                for (int i = 0; i < 4; i++) r[i] = ldg_rlx4((const uint32_t*)&g_f.cand[pass][i < 3 ? tid + 32 * i : t3]);
#pragma unroll
                for (int i = 0; i < 4; i++) ok = ok && (r[i].y >> 12) == tag && (r[i].w >> 12) == tag;
                if (__all_sync(0xffffffffu, ok)) break;
                __nanosleep(32);
                if (++n > SPIN_LIMIT) { ABORT(7); break; }
            }
            float b0 = __uint_as_float(r[0].x), b1 = __uint_as_float(r[0].z); int i0 = r[0].y & 4095, i1 = r[0].w & 4095;
#pragma unroll
            for (int i = 1; i < 4; i++) {
                if (i < 3 || t3 != tid) {
                    float c0 = __uint_as_float(r[i].x), c1 = __uint_as_float(r[i].z); int j0 = r[i].y & 4095, j1 = r[i].w & 4095;
                    if (cand_better(c0, j0, b0, i0)) {
                        if (cand_better(c1, j1, b0, i0)) { b1 = c1; i1 = j1; } else { b1 = b0; i1 = i0; }
                        b0 = c0; i0 = j0;
                    } else if (cand_better(c0, j0, b1, i1)) { b1 = c0; i1 = j0; }
                }
            }
#pragma unroll
            for (int o = 16; o; o >>= 1) {
                float c0 = __shfl_xor_sync(0xffffffffu, b0, o), c1 = __shfl_xor_sync(0xffffffffu, b1, o);
                int j0 = __shfl_xor_sync(0xffffffffu, i0, o), j1 = __shfl_xor_sync(0xffffffffu, i1, o);
                if (cand_better(c0, j0, b0, i0)) {
                    if (cand_better(c1, j1, b0, i0)) { b1 = c1; i1 = j1; } else { b1 = b0; i1 = i0; }
                    b0 = c0; i0 = j0;
                } else if (cand_better(c0, j0, b1, i1)) { b1 = c0; i1 = j0; }
            }
            i0 = min(i0, SQ - 1); i1 = min(i1, SQ - 1);
            if (i0 != p0 || i1 != p1) {
                n = 0;
#pragma unroll 1
                while (!__all_sync(0xffffffffu, (ldg_rlx(&g_f.rows[pass][tid]) == epoch) & (ldg_rlx(&g_f.rows[pass][tid + 32]) == epoch) &
                                                   (ldg_rlx(&g_f.rows[pass][tid + 64]) == epoch) & (ldg_rlx(&g_f.rows[pass][t3]) == epoch))) { __nanosleep(32); if (++n > SPIN_LIMIT) { ABORT(7); break; } }
            }
            int* sel = (int*)(smem + F_SEL);
            if (pass && tid == 0) GT(c * 8 + 5);
            if (tid == 0) { sel[0] = i0; sel[1] = i1; ((float*)sel)[2] = b0; ((float*)sel)[3] = b1; }
        }
        bar_sync(0, 384);
        const int t0 = ((int*)(smem + F_SEL))[0], t1 = ((int*)(smem + F_SEL))[1];
        if (c == 3 && tid == 0 && pass == 0) GT(1430);
        if (t0 == p0 && t1 == p1) break;
        const uint32_t ytag = epoch * 2 + pass + 1;
        if (worker) {
            float2* xs = (float2*)(smem + F_X);
            if (tid < 256) {
                uint32_t a = __ldcg((const uint32_t*)(g_hn + (size_t)t0 * DM) + tid), b = __ldcg((const uint32_t*)(g_hn + (size_t)t1 * DM) + tid);
                *(float4*)(xs + tid * 2) = make_float4(bf_lo(a), bf_lo(b), bf_hi(a), bf_hi(b));
            }
            mbar_wait(mb, 1);
            if (c == 3 && tid == 0 && pass == 0) GT(1431);
            bar_sync(0, 384);
            float4* red = (float4*)(smem + F_RED);
            if (tid < 256) {
                const int cp = tid & 31, kg = tid >> 5;
                const uint32_t* wp = (const uint32_t*)(smem + (cp < 16 ? F_WG : F_WU)) + (cp & 15);
                float a0 = 0.f, a1 = 0.f, b0 = 0.f, b1 = 0.f;
#pragma unroll 16
                for (int k = kg * 64; k < kg * 64 + 64; k++) {
                    uint32_t w = wp[k * 16]; float2 x = xs[k];
                    a0 = fmaf(x.x, bf_lo(w), a0); a1 = fmaf(x.x, bf_hi(w), a1); b0 = fmaf(x.y, bf_lo(w), b0); b1 = fmaf(x.y, bf_hi(w), b1);
                }
                red[kg * 32 + cp] = make_float4(a0, a1, b0, b1);
            }
            bar_sync(0, 384);
            float2* act = (float2*)(smem + F_ACT);
            if (tid < 64) {
                const int f = tid & 31, tk = tid >> 5;
                const float* r = (const float*)red + (f >> 1) * 4 + tk * 2 + (f & 1);
                float gsum = 0.f, usum = 0.f;
#pragma unroll
                for (int kg = 0; kg < 8; kg++) { gsum += r[kg * 128]; usum += r[kg * 128 + 64]; }
                gsum = rbf(gsum); usum = rbf(usum);
                float sg = rbf(gsum / (1.f + __expf(-gsum)));
                ((float*)act)[f * 2 + tk] = rbf(sg * usum);
            }
            bar_sync(0, 384);
            if (tid < 256) {
                const uint32_t* wp = (const uint32_t*)(smem + F_WD) + tid;
                float a0 = 0.f, a1 = 0.f, b0 = 0.f, b1 = 0.f;
#pragma unroll 16
                for (int f = 0; f < 32; f++) {
                    uint32_t w = wp[f * 256]; float2 x = act[f];
                    a0 = fmaf(x.x, bf_lo(w), a0); a1 = fmaf(x.x, bf_hi(w), a1); b0 = fmaf(x.y, bf_lo(w), b0); b1 = fmaf(x.y, bf_hi(w), b1);
                }
                asm volatile("st.relaxed.gpu.global.v4.b32 [%0], {%1,%2,%3,%2};" :: "l"(&g_yp[pass][c][tid]), "r"(FU(a0)), "r"(ytag), "r"(FU(a1)) : "memory");
                asm volatile("st.relaxed.gpu.global.v4.b32 [%0], {%1,%2,%3,%2};" :: "l"(&g_yp[pass][c][256 + tid]), "r"(FU(b0)), "r"(ytag), "r"(FU(b1)) : "memory");
            }
            if (c == 3 && tid == 0 && pass == 0) GT(1432);
        } else {
            const int r = c - NWK, j = tid & 63, part = tid >> 6, tk = r >> 2, dp = (r & 3) * 64 + j;
            const int tok = tk ? t1 : t0, old = tk ? p1 : p0;
            uint32_t hw = 0, nw = 0;
            if (part == 0) {
                hw = __ldcg((const uint32_t*)(g_h + (size_t)tok * DM) + dp); nw = __ldcg((const uint32_t*)(g_hn + (size_t)tok * DM) + dp);
                if (old >= 0 && old != t0 && old != t1) {
                    uint32_t ho = __ldcg((const uint32_t*)(g_h + (size_t)old * DM) + dp), no = __ldcg((const uint32_t*)(g_hn + (size_t)old * DM) + dp);
                    ((uint32_t*)(out + (size_t)old * DM))[dp] = pack2(bf_lo(ho) + bf_lo(no), bf_hi(ho) + bf_hi(no));
                }
            }
            float s0 = 0.f, s1 = 0.f;
            uint4 v[10]; uint32_t n = 0;
            bool ok;
#pragma unroll 1
            do {
                ok = true;
#pragma unroll
                for (int i = 0; i < 10; i++) {
                    const int src = part + 6 * i;
                    v[i] = src < NWK ? ldg_rlx4((const uint32_t*)&g_yp[pass][src][tk * 256 + dp]) : make_uint4(0, ytag, 0, ytag);
                }
#pragma unroll
                for (int i = 0; i < 10; i++) ok = ok && v[i].y == ytag && v[i].w == ytag;
                if (!ok) __nanosleep(100);
                if (++n > SPIN_LIMIT) { ABORT(7); break; }
            } while (!ok);
#pragma unroll
            for (int i = 0; i < 10; i++) { s0 += __uint_as_float(v[i].x); s1 += __uint_as_float(v[i].z); }
            float2* red = (float2*)(smem + F_RED);
            red[part * 64 + j] = make_float2(s0, s1);
            bar_sync(0, 384);
            if (part == 0) {
#pragma unroll
                for (int i = 1; i < 6; i++) { float2 q = red[i * 64 + j]; s0 += q.x; s1 += q.y; }
                const float rs = rbf(1.f / (1.f + __expf(-((float*)(smem + F_SEL))[2 + tk])));
                const float y0 = rbf(rbf(s0) * rs), y1 = rbf(rbf(s1) * rs);
                ((uint32_t*)(out + (size_t)tok * DM))[dp] = pack2(bf_lo(hw) + rbf(bf_lo(nw) + y0), bf_hi(hw) + rbf(bf_hi(nw) + y1));
            }
            if (tid == 0 && pass == 0 && r == 0) GT(1434);
        }
        p0 = t0; p1 = t1;
        if (c == 3 && tid == 0 && pass == 0) GT(1433);
        bar_sync(0, 384);
    }
}

constexpr int G_W = 0;
constexpr int G_RING = 131072;
constexpr int G_BUF = 163840;
constexpr int G_BAR = 229376;
constexpr int G_SMEM = G_BAR + 512;
enum { GB_W0 = 0, GB_W1, GB_WFREE, GB_FULL, GB_EMPTY = GB_FULL + 8, GB_KV = GB_EMPTY + 8, GB_STG = GB_KV + 2, GB_FREE = GB_STG + 2, GB_XN = GB_FREE + 2, GB_RL, GB_T1D, GB_VV, GB_KVF = GB_VV + 2, GB_VF, GB_N };
constexpr int SMEM_TOTAL = 232448;

__device__ __forceinline__ void wgmma_n128(float* d, uint64_t da, uint64_t db, int scale_d) {
    asm volatile("{\n.reg .pred p;\nsetp.ne.b32 p, %66, 0;\n"
        "wgmma.mma_async.sync.aligned.m64n128k16.f32.bf16.bf16 "
        "{%0,%1,%2,%3,%4,%5,%6,%7,%8,%9,%10,%11,%12,%13,%14,%15,%16,%17,%18,%19,%20,%21,%22,%23,%24,%25,%26,%27,%28,%29,%30,%31,"
        "%32,%33,%34,%35,%36,%37,%38,%39,%40,%41,%42,%43,%44,%45,%46,%47,%48,%49,%50,%51,%52,%53,%54,%55,%56,%57,%58,%59,%60,%61,%62,%63}, "
        "%64, %65, p, 1, 1, 0, 1;\n}"
        : "+f"(d[0]), "+f"(d[1]), "+f"(d[2]), "+f"(d[3]), "+f"(d[4]), "+f"(d[5]), "+f"(d[6]), "+f"(d[7]), "+f"(d[8]), "+f"(d[9]), "+f"(d[10]), "+f"(d[11]),
          "+f"(d[12]), "+f"(d[13]), "+f"(d[14]), "+f"(d[15]), "+f"(d[16]), "+f"(d[17]), "+f"(d[18]), "+f"(d[19]), "+f"(d[20]), "+f"(d[21]), "+f"(d[22]), "+f"(d[23]),
          "+f"(d[24]), "+f"(d[25]), "+f"(d[26]), "+f"(d[27]), "+f"(d[28]), "+f"(d[29]), "+f"(d[30]), "+f"(d[31]), "+f"(d[32]), "+f"(d[33]), "+f"(d[34]), "+f"(d[35]),
          "+f"(d[36]), "+f"(d[37]), "+f"(d[38]), "+f"(d[39]), "+f"(d[40]), "+f"(d[41]), "+f"(d[42]), "+f"(d[43]), "+f"(d[44]), "+f"(d[45]), "+f"(d[46]), "+f"(d[47]),
          "+f"(d[48]), "+f"(d[49]), "+f"(d[50]), "+f"(d[51]), "+f"(d[52]), "+f"(d[53]), "+f"(d[54]), "+f"(d[55]), "+f"(d[56]), "+f"(d[57]), "+f"(d[58]), "+f"(d[59]),
          "+f"(d[60]), "+f"(d[61]), "+f"(d[62]), "+f"(d[63])
        : "l"(da), "l"(db), "r"(scale_d));
}

__device__ __forceinline__ constexpr uint32_t slot_off(int slot) {
    return slot < 2 ? G_RING + slot * 16384 : G_BUF + (slot - 2) * 32768 + 16384;
}
template <int NSLOT>
__device__ __forceinline__ void gemm_tile(float* acc, uint32_t sb, int tile, int it, bool first, uint32_t wpar, int wg, bool pass, uint32_t l0) {
    const uint32_t bar = sb + G_BAR;
    bar_sync(3 + wg, 256);
    int prev = 0;
#pragma unroll
    for (int k = 0; k < 4; k++) {
        const int n = tile * 4 + k, slot = NSLOT == 4 ? k : n % 3;
        const uint32_t sz = sb + (((it + k) << 4) & sb & 0x3f0);
        const uint64_t da = desc_sw128(sz + slot_off(slot), 16, 1024), db0 = desc_sw128(sz + G_W, 65536, 1024);
        if ((k & 1) == 0 && first) mbar_wait_p(bar + 8 * (GB_W0 + (k >> 1)), wpar);
        bool rel = false;
        if (EREL && k > 0 && !__all_sync(0xffffffffu, mbar_test(bar + 8 * (GB_FULL + slot), tile & 1))) {
            asm volatile("wgmma.wait_group.sync.aligned 0;" ::: "memory");
            mbar_arrive2_if(bar + 8 * (GB_EMPTY + prev), l0);
            rel = true;
        }
        mbar_wait_p(bar + 8 * (GB_FULL + slot), NSLOT == 4 ? (tile & 1) : ((n / 3) & 1));
        if (k == 3 && pass) bar_arrive(3 + (wg ^ 1), 256);
        asm volatile("wgmma.fence.sync.aligned;" ::: "memory");
#pragma unroll
        for (int kk = 0; kk < 4; kk++) wgmma_n128(acc, da + kk * 2, db0 + k * 1024 + kk * 128, (k | kk) != 0);
        asm volatile("wgmma.commit_group.sync.aligned;" ::: "memory");
        if (k > 0) {
            asm volatile("wgmma.wait_group.sync.aligned 1;" ::: "memory");
            mbar_arrive2_if(bar + 8 * (GB_EMPTY + prev), rel ? 0 : l0);
        }
#pragma unroll
        for (int kk = 0; kk < 4; kk++) wgmma_n128(acc, da + 512 + kk * 2, db0 + k * 1024 + 512 + kk * 128, 1);
        asm volatile("wgmma.commit_group.sync.aligned;" ::: "memory");
        prev = slot;
    }
    asm volatile("wgmma.wait_group.sync.aligned 0;" ::: "memory");
    mbar_arrive2_if(bar + 8 * (GB_EMPTY + prev), l0);
}
__device__ __forceinline__ void stage_bf16(const float* acc, uint32_t buf, float s0, float s1) {
    const int lane = threadIdx.x & 31, wq = (threadIdx.x >> 5) & 3;
    const int row = wq * 16 + (lane & 7) + ((lane >> 3) & 1) * 8;
    const uint32_t base = buf + row * 128;
#pragma unroll
    for (int j = 0; j < 16; j += 2) {
        const int ch = (j & 7) + (lane >> 4);
        stsm4(base + (j >> 3) * 8192 + ((ch ^ (row & 7)) << 4),
              pack2(acc[4 * j] * s0, acc[4 * j + 1] * s0), pack2(acc[4 * j + 2] * s1, acc[4 * j + 3] * s1),
              pack2(acc[4 * j + 4] * s0, acc[4 * j + 5] * s0), pack2(acc[4 * j + 6] * s1, acc[4 * j + 7] * s1));
    }
}

__device__ __forceinline__ void store_perm(const float* acc, bf16* dst, int ld, float s0, float s1) {
#pragma unroll
    for (int i = 0; i < 4; i++) {
        const float* a = acc + 16 * i;
        *(uint4*)(dst + i * 32) = make_uint4(pack2(a[0] * s0, a[1] * s0), pack2(a[4] * s0, a[5] * s0), pack2(a[8] * s0, a[9] * s0), pack2(a[12] * s0, a[13] * s0));
        *(uint4*)(dst + 8 * ld + i * 32) = make_uint4(pack2(a[2] * s1, a[3] * s1), pack2(a[6] * s1, a[7] * s1), pack2(a[10] * s1, a[11] * s1), pack2(a[14] * s1, a[15] * s1));
    }
}
template <int ACC>
__device__ __forceinline__ void wgmma_rs64(float* d, const uint32_t* a, uint64_t db) {
    asm volatile("{\n.reg .pred p;\nsetp.ne.b32 p, %37, 0;\n"
        "wgmma.mma_async.sync.aligned.m64n64k16.f32.bf16.bf16 {%0,%1,%2,%3,%4,%5,%6,%7,%8,%9,%10,%11,%12,%13,%14,%15,%16,%17,%18,%19,%20,%21,%22,%23,%24,%25,%26,%27,%28,%29,%30,%31}, {%32,%33,%34,%35}, %36, p, 1, 1, 0;\n}"
        : "+f"(d[0]), "+f"(d[1]), "+f"(d[2]), "+f"(d[3]), "+f"(d[4]), "+f"(d[5]), "+f"(d[6]), "+f"(d[7]), "+f"(d[8]), "+f"(d[9]), "+f"(d[10]), "+f"(d[11]), "+f"(d[12]), "+f"(d[13]), "+f"(d[14]), "+f"(d[15]), "+f"(d[16]), "+f"(d[17]), "+f"(d[18]), "+f"(d[19]), "+f"(d[20]), "+f"(d[21]), "+f"(d[22]), "+f"(d[23]), "+f"(d[24]), "+f"(d[25]), "+f"(d[26]), "+f"(d[27]), "+f"(d[28]), "+f"(d[29]), "+f"(d[30]), "+f"(d[31])
        : "r"(a[0]), "r"(a[1]), "r"(a[2]), "r"(a[3]), "l"(db), "n"(ACC));
}
template <int ACC>
__device__ __forceinline__ void wgmma_rs128t(float* d, const uint32_t* a, uint64_t db) {
    asm volatile("{\n.reg .pred p;\nsetp.ne.b32 p, %69, 0;\n"
        "wgmma.mma_async.sync.aligned.m64n128k16.f32.bf16.bf16 {%0,%1,%2,%3,%4,%5,%6,%7,%8,%9,%10,%11,%12,%13,%14,%15,%16,%17,%18,%19,%20,%21,%22,%23,%24,%25,%26,%27,%28,%29,%30,%31,%32,%33,%34,%35,%36,%37,%38,%39,%40,%41,%42,%43,%44,%45,%46,%47,%48,%49,%50,%51,%52,%53,%54,%55,%56,%57,%58,%59,%60,%61,%62,%63}, {%64,%65,%66,%67}, %68, p, 1, 1, 1;\n}"
        : "+f"(d[0]), "+f"(d[1]), "+f"(d[2]), "+f"(d[3]), "+f"(d[4]), "+f"(d[5]), "+f"(d[6]), "+f"(d[7]), "+f"(d[8]), "+f"(d[9]), "+f"(d[10]), "+f"(d[11]), "+f"(d[12]), "+f"(d[13]), "+f"(d[14]), "+f"(d[15]), "+f"(d[16]), "+f"(d[17]), "+f"(d[18]), "+f"(d[19]), "+f"(d[20]), "+f"(d[21]), "+f"(d[22]), "+f"(d[23]), "+f"(d[24]), "+f"(d[25]), "+f"(d[26]), "+f"(d[27]), "+f"(d[28]), "+f"(d[29]), "+f"(d[30]), "+f"(d[31]), "+f"(d[32]), "+f"(d[33]), "+f"(d[34]), "+f"(d[35]), "+f"(d[36]), "+f"(d[37]), "+f"(d[38]), "+f"(d[39]), "+f"(d[40]), "+f"(d[41]), "+f"(d[42]), "+f"(d[43]), "+f"(d[44]), "+f"(d[45]), "+f"(d[46]), "+f"(d[47]), "+f"(d[48]), "+f"(d[49]), "+f"(d[50]), "+f"(d[51]), "+f"(d[52]), "+f"(d[53]), "+f"(d[54]), "+f"(d[55]), "+f"(d[56]), "+f"(d[57]), "+f"(d[58]), "+f"(d[59]), "+f"(d[60]), "+f"(d[61]), "+f"(d[62]), "+f"(d[63])
        : "r"(a[0]), "r"(a[1]), "r"(a[2]), "r"(a[3]), "l"(db), "n"(ACC));
}
__device__ __forceinline__ void attention_tile(float* acc, uint32_t sb, int tile, int h, int wg, int wq, uint32_t l0, uint32_t epoch, uint2 rec) {
    const uint32_t buf = sb + G_BUF + ((tile << 4) & sb & 0x3f0);
    const int lane = threadIdx.x & 31, g = lane >> 2, t = lane & 3;
    const int sg = wq >> 1, hf = wq & 1, seg = tile * 2 + sg;
    uint32_t qf[8][4];
#pragma unroll
    for (int kk = 0; kk < 8; kk++) {
        qf[kk][0] = pack2(acc[8 * kk], acc[8 * kk + 1]); qf[kk][1] = pack2(acc[8 * kk + 2], acc[8 * kk + 3]);
        qf[kk][2] = pack2(acc[8 * kk + 4], acc[8 * kk + 5]); qf[kk][3] = pack2(acc[8 * kk + 6], acc[8 * kk + 7]);
    }
    uint32_t* kvf = &g_KVf[seg][h][lane * 4];
    uint4 km[4], vm[4];
    const bool early = __all_sync(0xffffffffu, (rec.x >> 8) == epoch && (rec.y >> 8) == epoch && (rec.x & 255) > seg && (rec.y & 255) > seg);
#pragma unroll
    for (int i = 0; i < 4; i++) { km[i] = ldg_rlx4_if(kvf + i * 128, early); vm[i] = ldg_rlx4_if(kvf + 512 + i * 128, early); }
    mbar_wait_p(sb + G_BAR + 8 * (GB_KV + wg), (tile >> 1) & 1);
    if (h == 5 && (threadIdx.x & 127) == 0 && tile < 6) GT(1750 + tile * 8 + 2);
    float sc[5][4];
    {
        const uint64_t dk = desc_sw128(buf, 16, 1024);
        asm volatile("wgmma.fence.sync.aligned;" ::: "memory");
#pragma unroll
        for (int kk = 0; kk < 8; kk++) {
            if (kk == 0) wgmma_rs64<0>(acc, qf[kk], dk); else wgmma_rs64<1>(acc, qf[kk], dk + (kk >> 2) * 512 + (kk & 3) * 2);
        }
        asm volatile("wgmma.commit_group.sync.aligned;" ::: "memory");
        asm volatile("wgmma.wait_group.sync.aligned 0;" ::: "memory");
        mbar_arrive_if(sb + G_BAR + 8 * GB_KVF, l0);
#pragma unroll
        for (int i = 0; i < 32; i++) asm volatile("" : "+f"(acc[i]) :: "memory");
#pragma unroll
        for (int b = 0; b < 4; b++)
#pragma unroll
            for (int i = 0; i < 4; i++) sc[b][i] = sg ? acc[16 + 4 * b + i] : acc[4 * b + i];
        sc[4][0] = sc[4][1] = sc[4][2] = sc[4][3] = 0.f;
    }
    const float cexp = 0.08838834764831845f * 1.4426950408889634f;
    const int r0 = hf * 16 + g, r1 = r0 + 8;
#pragma unroll
    for (int b = 0; b < 4; b++) {
        const int j = b * 8 + 2 * t;
        if (j > r0) sc[b][0] = -INFINITY;
        if (j + 1 > r0) sc[b][1] = -INFINITY;
        if (j > r1) sc[b][2] = -INFINITY;
        if (j + 1 > r1) sc[b][3] = -INFINITY;
    }
    float m0 = -INFINITY, m1 = -INFINITY;
#pragma unroll
    for (int b = 0; b < 4; b++) { m0 = fmaxf(m0, fmaxf(sc[b][0], sc[b][1])); m1 = fmaxf(m1, fmaxf(sc[b][2], sc[b][3])); }
    m0 = fmaxf(m0, __shfl_xor_sync(0xffffffffu, m0, 1)); m0 = fmaxf(m0, __shfl_xor_sync(0xffffffffu, m0, 2));
    m1 = fmaxf(m1, __shfl_xor_sync(0xffffffffu, m1, 1)); m1 = fmaxf(m1, __shfl_xor_sync(0xffffffffu, m1, 2));
    float z0 = 0.f, z1 = 0.f;
    {
        const float c0 = -m0 * cexp, c1 = -m1 * cexp;
        uint32_t pf[4][2];
#pragma unroll
        for (int b = 0; b < 4; b++) {
            pf[b][0] = pack2(ex2(fmaf(sc[b][0], cexp, c0)), ex2(fmaf(sc[b][1], cexp, c0)));
            pf[b][1] = pack2(ex2(fmaf(sc[b][2], cexp, c1)), ex2(fmaf(sc[b][3], cexp, c1)));
            z0 += bf_lo(pf[b][0]) + bf_hi(pf[b][0]); z1 += bf_lo(pf[b][1]) + bf_hi(pf[b][1]);
        }
        uint32_t pa[4][4];
#pragma unroll
        for (int kk = 0; kk < 4; kk++)
#pragma unroll
            for (int i = 0; i < 4; i++) pa[kk][i] = (kk >> 1) == sg ? pf[(kk & 1) * 2 + (i >> 1)][i & 1] : 0u;
        const uint64_t dv = desc_sw128(buf + 32768, 8192, 1024);
        mbar_wait_p(sb + G_BAR + 8 * (GB_VV + wg), (tile >> 1) & 1);
        asm volatile("wgmma.fence.sync.aligned;" ::: "memory");
#pragma unroll
        for (int kk = 0; kk < 4; kk++) { if (kk == 0) wgmma_rs128t<0>(acc, pa[kk], dv); else wgmma_rs128t<1>(acc, pa[kk], dv + kk * 128); }
        asm volatile("wgmma.commit_group.sync.aligned;" ::: "memory");
        asm volatile("wgmma.wait_group.sync.aligned 0;" ::: "memory");
#pragma unroll
        for (int i = 0; i < 64; i++) asm volatile("" : "+f"(acc[i]) :: "memory");
    }
    mbar_arrive_if(sb + G_BAR + 8 * GB_VF, l0);
    if (h == 5 && (threadIdx.x & 127) == 0 && tile < 6) GT(1750 + tile * 8 + 3);
    if (!early) wait_rec(&g_f.rec[2 * h], epoch, seg + 1);
    if (seg == 63 && (threadIdx.x & 63) == 0) GT(1570 + h);
    if (h == 5 && (threadIdx.x & 127) == 0 && tile < 6) GT(1750 + tile * 8 + 4);
    __syncwarp();
    {
        uint32_t n = 0;
#pragma unroll 1
        while (true) {
            uint32_t mn = 0xffffffffu;
#pragma unroll
            for (int i = 0; i < 4; i++) mn = min(min(min(mn, min(km[i].x, km[i].y)), min(km[i].z, km[i].w)), min(min(vm[i].x, vm[i].y), min(vm[i].z, vm[i].w)));
            if (__all_sync(0xffffffffu, mn != 0)) break;
            if (++n > SPIN_LIMIT) { ABORT(4); break; }
#pragma unroll
            for (int i = 0; i < 4; i++) { km[i] = ldg_rlx4(kvf + i * 128); vm[i] = ldg_rlx4(kvf + 512 + i * 128); }
        }
#pragma unroll
        for (int i = 0; i < 4; i++) {
            km[i] = make_uint4(~km[i].x, ~km[i].y, ~km[i].z, ~km[i].w); vm[i] = make_uint4(~vm[i].x, ~vm[i].y, ~vm[i].z, ~vm[i].w);
        }
        if (hf) bar_arrive(5 + wg * 2 + sg, 64);
        float sb_[4] = {0.f, 0.f, 0.f, 0.f};
#pragma unroll
        for (int i = 0; i < 4; i++) { MMA(sc[4], qf[2 * i], km[i].x, km[i].y); MMA(sb_, qf[2 * i + 1], km[i].z, km[i].w); }
#pragma unroll
        for (int i = 0; i < 4; i++) sc[4][i] += sb_[i];
        float n0 = fmaxf(sc[4][0], sc[4][1]), n1 = fmaxf(sc[4][2], sc[4][3]);
        n0 = fmaxf(n0, __shfl_xor_sync(0xffffffffu, n0, 1)); n1 = fmaxf(n1, __shfl_xor_sync(0xffffffffu, n1, 1));
        n0 = fmaxf(n0, __shfl_xor_sync(0xffffffffu, n0, 2)); n1 = fmaxf(n1, __shfl_xor_sync(0xffffffffu, n1, 2));
        n0 = fmaxf(n0, m0); n1 = fmaxf(n1, m1);
        const float a0 = ex2((m0 - n0) * cexp), a1 = ex2((m1 - n1) * cexp);
        const float c0 = -n0 * cexp, c1 = -n1 * cexp;
        const uint32_t p0 = pack2(ex2(fmaf(sc[4][0], cexp, c0)), ex2(fmaf(sc[4][1], cexp, c0)));
        const uint32_t p1 = pack2(ex2(fmaf(sc[4][2], cexp, c1)), ex2(fmaf(sc[4][3], cexp, c1)));
        z0 = fmaf(z0, a0, bf_lo(p0) + bf_hi(p0)); z1 = fmaf(z1, a1, bf_lo(p1) + bf_hi(p1));
        const uint32_t* vmw = (const uint32_t*)vm;
#pragma unroll
        for (int j = 0; j < 16; j++) {
            float* o = acc + 4 * j;
            o[0] *= a0; o[1] *= a0; o[2] *= a1; o[3] *= a1;
            mma1688(o, p0, p1, vmw[j]);
        }
        z0 += __shfl_xor_sync(0xffffffffu, z0, 1); z1 += __shfl_xor_sync(0xffffffffu, z1, 1);
        z0 += __shfl_xor_sync(0xffffffffu, z0, 2); z1 += __shfl_xor_sync(0xffffffffu, z1, 2);
    }
    if (h == 5 && (threadIdx.x & 127) == 0 && tile < 6) GT(1750 + tile * 8 + 5);
    store_perm(acc, g_O + (size_t)(tile * 64 + wq * 16 + g) * HD + h * 128 + t * 8, HD, rcpf(z0), rcpf(z1));
    if (tile >= 2) mbar_wait_p(sb + G_BAR + 8 * (GB_FREE + wg), ((tile >> 1) - 1) & 1);
    mbar_arrive(sb + G_BAR + 8 * (GB_STG + wg));
    if (!hf) {
        bar_sync(5 + wg * 2 + sg, 64);
#pragma unroll
        for (int i = 0; i < 8; i++) stg4(kvf + i * 128, make_uint4(0, 0, 0, 0));
    }
}

__device__ __forceinline__ void g_consumer(uint32_t sb_, int g_, int wg_, uint32_t epoch) {
    const uint32_t sb = uni(sb_);
    const int g = uni(g_), wg = uni(wg_), wq = uni((threadIdx.x >> 5) & 3);
    const uint32_t l0 = opaque((threadIdx.x & 31) == 0);
    const uint32_t bar = sb + G_BAR, buf = sb + G_BUF + wg * 32768;
    const int lane = threadIdx.x & 31;
    float acc[64];
    if (wg == 1) bar_arrive(3, 256);
    const int n1 = g < 32 ? HSPLIT / 2 : NT - HSPLIT / 2;
#pragma unroll 1
    for (int i = 0; i < n1; i++) {
        gemm_tile<4>(acc, sb, wg, i, i == 0 || i == NT / 2, i >= NT / 2, wg, true, l0);
        if (i == n1 - 1 || i == NT / 2 - 1) mbar_arrive_if(bar + 8 * GB_WFREE, l0);
        if (threadIdx.x == 0 && i == 0) GT((64 + g) * 8 + 1);
        if (threadIdx.x == 128 && i == 3) GT((64 + g) * 8 + 2);
        if (i > 0) mbar_wait_p(bar + 8 * (GB_FREE + wg), (i - 1) & 1);
        stage_bf16(acc, buf, 1.f, 1.f);
        asm volatile("fence.proxy.async.shared::cta;" ::: "memory");
        mbar_arrive(bar + 8 * (GB_STG + wg));
    }
    if (threadIdx.x == 128) GT((64 + g) * 8 + 3);
    if (g < 32) {
#pragma unroll 1
        for (int i = 0; i < NT / 2; i++) {
            const int tile = 2 * i + wg;
            const uint2 rec = ldg_rlx2(&g_f.rec[2 * g]);
            gemm_tile<4>(acc, sb, tile, i, i == 0, 1, wg, tile != NT - 1, l0);
            if (threadIdx.x == 0 && i == 0) GT((64 + g) * 8 + 4);
            if (threadIdx.x == 128 && i == 3) GT((64 + g) * 8 + 5);
            if (g == 5 && (threadIdx.x & 127) == 0 && tile < 6) GT(1750 + tile * 8 + 1);
            attention_tile(acc, sb, tile, g, wg, wq, l0, epoch, rec);
            if (g == 5 && (threadIdx.x & 127) == 0 && tile < 6) GT(1750 + tile * 8 + 6);
        }
    } else {
#pragma unroll 1
        for (int i = 0; i < NT / 2; i++) {
            const int tile = 2 * i + wg;
            gemm_tile<4>(acc, sb, tile, i, i == 0, 0, wg, tile != NT - 1, l0);
            if (threadIdx.x == 0 && i == 0) GT((64 + g) * 8 + 4);
            if (threadIdx.x == 128 && i == 3) GT((64 + g) * 8 + 5);
            store_perm(acc, g_P + (size_t)(((g - 32) >> 2) * SQ + tile * 64 + wq * 16 + (lane >> 2)) * DM + ((g - 32) & 3) * 128 + (lane & 3) * 8, DM, 1.f, 1.f);
            mbar_wait_p(bar + 8 * (GB_FREE + wg), (i - 1) & 1);
            mbar_arrive(bar + 8 * (GB_STG + wg));
        }
    }
}

__device__ __forceinline__ void load_w(uint32_t sb, const CUtensorMap* tm, int col, int row, int k0 = 0, int k1 = 2) {
    const uint32_t bar = sb + G_BAR;
#pragma unroll
    for (int kh = k0; kh < k1; kh++) {
        mbar_expect_tx(bar + 8 * (GB_W0 + kh), 65536);
        tma2d(sb + G_W + kh * 32768, tm, col, row + kh * 256, bar + 8 * (GB_W0 + kh));
        tma2d(sb + G_W + 65536 + kh * 32768, tm, col + 64, row + kh * 256, bar + 8 * (GB_W0 + kh));
    }
}

__device__ __forceinline__ void rbf2(float& a, float& b) { uint32_t w = pack2(a, b); a = bf_lo(w); b = bf_hi(w); }
__device__ __forceinline__ void warp_sum2(float& a, float& b) {
#pragma unroll
    for (int o = 16; o; o >>= 1) { float c = __shfl_xor_sync(0xffffffffu, a, o), d = __shfl_xor_sync(0xffffffffu, b, o); a += c; b += d; }
}
__device__ __forceinline__ float sum16(const float* v) {
    return (((v[0] + v[1]) + (v[2] + v[3])) + ((v[4] + v[5]) + (v[6] + v[7]))) + (((v[8] + v[9]) + (v[10] + v[11])) + ((v[12] + v[13]) + (v[14] + v[15])));
}
__device__ __forceinline__ void ln_row2(float* v, float* u) {
    float sv = sum16(v), su = sum16(u);
    warp_sum2(sv, su);
    const float mv = sv * (1.f / DM), mu = su * (1.f / DM);
    float qv = 0.f, qu = 0.f, qv2 = 0.f, qu2 = 0.f;
#pragma unroll
    for (int i = 0; i < 16; i += 2) {
        float d0 = v[i] - mv, d1 = v[i + 1] - mv, e0 = u[i] - mu, e1 = u[i + 1] - mu;
        qv = fmaf(d0, d0, qv); qv2 = fmaf(d1, d1, qv2); qu = fmaf(e0, e0, qu); qu2 = fmaf(e1, e1, qu2);
    }
    qv += qv2; qu += qu2;
    warp_sum2(qv, qu);
    const float rv = rbf(mv), ru = rbf(mu);
    const float iv = __frcp_rn(rbf(sqrtf(rbf(rbf(qv * (1.f / DM)) + 1e-5f)))), iu = __frcp_rn(rbf(sqrtf(rbf(rbf(qu * (1.f / DM)) + 1e-5f))));
#pragma unroll
    for (int i = 0; i < 16; i += 2) {
        float a = v[i] - rv, b = v[i + 1] - rv, c = u[i] - ru, d = u[i + 1] - ru;
        rbf2(a, b); rbf2(c, d);
        a *= iv; b *= iv; c *= iu; d *= iu;
        rbf2(a, b); rbf2(c, d);
        v[i] = a; v[i + 1] = b; u[i] = c; u[i + 1] = d;
    }
}

__device__ __forceinline__ void ln_row1(float* v) {
    float sv = sum16(v);
#pragma unroll
    for (int o = 16; o; o >>= 1) sv += __shfl_xor_sync(0xffffffffu, sv, o);
    const float mv = sv * (1.f / DM);
    float qv = 0.f, qv2 = 0.f;
#pragma unroll
    for (int i = 0; i < 16; i += 2) { float d0 = v[i] - mv, d1 = v[i + 1] - mv; qv = fmaf(d0, d0, qv); qv2 = fmaf(d1, d1, qv2); }
    qv += qv2;
#pragma unroll
    for (int o = 16; o; o >>= 1) qv += __shfl_xor_sync(0xffffffffu, qv, o);
    const float rv = rbf(mv);
    float sq, iv;
    asm("sqrt.approx.f32 %0, %1;" : "=f"(sq) : "f"(rbf(rbf(qv * (1.f / DM)) + 1e-5f)));
    asm("rcp.approx.f32 %0, %1;" : "=f"(iv) : "f"(rbf(sq)));
#pragma unroll
    for (int i = 0; i < 16; i += 2) {
        float a = v[i] - rv, b = v[i + 1] - rv;
        rbf2(a, b);
        a *= iv; b *= iv;
        rbf2(a, b);
        v[i] = a; v[i + 1] = b;
    }
}
constexpr int FSPLIT = 28;
__device__ __forceinline__ int fin_row(int id, int i) {
    if (id < 64) { const int tile = i < FSPLIT / 2 ? 2 * i : i + FSPLIT / 2; return tile < NT ? tile * 64 + id : -1; }
    const int j = id - 64 + i * 48;
    return j < FSPLIT * 32 ? (j >> 6) * 128 + 64 + (j & 63) : -1;
}
__device__ __forceinline__ void finalizer(int id, const bf16* __restrict__ x, const bf16* __restrict__ wr, bf16* __restrict__ out, uint32_t epoch) {
    const int lane = threadIdx.x & 31;
    float b0 = -INFINITY, b1 = -INFINITY; int i0 = 0x7fffffff, i1 = 0x7fffffff;
    const uint32_t tag = (epoch & 0xfffffu) << 12;
    uint32_t fl = ~epoch;
    int row = fin_row(id, 0);
    const uint4 ra = *(const uint4*)(wr + lane * 8), rb = *(const uint4*)(wr + 256 + lane * 8);
    uint4 xa = *(const uint4*)(x + (size_t)row * DM + lane * 8), xb = *(const uint4*)(x + (size_t)row * DM + lane * 8 + 256);
#pragma unroll 1
    for (int it = 0; row >= 0; it++) {
        const int tile = row >> 6, nxt = fin_row(id, it + 1);
        const size_t o0 = (size_t)row * DM + lane * 8;
        uint32_t n = 0;
#pragma unroll 1
        while (!__all_sync(0xffffffffu, fl == epoch)) {
            if (n) __nanosleep(it ? 64 : 1000);
            fl = ldg_rlx(&g_f.p[tile][lane]);
            if (++n > SPIN_LIMIT) { ABORT(12); break; }
        }
        if (tile == NT - 1 && id == 63 && lane == 0) GT(1438);
        if ((id == 63 || id == 3 || id == 70) && lane == 0) GT(1800 + (id == 3) * 32 + tile);
        float v[16];
        {
            uint4 pa[8][2];
#pragma unroll
            for (int k = 0; k < 8; k++) {
                pa[k][0] = ldg_rlx4((const uint32_t*)(g_P + (size_t)k * SQ * DM + o0));
                pa[k][1] = ldg_rlx4((const uint32_t*)(g_P + (size_t)k * SQ * DM + o0 + 256));
            }
            fl = ldg_rlx(&g_f.p[max(nxt, 0) >> 6][lane]);
#pragma unroll
            for (int j = 0; j < 2; j++) {
#pragma unroll
                for (int i = 0; i < 4; i++) {
                    uint32_t w[8];
#pragma unroll
                    for (int k = 0; k < 8; k++) w[k] = i == 0 ? pa[k][j].x : (i == 1 ? pa[k][j].y : (i == 2 ? pa[k][j].z : pa[k][j].w));
                    v[j * 8 + 2 * i] = ((bf_lo(w[0]) + bf_lo(w[1])) + (bf_lo(w[2]) + bf_lo(w[3]))) + ((bf_lo(w[4]) + bf_lo(w[5])) + (bf_lo(w[6]) + bf_lo(w[7])));
                    v[j * 8 + 2 * i + 1] = ((bf_hi(w[0]) + bf_hi(w[1])) + (bf_hi(w[2]) + bf_hi(w[3]))) + ((bf_hi(w[4]) + bf_hi(w[5])) + (bf_hi(w[6]) + bf_hi(w[7])));
                }
            }
        }
        uint32_t hw[8];
        {
            const uint32_t xw[8] = {xa.x, xa.y, xa.z, xa.w, xb.x, xb.y, xb.z, xb.w};
            uint32_t aw[8];
#pragma unroll
            for (int i = 0; i < 8; i++) aw[i] = pack2(v[2 * i], v[2 * i + 1]);
#pragma unroll
            for (int d = 1; d <= 2; d++) {
                const bool up = lane & d;
#pragma unroll
                for (int i = 0; i < 8; i++) {
                    if (!(i & d)) {
                        const uint32_t r = __shfl_xor_sync(0xffffffffu, up ? aw[i] : aw[i | d], d);
                        if (up) aw[i] = r; else aw[i | d] = r;
                    }
                }
            }
#pragma unroll
            for (int i = 0; i < 8; i++) {
                hw[i] = pack2(bf_lo(aw[i]) + bf_lo(xw[i]), bf_hi(aw[i]) + bf_hi(xw[i]));
                v[2 * i] = bf_lo(hw[i]); v[2 * i + 1] = bf_hi(hw[i]);
            }
        }
        xa = *(const uint4*)(x + (size_t)max(nxt, 0) * DM + lane * 8); xb = *(const uint4*)(x + (size_t)max(nxt, 0) * DM + lane * 8 + 256);
        ln_row1(v);
        float r0 = 0.f, r1 = 0.f;
        {
            const uint32_t ww[8] = {ra.x, ra.y, ra.z, ra.w, rb.x, rb.y, rb.z, rb.w};
#pragma unroll
            for (int i = 0; i < 8; i++) { r0 = fmaf(v[2 * i], bf_lo(ww[i]), r0); r1 = fmaf(v[2 * i + 1], bf_hi(ww[i]), r1); }
        }
        r0 += r1;
#pragma unroll
        for (int o = 16; o; o >>= 1) r0 += __shfl_xor_sync(0xffffffffu, r0, o);
        r0 = rbf(r0);
        if (cand_better(r0, row, b0, i0)) { b1 = b0; i1 = i0; b0 = r0; i0 = row; }
        else if (cand_better(r0, row, b1, i1)) { b1 = r0; i1 = row; }
        if (tile == NT - 1 && id == 63 && lane == 0) GT(1439);
        const bool last = nxt < 0, spec = tile < SPEC_TILES && (last || (nxt >> 6) >= SPEC_TILES);
        const bool pub = (lane == 0 && spec) || (lane == 1 && last);
        if (pub)
            asm volatile("st.relaxed.gpu.global.v4.b32 [%0], {%1,%2,%3,%4};" :: "l"(&g_f.cand[lane][id]),
                         "r"(FU(b0)), "r"(tag | (uint32_t)min(i0, 4095)), "r"(FU(b1)), "r"(tag | (uint32_t)min(i1, 4095)) : "memory");
#pragma unroll
        for (int j = 0; j < 2; j++) {
            const uint32_t* hh = hw + j * 4; const float* nn = v + j * 8;
            *(uint4*)(out + o0 + j * 256) = make_uint4(pack2(bf_lo(hh[0]) + nn[0], bf_hi(hh[0]) + nn[1]), pack2(bf_lo(hh[1]) + nn[2], bf_hi(hh[1]) + nn[3]),
                                                       pack2(bf_lo(hh[2]) + nn[4], bf_hi(hh[2]) + nn[5]), pack2(bf_lo(hh[3]) + nn[6], bf_hi(hh[3]) + nn[7]));
            *(uint4*)(g_h + o0 + j * 256) = make_uint4(hh[0], hh[1], hh[2], hh[3]);
            *(uint4*)(g_hn + o0 + j * 256) = make_uint4(pack2(nn[0], nn[1]), pack2(nn[2], nn[3]), pack2(nn[4], nn[5]), pack2(nn[6], nn[7]));
        }
        if (last || spec) {
            __threadfence();
            __syncwarp();
            if (pub) stg_rlx(&g_f.rows[lane][id], epoch);
        }
        row = nxt;
    }
    if (id == 0 && lane == 0) { g_epoch = epoch; if (epoch == 0xffffffu) { g_ticket[0] = 0; g_ticket[32] = 0; } }
}

__device__ __forceinline__ void g_producer(uint32_t sb, int g, const Maps& maps, uint32_t epoch, const bf16* __restrict__ x, const bf16* __restrict__ wr, bf16* __restrict__ out) {
    const uint32_t bar = sb + G_BAR;
    const int warp = (threadIdx.x >> 5) - 8;
    if (threadIdx.x == 256 && g == 5) GT(1410);
    if (threadIdx.x == 256 && g == 5) GT(1411);
    if (warp == 3) {
        wait_eq4(&g_f.xn[(threadIdx.x & 31) * 4], epoch, 13);
        __syncwarp();
        if ((threadIdx.x & 31) == 0) mbar_arrive(bar + 8 * GB_XN);
        wait_eq2(&g_f.rload[(threadIdx.x & 31) * 2], epoch, 13);
        __syncwarp();
        if ((threadIdx.x & 31) == 0) mbar_arrive(bar + 8 * GB_RL);
        finalizer(g, x, wr, out, epoch);
        if (g == 63 && (threadIdx.x & 31) == 0) GT(128 * 8 + 6);
    }
    if ((threadIdx.x & 31) != 0) return;
    if (threadIdx.x == 256 && g == 5) GT(1412);
    if (warp == 0) {
        wait_eq4(&g_f.xn[0], epoch, 13);
        const int rk = g & 1;
        const int m1 = g < 32 ? HSPLIT : 2 * NT - HSPLIT;
#pragma unroll 1
        for (int it = 0; it < m1; it++) {
            const int tile = it < NT ? it : it - NT + HSPLIT;
            if (it == HOLD) mbar_wait(bar + 8 * GB_RL, 0);
            if (it == 1) wait_eq4(&g_f.xn[4], epoch, 13);
            if (it == 2) mbar_wait(bar + 8 * GB_XN, 0);
            if (it == NT) {
                mbar_wait(bar + 8 * GB_WFREE, 0);
                load_w(sb, (g & 1) ? &maps.wv : &maps.wk, ((g - 32) >> 1) * 128, 0);
            }
#pragma unroll
            for (int k = 0; k < 4; k++) {
                if (k == 2 && it == 0) load_w(sb, (g & 1) ? &maps.wv : &maps.wk, (g >> 1) * 128, 0, 1, 2);
                mbar_wait(bar + 8 * (GB_EMPTY + k), (it & 1) ^ 1);
                mbar_expect_tx(bar + 8 * (GB_FULL + k), 16384);
                tma2d_mc(sb + slot_off(k) + rk * 8192, &maps.xn2, (k * 2 + rk) * 64, tile * 64, bar + 8 * (GB_FULL + k));
            }
        }
        mbar_wait(bar + 8 * GB_WFREE, g >= 32);
        const int u = g - 32, ks = u >> 2, ns = u & 3;
        if (g < 32) load_w(sb, &maps.wq, g * 128, 0);
        else {
#pragma unroll
            for (int kh = 0; kh < 2; kh++) {
                mbar_expect_tx(bar + 8 * (GB_W0 + kh), 65536);
#pragma unroll
                for (int nh = 0; nh < 2; nh++)
                    asm volatile("cp.async.bulk.tensor.5d.shared::cluster.global.mbarrier::complete_tx::bytes [%0], [%1, {%3, %4, %4, %4, %5}], [%2];"
                        :: "r"(sb + G_W + nh * 65536 + kh * 32768), "l"((uint64_t)&maps.wo2), "r"(bar + 8 * (GB_W0 + kh)), "r"(ns * 128 + nh * 64), "r"(0), "r"(ks * 16 + kh * 8) : "memory");
            }
        }
        if (g < 32) {
#pragma unroll 1
            for (int n = 0; n < NT * 4; n++) {
                const int slot = n & 3;
                mbar_wait(bar + 8 * (GB_EMPTY + slot), ((n >> 2) & 1) ^ 1);
                mbar_expect_tx(bar + 8 * (GB_FULL + slot), 16384);
                tma2d_mc(sb + slot_off(slot) + rk * 8192, &maps.xn2, (slot * 2 + rk) * 64, (n >> 2) * 64, bar + 8 * (GB_FULL + slot));
            }
        } else {
#pragma unroll 1
            for (int tile = 0; tile < NT; tile++) {
                wait_eq4(&g_f.o[tile][ks][0], epoch, 9);
                if (g == 40 && tile == NT - 1) GT(1437);
                if (tile == NT - 1) GT(1690 + g - 32);
#pragma unroll
                for (int k = 0; k < 4; k++) {
                    mbar_wait(bar + 8 * (GB_EMPTY + k), (tile & 1) ^ 1);
                    mbar_expect_tx(bar + 8 * (GB_FULL + k), 16384);
                    tma2d_mc(sb + slot_off(k) + rk * 8192, &maps.ox2, (ks * 8 + k * 2 + rk) * 64, tile * 64, bar + 8 * (GB_FULL + k));
                }
            }
        }
    } else if (warp < 3) {
        const int wg = warp - 1;
        const uint32_t buf = sb + G_BUF + wg * 32768;
        const CUtensorMap* tkv = (g & 1) ? &maps.vx3 : &maps.kx3;
        const int n1 = g < 32 ? HSPLIT / 2 : NT - HSPLIT / 2;
#pragma unroll 1
        for (int i = 0; i < n1; i++) {
            const int tile = (i < NT / 2 ? 2 * i : 2 * i - NT + HSPLIT) + wg, hd = (i < NT / 2 ? g : g - 32) >> 1;
            mbar_wait(bar + 8 * (GB_STG + wg), i & 1);
            tma_store3d(tkv, buf, tile * 64, hd * 2);
            asm volatile("cp.async.bulk.commit_group;" ::: "memory");
            asm volatile("cp.async.bulk.wait_group.read 0;" ::: "memory");
            mbar_arrive(bar + 8 * (GB_FREE + wg));
            asm volatile("cp.async.bulk.wait_group 0;" ::: "memory");
            PUBLISH(&g_f.kv[tile][hd][g & 1], epoch);
        }
        if (wg == 0) mbar_arrive(bar + 8 * GB_T1D);
        if (g < 32 && wg == 1) {
            mbar_wait(bar + 8 * GB_T1D, 0);
#pragma unroll 1
            for (int tile = 0; tile < NT; tile++) {
                wait_eq2(&g_f.kv[tile][g][0], epoch, 10);
                if (tile > 0) mbar_wait(bar + 8 * GB_KVF, (tile - 1) & 1);
                mbar_expect_tx(bar + 8 * (GB_KV + (tile & 1)), 16384);
                tma3d(sb + G_BUF, &maps.kx3, tile * 64, g * 2, bar + 8 * (GB_KV + (tile & 1)));
                if (tile > 0) mbar_wait(bar + 8 * GB_VF, (tile - 1) & 1);
                mbar_expect_tx(bar + 8 * (GB_VV + (tile & 1)), 16384);
                tma3d(sb + G_BUF + 32768, &maps.vx3, tile * 64, g * 2, bar + 8 * (GB_VV + (tile & 1)));
                if (PFK && tile + PFK < NT) {
                    const uint2 v = ldg_rlx2(&g_f.kv[tile + PFK][g][0]);
                    if (v.x == epoch && v.y == epoch) { tma_pf3d(&maps.kx3, (tile + PFK) * 64, g * 2); tma_pf3d(&maps.vx3, (tile + PFK) * 64, g * 2); }
                }
            }
        } else {
#pragma unroll 1
            for (int tile = g < 32 ? 0 : wg; tile < NT; tile += g < 32 ? 1 : 2) {
                mbar_wait(bar + 8 * (GB_STG + (tile & 1)), (tile >> 1) & 1);
                mbar_arrive(bar + 8 * (GB_FREE + (tile & 1)));
                PUBLISH(g < 32 ? &g_f.o[tile][g >> 2][g & 3] : &g_f.p[tile][g - 32], epoch);
                if (g == 3 && tile == NT - 1) GT(1436);
                if (g == 3) GT(1896 + tile);
                if (g < 32 && tile == NT - 1) GT(1610 + g);
                if (g == 40 && tile == NT - 1) GT(1435);
                if (g == 40) GT(1864 + tile);
                if (g >= 32 && tile == NT - 1) GT(1650 + g - 32);
            }
        }
    }
}

struct WPtr { const bf16 *q, *k, *v, *o; };
__device__ __forceinline__ int startup(uint8_t* smem, const bf16* __restrict__ x, const Maps& maps, uint32_t& epoch, const WPtr& pw) {
    const int tid = threadIdx.x, lane = tid & 31, w = tid >> 5, cta = blockIdx.x;
    volatile uint32_t* sh = (volatile uint32_t*)(smem + SH_OFF);
    if (cta == 4 && tid == 0) GT(1399);
    epoch = (ldg_rlx(&g_epoch) + 1) & 0x00ffffffu;
    if (w < 4) {
        if (!(cta & 1)) {
            uint32_t* pp = (uint32_t*)(xpage() + ((XR3 ^ 0x3000u) ^ ((w == 1 || w == 2) ? 0x1000u : 0u) ^ ((w & 2) << 13))) + (cta >> 1) * 8;
            if (lane < 8) stg_rlx(pp + lane, 0u);
            __syncwarp();
            if (lane == 0) {
                uint32_t best = 0xffffffffu, a = 0;
#pragma unroll 1
                for (int r = 0; r < NPROBE; r++) {
                    uint32_t t0 = clk32();
                    asm volatile("atom.relaxed.gpu.global.add.u32 %0, [%1], %2;" : "=r"(a) : "l"(pp), "r"(a + 1) : "memory");
                    if (a == 0x7fffffffu) ABORT(15);
                    uint32_t t1 = clk32();
                    if (r > 0) best = min(best, t1 - t0);
                    else if (w == 0) {
                        asm volatile("red.relaxed.gpu.global.max.u32 [%0], %1;" :: "l"(&g_ticket[0]), "r"(epoch << 8) : "memory");
                        asm volatile("red.relaxed.gpu.global.max.u32 [%0], %1;" :: "l"(&g_ticket[32]), "r"(epoch << 8) : "memory");
                    }
                }
                sh[w] = best;
            }
        }
        if (!(cta & 1)) bar_sync(1, 128);
        if (cta == 4 && tid == 0) GT(1400);
        if (w == 0) {
            if (lane == 0) {
                uint32_t rp;
                if (!(cta & 1)) {
                    uint32_t a = sh[0], b = sh[1], c = sh[2], d = sh[3];
                    uint32_t mid = (min(min(a, b), min(c, d)) + max(max(a, b), max(c, d))) >> 1;
                    const int dd = (int)min(a, d) - (int)min(b, c);
                    uint32_t cls = abs(dd) > 60 ? dd > 0 : a > mid;
                    uint32_t t = atomicAdd(&g_ticket[cls * 32], 1u) & 255;
                    if (t >= (cls ? 34u : 32u)) { cls ^= 1; t = atomicAdd(&g_ticket[cls * 32], 1u) & 255; }
                    rp = min(cls ? 32 + t : t, 65u);
                    stg_rlx(&g_table[(cta >> 1) * 8], (epoch << 8) | rp);
                } else {
                    uint32_t v, n = 0;
#pragma unroll 1
                    while (((v = ldg_rlx(&g_table[(cta >> 1) * 8])) >> 8) != epoch) { if (++n > SPIN_LIMIT) { ABORT(14); break; } }
                    rp = v & 255;
                }
                const int role = rp * 2 + (cta & 1);
                sh[8] = role; sh[9] = epoch;
                while (sh[10] != epoch + 1 && cta < NWAITLN) {}
                if (role < 64) rec_first_loads(smem_u32(smem), role, maps);
                else if (role < 128) load_w(smem_u32(smem), (role & 1) ? &maps.wv : &maps.wk, ((role - 64) >> 1) * 128, 0, 0, 1);
                if (cta == 4) GT(1401);
            }
        }
    } else if (cta < 128) {
        uint4 u[2][2];
        const int row0 = cta * 16 + (w - 4) * 2;
#pragma unroll
        for (int r = 0; r < 2; r++)
#pragma unroll
            for (int j = 0; j < 2; j++) u[r][j] = *(const uint4*)(x + (size_t)(row0 + r) * DM + j * 256 + lane * 8);
        if (cta < 48) {
            const uint32_t b = cta >> 3, off = (b >= 4 ? 0x8000u + (b & 1) * 0x4000u : ((b & 1) ? 0x3000u : 0u) + ((b & 2) << 13)) ^ aslot(cta & 7);
            *(uint4*)(xpage() + off + (tid - 128) * 16) = make_uint4(0, 0, 0, 0);
        }
        float v[2][16];
#pragma unroll
        for (int r = 0; r < 2; r++)
#pragma unroll
            for (int j = 0; j < 2; j++) {
                uint32_t ww[4] = {u[r][j].x, u[r][j].y, u[r][j].z, u[r][j].w};
#pragma unroll
                for (int i = 0; i < 4; i++) { v[r][j * 8 + 2 * i] = bf_lo(ww[i]); v[r][j * 8 + 2 * i + 1] = bf_hi(ww[i]); }
            }
        ln_row2(v[0], v[1]);
#pragma unroll
        for (int r = 0; r < 2; r++)
#pragma unroll
            for (int j = 0; j < 2; j++)
                *(uint4*)(g_xn + (size_t)(row0 + r) * DM + j * 256 + lane * 8) =
                    make_uint4(pack2(v[r][j * 8], v[r][j * 8 + 1]), pack2(v[r][j * 8 + 2], v[r][j * 8 + 3]), pack2(v[r][j * 8 + 4], v[r][j * 8 + 5]), pack2(v[r][j * 8 + 6], v[r][j * 8 + 7]));
        bar_sync(2, 256);
        if (tid == 160 && cta < NWAITLN) { st_rel(&g_f.xn[cta], epoch); sh[10] = epoch + 1; }
        if (cta == 4 && tid == 160) GT(1403);
        __syncwarp();
    }
    if (cta == 4 && tid == 128) GT(1402);
    __syncthreads();
    if (tid == 160 && cta >= NWAITLN && cta < 128) st_rel(&g_f.xn[cta], epoch);
    __syncwarp();
    const int role = sh[8];
    return role;
}

__global__ void __cluster_dims__(2, 1, 1) __launch_bounds__(384, 1)
main_kernel(const __grid_constant__ Maps maps, const bf16* __restrict__ x, const bf16* __restrict__ mem0, const bf16* __restrict__ wr,
            const bf16* __restrict__ wd, bf16* __restrict__ out, const WPtr pw) {
    extern __shared__ __align__(1024) uint8_t smem[];
    const uint32_t sb = smem_u32(smem);
    if (threadIdx.x == 0) {
        for (int i = 0; i < MB_N; i++) mbar_init(sb + R_BAR + 8 * i, i == MB_V ? 4 : 1);
        for (int i = 0; i < GB_N; i++)
            mbar_init(sb + G_BAR + 8 * i, i == GB_WFREE || (i >= GB_EMPTY && i < GB_KV) ? 8 : (i >= GB_KVF ? 4 : (i >= GB_STG && i < GB_FREE ? 128 : 1)));
        asm volatile("fence.mbarrier_init.release.cluster;" ::: "memory");
    }
    __syncwarp();
    asm volatile("barrier.cluster.arrive.relaxed.aligned;" ::: "memory");
    if (threadIdx.x >= 352 && threadIdx.x < 352 + (int)(sizeof(Maps) / sizeof(CUtensorMap)))
        asm volatile("prefetch.tensormap [%0];" :: "l"((const CUtensorMap*)&maps + (threadIdx.x - 352)) : "memory");
    uint32_t epoch;
    asm volatile("fence.proxy.async.shared::cta;" ::: "memory");
    const int role = uni(startup(smem, x, maps, epoch, pw));
    asm volatile("barrier.cluster.wait.aligned;" ::: "memory");
    const int wg = uni(threadIdx.x >> 7);
    if (role < 64) {
#define SETREG(n) do { if ((n) < 168) asm volatile("setmaxnreg.dec.sync.aligned.u32 %0;" :: "n"(n)); if ((n) > 168) asm volatile("setmaxnreg.inc.sync.aligned.u32 %0;" :: "n"(n)); } while (0)
#define RESREG(n) do { if ((n) < 168) asm volatile("setmaxnreg.inc.sync.aligned.u32 168;"); if ((n) > 168) asm volatile("setmaxnreg.dec.sync.aligned.u32 168;"); } while (0)
        if (wg == 0) {
            SETREG(RGA);
            rec_a(sb, role, mem0, epoch);
            RESREG(RGA);
        } else if (wg == 1) {
            SETREG(RGB);
            rec_b(sb, role, epoch);
            RESREG(RGB);
        } else {
            SETREG(RGC);
            rec_c(sb, role, mem0, maps, epoch);
            RESREG(RGC);
        }
        ffn_phase(maps, wd, out);
        if (threadIdx.x == 0) GT(((volatile int*)(smem + SH_OFF))[8] * 8 + 6);
    } else if (role < 128) {
        if (wg < 2) {
            asm volatile("setmaxnreg.inc.sync.aligned.u32 192;");
            g_consumer(sb, role - 64, wg, epoch);
            if (threadIdx.x == 128) GT(role * 8 + 6);
        } else {
            asm volatile("setmaxnreg.dec.sync.aligned.u32 120;");
            g_producer(sb, role - 64, maps, epoch, x, wr, out);
        }
    } else {
        finalizer(64 + (threadIdx.x >> 5) * 4 + role - 128, x, wr, out, epoch);
    }
}

typedef CUresult (*EncodeFn)(CUtensorMap*, CUtensorMapDataType, cuuint32_t, void*, const cuuint64_t*, const cuuint64_t*, const cuuint32_t*, const cuuint32_t*,
                             CUtensorMapInterleave, CUtensorMapSwizzle, CUtensorMapL2promotion, CUtensorMapFloatOOBfill);
static void make_map3(EncodeFn fn, CUtensorMap* m, const void* ptr, uint64_t cols, uint64_t rows) {
    cuuint64_t dims[3] = {64, rows, cols / 64};
    cuuint64_t strides[2] = {cols * 2, 128};
    cuuint32_t box[3] = {64, 64, 2};
    cuuint32_t es[3] = {1, 1, 1};
    fn(m, CU_TENSOR_MAP_DATA_TYPE_BFLOAT16, 3, (void*)ptr, dims, strides, box, es, CU_TENSOR_MAP_INTERLEAVE_NONE, CU_TENSOR_MAP_SWIZZLE_128B,
       CU_TENSOR_MAP_L2_PROMOTION_L2_256B, CU_TENSOR_MAP_FLOAT_OOB_FILL_NONE);
}
static void make_map(EncodeFn fn, CUtensorMap* m, const void* ptr, uint64_t cols, uint64_t rows, uint32_t bcols, uint32_t brows,
                     bool f32 = false, CUtensorMapSwizzle sw = CU_TENSOR_MAP_SWIZZLE_128B) {
    cuuint64_t dims[2] = {cols, rows};
    cuuint64_t strides[1] = {cols * (f32 ? 4 : 2)};
    cuuint32_t box[2] = {bcols, brows};
    cuuint32_t es[2] = {1, 1};
    fn(m, f32 ? CU_TENSOR_MAP_DATA_TYPE_FLOAT32 : CU_TENSOR_MAP_DATA_TYPE_BFLOAT16, 2, (void*)ptr, dims, strides, box, es, CU_TENSOR_MAP_INTERLEAVE_NONE, sw,
       CU_TENSOR_MAP_L2_PROMOTION_L2_256B, CU_TENSOR_MAP_FLOAT_OOB_FILL_NONE);
}

extern "C" void kernel_launch(void* const* d_in, const int* in_sizes, int n_in, void* d_out, int out_size) {
    const bf16* x = (const bf16*)d_in[0];
    const bf16* mem0 = (const bf16*)d_in[1];
    const bf16* Wq = (const bf16*)d_in[2];
    const bf16* Wk = (const bf16*)d_in[3];
    const bf16* Wv = (const bf16*)d_in[4];
    const bf16* Wo = (const bf16*)d_in[5];
    const bf16* wr = (const bf16*)d_in[8];
    const bf16* wg = (const bf16*)d_in[9];
    const bf16* wu = (const bf16*)d_in[10];
    const bf16* wd = (const bf16*)d_in[11];
    bf16* out = (bf16*)d_out;

    static EncodeFn enc = nullptr;
    static void *pxn, *pK, *pV, *pO, *pacc;
    if (!enc) {
        cudaDriverEntryPointQueryResult qr;
        void* fn = nullptr;
        cudaGetDriverEntryPoint("cuTensorMapEncodeTiled", &fn, cudaEnableDefault, &qr);
        enc = (EncodeFn)fn;
        cudaGetSymbolAddress(&pxn, g_xn); cudaGetSymbolAddress(&pK, g_K); cudaGetSymbolAddress(&pV, g_V);
        cudaGetSymbolAddress(&pO, g_O); cudaGetSymbolAddress(&pacc, g_P);
        cudaFuncSetAttribute(main_kernel, cudaFuncAttributeMaxDynamicSharedMemorySize, SMEM_TOTAL);
    }
    Maps m;
    make_map(enc, &m.wq, Wq, HD, DM, 64, 256);
    make_map(enc, &m.wk, Wk, HD, DM, 64, 256);
    make_map(enc, &m.wv, Wv, HD, DM, 64, 256);
    make_map(enc, &m.wo, Wo, DM, HD, 64, 128);
    {
        cuuint64_t dims[5] = {DM, 2, 4, 4, HD / 32};
        cuuint64_t strides[4] = {DM * 2, 8 * DM * 2, 2 * DM * 2, 32 * DM * 2};
        cuuint32_t box[5] = {64, 2, 4, 4, 8};
        cuuint32_t es[5] = {1, 1, 1, 1, 1};
        enc(&m.wo2, CU_TENSOR_MAP_DATA_TYPE_BFLOAT16, 5, (void*)Wo, dims, strides, box, es, CU_TENSOR_MAP_INTERLEAVE_NONE, CU_TENSOR_MAP_SWIZZLE_128B,
            CU_TENSOR_MAP_L2_PROMOTION_L2_256B, CU_TENSOR_MAP_FLOAT_OOB_FILL_NONE);
    }
    make_map(enc, &m.kx, pK, HD, SQ, 64, 64);
    make_map(enc, &m.ox2, pO, HD, SQ, 64, 64);
    make_map(enc, &m.xn2, pxn, DM, SQ, 64, 64);
    make_map3(enc, &m.kx3, pK, HD, SQ); make_map3(enc, &m.vx3, pV, HD, SQ);
    make_map(enc, &m.wg, wg, FF, DM, 32, 256, false, CU_TENSOR_MAP_SWIZZLE_NONE);
    make_map(enc, &m.wu, wu, FF, DM, 32, 256, false, CU_TENSOR_MAP_SWIZZLE_NONE);

    cudaStream_t st = cudaStreamPerThread;
    main_kernel<<<NCTA, 384, SMEM_TOTAL, st>>>(m, x, mem0, wr, wd, out, WPtr{Wq, Wk, Wv, Wo});
}
```

```cpp
#include <cuda_runtime.h>
#include <cuda_bf16.h>
#include <cuda.h>
#include <stdint.h>
#include <stddef.h>

typedef __nv_bfloat16 bf16;

constexpr int SQ = 2048, DM = 512, NH = 32, DH = 128, NSEG = 64, HD = 4096, FF = 1792;

constexpr int NT = 32;
#define SPEC_TILES 30
__device__ __align__(1024) bf16 g_xn[SQ * DM];
__device__ __align__(1024) bf16 g_K[SQ * HD];
__device__ __align__(1024) bf16 g_V[SQ * HD];
__device__ __align__(1024) bf16 g_O[SQ * HD];
__device__ __align__(1024) uint32_t g_KVf[NSEG][NH][1024];
__device__ __align__(1024) bf16 g_P[8 * SQ * DM];
__device__ __align__(1024) bf16 g_h[SQ * DM];
__device__ __align__(1024) bf16 g_hn[SQ * DM];
__device__ uint8_t g_xraw[12 << 20];
#define XPG 0
__device__ __forceinline__ uint64_t xpage() { return (((uint64_t)g_xraw + (2 << 20) - 1) & ~(uint64_t)((2 << 20) - 1)) + ((uint64_t)XPG << 21); }
constexpr uint32_t XR3 = (1u << 20) | (1u << 19) | (1u << 12);
__device__ __forceinline__ uint32_t aslot(uint32_t s) { return ((s & 1) << 18) | ((s & 2) << 19) | ((s & 4) * 0xc000u); }
#define IL 1
constexpr int AC1 = IL ? 48 : 256;
__device__ __forceinline__ uint32_t acc_off(uint32_t W, uint32_t lane) {
    return ((W & 2) ? 0x3000u : 0u) + ((W & 4) << 12) + (W & 1) * 2048 + (IL ? (lane >> 2) * 256 : (lane >> 2) * 128 + (lane & 4) * 16) + (lane & 3) * 16;
}
#define XM 4
__device__ __forceinline__ uint32_t ext_base(uint32_t W) { return 0x8000u + ((W & 4) << 12) + (W & 3) * 1024; }
__device__ __forceinline__ uint32_t ext_lane(uint32_t lane) { return XM == 1 ? (lane >> 3) * 256 + (lane & 7) * 4 : (XM == 2 ? (lane >> 4) * 512 + (lane & 15) * 4 : lane * 4); }
__device__ __forceinline__ uint32_t zero_off(uint32_t c, uint32_t ln) {
    return ln < 16 ? ((c & 16) ? 0x3000u : 0u) + ((c & 32) << 9) + (c & 15) * 256 + ln * 16 : ext_base(c >> 3) + ext_lane((c & 7) * 4);
}
struct Flags {
    uint32_t kv[NT][NH][2];
    uint32_t o[NT][8][32];
    uint32_t rec[64];
    uint32_t xn[128];
    uint32_t rload[64];
    uint32_t p[NT][32];
    uint32_t rows[2][128];
    uint4 cand[2][128];
    uint4 norm[64];
};
__device__ __align__(1024) Flags g_f;
__device__ __align__(1024) uint4 g_yp[2][FF / 32][DM];
__device__ __align__(1024) uint32_t g_table[66 * 8];
__device__ __align__(256) uint32_t g_ticket[64];
__device__ uint32_t g_epoch;
#define HOLD 6
#define HSPLIT 24
#define EREL 0
#define PFK 2
#define PFO 0
#define PFS 0
#define NWAITLN 8
#define WGA 0
#define WGB 1
#define WGC (3 - WGA - WGB)
#define NPROBE 3
constexpr int NCTA = 132;
constexpr int NFW = 112;
__device__ uint32_t g_abort;
__device__ long long g_dbg[4096];
#define TR(slot, v)

__device__ __forceinline__ uint32_t smem_u32(const void* p) { return (uint32_t)__cvta_generic_to_shared(p); }
__device__ __forceinline__ void mbar_init(uint32_t a, uint32_t c) { asm volatile("mbarrier.init.shared::cta.b64 [%0], %1;" :: "r"(a), "r"(c) : "memory"); }
__device__ __forceinline__ void mbar_expect_tx(uint32_t a, uint32_t tx) { asm volatile("mbarrier.arrive.expect_tx.shared::cta.b64 _, [%0], %1;" :: "r"(a), "r"(tx) : "memory"); }
__device__ __forceinline__ void mbar_arrive(uint32_t a) { asm volatile("mbarrier.arrive.shared::cta.b64 _, [%0];" :: "r"(a) : "memory"); }
__device__ __forceinline__ void mbar_arrive_if(uint32_t a, uint32_t pred) {
    asm volatile("{\n.reg .pred p;\nsetp.ne.u32 p, %1, 0;\n@p mbarrier.arrive.shared::cta.b64 _, [%0];\n}" :: "r"(a), "r"(pred) : "memory");
}
__device__ __forceinline__ bool mbar_try(uint32_t a, uint32_t ph) {
    uint32_t ok;
    asm volatile("{\n.reg .pred p;\nmbarrier.try_wait.parity.shared::cta.b64 p, [%1], %2;\nselp.u32 %0, 1, 0, p;\n}" : "=r"(ok) : "r"(a), "r"(ph) : "memory");
    return ok != 0;
}
#define SPINLOG 20
constexpr uint32_t SPIN_LIMIT = 1u << SPINLOG;
#define ABORT(code_) atomicCAS(&g_abort, 0u, (code_))
__device__ __forceinline__ void mbar_wait(uint32_t a, uint32_t ph) {
    uint32_t n = 0;
#pragma unroll 1
    while (!mbar_try(a, ph)) { if (++n > SPIN_LIMIT) { ABORT(1); break; } }
}
__device__ __forceinline__ void bar_sync(int id, int n) { asm volatile("bar.sync %0, %1;" :: "r"(id), "r"(n) : "memory"); }
__device__ __forceinline__ void bar_arrive(int id, int n) { asm volatile("bar.arrive %0, %1;" :: "r"(id), "r"(n) : "memory"); }

__device__ __forceinline__ void ldsm4(uint32_t* r, uint32_t a) {
    asm volatile("ldmatrix.sync.aligned.m8n8.x4.shared.b16 {%0,%1,%2,%3}, [%4];" : "=r"(r[0]), "=r"(r[1]), "=r"(r[2]), "=r"(r[3]) : "r"(a) : "memory");
}
__device__ __forceinline__ void ldsm4t(uint32_t* r, uint32_t a) {
    asm volatile("ldmatrix.sync.aligned.m8n8.x4.trans.shared.b16 {%0,%1,%2,%3}, [%4];" : "=r"(r[0]), "=r"(r[1]), "=r"(r[2]), "=r"(r[3]) : "r"(a) : "memory");
}
__device__ __forceinline__ void stsm4t(uint32_t a, uint32_t r0, uint32_t r1, uint32_t r2, uint32_t r3) {
    asm volatile("stmatrix.sync.aligned.m8n8.x4.trans.shared.b16 [%0], {%1,%2,%3,%4};" :: "r"(a), "r"(r0), "r"(r1), "r"(r2), "r"(r3) : "memory");
}
__device__ __forceinline__ void stsm4(uint32_t a, uint32_t r0, uint32_t r1, uint32_t r2, uint32_t r3) {
    asm volatile("stmatrix.sync.aligned.m8n8.x4.shared.b16 [%0], {%1,%2,%3,%4};" :: "r"(a), "r"(r0), "r"(r1), "r"(r2), "r"(r3) : "memory");
}
__device__ __forceinline__ uint32_t movm(uint32_t a) { uint32_t d; asm volatile("movmatrix.sync.aligned.m8n8.trans.b16 %0, %1;" : "=r"(d) : "r"(a)); return d; }
__device__ __forceinline__ void mma16816(float* d, uint32_t a0, uint32_t a1, uint32_t a2, uint32_t a3, uint32_t b0, uint32_t b1) {
    asm volatile("mma.sync.aligned.m16n8k16.row.col.f32.bf16.bf16.f32 {%0,%1,%2,%3}, {%4,%5,%6,%7}, {%8,%9}, {%0,%1,%2,%3};"
        : "+f"(d[0]), "+f"(d[1]), "+f"(d[2]), "+f"(d[3]) : "r"(a0), "r"(a1), "r"(a2), "r"(a3), "r"(b0), "r"(b1));
}
__device__ __forceinline__ void mma1688(float* d, uint32_t a0, uint32_t a1, uint32_t b0) {
    asm volatile("mma.sync.aligned.m16n8k8.row.col.f32.bf16.bf16.f32 {%0,%1,%2,%3}, {%4,%5}, {%6}, {%0,%1,%2,%3};"
        : "+f"(d[0]), "+f"(d[1]), "+f"(d[2]), "+f"(d[3]) : "r"(a0), "r"(a1), "r"(b0));
}
__device__ __forceinline__ uint32_t pack2(float a, float b) { uint32_t d; asm("cvt.rn.bf16x2.f32 %0, %1, %2;" : "=r"(d) : "f"(b), "f"(a)); return d; }
__device__ __forceinline__ float bf_lo(uint32_t w) { return __uint_as_float(w << 16); }
__device__ __forceinline__ float bf_hi(uint32_t w) { return __uint_as_float(w & 0xffff0000u); }
__device__ __forceinline__ float rbf(float x) { return __bfloat162float(__float2bfloat16_rn(x)); }

__device__ __forceinline__ void sts128(uint32_t a, float x, float y, float z, float w) { asm volatile("st.shared.v4.f32 [%0], {%1,%2,%3,%4};" :: "r"(a), "f"(x), "f"(y), "f"(z), "f"(w) : "memory"); }
__device__ __forceinline__ void sts128u(uint32_t a, uint32_t x, uint32_t y, uint32_t z, uint32_t w) { asm volatile("st.shared.v4.b32 [%0], {%1,%2,%3,%4};" :: "r"(a), "r"(x), "r"(y), "r"(z), "r"(w) : "memory"); }
__device__ __forceinline__ void sts64(uint32_t a, float x, float y) { asm volatile("st.shared.v2.f32 [%0], {%1,%2};" :: "r"(a), "f"(x), "f"(y) : "memory"); }
__device__ __forceinline__ float4 lds128(uint32_t a) { float4 v; asm volatile("ld.shared.v4.f32 {%0,%1,%2,%3}, [%4];" : "=f"(v.x), "=f"(v.y), "=f"(v.z), "=f"(v.w) : "r"(a) : "memory"); return v; }
__device__ __forceinline__ float2 lds64(uint32_t a) { float2 v; asm volatile("ld.shared.v2.f32 {%0,%1}, [%2];" : "=f"(v.x), "=f"(v.y) : "r"(a) : "memory"); return v; }
__device__ __forceinline__ uint2 lds64u(uint32_t a) { uint2 v; asm volatile("ld.shared.v2.b32 {%0,%1}, [%2];" : "=r"(v.x), "=r"(v.y) : "r"(a) : "memory"); return v; }
__device__ __forceinline__ float4 lds128v(uint32_t a) { float4 v; asm volatile("ld.volatile.shared.v4.f32 {%0,%1,%2,%3}, [%4];" : "=f"(v.x), "=f"(v.y), "=f"(v.z), "=f"(v.w) : "r"(a) : "memory"); return v; }
__device__ __forceinline__ float2 lds64v(uint32_t a) { float2 v; asm volatile("ld.volatile.shared.v2.f32 {%0,%1}, [%2];" : "=f"(v.x), "=f"(v.y) : "r"(a) : "memory"); return v; }
__device__ __forceinline__ uint4 lds128uv(uint32_t a) { uint4 v; asm volatile("ld.volatile.shared.v4.b32 {%0,%1,%2,%3}, [%4];" : "=r"(v.x), "=r"(v.y), "=r"(v.z), "=r"(v.w) : "r"(a) : "memory"); return v; }
__device__ __forceinline__ void st_async4(uint32_t a, float x, float y, float z, float w, uint32_t mb) {
    asm volatile("st.async.weak.shared::cluster.mbarrier::complete_tx::bytes.v4.f32 [%0], {%1,%2,%3,%4}, [%5];" :: "r"(a), "f"(x), "f"(y), "f"(z), "f"(w), "r"(mb) : "memory");
}
__device__ __forceinline__ void st_async2(uint32_t a, uint32_t x, uint32_t y, uint32_t mb) {
    asm volatile("st.async.weak.shared::cluster.mbarrier::complete_tx::bytes.v2.b32 [%0], {%1,%2}, [%3];" :: "r"(a), "r"(x), "r"(y), "r"(mb) : "memory");
}
__device__ __forceinline__ uint32_t ldg_rlx(const uint32_t* p) { uint32_t v; asm volatile("ld.relaxed.gpu.global.b32 %0, [%1];" : "=r"(v) : "l"(p) : "memory"); return v; }
__device__ __forceinline__ uint4 ldg_rlx4(const uint32_t* p) { uint4 v; asm volatile("ld.relaxed.gpu.global.v4.b32 {%0,%1,%2,%3}, [%4];" : "=r"(v.x), "=r"(v.y), "=r"(v.z), "=r"(v.w) : "l"(p) : "memory"); return v; }
__device__ __forceinline__ uint4 ldg_rlx4_if(const uint32_t* p, bool c) {
    uint4 v;
    asm volatile("{\n.reg .pred p;\nsetp.ne.u32 p, %5, 0;\nmov.b32 %0, 0;\nmov.b32 %1, 0;\nmov.b32 %2, 0;\nmov.b32 %3, 0;\n@p ld.relaxed.gpu.global.v4.b32 {%0,%1,%2,%3}, [%4];\n}"
                 : "=r"(v.x), "=r"(v.y), "=r"(v.z), "=r"(v.w) : "l"(p), "r"((uint32_t)c) : "memory");
    return v;
}
__device__ __forceinline__ void stg_rlx(uint32_t* p, uint32_t v) { asm volatile("st.relaxed.gpu.global.b32 [%0], %1;" :: "l"(p), "r"(v) : "memory"); }
__device__ __forceinline__ void tma2d(uint32_t dst, const CUtensorMap* tm, int c0, int c1, uint32_t mb) {
    asm volatile("cp.async.bulk.tensor.2d.shared::cluster.global.mbarrier::complete_tx::bytes [%0], [%1, {%3, %4}], [%2];"
        :: "r"(dst), "l"((uint64_t)tm), "r"(mb), "r"(c0), "r"(c1) : "memory");
}

__device__ __forceinline__ void tma3d(uint32_t dst, const CUtensorMap* tm, int row, int chunk, uint32_t mb) {
    asm volatile("cp.async.bulk.tensor.3d.shared::cluster.global.mbarrier::complete_tx::bytes [%0], [%1, {%3, %4, %5}], [%2];"
        :: "r"(dst), "l"((uint64_t)tm), "r"(mb), "r"(0), "r"(row), "r"(chunk) : "memory");
}
__device__ __forceinline__ void tma2d_mc(uint32_t dst, const CUtensorMap* tm, int c0, int c1, uint32_t mb) {
    asm volatile("cp.async.bulk.tensor.2d.shared::cluster.global.mbarrier::complete_tx::bytes.multicast::cluster [%0], [%1, {%3, %4}], [%2], %5;"
        :: "r"(dst), "l"((uint64_t)tm), "r"(mb), "r"(c0), "r"(c1), "h"((uint16_t)3) : "memory");
}
__device__ __forceinline__ void mbar_arrive2_if(uint32_t a, uint32_t pred) {
    asm volatile("{\n.reg .pred p;\nsetp.ne.u32 p, %1, 0;\n@p mbarrier.arrive.shared::cta.b64 _, [%0];\n@p mbarrier.arrive.shared::cluster.b64 _, [%2];\n}"
                 :: "r"(a), "r"(pred), "r"(a ^ 0x01000000u) : "memory");
}
__device__ __forceinline__ void tma_pf3d(const CUtensorMap* tm, int row, int chunk) {
    asm volatile("cp.async.bulk.prefetch.tensor.3d.L2.global.tile [%0, {%1, %2, %3}];" :: "l"((uint64_t)tm), "r"(0), "r"(row), "r"(chunk) : "memory");
}
__device__ __forceinline__ void tma_pf2d(const CUtensorMap* tm, int c0, int c1) {
    asm volatile("cp.async.bulk.prefetch.tensor.2d.L2.global.tile [%0, {%1, %2}];" :: "l"((uint64_t)tm), "r"(c0), "r"(c1) : "memory");
}
__device__ __forceinline__ void tma_store3d(const CUtensorMap* tm, uint32_t src, int row, int chunk) {
    asm volatile("cp.async.bulk.tensor.3d.global.shared::cta.bulk_group [%0, {%2, %3, %4}], [%1];" :: "l"((uint64_t)tm), "r"(src), "r"(0), "r"(row), "r"(chunk) : "memory");
}
__device__ __forceinline__ void bulk_store(void* dst, uint32_t src, uint32_t bytes) {
    asm volatile("cp.async.bulk.global.shared::cta.bulk_group [%0], [%1], %2;" :: "l"(dst), "r"(src), "r"(bytes) : "memory");
}
#define GT(slot)
#define CNT(k)
#define CNT2(k, c)
#define TS(i, dep)
#define TSACC()
#define TSDECL
struct Maps { CUtensorMap wq, wk, wv, wo, wo2, kx, ox2, kx3, vx3, xn2, wg, wu; };
typedef Maps RecMaps;
__device__ __forceinline__ void st_rel(uint32_t* p, uint32_t v) { asm volatile("st.release.gpu.global.u32 [%0], %1;" :: "l"(p), "r"(v) : "memory"); }
#define PUBLISH(p, v) st_rel(p, v)
__device__ __forceinline__ uint2 ldg_rlx2(const uint32_t* p) { uint2 v; asm volatile("ld.relaxed.gpu.global.v2.b32 {%0,%1}, [%2];" : "=r"(v.x), "=r"(v.y) : "l"(p) : "memory"); return v; }
__device__ __forceinline__ void wait_eq2(const uint32_t* p, uint32_t e, int code) {
    uint32_t n = 0;
#pragma unroll 1
    while (true) { uint2 v = ldg_rlx2(p); if (v.x == e && v.y == e) break; __nanosleep(64); if (++n > SPIN_LIMIT) { ABORT(code); break; } }
}
__device__ __forceinline__ void wait_eq4(const uint32_t* p, uint32_t e, int code) {
    uint32_t n = 0;
#pragma unroll 1
    while (true) { uint4 v = ldg_rlx4(p); if (v.x == e && v.y == e && v.z == e && v.w == e) break; __nanosleep(64); if (++n > SPIN_LIMIT) { ABORT(code); break; } }
}
__device__ __forceinline__ void wait_rec(const uint32_t* p, uint32_t e, uint32_t steps) {
    uint32_t n = 0;
#pragma unroll 1
    while (true) {
        uint2 v = ldg_rlx2(p);
        if (__all_sync(0xffffffffu, (v.x >> 8) == e && (v.y >> 8) == e && (v.x & 255) >= steps && (v.y & 255) >= steps)) break;
        __nanosleep(64); if (++n > SPIN_LIMIT) { ABORT(8); break; }
    }
}

constexpr int R_QK1 = 0;
constexpr int R_WO = 65536;
constexpr int R_T = 131072;
constexpr int R_SLOT1 = R_T;
constexpr int R_MEMB = R_T + 24576;
constexpr int R_QP = R_MEMB + 8192;
constexpr int R_VRED = R_QP + 4096;
constexpr int R_STG = R_VRED + 2048;
constexpr int R_AX = R_STG + 2048;
constexpr int R_SLOT0 = 196608;
constexpr int R_SLOC = R_SLOT0 + 24576;
constexpr int R_SREM = R_SLOC + 1536;
constexpr int R_VB = R_SREM + 1536;
constexpr int R_MISC = R_VB + 2048;
constexpr int R_LT = R_MISC + 128;
constexpr int R_BAR = 229888;
constexpr int R_TS = 229888 + 128;
static_assert(R_AX + 24576 <= R_SLOT0 && R_LT + 2560 <= 229376, "smem map");
enum { MB_W0 = 0, MB_W1, MB_WV, MB_WO, MB_S, MB_FULL0, MB_FULL1, MB_V, MB_N };

__device__ __forceinline__ float ex2(float x) { float y; asm("ex2.approx.ftz.f32 %0, %1;" : "=f"(y) : "f"(x)); return y; }
__device__ __forceinline__ float rcpf(float x) { float y; asm("rcp.approx.ftz.f32 %0, %1;" : "=f"(y) : "f"(x)); return y; }
__device__ __forceinline__ void mma16816z(float* d, uint32_t a0, uint32_t a1, uint32_t a2, uint32_t a3, uint32_t b0, uint32_t b1) {
    asm volatile("mma.sync.aligned.m16n8k16.row.col.f32.bf16.bf16.f32 {%0,%1,%2,%3}, {%4,%5,%6,%7}, {%8,%9}, {%10,%10,%10,%10};"
        : "=f"(d[0]), "=f"(d[1]), "=f"(d[2]), "=f"(d[3]) : "r"(a0), "r"(a1), "r"(a2), "r"(a3), "r"(b0), "r"(b1), "f"(0.f));
}
__device__ __forceinline__ void mma1688hz(float* d, uint32_t a0, uint32_t a1, uint32_t b0) {
    asm volatile("mma.sync.aligned.m16n8k8.row.col.f32.f16.f16.f32 {%0,%1,%2,%3}, {%4,%5}, {%6}, {%7,%7,%7,%7};"
        : "=f"(d[0]), "=f"(d[1]), "=f"(d[2]), "=f"(d[3]) : "r"(a0), "r"(a1), "r"(b0), "f"(0.f));
}
#define MMA(d, a, b0, b1) mma16816(d, a[0], a[1], a[2], a[3], b0, b1)
#define MMAZ(d, a, b0, b1) mma16816z(d, a[0], a[1], a[2], a[3], b0, b1)
#define MMAF(first, d, a, b0, b1) do { if (first) MMAZ(d, a, b0, b1); else MMA(d, a, b0, b1); } while (0)

__device__ __forceinline__ uint32_t uni(uint32_t x) { return __reduce_max_sync(0xffffffffu, x); }
__device__ __forceinline__ void mbar_wait_u(uint32_t a, uint32_t ph) {
    uint32_t n = 0;
#pragma unroll 1
    while (!__all_sync(0xffffffffu, mbar_try(a, ph))) { if (++n > SPIN_LIMIT) { ABORT(1); break; } }
}
__device__ __forceinline__ void mbar_wait_p(uint32_t a, uint32_t ph) {
    asm volatile("{\n.reg .pred p, q;\n.reg .u32 n;\nmov.u32 n, 0;\nWL: mbarrier.try_wait.parity.shared::cta.b64 p, [%0], %1;\nadd.u32 n, n, 1;\n"
                 "setp.lt.and.u32 q, n, %2, !p;\n@q bra.uni WL;\n}" :: "r"(a), "r"(ph), "n"(SPIN_LIMIT) : "memory");
}
__device__ __forceinline__ uint32_t mbar_test(uint32_t a, uint32_t ph) {
    uint32_t ok;
    asm volatile("{\n.reg .pred p;\nmbarrier.test_wait.parity.shared::cta.b64 p, [%1], %2;\nselp.u32 %0, 1, 0, p;\n}" : "=r"(ok) : "r"(a), "r"(ph) : "memory");
    return ok;
}
__device__ __forceinline__ uint32_t opaque(uint32_t x) { return __shfl_sync(0xffffffffu, x, threadIdx.x & 31); }
__device__ __forceinline__ const uint32_t* mkptr(uint32_t lo, uint32_t hi) { uint64_t r; asm("mov.b64 %0, {%1, %2};" : "=l"(r) : "r"(lo), "r"(hi)); return (const uint32_t*)r; }
__device__ __forceinline__ uint32_t prmt(uint32_t a, uint32_t b, uint32_t s) { uint32_t d; asm("prmt.b32 %0, %1, %2, %3;" : "=r"(d) : "r"(a), "r"(b), "r"(s)); return d; }
__device__ __forceinline__ uint32_t packh2(float a, float b) { uint32_t d; asm("cvt.rn.f16x2.f32 %0, %1, %2;" : "=r"(d) : "f"(b), "f"(a)); return d; }
__device__ __forceinline__ uint32_t hadd2b(uint32_t a, uint32_t b) { uint32_t d; asm("add.rn.bf16x2 %0, %1, %2;" : "=r"(d) : "r"(a), "r"(b)); return d; }
__device__ __forceinline__ uint32_t hmul2b(uint32_t a, uint32_t b) { uint32_t d; asm("mul.rn.bf16x2 %0, %1, %2;" : "=r"(d) : "r"(a), "r"(b)); return d; }
__device__ __forceinline__ uint32_t amax2b(uint32_t a, uint32_t b) { uint32_t d; asm("max.xorsign.abs.bf16x2 %0, %1, %2;" : "=r"(d) : "r"(a), "r"(b)); return d; }
__device__ __forceinline__ uint32_t amax2h(uint32_t a, uint32_t b) { uint32_t d; asm("max.xorsign.abs.f16x2 %0, %1, %2;" : "=r"(d) : "r"(a), "r"(b)); return d; }
__device__ __forceinline__ void sts32(uint32_t a, uint32_t x) { asm volatile("st.shared.b32 [%0], %1;" :: "r"(a), "r"(x) : "memory"); }
__device__ __forceinline__ uint32_t lds32v_(uint32_t a) { uint32_t v; asm volatile("ld.volatile.shared.b32 %0, [%1];" : "=r"(v) : "r"(a) : "memory"); return v; }
__device__ __forceinline__ void stg4(void* p, uint4 v) { asm volatile("st.relaxed.gpu.global.v4.b32 [%0], {%1,%2,%3,%4};" :: "l"(p), "r"(v.x), "r"(v.y), "r"(v.z), "r"(v.w) : "memory"); }
__device__ __forceinline__ void lds_frag(uint32_t* r, uint32_t a) {
    asm volatile("ld.shared.v4.b32 {%0,%1,%2,%3}, [%4];" : "=r"(r[0]), "=r"(r[1]), "=r"(r[2]), "=r"(r[3]) : "r"(a) : "memory");
}
__device__ __forceinline__ void lds_fragv(uint32_t* r, uint32_t a) {
    asm volatile("ld.volatile.shared.v4.b32 {%0,%1,%2,%3}, [%4];" : "=r"(r[0]), "=r"(r[1]), "=r"(r[2]), "=r"(r[3]) : "r"(a) : "memory");
}
__device__ __forceinline__ uint32_t xorv(uint32_t a, uint32_t b) { uint32_t d; asm volatile("xor.b32 %0, %1, %2;" : "=r"(d) : "r"(a), "r"(b)); return d; }
#define SCHED(k) asm volatile("{\n.reg .pred p;\nsetp.ne.u32 p, %0, %1;\n@p bra.uni SD;\nSL: nanosleep.u32 64;\nbra.uni SL;\nSD:\n}" :: "r"(sbu - s), "n"(k) : "memory")
#define PINM() asm volatile("{\n.reg .pred p;\nsetp.eq.u32 p, %0, 1;\n@p st.shared.u32 [%0], %0;\n}" :: "r"(sbu) : "memory")
__device__ __forceinline__ uint32_t or_and(uint32_t a, uint32_t b, uint32_t c) { uint32_t d; asm("lop3.b32 %0, %1, %2, %3, 0xF8;" : "=r"(d) : "r"(a), "r"(b), "r"(c)); return d; }
__device__ __forceinline__ uint32_t pack2v(float a, float b) { uint32_t d; asm volatile("cvt.rn.bf16x2.f32 %0, %1, %2;" : "=r"(d) : "f"(b), "f"(a)); return d; }
#define FU(x) __float_as_uint(x)
__device__ __forceinline__ uint32_t clk32() { uint32_t t; asm volatile("mov.u32 %0, %%clock;" : "=r"(t) :: "memory"); return t; }
__device__ __forceinline__ void spin_until(uint32_t t0, uint32_t d) {
    if (d) {
#pragma unroll 1
        while (__any_sync(0xffffffffu, clk32() - t0 < d)) {}
    }
}
constexpr int SH_OFF = 229376 + 384;
constexpr uint32_t HONE2 = 0x3c003c00u, HCNT2 = 0x50005000u;

__device__ __forceinline__ uint64_t desc_sw128(uint32_t addr, uint32_t lbo, uint32_t sbo) {
    return (uint64_t)((addr & 0x3FFFF) >> 4) | ((uint64_t)(lbo >> 4) << 16) | ((uint64_t)(sbo >> 4) << 32) | (1ull << 62);
}
#define DP 440
#define NAX 4
#define NXL 0
#define NCX 2
#define NCL 1
#define DC 100
#define DEC 1
#define FLIP 1
#define KXB 4
#define KXI 5
#define ANB 3
#define BNB 3
#define CNB 3
#define SMA 0
#define SMB 0
#define SMC 0x01
#define IVA 0
#define RGA 160
#define RGC 160
#define RGB (504 - RGA - RGC)
#define NRW 8
#define NBR 16
#define E0 0
#define E1 6
#define E2 4
#define E3 10
#define IV 2
#define DEX 0
#define STAG 1
#define VDEP 0
#define AEARLY 0
#define VTP 1
#define LORD 1
#define TRK 1
#define TW 0
#define T2N 14
#define TEARLY 1
#define DT 0
#define NB1 10
#define DB2 80
#define DITHER 0
#define DA 40
#define DB 40
#define DS 200

template <int K> __device__ __forceinline__ void sched(uint32_t key) {
    asm volatile("{\n.reg .pred p;\nsetp.ne.u32 p, %0, %1;\n@p bra.uni SD;\nSL: nanosleep.u32 64;\nbra.uni SL;\nSD:\n}" :: "r"(key), "n"(K) : "memory");
}
__device__ __forceinline__ void sched_i(int i, uint32_t key) {
    if (i == -1) sched<20>(key); if (i == 0) sched<21>(key); if (i == 1) sched<22>(key); if (i == 2) sched<23>(key);
    if (i == 3) sched<24>(key); if (i == 4) sched<25>(key); if (i == 5) sched<26>(key); if (i == 6) sched<27>(key);
}
template <int NB, int SM, class F>
__device__ __forceinline__ void g1(float* q0, float* k0, uint32_t (*wq)[4], uint32_t (*wk)[4], uint32_t ga, uint32_t key, F&& hook) {
    float q1[4], k1[4];
    uint32_t b[NB][4];
#pragma unroll
    for (int i = 0; i < NB; i++) ldsm4(b[i], ga + i * 512);
    hook(-1, b[0]);
    if (SM & 1) sched_i(-1, key);
#pragma unroll
    for (int i = 0; i < 8; i++) {
        uint32_t* c = b[i % NB];
        MMAF(i == 0, q0, wq[2 * i], c[0], c[1]); MMAF(i == 0, k0, wk[2 * i], c[0], c[1]);
        MMAF(i == 0, q1, wq[2 * i + 1], c[2], c[3]); MMAF(i == 0, k1, wk[2 * i + 1], c[2], c[3]);
        const uint32_t cc_[4] = {c[0], c[1], c[2], c[3]};
        if (i + NB < 8) ldsm4(b[i % NB], ga + (i + NB) * 512);
        hook(i, cc_);
        if ((SM >> (i + 1)) & 1) sched_i(i, key);
    }
#pragma unroll
    for (int i = 0; i < 4; i++) { q0[i] += q1[i]; k0[i] += k1[i]; }
}
__device__ __forceinline__ float frag_norm2(uint32_t (*w)[4]) {
    float d0[4], d1[4];
#pragma unroll
    for (int i = 0; i < 32; i++) { MMAF(i == 0, d0, w[i], w[i][0], w[i][2]); MMAF(i == 0, d1, w[i], w[i][1], w[i][3]); }
    const int lane = threadIdx.x & 31, g = lane >> 2, t = lane & 3;
    float v = g == 2 * t ? d0[0] + d1[2] : (g == 2 * t + 1 ? d0[1] + d1[3] : 0.f);
#pragma unroll
    for (int o = 16; o; o >>= 1) v += __shfl_xor_sync(0xffffffffu, v, o);
    return v;
}
__device__ __forceinline__ void load_slot(uint32_t sb, int c, int tile, const Maps& maps) {
    const uint32_t dst = sb + ((tile & 1) ? R_SLOT1 : R_SLOT0), mb = sb + R_BAR + 8 * (MB_FULL0 + (tile & 1));
    mbar_expect_tx(mb, 24576);
    tma2d(dst + 16384, &maps.kx, c * 64, tile * 64, mb);
    tma3d(dst, &maps.vx3, tile * 64, (c >> 1) * 2, mb);
}
__device__ __forceinline__ uint32_t put_mem0(uint32_t sb, int W, const bf16* __restrict__ mem0) {
    const int lane = threadIdx.x & 31;
    const uint4 m0 = *(const uint4*)(mem0 + (lane & 7) * DM + (W * 8 + (lane >> 3)) * 8), m1 = *(const uint4*)(mem0 + (lane & 7) * DM + (W * 8 + 4 + (lane >> 3)) * 8);
    bar_sync(3, 256);
    sts128u(sb + R_MEMB + W * 1024 + lane * 16, m0.x, m0.y, m0.z, m0.w);
    sts128u(sb + R_MEMB + W * 1024 + 512 + lane * 16, m1.x, m1.y, m1.z, m1.w);
    return amax2b(amax2b(amax2b(m0.x, m0.y), amax2b(m0.z, m0.w)), amax2b(amax2b(m1.x, m1.y), amax2b(m1.z, m1.w)));
}
#define PUT_MAX(W, dep) { uint32_t m_ = amax2b(amax2b(mx, my), mz | (dep)); sts32(sbu + R_MISC + (W) * 4, __reduce_max_sync(0xffffffffu, amax2b(m_, m_ << 16) & 0x7f800000u)); }
#define GATHER1(HALF)                                                                                           \
        {                                                                                                       \
            float d0[4], d1[4], d2[4], d3[4];                                                                   \
            const uint4 x0 = ldg_rlx4(pm), x1 = ldg_rlx4(pm + AC1); const uint32_t y = ldg_rlx(px);               \
            mma1688hz(d0, x0.x, x0.y, lt.z); mma1688hz(d1, x1.x, x1.y, lt.z);                                   \
            cw = (lt.w & 0x4000u) ? prmt(x0.w, x1.w, 0x7632u) : y;                                              \
            mma1688hz(d2, x0.z, prmt(x0.w, y, lt.w), lt.z); mma1688hz(d3, x1.z, prmt(x1.w, y, lt.w | 0x2200u), lt.z);          \
            const uint32_t p0 = pack2(d0[0], d0[1]), p1 = pack2(d0[2], d0[3]), p2 = pack2(d2[0], d2[1]), p3 = pack2(d2[2], d2[3]);       \
            stsm4t(rG + R_MEMB + HALF * 4096, p0, p1, p2, p3);                                                  \
            const uint32_t p4 = pack2(d1[0], d1[1]), p5 = pack2(d1[2], d1[3]), p6 = pack2(d3[0], d3[1]), p7 = pack2(d3[2], d3[3]);       \
            stsm4t(rG + R_MEMB + HALF * 4096 + 512, p4, p5, p6, p7);                                            \
            mx = amax2b(amax2b(p0, p1), amax2b(p2, p3)); my = amax2b(p4, p5); mz = amax2b(p6, p7);              \
        }
__device__ __forceinline__ uint32_t h2b(uint32_t w) {
    uint32_t d;
    asm("{\n.reg .f16 l, h;\n.reg .f32 a, b;\nmov.b32 {l, h}, %1;\ncvt.f32.f16 a, l;\ncvt.f32.f16 b, h;\ncvt.rn.bf16x2.f32 %0, b, a;\n}" : "=r"(d) : "r"(w));
    return d;
}
#define GATHER2(HALF)                                                                                           \
        {                                                                                                       \
            const uint4 x0 = ldg_rlx4(pm), x1 = ldg_rlx4(pm + AC1); const uint32_t y = ldg_rlx(px);               \
            cw = (lt.w & 0x4000u) ? prmt(x0.w, x1.w, 0x7632u) : y;                                              \
            const uint32_t p0 = h2b(x0.x), p1 = h2b(x0.y), p2 = h2b(x0.z), p3 = h2b(prmt(x0.w, y, lt.w));       \
            stsm4t(rG + R_MEMB + HALF * 4096, p0, p1, p2, p3);                                                  \
            const uint32_t p4 = h2b(x1.x), p5 = h2b(x1.y), p6 = h2b(x1.z), p7 = h2b(prmt(x1.w, y, lt.w | 0x2200u)); \
            stsm4t(rG + R_MEMB + HALF * 4096 + 512, p4, p5, p6, p7);                                            \
            mx = amax2b(amax2b(p0, p1), amax2b(p2, p3)); my = amax2b(p4, p5); mz = amax2b(p6, p7);              \
        }
#define GATHER(HALF, PRE, SYNC, AFTER)                                                                                      \
        {                                                                                                       \
            const uint32_t so = aslot(s);                                                                       \
            const uint32_t ua = (glo + acc_off(HALF * 4 + fo, 0)) ^ so, ux = (glo + ext_base(HALF * 4 + fo)) ^ so; \
            uint4 lt;                                                                                           \
            lt.x = lds32v_(rL + R_LT); lt.y = lds32v_(rL + R_LT + 4); lt.z = DEC ? 0 : lds32v_(rL + R_LT + 8); lt.w = lds32v_(rL + R_LT + 12); \
            const uint32_t* pm = mkptr(ua + lt.x, ghi);                                                         \
            const uint32_t* px = mkptr(ux + lt.y, ghi);                                                         \
            PRE                                                                                                 \
            bar_sync(5, 384);                                                                                   \
            const uint32_t t0 = clk32();                                                                        \
            TSACC();                                                                        \
            SYNC                                                                                                \
            spin_until(t0, DP + DITHER);                                                                                 \
            \
            TS(10, 0);                                                                                          \
            uint32_t cw, nr = 0;                                                                                \
            _Pragma("unroll 1") do {                                                                            \
                if (DEC) GATHER2(HALF) else GATHER1(HALF)                                                       \
                nr++;                                                                                           \
            } while (__any_sync(0xffffffffu, cw != HCNT2 && nr < SPIN_LIMIT));                                  \
            TS(11, cw);                                                                                         \
            AFTER                                                                                               \
            CNT2(HALF * 4 + (s & 1) * 2 + (nr > 2), nr > 1);                                                    \
            \
        }
#define GOBAR (fo == 3 ? 14 : 10 + fo)

__device__ __forceinline__ void rec_a(uint32_t sb, int c, const bf16* __restrict__ mem0, uint32_t epoch) {
    const int tid = threadIdx.x - WGA * 128, lane = tid & 31, f = tid >> 5;
    uint32_t wq[16][4], wk[16][4], mx, my = 0, mz = 0;
    const int lrow = ((lane >> 4) << 3) + (lane & 7), lsel = (lane >> 3) & 1;
    {
        mbar_wait(sb + R_BAR + 8 * MB_W0, 0);
        if (c == 7 && tid == 0) GT(1421);
        const uint32_t a = sb + R_T + lrow * 128 + (((2 * f + lsel) ^ (lane & 7)) << 4);
#pragma unroll
        for (int kk = 0; kk < 16; kk++) { ldsm4t(wq[kk], a + kk * 2048); ldsm4t(wk[kk], a + 32768 + kk * 2048); }
        __syncwarp();
        mx = put_mem0(sb, f, mem0);
    }
    const uint32_t rL = opaque(sb + lane * 16), rG = opaque(sb + lane * 16 + f * 1024);
    const uint32_t sbu = uni(sb), fo = uni(f), cc = uni(c);
    const uint64_t gx = xpage();
    const uint32_t ghi = uni((uint32_t)(gx >> 32)), glo = uni((uint32_t)gx);
#pragma unroll
    for (int i = 0; i < NAX; i++) {
        sts128u(rG + R_AX + 4096 * i, wq[i][0], wq[i][1], wq[i][2], wq[i][3]);
        sts128u(rG + R_AX + 4096 * i + 512, wk[i][0], wk[i][1], wk[i][2], wk[i][3]);
    }
    sts128u(rL + R_LT + 512 + f * 512, (sb + R_SREM + (f >= 2 ? lane * 8 + f * 256 : lane * 16 + f * 1024)) ^ 0x01000000u, (sb + R_BAR + 8 * MB_S) ^ 0x01000000u,
            sb + R_QP + (lane >> 4) * 128 + lsel * 512 + (lane & 7) * 16 + (f == 3 ? 2048 : 0), sb + lrow * 128 + ((lsel ^ (lane & 7)) << 4));
    __syncwarp();
    if (tid == 0) GT(c * 8 + 1);
    TSDECL;
    const float cexp = 0.08838834764831845f * 1.4426950408889634f;
    float cs = cexp;
    auto step = [&](int s, bool first) -> bool {
        bar_sync(1, 128);
        float q0[4], k0[4];
        uint4 ta;
        const uint32_t ro = ((s & 2) ? R_SLOT1 : R_SLOT0) + (s & 1) * 4096;
        g1<ANB, SMA>(q0, k0, wq, wk, rL + R_MEMB, sbu - s, [&](int i, const uint32_t* c_) {
            if (i == 0) TS(0, c_[0]);
            if (i == -1) {
#pragma unroll
                for (int n = NAX - NXL; n < NAX; n++) { lds_fragv(wq[n], rG + R_AX + 4096 * n); lds_fragv(wk[n], rG + R_AX + 4096 * n + 512); }
                ta = lds128uv(rL + R_LT + 512 + fo * 512);
            }
            if (i == IVA) bar_arrive(GOBAR, 96);
        });
        stsm4t(rG + R_QP, pack2(q0[0], q0[1]), pack2(q0[2], q0[3]), pack2(k0[0], k0[1]), pack2(k0[2], k0[3]));
        TS(1, FU(k0[3]));
        if (first) mbar_wait_p(sbu + R_BAR + 8 * MB_FULL0, 0);
        if (__builtin_expect(fo < 2, FLIP)) {
            uint32_t qa[4][4], kx[4][4];
#pragma unroll
            for (int kk = 0; kk < KXB; kk++) ldsm4(kx[kk], (ta.w ^ (kk * 32)) + (ro + 16384 + fo * 2048));
            bar_sync(3, 256);
#pragma unroll
            for (int kk = 0; kk < 4; kk++) {
                if (kk == 2 && (!TRK || TW)) bar_arrive(13, 256);
                if (kk >= KXB) ldsm4(kx[kk], (ta.w ^ (kk * 32)) + (ro + 16384 + fo * 2048));
                ldsm4(qa[kk], ta.z + kk * 1024);
            }
            float s0[4], s1[4], s2[4], s3[4];
            MMAZ(s0, qa[0], kx[0][0], kx[0][1]); MMAZ(s1, qa[0], kx[0][2], kx[0][3]);
            MMAZ(s2, qa[1], kx[1][0], kx[1][1]); MMAZ(s3, qa[1], kx[1][2], kx[1][3]);
            MMA(s0, qa[2], kx[2][0], kx[2][1]); MMA(s1, qa[2], kx[2][2], kx[2][3]);
            MMA(s2, qa[3], kx[3][0], kx[3][1]); MMA(s3, qa[3], kx[3][2], kx[3][3]);
            const float x = ((s0[0] + s0[2]) + (s2[0] + s2[2])) * cs, y = ((s0[1] + s0[3]) + (s2[1] + s2[3])) * cs;
            const float z = ((s1[0] + s1[2]) + (s3[0] + s3[2])) * cs, w = ((s1[1] + s1[3]) + (s3[1] + s3[3])) * cs;
            st_async4(ta.x, x, y, z, w, ta.y);
            TS(2, qa[0][0]); TS(3, FU(w));
            sts128(rG + R_SLOC, x, y, z, w);
        } else {
            bar_sync(3, 256);
            uint32_t kb[4], kc[4], qa[4], qc[4];
            ldsm4(kb, ta.z + 256); ldsm4(qa, ta.z); if (!TRK || TW) bar_arrive(13, 256);
            ldsm4(kc, ta.z + 1280); ldsm4(qc, ta.z + 1024);
            const uint32_t k0_ = hadd2b(kb[0], kb[1]), k1_ = hadd2b(kb[2], kb[3]), k2_ = hadd2b(kc[0], kc[1]), k3_ = hadd2b(kc[2], kc[3]);
            float s0[4], s2[4];
            MMAZ(s0, qa, k0_, k1_); MMAZ(s2, qc, k2_, k3_);
            const float x = ((s0[0] + s0[2]) + (s2[0] + s2[2])) * cs, y = ((s0[1] + s0[3]) + (s2[1] + s2[3])) * cs;
            st_async2(ta.x, FU(x), FU(y), ta.y);
            TS(2, kb[0]); TS(3, FU(y));
            sts64((ta.x ^ 0x01000000u) + (R_SLOC - R_SREM), x, y);
            sts128u(rL + R_STG + (fo & 1) * 512, k0_, k1_, k2_, k3_);
        }
        const uint32_t r8 = (rL + sbu) >> 1;
        uint32_t vt00[4], vt01[4], vt10[4], vt11[4];
        const uint32_t rV = ta.w ^ ((fo & 1) * 64), vo = ro + (fo >> 1) * 8192;
        if (VTP < 2) { ldsm4t(vt00, rV + vo); ldsm4t(vt10, (rV ^ 32) + vo); }
        if (VTP < 1) { ldsm4t(vt01, rV + vo + 2048); ldsm4t(vt11, (rV ^ 32) + vo + 2048); }
        bar_sync(4, 128);
        const float4 l0 = lds128v(rL + R_SLOC), l1 = lds128v(rL + R_SLOC + 1024);
        const float2 l2 = lds64v(r8 + R_SLOC + 512), l3 = lds64v(r8 + R_SLOC + 768);
        if (E2 && !TRK) bar_arrive(15, 256);
        PUT_MAX(fo, 0)
        bar_arrive(9, 256);
        if (s == NSEG - 1) { mbar_wait_u(sbu + R_BAR + 8 * MB_S, 1); mbar_wait_u(sbu + R_BAR + 8 * MB_V, 1); return true; }
        mbar_wait_p(sbu + R_BAR + 8 * MB_S, s & 1);
        {
            const float4 r0 = lds128v(rL + R_SREM), r1 = lds128v(rL + R_SREM + 1024);
            const float2 r2 = lds64v(r8 + R_SREM + 512), r3 = lds64v(r8 + R_SREM + 768);
            if (VTP >= 1) PINM();
            if (VTP >= 2) { ldsm4t(vt00, rV + vo); ldsm4t(vt10, (rV ^ 32) + vo); }
            if (VTP >= 1) { ldsm4t(vt01, rV + vo + 2048); ldsm4t(vt11, (rV ^ 32) + vo + 2048); }
            float sv[10];
            sv[0] = l0.x + r0.x; sv[1] = l0.y + r0.y; sv[2] = l0.z + r0.z; sv[3] = l0.w + r0.w;
            sv[4] = l1.x + r1.x; sv[5] = l1.y + r1.y; sv[6] = l1.z + r1.z; sv[7] = l1.w + r1.w;
            sv[8] = ((l2.x + l3.x) + r2.x) + r3.x; sv[9] = ((l2.y + l3.y) + r2.y) + r3.y;
            float m = fmaxf(fmaxf(fmaxf(sv[0], sv[1]), fmaxf(sv[2], sv[3])), fmaxf(fmaxf(sv[4], sv[5]), fmaxf(sv[6], sv[7])));
            m = fmaxf(m, fmaxf(sv[8], sv[9]));
            {
                const float m1 = __shfl_xor_sync(0xffffffffu, m, 1), m2 = __shfl_xor_sync(0xffffffffu, m, 2), m3 = __shfl_xor_sync(0xffffffffu, m, 3);
                m = fmaxf(fmaxf(m, m1), fmaxf(m2, m3));
            }
            TS(4, FU(r0.x)); TS(5, FU(m));
            const uint32_t ONE2 = 0x3f803f80u;
            float o0[4], o1[4], sm[4];
            const uint32_t pb0 = pack2(ex2(sv[0] - m), ex2(sv[1] - m)), pb1 = pack2(ex2(sv[2] - m), ex2(sv[3] - m));
            mma16816z(sm, ONE2, ONE2, ONE2, ONE2, pb0, pb1);
            MMAZ(o0, vt00, pb0, pb1); MMAZ(o1, vt10, pb0, pb1);
            const uint32_t z = (VDEP == 0 ? FU(m) : pb0) & (sbu & 8);
            const uint32_t vok = mbar_test(sbu + R_BAR + 8 * MB_V + z, s & 1);
            const uint32_t rv = r8 + vok * 8;
            float2 va = lds64v(rv + R_VB - 8 + fo * 512);
            if (!TRK) bar_arrive(13, 256);
            float2 vb = lds64v(rv + R_VB - 8 + fo * 512 + 256);
            float sig = __uint_as_float(lds32v_(sbu + R_MISC + 40));
            const uint32_t pb2 = pack2(ex2(sv[4] - m), ex2(sv[5] - m)), pb3 = pack2(ex2(sv[6] - m), ex2(sv[7] - m));
            mma16816(sm, ONE2, ONE2, ONE2, ONE2, pb2, pb3);
            const uint32_t pb4 = pack2(ex2(sv[8] - m), ex2(sv[9] - m));
            MMA(o0, vt01, pb2, pb3); MMA(o1, vt11, pb2, pb3);
            mma1688(sm, ONE2, ONE2, pb4);
            const float z0 = rcpf(sm[0]), z1 = rcpf(sm[1]);
#define PUT_O()                                                                                                   \
            {                                                                                                     \
                float a0[4] = {o0[0], o0[1], o0[2], o0[3]}, a1[4] = {o1[0], o1[1], o1[2], o1[3]};                 \
                mma1688(a0, FU(va.x), FU(va.y), pb4); mma1688(a1, FU(vb.x), FU(vb.y), pb4);                       \
                const float i0 = z0 * sig, i1 = z1 * sig;                                                         \
                stsm4t(rG + R_QP, pack2(a0[0] * i0, a0[1] * i1), pack2(a0[2] * i0, a0[3] * i1), pack2(a1[0] * i0, a1[1] * i1), pack2(a1[2] * i0, a1[3] * i1)); \
            }
            PUT_O()
            asm volatile("{\n.reg .pred p;\nsetp.ne.u32 p, %0, 0;\n@p bar.arrive 8, 256;\n}" :: "r"(vok) : "memory");
            if (__builtin_expect(__any_sync(0xffffffffu, vok == 0), 0)) {
                mbar_wait_p(sbu + R_BAR + 8 * MB_V, s & 1);
                va = lds64v(r8 + R_VB + fo * 512); vb = lds64v(r8 + R_VB + fo * 512 + 256);
                sig = __uint_as_float(lds32v_(sbu + R_MISC + 40));
                PUT_O()
                bar_arrive(8, 256);
                CNT(8);
            }
            TS(6, 0);
            const float r = __uint_as_float(0x7f000000u - FU(sig));
            cs = cexp * r * (fo >= 2 ? r : 1.f);
        }
        return false;
    };
    step(0, true);
#pragma unroll 1
    for (int s = 0;; s++) {
        if (s & 1) mbar_wait_p(sbu + R_BAR + 8 * (MB_FULL0 + (((s + 1) >> 1) & 1)), ((s + 1) >> 2) & 1);
        auto early = [&]() {
            SCHED(13);
#pragma unroll
            for (int i = 0; i < NAX - NXL; i++) { lds_fragv(wq[i], rG + R_AX + 4096 * i); lds_fragv(wk[i], rG + R_AX + 4096 * i + 512); }
        };
        GATHER(0, , early();, )
        if (step(s + 1, false)) break;
    }
    CNT(9);
    if (rG == sbu) GT(cc * 8 + 4);
}

__device__ __forceinline__ void rec_b(uint32_t sb, int c, uint32_t epoch) {
    const int tid = threadIdx.x - WGB * 128, lane = tid & 31, f = tid >> 5;
    uint32_t wq[16][4], wk[16][4], wo[32][4];
    const int lrow = ((lane >> 4) << 3) + (lane & 7), lsel = (lane >> 3) & 1;
    const uint32_t rL = opaque(sb + lane * 16), rW = opaque(sb + lane * 16 + f * 16384);
    const uint32_t sbu = uni(sb), fo = uni(f), cc = uni(c), po = cc & 1, ep = uni(epoch);
    {
        mbar_wait(sb + R_BAR + 8 * MB_WO, 0);
        if (c == 7 && tid == 0) GT(1426);
        const uint32_t aO = sb + R_WO + f * 16384 + lrow * 128 + ((lsel ^ (lane & 7)) << 4);
#pragma unroll
        for (int i = 0; i < 32; i++) {
            const int tile = STAG ? (i >> 4) * 2 + (i & 1) : i & 3, kk = STAG ? (i >> 1) & 7 : i >> 2;
            ldsm4t(wo[i], (aO ^ (32 * tile)) + kk * 2048);
        }
        const float no = frag_norm2(wo);
        if (lane == 0) sts32(sb + R_MISC + 80 + f * 4, FU(no));
        __syncwarp();
        bar_sync(15, 256);
        if (tid == 0) {
            const float4 a = lds128(sb + R_MISC + 64), b = lds128(sb + R_MISC + 80);
            stg4(&g_f.norm[c], make_uint4(FU((a.x + a.y) + (a.z + a.w)), epoch, FU((b.x + b.y) + (b.z + b.w)), epoch));
        }
        __syncwarp();
#pragma unroll
        for (int i = NRW; i < 32; i++) sts128u(rW + R_WO + i * 512, wo[i][0], wo[i][1], wo[i][2], wo[i][3]);
        mbar_wait(sb + R_BAR + 8 * MB_W1, 0);
        if (c == 7 && tid == 0) GT(1422);
        if (tid == 0) stg_rlx(&g_f.rload[c], epoch);
        __syncwarp();
        const uint32_t a = sb + R_QK1 + lrow * 128 + (((2 * f + lsel) ^ (lane & 7)) << 4);
#pragma unroll
        for (int kk = 0; kk < 16; kk++) { ldsm4t(wq[kk], a + kk * 2048); ldsm4t(wk[kk], a + 32768 + kk * 2048); }
        bar_sync(13, 128);
#pragma unroll
        for (int i = 0; i < 16; i++) {
            sts128u(rW + R_QK1 + i * 1024, wq[i][0], wq[i][1], wq[i][2], wq[i][3]);
            sts128u(rW + R_QK1 + i * 1024 + 512, wk[i][0], wk[i][1], wk[i][2], wk[i][3]);
        }
        __syncwarp();
    }
    const uint64_t gx = xpage();
    const uint32_t ghi = uni((uint32_t)(gx >> 32)), glo = uni((uint32_t)gx);
    TSDECL;
#pragma unroll 1
    for (int s = 0;; s++) {
        bar_sync(2, 256);
        float q0[4], k0[4];
        g1<BNB, SMB>(q0, k0, wq, wk, rL + R_MEMB + 4096, sbu - s, [&](int i, const uint32_t* c_) {
            if (i == 0) TS(0, c_[0]);
            if (i >= 2 && i < 6) {
#pragma unroll
                for (int n = NRW + (i - 2) * E0 / 4; n < NRW + (i - 1) * E0 / 4; n++) lds_fragv(wo[n], rW + R_WO + n * 512);
            }
            if (i == IV) bar_arrive(GOBAR, 96);
        });
        stsm4t(rL + fo * 1024 + R_QP + 512, pack2(q0[0], q0[1]), pack2(q0[2], q0[3]), pack2(k0[0], k0[1]), pack2(k0[2], k0[3]));
        bar_arrive(3, 256);
        TS(1, FU(k0[3]));
        const uint32_t so = aslot(s);
        const uint4 lt = lds128uv(rL + R_LT);
        uint32_t* pm = (uint32_t*)mkptr(((glo + acc_off(po * 4 + fo, 0)) ^ so) + lt.x, ghi);
        uint32_t* px = (uint32_t*)mkptr(((glo + ext_base(po * 4 + fo)) ^ so) + lt.y, ghi);
        if (TW) bar_sync(13, 256);
        if (s == NSEG - 1) break;
        {
            const uint32_t z = lt.x & 1;
#pragma unroll
            for (int n = NRW; n < NRW + E0 + E1 + E2 + E3; n++) {
                const int d = n - (n < NRW + T2N ? TRK + 1 : TRK);
                lds_fragv(wo[n], (d >= NRW ? or_and(rW, wo[d][0], z) : rW) + R_WO + n * 512);
            }
        }
        TS(2, wo[NRW + E0 + E1 + E2 + E3 - 1][0]);
        SCHED(4);
        bar_sync(8, 256);
        {
            float o[4][4];
            uint32_t b[4][4];
#pragma unroll
            for (int i = 0; i < 4; i++) ldsm4(b[i], rL + R_QP + i * 1024);
            PINM();
#pragma unroll
            for (int n = NRW + E0 + E1 + E2 + E3; n < 32; n++) lds_fragv(wo[n], rW + R_WO + n * 512);
            float p[4][4];
#define G2_STEP(o, hf, kk) _Pragma("unroll") for (int i = 0; i < 2; i++) MMAF((kk) < 2, o[((kk) & 1) * 2 + i], wo[(hf) * 16 + (kk) * 2 + i], b[(kk) >> 1][((kk) & 1) * 2], b[(kk) >> 1][((kk) & 1) * 2 + 1])
#define G2_RED(o, wl, ptr) const uint32_t wl = packh2(o[1][2] + o[3][2], o[1][3] + o[3][3]);                          \
                asm volatile("red.relaxed.gpu.global.add.noftz.v4.f16x2 [%0], {%1,%2,%3,%4};" :: "l"(ptr),           \
                    "r"(packh2(o[0][0] + o[2][0], o[0][1] + o[2][1])), "r"(packh2(o[0][2] + o[2][2], o[0][3] + o[2][3])), \
                    "r"(packh2(o[1][0] + o[3][0], o[1][1] + o[3][1])), "r"(prmt(wl, HONE2, lt.w)) : "memory")
#pragma unroll
            for (int kk = 0; kk < 8; kk++) { G2_STEP(o, 0, kk); }
            TS(7, b[0][0]);
            SCHED(11);
#pragma unroll
            for (int kk = 0; kk < 4; kk++) { G2_STEP(p, 1, kk); }
            G2_RED(o, w3, pm);
            TS(8, w3);
            SCHED(12);
#pragma unroll
            for (int kk = 4; kk < 8; kk++) { G2_STEP(p, 1, kk); }
            G2_RED(p, w7, pm + AC1);
            asm volatile("red.relaxed.gpu.global.add.noftz.f16x2 [%0], %1;" :: "l"(px), "r"((lt.w & 0x4000u) ? prmt(w3, w7, 0x7632u) : HONE2) : "memory");
            TS(9, w7);
        }
        bar_arrive(5, 384);
        asm volatile("{\n.reg .pred p;\nsetp.eq.u32 p, %0, %1;\n@p mbarrier.arrive.expect_tx.shared::cta.b64 _, [%2], 1536;\n}"
                     :: "r"(rW), "r"(sbu), "r"(sbu + R_BAR + 8 * MB_S) : "memory");
        const uint32_t tb = clk32();
        TSACC();
        spin_until(tb, DB);
#pragma unroll
        for (int i = 0; i < NBR; i++) {
            if (i == NB1) spin_until(tb, DP + DB2);
            lds_fragv(wq[i], rW + R_QK1 + i * 1024); lds_fragv(wk[i], rW + R_QK1 + i * 1024 + 512);
        }
    }
}

#undef lds_fragv
__device__ __forceinline__ void rec_first_loads(uint32_t sb, int c, const Maps& maps) {
    const uint32_t bar = sb + R_BAR;
    const int F0 = c * 64;
    mbar_expect_tx(bar + 8 * MB_W0, 65536); mbar_expect_tx(bar + 8 * MB_WO, 65536); mbar_expect_tx(bar + 8 * MB_WV, 65536);
    tma2d(sb + R_QK1, &maps.wv, F0, 0, bar + 8 * MB_WV); tma2d(sb + R_QK1 + 32768, &maps.wv, F0, 256, bar + 8 * MB_WV);
    tma2d(sb + R_T + 32768, &maps.wk, F0, 0, bar + 8 * MB_W0);
    if (!LORD) {
        for (int i = 0; i < 4; i++) tma2d(sb + R_WO + i * 16384, &maps.wo, (c & 1) * 256 + i * 64, (c >> 1) * 128, bar + 8 * MB_WO);
        tma2d(sb + R_T, &maps.wq, F0, 0, bar + 8 * MB_W0);
    }
    mbar_expect_tx(bar + 8 * MB_S, 1536);
}
__device__ __forceinline__ void rec_c(uint32_t sb, int c, const bf16* __restrict__ mem0, const Maps& maps, uint32_t epoch) {
    const int tid = threadIdx.x - WGC * 128, lane = tid & 31, u = tid >> 5;
    const uint32_t bar = sb + R_BAR;
    const int lrow = ((lane >> 4) << 3) + (lane & 7), lsel = (lane >> 3) & 1;
    const int kh = u >> 1, j = u & 1;
    uint32_t wv[32][4], mx, my = 0, mz = 0;
    {
        if (u == 0) {
            sts128u(sb + lane * 16 + R_LT, acc_off(0, lane), ext_lane(lane),
                    ((lane >> 2) == 2 * (lane & 3) ? 0x3c00u : 0u) | ((lane >> 2) == 2 * (lane & 3) + 1 ? 0x3c000000u : 0u), (lane & 1) ? 0x5410u : 0x3210u);
        }
        mbar_wait(bar + 8 * MB_WV, 0);
        if (c == 7 && tid == 0) GT(1425);
        if (LORD && tid == 32) {
            for (int i = 0; i < 4; i++) tma2d(sb + R_WO + i * 16384, &maps.wo, (c & 1) * 256 + i * 64, (c >> 1) * 128, bar + 8 * MB_WO);
            tma2d(sb + R_T, &maps.wq, c * 64, 0, bar + 8 * MB_W0);
        }
        __syncwarp();
        const uint32_t aa = sb + R_QK1 + (kh * 256 + lrow) * 128 + (((4 * j + 2 * kh + lsel) ^ (lane & 7)) << 4);
#pragma unroll
        for (int kk = 0; kk < 16; kk++) { ldsm4t(wv[kk], aa + kk * 2048); ldsm4t(wv[16 + kk], (aa ^ 32) + kk * 2048); }
        bar_sync(9, 128);
        if (c == 7 && tid == 0) GT(1423);
        if (tid == 0) {
            mbar_expect_tx(bar + 8 * MB_W1, 65536);
            tma2d(sb + R_QK1 + 32768, &maps.wk, c * 64, 256, bar + 8 * MB_W1); tma2d(sb + R_QK1, &maps.wq, c * 64, 256, bar + 8 * MB_W1);
        }
        __syncwarp();
        const float nv = frag_norm2(wv);
        if (lane == 0) sts32(sb + R_MISC + 64 + u * 4, FU(nv));
        __syncwarp();
        bar_arrive(15, 256);
        mx = put_mem0(sb, 4 + u, mem0);
    }
    const uint32_t rL = opaque(sb + lane * 16), rG = opaque(sb + lane * 16 + u * 1024);
    const uint32_t sbu = uni(sb), fo = uni(u), cc = uni(c), ep = uni(epoch);
    const uint64_t gx = xpage();
    const uint32_t ghi = uni((uint32_t)(gx >> 32)), glo = uni((uint32_t)gx);
    constexpr int CX = R_AX + NAX * 4096;
    static_assert(NAX + NCX <= 6, "AX");
#pragma unroll
    for (int i = 0; i < NCX; i++) {
        sts128u(rG + CX + 4096 * i, wv[i][0], wv[i][1], wv[i][2], wv[i][3]);
        sts128u(rG + CX + 4096 * i + 512, wv[16 + i][0], wv[16 + i][1], wv[16 + i][2], wv[16 + i][3]);
    }
    __syncwarp();
    TSDECL;
    uint32_t rpb = 0x3f800000u;
    bar_arrive(2, 256);
    if (fo == 3) {
        uint32_t n = 0;
#pragma unroll 1
        while (true) {
            const uint2 v = ldg_rlx2(&g_f.kv[0][cc >> 1][0]);
            if (__all_sync(0xffffffffu, v.x == ep && v.y == ep)) break;
            __nanosleep(32);
            if (++n > SPIN_LIMIT) { ABORT(6); break; }
        }
        if (rL == sbu) load_slot(sbu, cc, 0, maps);
        __syncwarp();
        if (cc == 7 && rL == sbu) GT(1427);
    }
#pragma unroll 1
    for (int s = 0;; s++) {
        if (TEARLY && fo == 3 && !(s & 1) && s > 0 && s + 2 < NSEG) {
            if (rL == sbu) load_slot(sbu, cc, (s + 2) >> 1, maps);
            __syncwarp();
        } else spin_until(clk32(), DC);
#pragma unroll
        for (int i = NCX - NCL; i < NCX; i++) { lds_fragv(wv[i], rG + CX + 4096 * i); lds_fragv(wv[16 + i], rG + CX + 4096 * i + 512); }
        PUT_MAX(4 + fo, 0)
        bar_sync(GOBAR, 96);
        float v0[4], v1[4];
        g1<CNB, SMC>(v0, v1, wv, wv + 16, rL + R_MEMB + (fo >> 1) * 4096, sbu - s, [&](int i, const uint32_t* c_) { if (i == 0) TS(0, c_[0]); });
        TS(1, FU(v1[3]));
        const uint32_t l16 = (rL ^ sbu) | (lds32v_(rL + R_LT + 4) & 1);
        const uint32_t r8 = sbu + (l16 >> 1);
        {
            sts128(rL + R_VRED + fo * 512, v1[0], v1[1], v1[2], v1[3]);
            const uint32_t d = r8 + R_VB + ((cc & 1) * 4 + (fo & 1) * 2 + (fo >> 1)) * 256;
            const uint32_t dr = xorv(d, 0x01000000u), br = xorv(sbu + R_BAR + 8 * MB_V, 0x01000000u);
            bar_sync(6 + (fo & 1), 64);
            const float4 a0 = lds128(rL + R_VRED + (fo ^ 2) * 512);
            const float rp = __uint_as_float(rpb);
            const uint32_t w0 = pack2((v0[0] + a0.x) * rp, (v0[1] + a0.y) * rp), w1 = pack2((v0[2] + a0.z) * rp, (v0[3] + a0.w) * rp);
            st_async2(dr, w0, w1, br);
            TS(3, w1);
            sts64(d, __uint_as_float(w0), __uint_as_float(w1));
            __syncwarp();
            asm volatile("{\n.reg .pred p;\nsetp.eq.u32 p, %0, %1;\n@p mbarrier.arrive.expect_tx.shared::cta.b64 _, [%2], 256;\n}"
                         :: "r"(rL), "r"(sbu), "r"(sbu + R_BAR + 8 * MB_V) : "memory");
        }
        if (fo == 1) {
            bar_sync(9, 256);
            {
                if (s == 0) {
                    const uint32_t* np = (const uint32_t*)&g_f.norm[0] + (l16 >> 2);
                    uint4 r, q; uint32_t n = 0;
#pragma unroll 1
                    while (true) {
                        r = ldg_rlx4(np); q = ldg_rlx4(np + 128);
                        const uint2 z = ldg_rlx2(&g_f.xn[l16 >> 3]);
                        if (__all_sync(0xffffffffu, r.y == ep && r.w == ep && q.y == ep && q.w == ep && z.x == ep && z.y == ep)) break;
                        if (++n > SPIN_LIMIT) { ABORT(5); break; }
                    }
                    float nv = __uint_as_float(r.x) + __uint_as_float(q.x), no = __uint_as_float(r.z) + __uint_as_float(q.z);
#pragma unroll
                    for (int o = 16; o; o >>= 1) { nv += __shfl_xor_sync(0xffffffffu, nv, o); no += __shfl_xor_sync(0xffffffffu, no, o); }
                    const int lc = ((int)(FU(nv) >> 23) + (int)(FU(no) >> 23) - 252 + 9 + 1) >> 1;
                    sts32(sbu + R_MISC + 32, 140 - lc);
                    __syncwarp();
                }
                const uint4 ma = lds128uv(sbu + R_MISC), mb = lds128uv(sbu + R_MISC + 16);
                const int em = (int)(max(max(max(ma.x, ma.y), max(ma.z, ma.w)), max(max(mb.x, mb.y), max(mb.z, mb.w))) >> 23) + (int)(rpb >> 23) - 127;
                const int es = min(max((int)lds32v_(sbu + R_MISC + 32) - max(em, 127), -60), 60);
                sts32(sbu + R_MISC + 40, (127 + es) << 23);
                mbar_arrive_if(sbu + R_BAR + 8 * MB_V, l16 == 0);
                TS(4, es);
            }
            uint8_t* dst = (uint8_t*)&g_KVf[s][cc >> 1][(cc & 1) * 256] + l16;
            const uint32_t r2 = prmt(rpb, 0, 0x3232u);
#pragma unroll
            for (int i = 0; i < 2; i++) {
                const uint4 a = lds128uv(rL + R_STG + i * 512);
                stg4(dst + i * 512, make_uint4(~hmul2b(a.x, r2), ~hmul2b(a.y, r2), ~hmul2b(a.z, r2), ~hmul2b(a.w, r2)));
                const float2 b0 = lds64v(r8 + R_VB + (cc & 1) * 1024 + i * 512), b1 = lds64v(r8 + R_VB + (cc & 1) * 1024 + i * 512 + 256);
                stg4(dst + 2048 + i * 512, make_uint4(~FU(b0.x), ~FU(b0.y), ~FU(b1.x), ~FU(b1.y)));
            }
            __syncwarp();
            if (l16 == 0) { stg_rlx(&g_f.rec[cc], (ep << 8) | (s + 1)); if (s == NSEG - 1) GT(1500 + cc); }
            __syncwarp();
        } else {
            bar_arrive(9, 256);
            if (fo == 2) {
                if (l16 < 272) stg4((void*)mkptr((glo + zero_off(cc, l16 >> 4)) ^ aslot(s + 4), ghi), make_uint4(0, 0, 0, 0));
                __syncwarp();
            } else if (fo == 3) {
                if (((s & 1) || s == 0) && s + 3 < NSEG) {
                    const uint32_t* fp = &g_f.kv[(s + 3) >> 1][cc >> 1][0];
                    uint32_t n = 0;
#pragma unroll 1
                    while (true) {
                        const uint2 v = ldg_rlx2(fp);
                        if (__all_sync(0xffffffffu, v.x == ep && v.y == ep)) break;
                        __nanosleep(64);
                        if (++n > SPIN_LIMIT) { ABORT(6); break; }
                    }
                }
                if (!(s & 1) && s + 2 < NSEG && (!TEARLY || s == 0)) {
                    spin_until(clk32(), DT);
                    if (l16 == 0) load_slot(sbu, cc, (s + 2) >> 1, maps);
                    __syncwarp();
                }
            }
        }
        if (s == NSEG - 1) break;
        auto early = [&]() {
#pragma unroll
            for (int i = 0; i < NCX - NCL; i++) { lds_fragv(wv[i], rG + CX + 4096 * i); lds_fragv(wv[16 + i], rG + CX + 4096 * i + 512); }
        };
        GATHER(1, , early(); rpb = 0x7f000000u - lds32v_(sbu + R_MISC + 40);, bar_arrive(2, 256);)
    }
}

__device__ __forceinline__ bool cand_better(float v, int i, float bv, int bi) { return v > bv || (v == bv && i < bi); }
constexpr int F_WG = 0, F_WU = 32768, F_WD = 65536, F_X = 98304, F_RED = F_X + 4096, F_ACT = F_RED + 8192, F_SEL = F_ACT + 256;

__device__ __noinline__ void ffn_phase(const Maps& maps, const bf16* __restrict__ wd, bf16* __restrict__ out) {
    extern __shared__ __align__(1024) uint8_t smem[];
    const uint32_t sb = smem_u32(smem);
    const int c = ((volatile int*)(smem + SH_OFF))[8];
    const uint32_t epoch = ((volatile uint32_t*)(smem + SH_OFF))[9];
    const int tid = threadIdx.x;
    constexpr int NWK = FF / 32;
    const bool worker = c < NWK;
    bar_sync(0, 384);
    const uint32_t mb = sb + R_BAR + 8 * MB_W0;
    if (tid == 32 && worker) {
        asm volatile("fence.proxy.async.shared::cta;" ::: "memory");
        mbar_expect_tx(mb, 98304);
        tma2d(sb + F_WG, &maps.wg, c * 32, 0, mb); tma2d(sb + F_WG + 16384, &maps.wg, c * 32, 256, mb);
        tma2d(sb + F_WU, &maps.wu, c * 32, 0, mb); tma2d(sb + F_WU + 16384, &maps.wu, c * 32, 256, mb);
        asm volatile("cp.async.bulk.shared::cluster.global.mbarrier::complete_tx::bytes [%0], [%1], %2, [%3];"
            :: "r"(sb + F_WD), "l"(wd + (size_t)c * 32 * DM), "r"(32768), "r"(mb) : "memory");
    }
    int p0 = -1, p1 = -1;
#pragma unroll 1
    for (int pass = 0; pass < 2; pass++) {
        if (tid < 32) {
            const uint32_t tag = epoch & 0xfffffu;
            uint4 r[4]; uint32_t n = 0;
            const int t3 = tid + 96 < NFW ? tid + 96 : tid;
#pragma unroll 1
            while (true) {
                bool ok = true;
#pragma unroll
                for (int i = 0; i < 4; i++) r[i] = ldg_rlx4((const uint32_t*)&g_f.cand[pass][i < 3 ? tid + 32 * i : t3]);
#pragma unroll
                for (int i = 0; i < 4; i++) ok = ok && (r[i].y >> 12) == tag && (r[i].w >> 12) == tag;
                if (__all_sync(0xffffffffu, ok)) break;
                __nanosleep(32);
                if (++n > SPIN_LIMIT) { ABORT(7); break; }
            }
            float b0 = __uint_as_float(r[0].x), b1 = __uint_as_float(r[0].z); int i0 = r[0].y & 4095, i1 = r[0].w & 4095;
#pragma unroll
            for (int i = 1; i < 4; i++) {
                if (i < 3 || t3 != tid) {
                    float c0 = __uint_as_float(r[i].x), c1 = __uint_as_float(r[i].z); int j0 = r[i].y & 4095, j1 = r[i].w & 4095;
                    if (cand_better(c0, j0, b0, i0)) {
                        if (cand_better(c1, j1, b0, i0)) { b1 = c1; i1 = j1; } else { b1 = b0; i1 = i0; }
                        b0 = c0; i0 = j0;
                    } else if (cand_better(c0, j0, b1, i1)) { b1 = c0; i1 = j0; }
                }
            }
#pragma unroll
            for (int o = 16; o; o >>= 1) {
                float c0 = __shfl_xor_sync(0xffffffffu, b0, o), c1 = __shfl_xor_sync(0xffffffffu, b1, o);
                int j0 = __shfl_xor_sync(0xffffffffu, i0, o), j1 = __shfl_xor_sync(0xffffffffu, i1, o);
                if (cand_better(c0, j0, b0, i0)) {
                    if (cand_better(c1, j1, b0, i0)) { b1 = c1; i1 = j1; } else { b1 = b0; i1 = i0; }
                    b0 = c0; i0 = j0;
                } else if (cand_better(c0, j0, b1, i1)) { b1 = c0; i1 = j0; }
            }
            i0 = min(i0, SQ - 1); i1 = min(i1, SQ - 1);
            if (i0 != p0 || i1 != p1) {
                n = 0;
#pragma unroll 1
                while (!__all_sync(0xffffffffu, (ldg_rlx(&g_f.rows[pass][tid]) == epoch) & (ldg_rlx(&g_f.rows[pass][tid + 32]) == epoch) &
                                                   (ldg_rlx(&g_f.rows[pass][tid + 64]) == epoch) & (ldg_rlx(&g_f.rows[pass][t3]) == epoch))) { __nanosleep(32); if (++n > SPIN_LIMIT) { ABORT(7); break; } }
            }
            int* sel = (int*)(smem + F_SEL);
            if (pass && tid == 0) GT(c * 8 + 5);
            if (tid == 0) { sel[0] = i0; sel[1] = i1; ((float*)sel)[2] = b0; ((float*)sel)[3] = b1; }
        }
        bar_sync(0, 384);
        const int t0 = ((int*)(smem + F_SEL))[0], t1 = ((int*)(smem + F_SEL))[1];
        if (c == 3 && tid == 0 && pass == 0) GT(1430);
        if (t0 == p0 && t1 == p1) break;
        const uint32_t ytag = epoch * 2 + pass + 1;
        if (worker) {
            float2* xs = (float2*)(smem + F_X);
            if (tid < 256) {
                uint32_t a = __ldcg((const uint32_t*)(g_hn + (size_t)t0 * DM) + tid), b = __ldcg((const uint32_t*)(g_hn + (size_t)t1 * DM) + tid);
                *(float4*)(xs + tid * 2) = make_float4(bf_lo(a), bf_lo(b), bf_hi(a), bf_hi(b));
            }
            mbar_wait(mb, 1);
            if (c == 3 && tid == 0 && pass == 0) GT(1431);
            bar_sync(0, 384);
            float4* red = (float4*)(smem + F_RED);
            if (tid < 256) {
                const int cp = tid & 31, kg = tid >> 5;
                const uint32_t* wp = (const uint32_t*)(smem + (cp < 16 ? F_WG : F_WU)) + (cp & 15);
                float a0 = 0.f, a1 = 0.f, b0 = 0.f, b1 = 0.f;
#pragma unroll 16
                for (int k = kg * 64; k < kg * 64 + 64; k++) {
                    uint32_t w = wp[k * 16]; float2 x = xs[k];
                    a0 = fmaf(x.x, bf_lo(w), a0); a1 = fmaf(x.x, bf_hi(w), a1); b0 = fmaf(x.y, bf_lo(w), b0); b1 = fmaf(x.y, bf_hi(w), b1);
                }
                red[kg * 32 + cp] = make_float4(a0, a1, b0, b1);
            }
            bar_sync(0, 384);
            float2* act = (float2*)(smem + F_ACT);
            if (tid < 64) {
                const int f = tid & 31, tk = tid >> 5;
                const float* r = (const float*)red + (f >> 1) * 4 + tk * 2 + (f & 1);
                float gsum = 0.f, usum = 0.f;
#pragma unroll
                for (int kg = 0; kg < 8; kg++) { gsum += r[kg * 128]; usum += r[kg * 128 + 64]; }
                gsum = rbf(gsum); usum = rbf(usum);
                float sg = rbf(gsum / (1.f + __expf(-gsum)));
                ((float*)act)[f * 2 + tk] = rbf(sg * usum);
            }
            bar_sync(0, 384);
            if (tid < 256) {
                const uint32_t* wp = (const uint32_t*)(smem + F_WD) + tid;
                float a0 = 0.f, a1 = 0.f, b0 = 0.f, b1 = 0.f;
#pragma unroll 16
                for (int f = 0; f < 32; f++) {
                    uint32_t w = wp[f * 256]; float2 x = act[f];
                    a0 = fmaf(x.x, bf_lo(w), a0); a1 = fmaf(x.x, bf_hi(w), a1); b0 = fmaf(x.y, bf_lo(w), b0); b1 = fmaf(x.y, bf_hi(w), b1);
                }
                asm volatile("st.relaxed.gpu.global.v4.b32 [%0], {%1,%2,%3,%2};" :: "l"(&g_yp[pass][c][tid]), "r"(FU(a0)), "r"(ytag), "r"(FU(a1)) : "memory");
                asm volatile("st.relaxed.gpu.global.v4.b32 [%0], {%1,%2,%3,%2};" :: "l"(&g_yp[pass][c][256 + tid]), "r"(FU(b0)), "r"(ytag), "r"(FU(b1)) : "memory");
            }
            if (c == 3 && tid == 0 && pass == 0) GT(1432);
        } else {
            const int r = c - NWK, j = tid & 63, part = tid >> 6, tk = r >> 2, dp = (r & 3) * 64 + j;
            const int tok = tk ? t1 : t0, old = tk ? p1 : p0;
            uint32_t hw = 0, nw = 0;
            if (part == 0) {
                hw = __ldcg((const uint32_t*)(g_h + (size_t)tok * DM) + dp); nw = __ldcg((const uint32_t*)(g_hn + (size_t)tok * DM) + dp);
                if (old >= 0 && old != t0 && old != t1) {
                    uint32_t ho = __ldcg((const uint32_t*)(g_h + (size_t)old * DM) + dp), no = __ldcg((const uint32_t*)(g_hn + (size_t)old * DM) + dp);
                    ((uint32_t*)(out + (size_t)old * DM))[dp] = pack2(bf_lo(ho) + bf_lo(no), bf_hi(ho) + bf_hi(no));
                }
            }
            float s0 = 0.f, s1 = 0.f;
            uint4 v[10]; uint32_t n = 0;
            bool ok;
#pragma unroll 1
            do {
                ok = true;
#pragma unroll
                for (int i = 0; i < 10; i++) {
                    const int src = part + 6 * i;
                    v[i] = src < NWK ? ldg_rlx4((const uint32_t*)&g_yp[pass][src][tk * 256 + dp]) : make_uint4(0, ytag, 0, ytag);
                }
#pragma unroll
                for (int i = 0; i < 10; i++) ok = ok && v[i].y == ytag && v[i].w == ytag;
                if (!ok) __nanosleep(100);
                if (++n > SPIN_LIMIT) { ABORT(7); break; }
            } while (!ok);
#pragma unroll
            for (int i = 0; i < 10; i++) { s0 += __uint_as_float(v[i].x); s1 += __uint_as_float(v[i].z); }
            float2* red = (float2*)(smem + F_RED);
            red[part * 64 + j] = make_float2(s0, s1);
            bar_sync(0, 384);
            if (part == 0) {
#pragma unroll
                for (int i = 1; i < 6; i++) { float2 q = red[i * 64 + j]; s0 += q.x; s1 += q.y; }
                const float rs = rbf(1.f / (1.f + __expf(-((float*)(smem + F_SEL))[2 + tk])));
                const float y0 = rbf(rbf(s0) * rs), y1 = rbf(rbf(s1) * rs);
                ((uint32_t*)(out + (size_t)tok * DM))[dp] = pack2(bf_lo(hw) + rbf(bf_lo(nw) + y0), bf_hi(hw) + rbf(bf_hi(nw) + y1));
            }
            if (tid == 0 && pass == 0 && r == 0) GT(1434);
        }
        p0 = t0; p1 = t1;
        if (c == 3 && tid == 0 && pass == 0) GT(1433);
        bar_sync(0, 384);
    }
}

constexpr int G_W = 0;
constexpr int G_RING = 131072;
constexpr int G_BUF = 163840;
constexpr int G_BAR = 229376;
constexpr int G_SMEM = G_BAR + 512;
enum { GB_W0 = 0, GB_W1, GB_WFREE, GB_FULL, GB_EMPTY = GB_FULL + 8, GB_KV = GB_EMPTY + 8, GB_STG = GB_KV + 2, GB_FREE = GB_STG + 2, GB_XN = GB_FREE + 2, GB_RL, GB_T1D, GB_VV, GB_KVF = GB_VV + 2, GB_VF, GB_N };
constexpr int SMEM_TOTAL = 232448;

__device__ __forceinline__ void wgmma_n128(float* d, uint64_t da, uint64_t db, int scale_d) {
    asm volatile("{\n.reg .pred p;\nsetp.ne.b32 p, %66, 0;\n"
        "wgmma.mma_async.sync.aligned.m64n128k16.f32.bf16.bf16 "
        "{%0,%1,%2,%3,%4,%5,%6,%7,%8,%9,%10,%11,%12,%13,%14,%15,%16,%17,%18,%19,%20,%21,%22,%23,%24,%25,%26,%27,%28,%29,%30,%31,"
        "%32,%33,%34,%35,%36,%37,%38,%39,%40,%41,%42,%43,%44,%45,%46,%47,%48,%49,%50,%51,%52,%53,%54,%55,%56,%57,%58,%59,%60,%61,%62,%63}, "
        "%64, %65, p, 1, 1, 0, 1;\n}"
        : "+f"(d[0]), "+f"(d[1]), "+f"(d[2]), "+f"(d[3]), "+f"(d[4]), "+f"(d[5]), "+f"(d[6]), "+f"(d[7]), "+f"(d[8]), "+f"(d[9]), "+f"(d[10]), "+f"(d[11]),
          "+f"(d[12]), "+f"(d[13]), "+f"(d[14]), "+f"(d[15]), "+f"(d[16]), "+f"(d[17]), "+f"(d[18]), "+f"(d[19]), "+f"(d[20]), "+f"(d[21]), "+f"(d[22]), "+f"(d[23]),
          "+f"(d[24]), "+f"(d[25]), "+f"(d[26]), "+f"(d[27]), "+f"(d[28]), "+f"(d[29]), "+f"(d[30]), "+f"(d[31]), "+f"(d[32]), "+f"(d[33]), "+f"(d[34]), "+f"(d[35]),
          "+f"(d[36]), "+f"(d[37]), "+f"(d[38]), "+f"(d[39]), "+f"(d[40]), "+f"(d[41]), "+f"(d[42]), "+f"(d[43]), "+f"(d[44]), "+f"(d[45]), "+f"(d[46]), "+f"(d[47]),
          "+f"(d[48]), "+f"(d[49]), "+f"(d[50]), "+f"(d[51]), "+f"(d[52]), "+f"(d[53]), "+f"(d[54]), "+f"(d[55]), "+f"(d[56]), "+f"(d[57]), "+f"(d[58]), "+f"(d[59]),
          "+f"(d[60]), "+f"(d[61]), "+f"(d[62]), "+f"(d[63])
        : "l"(da), "l"(db), "r"(scale_d));
}

__device__ __forceinline__ constexpr uint32_t slot_off(int slot) {
    return slot < 2 ? G_RING + slot * 16384 : G_BUF + (slot - 2) * 32768 + 16384;
}
template <int NSLOT>
__device__ __forceinline__ void gemm_tile(float* acc, uint32_t sb, int tile, int it, bool first, uint32_t wpar, int wg, bool pass, uint32_t l0) {
    const uint32_t bar = sb + G_BAR;
    bar_sync(3 + wg, 256);
    int prev = 0;
#pragma unroll
    for (int k = 0; k < 4; k++) {
        const int n = tile * 4 + k, slot = NSLOT == 4 ? k : n % 3;
        const uint32_t sz = sb + (((it + k) << 4) & sb & 0x3f0);
        const uint64_t da = desc_sw128(sz + slot_off(slot), 16, 1024), db0 = desc_sw128(sz + G_W, 65536, 1024);
        if ((k & 1) == 0 && first) mbar_wait_p(bar + 8 * (GB_W0 + (k >> 1)), wpar);
        bool rel = false;
        if (EREL && k > 0 && !__all_sync(0xffffffffu, mbar_test(bar + 8 * (GB_FULL + slot), tile & 1))) {
            asm volatile("wgmma.wait_group.sync.aligned 0;" ::: "memory");
            mbar_arrive2_if(bar + 8 * (GB_EMPTY + prev), l0);
            rel = true;
        }
        mbar_wait_p(bar + 8 * (GB_FULL + slot), NSLOT == 4 ? (tile & 1) : ((n / 3) & 1));
        if (k == 3 && pass) bar_arrive(3 + (wg ^ 1), 256);
        asm volatile("wgmma.fence.sync.aligned;" ::: "memory");
#pragma unroll
        for (int kk = 0; kk < 4; kk++) wgmma_n128(acc, da + kk * 2, db0 + k * 1024 + kk * 128, (k | kk) != 0);
        asm volatile("wgmma.commit_group.sync.aligned;" ::: "memory");
        if (k > 0) {
            asm volatile("wgmma.wait_group.sync.aligned 1;" ::: "memory");
            mbar_arrive2_if(bar + 8 * (GB_EMPTY + prev), rel ? 0 : l0);
        }
#pragma unroll
        for (int kk = 0; kk < 4; kk++) wgmma_n128(acc, da + 512 + kk * 2, db0 + k * 1024 + 512 + kk * 128, 1);
        asm volatile("wgmma.commit_group.sync.aligned;" ::: "memory");
        prev = slot;
    }
    asm volatile("wgmma.wait_group.sync.aligned 0;" ::: "memory");
    mbar_arrive2_if(bar + 8 * (GB_EMPTY + prev), l0);
}
__device__ __forceinline__ void stage_bf16(const float* acc, uint32_t buf, float s0, float s1) {
    const int lane = threadIdx.x & 31, wq = (threadIdx.x >> 5) & 3;
    const int row = wq * 16 + (lane & 7) + ((lane >> 3) & 1) * 8;
    const uint32_t base = buf + row * 128;
#pragma unroll
    for (int j = 0; j < 16; j += 2) {
        const int ch = (j & 7) + (lane >> 4);
        stsm4(base + (j >> 3) * 8192 + ((ch ^ (row & 7)) << 4),
              pack2(acc[4 * j] * s0, acc[4 * j + 1] * s0), pack2(acc[4 * j + 2] * s1, acc[4 * j + 3] * s1),
              pack2(acc[4 * j + 4] * s0, acc[4 * j + 5] * s0), pack2(acc[4 * j + 6] * s1, acc[4 * j + 7] * s1));
    }
}

__device__ __forceinline__ void store_perm(const float* acc, bf16* dst, int ld, float s0, float s1) {
#pragma unroll
    for (int i = 0; i < 4; i++) {
        const float* a = acc + 16 * i;
        *(uint4*)(dst + i * 32) = make_uint4(pack2(a[0] * s0, a[1] * s0), pack2(a[4] * s0, a[5] * s0), pack2(a[8] * s0, a[9] * s0), pack2(a[12] * s0, a[13] * s0));
        *(uint4*)(dst + 8 * ld + i * 32) = make_uint4(pack2(a[2] * s1, a[3] * s1), pack2(a[6] * s1, a[7] * s1), pack2(a[10] * s1, a[11] * s1), pack2(a[14] * s1, a[15] * s1));
    }
}
template <int ACC>
__device__ __forceinline__ void wgmma_rs64(float* d, const uint32_t* a, uint64_t db) {
    asm volatile("{\n.reg .pred p;\nsetp.ne.b32 p, %37, 0;\n"
        "wgmma.mma_async.sync.aligned.m64n64k16.f32.bf16.bf16 {%0,%1,%2,%3,%4,%5,%6,%7,%8,%9,%10,%11,%12,%13,%14,%15,%16,%17,%18,%19,%20,%21,%22,%23,%24,%25,%26,%27,%28,%29,%30,%31}, {%32,%33,%34,%35}, %36, p, 1, 1, 0;\n}"
        : "+f"(d[0]), "+f"(d[1]), "+f"(d[2]), "+f"(d[3]), "+f"(d[4]), "+f"(d[5]), "+f"(d[6]), "+f"(d[7]), "+f"(d[8]), "+f"(d[9]), "+f"(d[10]), "+f"(d[11]), "+f"(d[12]), "+f"(d[13]), "+f"(d[14]), "+f"(d[15]), "+f"(d[16]), "+f"(d[17]), "+f"(d[18]), "+f"(d[19]), "+f"(d[20]), "+f"(d[21]), "+f"(d[22]), "+f"(d[23]), "+f"(d[24]), "+f"(d[25]), "+f"(d[26]), "+f"(d[27]), "+f"(d[28]), "+f"(d[29]), "+f"(d[30]), "+f"(d[31])
        : "r"(a[0]), "r"(a[1]), "r"(a[2]), "r"(a[3]), "l"(db), "n"(ACC));
}
template <int ACC>
__device__ __forceinline__ void wgmma_rs128t(float* d, const uint32_t* a, uint64_t db) {
    asm volatile("{\n.reg .pred p;\nsetp.ne.b32 p, %69, 0;\n"
        "wgmma.mma_async.sync.aligned.m64n128k16.f32.bf16.bf16 {%0,%1,%2,%3,%4,%5,%6,%7,%8,%9,%10,%11,%12,%13,%14,%15,%16,%17,%18,%19,%20,%21,%22,%23,%24,%25,%26,%27,%28,%29,%30,%31,%32,%33,%34,%35,%36,%37,%38,%39,%40,%41,%42,%43,%44,%45,%46,%47,%48,%49,%50,%51,%52,%53,%54,%55,%56,%57,%58,%59,%60,%61,%62,%63}, {%64,%65,%66,%67}, %68, p, 1, 1, 1;\n}"
        : "+f"(d[0]), "+f"(d[1]), "+f"(d[2]), "+f"(d[3]), "+f"(d[4]), "+f"(d[5]), "+f"(d[6]), "+f"(d[7]), "+f"(d[8]), "+f"(d[9]), "+f"(d[10]), "+f"(d[11]), "+f"(d[12]), "+f"(d[13]), "+f"(d[14]), "+f"(d[15]), "+f"(d[16]), "+f"(d[17]), "+f"(d[18]), "+f"(d[19]), "+f"(d[20]), "+f"(d[21]), "+f"(d[22]), "+f"(d[23]), "+f"(d[24]), "+f"(d[25]), "+f"(d[26]), "+f"(d[27]), "+f"(d[28]), "+f"(d[29]), "+f"(d[30]), "+f"(d[31]), "+f"(d[32]), "+f"(d[33]), "+f"(d[34]), "+f"(d[35]), "+f"(d[36]), "+f"(d[37]), "+f"(d[38]), "+f"(d[39]), "+f"(d[40]), "+f"(d[41]), "+f"(d[42]), "+f"(d[43]), "+f"(d[44]), "+f"(d[45]), "+f"(d[46]), "+f"(d[47]), "+f"(d[48]), "+f"(d[49]), "+f"(d[50]), "+f"(d[51]), "+f"(d[52]), "+f"(d[53]), "+f"(d[54]), "+f"(d[55]), "+f"(d[56]), "+f"(d[57]), "+f"(d[58]), "+f"(d[59]), "+f"(d[60]), "+f"(d[61]), "+f"(d[62]), "+f"(d[63])
        : "r"(a[0]), "r"(a[1]), "r"(a[2]), "r"(a[3]), "l"(db), "n"(ACC));
}
__device__ __forceinline__ void attention_tile(float* acc, uint32_t sb, int tile, int h, int wg, int wq, uint32_t l0, uint32_t epoch, uint2 rec) {
    const uint32_t buf = sb + G_BUF + ((tile << 4) & sb & 0x3f0);
    const int lane = threadIdx.x & 31, g = lane >> 2, t = lane & 3;
    const int sg = wq >> 1, hf = wq & 1, seg = tile * 2 + sg;
    uint32_t qf[8][4];
#pragma unroll
    for (int kk = 0; kk < 8; kk++) {
        qf[kk][0] = pack2(acc[8 * kk], acc[8 * kk + 1]); qf[kk][1] = pack2(acc[8 * kk + 2], acc[8 * kk + 3]);
        qf[kk][2] = pack2(acc[8 * kk + 4], acc[8 * kk + 5]); qf[kk][3] = pack2(acc[8 * kk + 6], acc[8 * kk + 7]);
    }
    uint32_t* kvf = &g_KVf[seg][h][lane * 4];
    uint4 km[4], vm[4];
    const bool early = __all_sync(0xffffffffu, (rec.x >> 8) == epoch && (rec.y >> 8) == epoch && (rec.x & 255) > seg && (rec.y & 255) > seg);
#pragma unroll
    for (int i = 0; i < 4; i++) { km[i] = ldg_rlx4_if(kvf + i * 128, early); vm[i] = ldg_rlx4_if(kvf + 512 + i * 128, early); }
    mbar_wait_p(sb + G_BAR + 8 * (GB_KV + wg), (tile >> 1) & 1);
    if (h == 5 && (threadIdx.x & 127) == 0 && tile < 6) GT(1750 + tile * 8 + 2);
    float sc[5][4];
    {
        const uint64_t dk = desc_sw128(buf, 16, 1024);
        asm volatile("wgmma.fence.sync.aligned;" ::: "memory");
#pragma unroll
        for (int kk = 0; kk < 8; kk++) {
            if (kk == 0) wgmma_rs64<0>(acc, qf[kk], dk); else wgmma_rs64<1>(acc, qf[kk], dk + (kk >> 2) * 512 + (kk & 3) * 2);
        }
        asm volatile("wgmma.commit_group.sync.aligned;" ::: "memory");
        asm volatile("wgmma.wait_group.sync.aligned 0;" ::: "memory");
        mbar_arrive_if(sb + G_BAR + 8 * GB_KVF, l0);
#pragma unroll
        for (int i = 0; i < 32; i++) asm volatile("" : "+f"(acc[i]) :: "memory");
#pragma unroll
        for (int b = 0; b < 4; b++)
#pragma unroll
            for (int i = 0; i < 4; i++) sc[b][i] = sg ? acc[16 + 4 * b + i] : acc[4 * b + i];
        sc[4][0] = sc[4][1] = sc[4][2] = sc[4][3] = 0.f;
    }
    const float cexp = 0.08838834764831845f * 1.4426950408889634f;
    const int r0 = hf * 16 + g, r1 = r0 + 8;
#pragma unroll
    for (int b = 0; b < 4; b++) {
        const int j = b * 8 + 2 * t;
        if (j > r0) sc[b][0] = -INFINITY;
        if (j + 1 > r0) sc[b][1] = -INFINITY;
        if (j > r1) sc[b][2] = -INFINITY;
        if (j + 1 > r1) sc[b][3] = -INFINITY;
    }
    float m0 = -INFINITY, m1 = -INFINITY;
#pragma unroll
    for (int b = 0; b < 4; b++) { m0 = fmaxf(m0, fmaxf(sc[b][0], sc[b][1])); m1 = fmaxf(m1, fmaxf(sc[b][2], sc[b][3])); }
    m0 = fmaxf(m0, __shfl_xor_sync(0xffffffffu, m0, 1)); m0 = fmaxf(m0, __shfl_xor_sync(0xffffffffu, m0, 2));
    m1 = fmaxf(m1, __shfl_xor_sync(0xffffffffu, m1, 1)); m1 = fmaxf(m1, __shfl_xor_sync(0xffffffffu, m1, 2));
    float z0 = 0.f, z1 = 0.f;
    {
        const float c0 = -m0 * cexp, c1 = -m1 * cexp;
        uint32_t pf[4][2];
#pragma unroll
        for (int b = 0; b < 4; b++) {
            pf[b][0] = pack2(ex2(fmaf(sc[b][0], cexp, c0)), ex2(fmaf(sc[b][1], cexp, c0)));
            pf[b][1] = pack2(ex2(fmaf(sc[b][2], cexp, c1)), ex2(fmaf(sc[b][3], cexp, c1)));
            z0 += bf_lo(pf[b][0]) + bf_hi(pf[b][0]); z1 += bf_lo(pf[b][1]) + bf_hi(pf[b][1]);
        }
        uint32_t pa[4][4];
#pragma unroll
        for (int kk = 0; kk < 4; kk++)
#pragma unroll
            for (int i = 0; i < 4; i++) pa[kk][i] = (kk >> 1) == sg ? pf[(kk & 1) * 2 + (i >> 1)][i & 1] : 0u;
        const uint64_t dv = desc_sw128(buf + 32768, 8192, 1024);
        mbar_wait_p(sb + G_BAR + 8 * (GB_VV + wg), (tile >> 1) & 1);
        asm volatile("wgmma.fence.sync.aligned;" ::: "memory");
#pragma unroll
        for (int kk = 0; kk < 4; kk++) { if (kk == 0) wgmma_rs128t<0>(acc, pa[kk], dv); else wgmma_rs128t<1>(acc, pa[kk], dv + kk * 128); }
        asm volatile("wgmma.commit_group.sync.aligned;" ::: "memory");
        asm volatile("wgmma.wait_group.sync.aligned 0;" ::: "memory");
#pragma unroll
        for (int i = 0; i < 64; i++) asm volatile("" : "+f"(acc[i]) :: "memory");
    }
    mbar_arrive_if(sb + G_BAR + 8 * GB_VF, l0);
    if (h == 5 && (threadIdx.x & 127) == 0 && tile < 6) GT(1750 + tile * 8 + 3);
    if (!early) wait_rec(&g_f.rec[2 * h], epoch, seg + 1);
    if (seg == 63 && (threadIdx.x & 63) == 0) GT(1570 + h);
    if (h == 5 && (threadIdx.x & 127) == 0 && tile < 6) GT(1750 + tile * 8 + 4);
    __syncwarp();
    {
        uint32_t n = 0;
#pragma unroll 1
        while (true) {
            uint32_t mn = 0xffffffffu;
#pragma unroll
            for (int i = 0; i < 4; i++) mn = min(min(min(mn, min(km[i].x, km[i].y)), min(km[i].z, km[i].w)), min(min(vm[i].x, vm[i].y), min(vm[i].z, vm[i].w)));
            if (__all_sync(0xffffffffu, mn != 0)) break;
            if (++n > SPIN_LIMIT) { ABORT(4); break; }
#pragma unroll
            for (int i = 0; i < 4; i++) { km[i] = ldg_rlx4(kvf + i * 128); vm[i] = ldg_rlx4(kvf + 512 + i * 128); }
        }
#pragma unroll
        for (int i = 0; i < 4; i++) {
            km[i] = make_uint4(~km[i].x, ~km[i].y, ~km[i].z, ~km[i].w); vm[i] = make_uint4(~vm[i].x, ~vm[i].y, ~vm[i].z, ~vm[i].w);
        }
        if (hf) bar_arrive(5 + wg * 2 + sg, 64);
        float sb_[4] = {0.f, 0.f, 0.f, 0.f};
#pragma unroll
        for (int i = 0; i < 4; i++) { MMA(sc[4], qf[2 * i], km[i].x, km[i].y); MMA(sb_, qf[2 * i + 1], km[i].z, km[i].w); }
#pragma unroll
        for (int i = 0; i < 4; i++) sc[4][i] += sb_[i];
        float n0 = fmaxf(sc[4][0], sc[4][1]), n1 = fmaxf(sc[4][2], sc[4][3]);
        n0 = fmaxf(n0, __shfl_xor_sync(0xffffffffu, n0, 1)); n1 = fmaxf(n1, __shfl_xor_sync(0xffffffffu, n1, 1));
        n0 = fmaxf(n0, __shfl_xor_sync(0xffffffffu, n0, 2)); n1 = fmaxf(n1, __shfl_xor_sync(0xffffffffu, n1, 2));
        n0 = fmaxf(n0, m0); n1 = fmaxf(n1, m1);
        const float a0 = ex2((m0 - n0) * cexp), a1 = ex2((m1 - n1) * cexp);
        const float c0 = -n0 * cexp, c1 = -n1 * cexp;
        const uint32_t p0 = pack2(ex2(fmaf(sc[4][0], cexp, c0)), ex2(fmaf(sc[4][1], cexp, c0)));
        const uint32_t p1 = pack2(ex2(fmaf(sc[4][2], cexp, c1)), ex2(fmaf(sc[4][3], cexp, c1)));
        z0 = fmaf(z0, a0, bf_lo(p0) + bf_hi(p0)); z1 = fmaf(z1, a1, bf_lo(p1) + bf_hi(p1));
        const uint32_t* vmw = (const uint32_t*)vm;
#pragma unroll
        for (int j = 0; j < 16; j++) {
            float* o = acc + 4 * j;
            o[0] *= a0; o[1] *= a0; o[2] *= a1; o[3] *= a1;
            mma1688(o, p0, p1, vmw[j]);
        }
        z0 += __shfl_xor_sync(0xffffffffu, z0, 1); z1 += __shfl_xor_sync(0xffffffffu, z1, 1);
        z0 += __shfl_xor_sync(0xffffffffu, z0, 2); z1 += __shfl_xor_sync(0xffffffffu, z1, 2);
    }
    if (h == 5 && (threadIdx.x & 127) == 0 && tile < 6) GT(1750 + tile * 8 + 5);
    store_perm(acc, g_O + (size_t)(tile * 64 + wq * 16 + g) * HD + h * 128 + t * 8, HD, rcpf(z0), rcpf(z1));
    if (tile >= 2) mbar_wait_p(sb + G_BAR + 8 * (GB_FREE + wg), ((tile >> 1) - 1) & 1);
    mbar_arrive(sb + G_BAR + 8 * (GB_STG + wg));
    if (!hf) {
        bar_sync(5 + wg * 2 + sg, 64);
#pragma unroll
        for (int i = 0; i < 8; i++) stg4(kvf + i * 128, make_uint4(0, 0, 0, 0));
    }
}

__device__ __forceinline__ void g_consumer(uint32_t sb_, int g_, int wg_, uint32_t epoch) {
    const uint32_t sb = uni(sb_);
    const int g = uni(g_), wg = uni(wg_), wq = uni((threadIdx.x >> 5) & 3);
    const uint32_t l0 = opaque((threadIdx.x & 31) == 0);
    const uint32_t bar = sb + G_BAR, buf = sb + G_BUF + wg * 32768;
    const int lane = threadIdx.x & 31;
    float acc[64];
    if (wg == 1) bar_arrive(3, 256);
    const int n1 = g < 32 ? HSPLIT / 2 : NT - HSPLIT / 2;
#pragma unroll 1
    for (int i = 0; i < n1; i++) {
        gemm_tile<4>(acc, sb, wg, i, i == 0 || i == NT / 2, i >= NT / 2, wg, true, l0);
        if (i == n1 - 1 || i == NT / 2 - 1) mbar_arrive_if(bar + 8 * GB_WFREE, l0);
        if (threadIdx.x == 0 && i == 0) GT((64 + g) * 8 + 1);
        if (threadIdx.x == 128 && i == 3) GT((64 + g) * 8 + 2);
        if (i > 0) mbar_wait_p(bar + 8 * (GB_FREE + wg), (i - 1) & 1);
        stage_bf16(acc, buf, 1.f, 1.f);
        asm volatile("fence.proxy.async.shared::cta;" ::: "memory");
        mbar_arrive(bar + 8 * (GB_STG + wg));
    }
    if (threadIdx.x == 128) GT((64 + g) * 8 + 3);
    if (g < 32) {
#pragma unroll 1
        for (int i = 0; i < NT / 2; i++) {
            const int tile = 2 * i + wg;
            const uint2 rec = ldg_rlx2(&g_f.rec[2 * g]);
            gemm_tile<4>(acc, sb, tile, i, i == 0, 1, wg, tile != NT - 1, l0);
            if (threadIdx.x == 0 && i == 0) GT((64 + g) * 8 + 4);
            if (threadIdx.x == 128 && i == 3) GT((64 + g) * 8 + 5);
            if (g == 5 && (threadIdx.x & 127) == 0 && tile < 6) GT(1750 + tile * 8 + 1);
            attention_tile(acc, sb, tile, g, wg, wq, l0, epoch, rec);
            if (g == 5 && (threadIdx.x & 127) == 0 && tile < 6) GT(1750 + tile * 8 + 6);
        }
    } else {
#pragma unroll 1
        for (int i = 0; i < NT / 2; i++) {
            const int tile = 2 * i + wg;
            gemm_tile<4>(acc, sb, tile, i, i == 0, 0, wg, tile != NT - 1, l0);
            if (threadIdx.x == 0 && i == 0) GT((64 + g) * 8 + 4);
            if (threadIdx.x == 128 && i == 3) GT((64 + g) * 8 + 5);
            store_perm(acc, g_P + (size_t)(((g - 32) >> 2) * SQ + tile * 64 + wq * 16 + (lane >> 2)) * DM + ((g - 32) & 3) * 128 + (lane & 3) * 8, DM, 1.f, 1.f);
            mbar_wait_p(bar + 8 * (GB_FREE + wg), (i - 1) & 1);
            mbar_arrive(bar + 8 * (GB_STG + wg));
        }
    }
}

__device__ __forceinline__ void load_w(uint32_t sb, const CUtensorMap* tm, int col, int row, int k0 = 0, int k1 = 2) {
    const uint32_t bar = sb + G_BAR;
#pragma unroll
    for (int kh = k0; kh < k1; kh++) {
        mbar_expect_tx(bar + 8 * (GB_W0 + kh), 65536);
        tma2d(sb + G_W + kh * 32768, tm, col, row + kh * 256, bar + 8 * (GB_W0 + kh));
        tma2d(sb + G_W + 65536 + kh * 32768, tm, col + 64, row + kh * 256, bar + 8 * (GB_W0 + kh));
    }
}

__device__ __forceinline__ void rbf2(float& a, float& b) { uint32_t w = pack2(a, b); a = bf_lo(w); b = bf_hi(w); }
__device__ __forceinline__ void warp_sum2(float& a, float& b) {
#pragma unroll
    for (int o = 16; o; o >>= 1) { float c = __shfl_xor_sync(0xffffffffu, a, o), d = __shfl_xor_sync(0xffffffffu, b, o); a += c; b += d; }
}
__device__ __forceinline__ float sum16(const float* v) {
    return (((v[0] + v[1]) + (v[2] + v[3])) + ((v[4] + v[5]) + (v[6] + v[7]))) + (((v[8] + v[9]) + (v[10] + v[11])) + ((v[12] + v[13]) + (v[14] + v[15])));
}
__device__ __forceinline__ void ln_row2(float* v, float* u) {
    float sv = sum16(v), su = sum16(u);
    warp_sum2(sv, su);
    const float mv = sv * (1.f / DM), mu = su * (1.f / DM);
    float qv = 0.f, qu = 0.f, qv2 = 0.f, qu2 = 0.f;
#pragma unroll
    for (int i = 0; i < 16; i += 2) {
        float d0 = v[i] - mv, d1 = v[i + 1] - mv, e0 = u[i] - mu, e1 = u[i + 1] - mu;
        qv = fmaf(d0, d0, qv); qv2 = fmaf(d1, d1, qv2); qu = fmaf(e0, e0, qu); qu2 = fmaf(e1, e1, qu2);
    }
    qv += qv2; qu += qu2;
    warp_sum2(qv, qu);
    const float rv = rbf(mv), ru = rbf(mu);
    const float iv = __frcp_rn(rbf(sqrtf(rbf(rbf(qv * (1.f / DM)) + 1e-5f)))), iu = __frcp_rn(rbf(sqrtf(rbf(rbf(qu * (1.f / DM)) + 1e-5f))));
#pragma unroll
    for (int i = 0; i < 16; i += 2) {
        float a = v[i] - rv, b = v[i + 1] - rv, c = u[i] - ru, d = u[i + 1] - ru;
        rbf2(a, b); rbf2(c, d);
        a *= iv; b *= iv; c *= iu; d *= iu;
        rbf2(a, b); rbf2(c, d);
        v[i] = a; v[i + 1] = b; u[i] = c; u[i + 1] = d;
    }
}

__device__ __forceinline__ void ln_row1(float* v) {
    float sv = sum16(v);
#pragma unroll
    for (int o = 16; o; o >>= 1) sv += __shfl_xor_sync(0xffffffffu, sv, o);
    const float mv = sv * (1.f / DM);
    float qv = 0.f, qv2 = 0.f;
#pragma unroll
    for (int i = 0; i < 16; i += 2) { float d0 = v[i] - mv, d1 = v[i + 1] - mv; qv = fmaf(d0, d0, qv); qv2 = fmaf(d1, d1, qv2); }
    qv += qv2;
#pragma unroll
    for (int o = 16; o; o >>= 1) qv += __shfl_xor_sync(0xffffffffu, qv, o);
    const float rv = rbf(mv);
    float sq, iv;
    asm("sqrt.approx.f32 %0, %1;" : "=f"(sq) : "f"(rbf(rbf(qv * (1.f / DM)) + 1e-5f)));
    asm("rcp.approx.f32 %0, %1;" : "=f"(iv) : "f"(rbf(sq)));
#pragma unroll
    for (int i = 0; i < 16; i += 2) {
        float a = v[i] - rv, b = v[i + 1] - rv;
        rbf2(a, b);
        a *= iv; b *= iv;
        rbf2(a, b);
        v[i] = a; v[i + 1] = b;
    }
}
constexpr int FSPLIT = 28;
__device__ __forceinline__ int fin_row(int id, int i) {
    if (id < 64) { const int tile = i < FSPLIT / 2 ? 2 * i : i + FSPLIT / 2; return tile < NT ? tile * 64 + id : -1; }
    const int j = id - 64 + i * 48;
    return j < FSPLIT * 32 ? (j >> 6) * 128 + 64 + (j & 63) : -1;
}
__device__ __forceinline__ void finalizer(int id, const bf16* __restrict__ x, const bf16* __restrict__ wr, bf16* __restrict__ out, uint32_t epoch) {
    const int lane = threadIdx.x & 31;
    float b0 = -INFINITY, b1 = -INFINITY; int i0 = 0x7fffffff, i1 = 0x7fffffff;
    const uint32_t tag = (epoch & 0xfffffu) << 12;
    uint32_t fl = ~epoch;
    int row = fin_row(id, 0);
    const uint4 ra = *(const uint4*)(wr + lane * 8), rb = *(const uint4*)(wr + 256 + lane * 8);
    uint4 xa = *(const uint4*)(x + (size_t)row * DM + lane * 8), xb = *(const uint4*)(x + (size_t)row * DM + lane * 8 + 256);
#pragma unroll 1
    for (int it = 0; row >= 0; it++) {
        const int tile = row >> 6, nxt = fin_row(id, it + 1);
        const size_t o0 = (size_t)row * DM + lane * 8;
        uint32_t n = 0;
#pragma unroll 1
        while (!__all_sync(0xffffffffu, fl == epoch)) {
            if (n) __nanosleep(it ? 64 : 1000);
            fl = ldg_rlx(&g_f.p[tile][lane]);
            if (++n > SPIN_LIMIT) { ABORT(12); break; }
        }
        if (tile == NT - 1 && id == 63 && lane == 0) GT(1438);
        if ((id == 63 || id == 3 || id == 70) && lane == 0) GT(1800 + (id == 3) * 32 + tile);
        float v[16];
        {
            uint4 pa[8][2];
#pragma unroll
            for (int k = 0; k < 8; k++) {
                pa[k][0] = ldg_rlx4((const uint32_t*)(g_P + (size_t)k * SQ * DM + o0));
                pa[k][1] = ldg_rlx4((const uint32_t*)(g_P + (size_t)k * SQ * DM + o0 + 256));
            }
            fl = ldg_rlx(&g_f.p[max(nxt, 0) >> 6][lane]);
#pragma unroll
            for (int j = 0; j < 2; j++) {
#pragma unroll
                for (int i = 0; i < 4; i++) {
                    uint32_t w[8];
#pragma unroll
                    for (int k = 0; k < 8; k++) w[k] = i == 0 ? pa[k][j].x : (i == 1 ? pa[k][j].y : (i == 2 ? pa[k][j].z : pa[k][j].w));
                    v[j * 8 + 2 * i] = ((bf_lo(w[0]) + bf_lo(w[1])) + (bf_lo(w[2]) + bf_lo(w[3]))) + ((bf_lo(w[4]) + bf_lo(w[5])) + (bf_lo(w[6]) + bf_lo(w[7])));
                    v[j * 8 + 2 * i + 1] = ((bf_hi(w[0]) + bf_hi(w[1])) + (bf_hi(w[2]) + bf_hi(w[3]))) + ((bf_hi(w[4]) + bf_hi(w[5])) + (bf_hi(w[6]) + bf_hi(w[7])));
                }
            }
        }
        uint32_t hw[8];
        {
            const uint32_t xw[8] = {xa.x, xa.y, xa.z, xa.w, xb.x, xb.y, xb.z, xb.w};
            uint32_t aw[8];
#pragma unroll
            for (int i = 0; i < 8; i++) aw[i] = pack2(v[2 * i], v[2 * i + 1]);
#pragma unroll
            for (int d = 1; d <= 2; d++) {
                const bool up = lane & d;
#pragma unroll
                for (int i = 0; i < 8; i++) {
                    if (!(i & d)) {
                        const uint32_t r = __shfl_xor_sync(0xffffffffu, up ? aw[i] : aw[i | d], d);
                        if (up) aw[i] = r; else aw[i | d] = r;
                    }
                }
            }
#pragma unroll
            for (int i = 0; i < 8; i++) {
                hw[i] = pack2(bf_lo(aw[i]) + bf_lo(xw[i]), bf_hi(aw[i]) + bf_hi(xw[i]));
                v[2 * i] = bf_lo(hw[i]); v[2 * i + 1] = bf_hi(hw[i]);
            }
        }
        xa = *(const uint4*)(x + (size_t)max(nxt, 0) * DM + lane * 8); xb = *(const uint4*)(x + (size_t)max(nxt, 0) * DM + lane * 8 + 256);
        ln_row1(v);
        float r0 = 0.f, r1 = 0.f;
        {
            const uint32_t ww[8] = {ra.x, ra.y, ra.z, ra.w, rb.x, rb.y, rb.z, rb.w};
#pragma unroll
            for (int i = 0; i < 8; i++) { r0 = fmaf(v[2 * i], bf_lo(ww[i]), r0); r1 = fmaf(v[2 * i + 1], bf_hi(ww[i]), r1); }
        }
        r0 += r1;
#pragma unroll
        for (int o = 16; o; o >>= 1) r0 += __shfl_xor_sync(0xffffffffu, r0, o);
        r0 = rbf(r0);
        if (cand_better(r0, row, b0, i0)) { b1 = b0; i1 = i0; b0 = r0; i0 = row; }
        else if (cand_better(r0, row, b1, i1)) { b1 = r0; i1 = row; }
        if (tile == NT - 1 && id == 63 && lane == 0) GT(1439);
        const bool last = nxt < 0, spec = tile < SPEC_TILES && (last || (nxt >> 6) >= SPEC_TILES);
        const bool pub = (lane == 0 && spec) || (lane == 1 && last);
        if (pub)
            asm volatile("st.relaxed.gpu.global.v4.b32 [%0], {%1,%2,%3,%4};" :: "l"(&g_f.cand[lane][id]),
                         "r"(FU(b0)), "r"(tag | (uint32_t)min(i0, 4095)), "r"(FU(b1)), "r"(tag | (uint32_t)min(i1, 4095)) : "memory");
#pragma unroll
        for (int j = 0; j < 2; j++) {
            const uint32_t* hh = hw + j * 4; const float* nn = v + j * 8;
            *(uint4*)(out + o0 + j * 256) = make_uint4(pack2(bf_lo(hh[0]) + nn[0], bf_hi(hh[0]) + nn[1]), pack2(bf_lo(hh[1]) + nn[2], bf_hi(hh[1]) + nn[3]),
                                                       pack2(bf_lo(hh[2]) + nn[4], bf_hi(hh[2]) + nn[5]), pack2(bf_lo(hh[3]) + nn[6], bf_hi(hh[3]) + nn[7]));
            *(uint4*)(g_h + o0 + j * 256) = make_uint4(hh[0], hh[1], hh[2], hh[3]);
            *(uint4*)(g_hn + o0 + j * 256) = make_uint4(pack2(nn[0], nn[1]), pack2(nn[2], nn[3]), pack2(nn[4], nn[5]), pack2(nn[6], nn[7]));
        }
        if (last || spec) {
            __threadfence();
            __syncwarp();
            if (pub) stg_rlx(&g_f.rows[lane][id], epoch);
        }
        row = nxt;
    }
    if (id == 0 && lane == 0) { g_epoch = epoch; if (epoch == 0xffffffu) { g_ticket[0] = 0; g_ticket[32] = 0; } }
}

__device__ __forceinline__ void g_producer(uint32_t sb, int g, const Maps& maps, uint32_t epoch, const bf16* __restrict__ x, const bf16* __restrict__ wr, bf16* __restrict__ out) {
    const uint32_t bar = sb + G_BAR;
    const int warp = (threadIdx.x >> 5) - 8;
    if (threadIdx.x == 256 && g == 5) GT(1410);
    if (threadIdx.x == 256 && g == 5) GT(1411);
    if (warp == 3) {
        wait_eq4(&g_f.xn[(threadIdx.x & 31) * 4], epoch, 13);
        __syncwarp();
        if ((threadIdx.x & 31) == 0) mbar_arrive(bar + 8 * GB_XN);
        wait_eq2(&g_f.rload[(threadIdx.x & 31) * 2], epoch, 13);
        __syncwarp();
        if ((threadIdx.x & 31) == 0) mbar_arrive(bar + 8 * GB_RL);
        finalizer(g, x, wr, out, epoch);
        if (g == 63 && (threadIdx.x & 31) == 0) GT(128 * 8 + 6);
    }
    if ((threadIdx.x & 31) != 0) return;
    if (threadIdx.x == 256 && g == 5) GT(1412);
    if (warp == 0) {
        wait_eq4(&g_f.xn[0], epoch, 13);
        const int rk = g & 1;
        const int m1 = g < 32 ? HSPLIT : 2 * NT - HSPLIT;
#pragma unroll 1
        for (int it = 0; it < m1; it++) {
            const int tile = it < NT ? it : it - NT + HSPLIT;
            if (it == HOLD) mbar_wait(bar + 8 * GB_RL, 0);
            if (it == 1) wait_eq4(&g_f.xn[4], epoch, 13);
            if (it == 2) mbar_wait(bar + 8 * GB_XN, 0);
            if (it == NT) {
                mbar_wait(bar + 8 * GB_WFREE, 0);
                load_w(sb, (g & 1) ? &maps.wv : &maps.wk, ((g - 32) >> 1) * 128, 0);
            }
#pragma unroll
            for (int k = 0; k < 4; k++) {
                if (k == 2 && it == 0) load_w(sb, (g & 1) ? &maps.wv : &maps.wk, (g >> 1) * 128, 0, 1, 2);
                mbar_wait(bar + 8 * (GB_EMPTY + k), (it & 1) ^ 1);
                mbar_expect_tx(bar + 8 * (GB_FULL + k), 16384);
                tma2d_mc(sb + slot_off(k) + rk * 8192, &maps.xn2, (k * 2 + rk) * 64, tile * 64, bar + 8 * (GB_FULL + k));
            }
        }
        mbar_wait(bar + 8 * GB_WFREE, g >= 32);
        const int u = g - 32, ks = u >> 2, ns = u & 3;
        if (g < 32) load_w(sb, &maps.wq, g * 128, 0);
        else {
#pragma unroll
            for (int kh = 0; kh < 2; kh++) {
                mbar_expect_tx(bar + 8 * (GB_W0 + kh), 65536);
#pragma unroll
                for (int nh = 0; nh < 2; nh++)
                    asm volatile("cp.async.bulk.tensor.5d.shared::cluster.global.mbarrier::complete_tx::bytes [%0], [%1, {%3, %4, %4, %4, %5}], [%2];"
                        :: "r"(sb + G_W + nh * 65536 + kh * 32768), "l"((uint64_t)&maps.wo2), "r"(bar + 8 * (GB_W0 + kh)), "r"(ns * 128 + nh * 64), "r"(0), "r"(ks * 16 + kh * 8) : "memory");
            }
        }
        if (g < 32) {
#pragma unroll 1
            for (int n = 0; n < NT * 4; n++) {
                const int slot = n & 3;
                mbar_wait(bar + 8 * (GB_EMPTY + slot), ((n >> 2) & 1) ^ 1);
                mbar_expect_tx(bar + 8 * (GB_FULL + slot), 16384);
                tma2d_mc(sb + slot_off(slot) + rk * 8192, &maps.xn2, (slot * 2 + rk) * 64, (n >> 2) * 64, bar + 8 * (GB_FULL + slot));
            }
        } else {
#pragma unroll 1
            for (int tile = 0; tile < NT; tile++) {
                wait_eq4(&g_f.o[tile][ks][0], epoch, 9);
                if (g == 40 && tile == NT - 1) GT(1437);
                if (tile == NT - 1) GT(1690 + g - 32);
#pragma unroll
                for (int k = 0; k < 4; k++) {
                    mbar_wait(bar + 8 * (GB_EMPTY + k), (tile & 1) ^ 1);
                    mbar_expect_tx(bar + 8 * (GB_FULL + k), 16384);
                    tma2d_mc(sb + slot_off(k) + rk * 8192, &maps.ox2, (ks * 8 + k * 2 + rk) * 64, tile * 64, bar + 8 * (GB_FULL + k));
                }
            }
        }
    } else if (warp < 3) {
        const int wg = warp - 1;
        const uint32_t buf = sb + G_BUF + wg * 32768;
        const CUtensorMap* tkv = (g & 1) ? &maps.vx3 : &maps.kx3;
        const int n1 = g < 32 ? HSPLIT / 2 : NT - HSPLIT / 2;
#pragma unroll 1
        for (int i = 0; i < n1; i++) {
            const int tile = (i < NT / 2 ? 2 * i : 2 * i - NT + HSPLIT) + wg, hd = (i < NT / 2 ? g : g - 32) >> 1;
            mbar_wait(bar + 8 * (GB_STG + wg), i & 1);
            tma_store3d(tkv, buf, tile * 64, hd * 2);
            asm volatile("cp.async.bulk.commit_group;" ::: "memory");
            asm volatile("cp.async.bulk.wait_group.read 0;" ::: "memory");
            mbar_arrive(bar + 8 * (GB_FREE + wg));
            asm volatile("cp.async.bulk.wait_group 0;" ::: "memory");
            PUBLISH(&g_f.kv[tile][hd][g & 1], epoch);
        }
        if (wg == 0) mbar_arrive(bar + 8 * GB_T1D);
        if (g < 32 && wg == 1) {
            mbar_wait(bar + 8 * GB_T1D, 0);
#pragma unroll 1
            for (int tile = 0; tile < NT; tile++) {
                wait_eq2(&g_f.kv[tile][g][0], epoch, 10);
                if (tile > 0) mbar_wait(bar + 8 * GB_KVF, (tile - 1) & 1);
                mbar_expect_tx(bar + 8 * (GB_KV + (tile & 1)), 16384);
                tma3d(sb + G_BUF, &maps.kx3, tile * 64, g * 2, bar + 8 * (GB_KV + (tile & 1)));
                if (tile > 0) mbar_wait(bar + 8 * GB_VF, (tile - 1) & 1);
                mbar_expect_tx(bar + 8 * (GB_VV + (tile & 1)), 16384);
                tma3d(sb + G_BUF + 32768, &maps.vx3, tile * 64, g * 2, bar + 8 * (GB_VV + (tile & 1)));
                if (PFK && tile + PFK < NT) {
                    const uint2 v = ldg_rlx2(&g_f.kv[tile + PFK][g][0]);
                    if (v.x == epoch && v.y == epoch) { tma_pf3d(&maps.kx3, (tile + PFK) * 64, g * 2); tma_pf3d(&maps.vx3, (tile + PFK) * 64, g * 2); }
                }
            }
        } else {
#pragma unroll 1
            for (int tile = g < 32 ? 0 : wg; tile < NT; tile += g < 32 ? 1 : 2) {
                mbar_wait(bar + 8 * (GB_STG + (tile & 1)), (tile >> 1) & 1);
                mbar_arrive(bar + 8 * (GB_FREE + (tile & 1)));
                PUBLISH(g < 32 ? &g_f.o[tile][g >> 2][g & 3] : &g_f.p[tile][g - 32], epoch);
                if (g == 3 && tile == NT - 1) GT(1436);
                if (g == 3) GT(1896 + tile);
                if (g < 32 && tile == NT - 1) GT(1610 + g);
                if (g == 40 && tile == NT - 1) GT(1435);
                if (g == 40) GT(1864 + tile);
                if (g >= 32 && tile == NT - 1) GT(1650 + g - 32);
            }
        }
    }
}

struct WPtr { const bf16 *q, *k, *v, *o; };
__device__ __forceinline__ int startup(uint8_t* smem, const bf16* __restrict__ x, const Maps& maps, uint32_t& epoch, const WPtr& pw) {
    const int tid = threadIdx.x, lane = tid & 31, w = tid >> 5, cta = blockIdx.x;
    volatile uint32_t* sh = (volatile uint32_t*)(smem + SH_OFF);
    if (cta == 4 && tid == 0) GT(1399);
    epoch = (ldg_rlx(&g_epoch) + 1) & 0x00ffffffu;
    if (w < 4) {
        if (!(cta & 1)) {
            uint32_t* pp = (uint32_t*)(xpage() + ((XR3 ^ 0x3000u) ^ ((w == 1 || w == 2) ? 0x1000u : 0u) ^ ((w & 2) << 13))) + (cta >> 1) * 8;
            if (lane < 8) stg_rlx(pp + lane, 0u);
            __syncwarp();
            if (lane == 0) {
                uint32_t best = 0xffffffffu, a = 0;
#pragma unroll 1
                for (int r = 0; r < NPROBE; r++) {
                    uint32_t t0 = clk32();
                    asm volatile("atom.relaxed.gpu.global.add.u32 %0, [%1], %2;" : "=r"(a) : "l"(pp), "r"(a + 1) : "memory");
                    if (a == 0x7fffffffu) ABORT(15);
                    uint32_t t1 = clk32();
                    if (r > 0) best = min(best, t1 - t0);
                    else if (w == 0) {
                        asm volatile("red.relaxed.gpu.global.max.u32 [%0], %1;" :: "l"(&g_ticket[0]), "r"(epoch << 8) : "memory");
                        asm volatile("red.relaxed.gpu.global.max.u32 [%0], %1;" :: "l"(&g_ticket[32]), "r"(epoch << 8) : "memory");
                    }
                }
                sh[w] = best;
            }
        }
        if (!(cta & 1)) bar_sync(1, 128);
        if (cta == 4 && tid == 0) GT(1400);
        if (w == 0) {
            if (lane == 0) {
                uint32_t rp;
                if (!(cta & 1)) {
                    uint32_t a = sh[0], b = sh[1], c = sh[2], d = sh[3];
                    uint32_t mid = (min(min(a, b), min(c, d)) + max(max(a, b), max(c, d))) >> 1;
                    const int dd = (int)min(a, d) - (int)min(b, c);
                    uint32_t cls = abs(dd) > 60 ? dd > 0 : a > mid;
                    uint32_t t = atomicAdd(&g_ticket[cls * 32], 1u) & 255;
                    if (t >= (cls ? 34u : 32u)) { cls ^= 1; t = atomicAdd(&g_ticket[cls * 32], 1u) & 255; }
                    rp = min(cls ? 32 + t : t, 65u);
                    stg_rlx(&g_table[(cta >> 1) * 8], (epoch << 8) | rp);
                } else {
                    uint32_t v, n = 0;
#pragma unroll 1
                    while (((v = ldg_rlx(&g_table[(cta >> 1) * 8])) >> 8) != epoch) { if (++n > SPIN_LIMIT) { ABORT(14); break; } }
                    rp = v & 255;
                }
                const int role = rp * 2 + (cta & 1);
                sh[8] = role; sh[9] = epoch;
                while (sh[10] != epoch + 1 && cta < NWAITLN) {}
                if (role < 64) rec_first_loads(smem_u32(smem), role, maps);
                else if (role < 128) load_w(smem_u32(smem), (role & 1) ? &maps.wv : &maps.wk, ((role - 64) >> 1) * 128, 0, 0, 1);
                if (cta == 4) GT(1401);
            }
        }
    } else if (cta < 128) {
        uint4 u[2][2];
        const int row0 = cta * 16 + (w - 4) * 2;
#pragma unroll
        for (int r = 0; r < 2; r++)
#pragma unroll
            for (int j = 0; j < 2; j++) u[r][j] = *(const uint4*)(x + (size_t)(row0 + r) * DM + j * 256 + lane * 8);
        if (cta < 48) {
            const uint32_t b = cta >> 3, off = (b >= 4 ? 0x8000u + (b & 1) * 0x4000u : ((b & 1) ? 0x3000u : 0u) + ((b & 2) << 13)) ^ aslot(cta & 7);
            *(uint4*)(xpage() + off + (tid - 128) * 16) = make_uint4(0, 0, 0, 0);
        }
        float v[2][16];
#pragma unroll
        for (int r = 0; r < 2; r++)
#pragma unroll
            for (int j = 0; j < 2; j++) {
                uint32_t ww[4] = {u[r][j].x, u[r][j].y, u[r][j].z, u[r][j].w};
#pragma unroll
                for (int i = 0; i < 4; i++) { v[r][j * 8 + 2 * i] = bf_lo(ww[i]); v[r][j * 8 + 2 * i + 1] = bf_hi(ww[i]); }
            }
        ln_row2(v[0], v[1]);
#pragma unroll
        for (int r = 0; r < 2; r++)
#pragma unroll
            for (int j = 0; j < 2; j++)
                *(uint4*)(g_xn + (size_t)(row0 + r) * DM + j * 256 + lane * 8) =
                    make_uint4(pack2(v[r][j * 8], v[r][j * 8 + 1]), pack2(v[r][j * 8 + 2], v[r][j * 8 + 3]), pack2(v[r][j * 8 + 4], v[r][j * 8 + 5]), pack2(v[r][j * 8 + 6], v[r][j * 8 + 7]));
        bar_sync(2, 256);
        if (tid == 160 && cta < NWAITLN) { st_rel(&g_f.xn[cta], epoch); sh[10] = epoch + 1; }
        if (cta == 4 && tid == 160) GT(1403);
        __syncwarp();
    }
    if (cta == 4 && tid == 128) GT(1402);
    __syncthreads();
    if (tid == 160 && cta >= NWAITLN && cta < 128) st_rel(&g_f.xn[cta], epoch);
    __syncwarp();
    const int role = sh[8];
    return role;
}

__global__ void __cluster_dims__(2, 1, 1) __launch_bounds__(384, 1)
main_kernel(const __grid_constant__ Maps maps, const bf16* __restrict__ x, const bf16* __restrict__ mem0, const bf16* __restrict__ wr,
            const bf16* __restrict__ wd, bf16* __restrict__ out, const WPtr pw) {
    extern __shared__ __align__(1024) uint8_t smem[];
    const uint32_t sb = smem_u32(smem);
    if (threadIdx.x == 0) {
        for (int i = 0; i < MB_N; i++) mbar_init(sb + R_BAR + 8 * i, i == MB_V ? 5 : 1);
        for (int i = 0; i < GB_N; i++)
            mbar_init(sb + G_BAR + 8 * i, i == GB_WFREE || (i >= GB_EMPTY && i < GB_KV) ? 8 : (i >= GB_KVF ? 4 : (i >= GB_STG && i < GB_FREE ? 128 : 1)));
        asm volatile("fence.mbarrier_init.release.cluster;" ::: "memory");
    }
    __syncwarp();
    asm volatile("barrier.cluster.arrive.relaxed.aligned;" ::: "memory");
    if (threadIdx.x >= 352 && threadIdx.x < 352 + (int)(sizeof(Maps) / sizeof(CUtensorMap)))
        asm volatile("prefetch.tensormap [%0];" :: "l"((const CUtensorMap*)&maps + (threadIdx.x - 352)) : "memory");
    uint32_t epoch;
    asm volatile("fence.proxy.async.shared::cta;" ::: "memory");
    const int role = uni(startup(smem, x, maps, epoch, pw));
    asm volatile("barrier.cluster.wait.aligned;" ::: "memory");
    const int wg = uni(threadIdx.x >> 7);
    if (role < 64) {
#define SETREG(n) do { if ((n) < 168) asm volatile("setmaxnreg.dec.sync.aligned.u32 %0;" :: "n"(n)); if ((n) > 168) asm volatile("setmaxnreg.inc.sync.aligned.u32 %0;" :: "n"(n)); } while (0)
#define RESREG(n) do { if ((n) < 168) asm volatile("setmaxnreg.inc.sync.aligned.u32 168;"); if ((n) > 168) asm volatile("setmaxnreg.dec.sync.aligned.u32 168;"); } while (0)
        if (wg == WGA) {
            SETREG(RGA);
            rec_a(sb, role, mem0, epoch);
            RESREG(RGA);
        } else if (wg == WGB) {
            SETREG(RGB);
            rec_b(sb, role, epoch);
            RESREG(RGB);
        } else {
            SETREG(RGC);
            rec_c(sb, role, mem0, maps, epoch);
            RESREG(RGC);
        }
        ffn_phase(maps, wd, out);
        if (threadIdx.x == 0) GT(((volatile int*)(smem + SH_OFF))[8] * 8 + 6);
    } else if (role < 128) {
        if (wg < 2) {
            asm volatile("setmaxnreg.inc.sync.aligned.u32 192;");
            g_consumer(sb, role - 64, wg, epoch);
            if (threadIdx.x == 128) GT(role * 8 + 6);
        } else {
            asm volatile("setmaxnreg.dec.sync.aligned.u32 120;");
            g_producer(sb, role - 64, maps, epoch, x, wr, out);
        }
    } else {
        finalizer(64 + (threadIdx.x >> 5) * 4 + role - 128, x, wr, out, epoch);
    }
}

typedef CUresult (*EncodeFn)(CUtensorMap*, CUtensorMapDataType, cuuint32_t, void*, const cuuint64_t*, const cuuint64_t*, const cuuint32_t*, const cuuint32_t*,
                             CUtensorMapInterleave, CUtensorMapSwizzle, CUtensorMapL2promotion, CUtensorMapFloatOOBfill);
static void make_map3(EncodeFn fn, CUtensorMap* m, const void* ptr, uint64_t cols, uint64_t rows) {
    cuuint64_t dims[3] = {64, rows, cols / 64};
    cuuint64_t strides[2] = {cols * 2, 128};
    cuuint32_t box[3] = {64, 64, 2};
    cuuint32_t es[3] = {1, 1, 1};
    fn(m, CU_TENSOR_MAP_DATA_TYPE_BFLOAT16, 3, (void*)ptr, dims, strides, box, es, CU_TENSOR_MAP_INTERLEAVE_NONE, CU_TENSOR_MAP_SWIZZLE_128B,
       CU_TENSOR_MAP_L2_PROMOTION_L2_256B, CU_TENSOR_MAP_FLOAT_OOB_FILL_NONE);
}
static void make_map(EncodeFn fn, CUtensorMap* m, const void* ptr, uint64_t cols, uint64_t rows, uint32_t bcols, uint32_t brows,
                     bool f32 = false, CUtensorMapSwizzle sw = CU_TENSOR_MAP_SWIZZLE_128B) {
    cuuint64_t dims[2] = {cols, rows};
    cuuint64_t strides[1] = {cols * (f32 ? 4 : 2)};
    cuuint32_t box[2] = {bcols, brows};
    cuuint32_t es[2] = {1, 1};
    fn(m, f32 ? CU_TENSOR_MAP_DATA_TYPE_FLOAT32 : CU_TENSOR_MAP_DATA_TYPE_BFLOAT16, 2, (void*)ptr, dims, strides, box, es, CU_TENSOR_MAP_INTERLEAVE_NONE, sw,
       CU_TENSOR_MAP_L2_PROMOTION_L2_256B, CU_TENSOR_MAP_FLOAT_OOB_FILL_NONE);
}

extern "C" void kernel_launch(void* const* d_in, const int* in_sizes, int n_in, void* d_out, int out_size) {
    const bf16* x = (const bf16*)d_in[0];
    const bf16* mem0 = (const bf16*)d_in[1];
    const bf16* Wq = (const bf16*)d_in[2];
    const bf16* Wk = (const bf16*)d_in[3];
    const bf16* Wv = (const bf16*)d_in[4];
    const bf16* Wo = (const bf16*)d_in[5];
    const bf16* wr = (const bf16*)d_in[8];
    const bf16* wg = (const bf16*)d_in[9];
    const bf16* wu = (const bf16*)d_in[10];
    const bf16* wd = (const bf16*)d_in[11];
    bf16* out = (bf16*)d_out;

    static EncodeFn enc = nullptr;
    static void *pxn, *pK, *pV, *pO, *pacc;
    if (!enc) {
        cudaDriverEntryPointQueryResult qr;
        void* fn = nullptr;
        cudaGetDriverEntryPoint("cuTensorMapEncodeTiled", &fn, cudaEnableDefault, &qr);
        enc = (EncodeFn)fn;
        cudaGetSymbolAddress(&pxn, g_xn); cudaGetSymbolAddress(&pK, g_K); cudaGetSymbolAddress(&pV, g_V);
        cudaGetSymbolAddress(&pO, g_O); cudaGetSymbolAddress(&pacc, g_P);
        cudaFuncSetAttribute(main_kernel, cudaFuncAttributeMaxDynamicSharedMemorySize, SMEM_TOTAL);
    }
    Maps m;
    make_map(enc, &m.wq, Wq, HD, DM, 64, 256);
    make_map(enc, &m.wk, Wk, HD, DM, 64, 256);
    make_map(enc, &m.wv, Wv, HD, DM, 64, 256);
    make_map(enc, &m.wo, Wo, DM, HD, 64, 128);
    {
        cuuint64_t dims[5] = {DM, 2, 4, 4, HD / 32};
        cuuint64_t strides[4] = {DM * 2, 8 * DM * 2, 2 * DM * 2, 32 * DM * 2};
        cuuint32_t box[5] = {64, 2, 4, 4, 8};
        cuuint32_t es[5] = {1, 1, 1, 1, 1};
        enc(&m.wo2, CU_TENSOR_MAP_DATA_TYPE_BFLOAT16, 5, (void*)Wo, dims, strides, box, es, CU_TENSOR_MAP_INTERLEAVE_NONE, CU_TENSOR_MAP_SWIZZLE_128B,
            CU_TENSOR_MAP_L2_PROMOTION_L2_256B, CU_TENSOR_MAP_FLOAT_OOB_FILL_NONE);
    }
    make_map(enc, &m.kx, pK, HD, SQ, 64, 64);
    make_map(enc, &m.ox2, pO, HD, SQ, 64, 64);
    make_map(enc, &m.xn2, pxn, DM, SQ, 64, 64);
    make_map3(enc, &m.kx3, pK, HD, SQ); make_map3(enc, &m.vx3, pV, HD, SQ);
    make_map(enc, &m.wg, wg, FF, DM, 32, 256, false, CU_TENSOR_MAP_SWIZZLE_NONE);
    make_map(enc, &m.wu, wu, FF, DM, 32, 256, false, CU_TENSOR_MAP_SWIZZLE_NONE);

    cudaStream_t st = cudaStreamPerThread;
    main_kernel<<<NCTA, 384, SMEM_TOTAL, st>>>(m, x, mem0, wr, wd, out, WPtr{Wq, Wk, Wv, Wo});
}
```

```cpp
#include <cuda_runtime.h>
#include <cuda_bf16.h>
#include <cuda.h>
#include <stdint.h>
#include <stddef.h>

typedef __nv_bfloat16 bf16;

constexpr int SQ = 2048, DM = 512, NH = 32, DH = 128, NSEG = 64, HD = 4096, FF = 1792;

constexpr int NT = 32;
#define SPEC_TILES 30
__device__ __align__(1024) bf16 g_xn[SQ * DM];
__device__ __align__(1024) bf16 g_K[SQ * HD];
__device__ __align__(1024) bf16 g_V[SQ * HD];
__device__ __align__(1024) bf16 g_O[SQ * HD];
__device__ __align__(1024) uint32_t g_KVf[NSEG][NH][1024];
__device__ __align__(1024) bf16 g_P[8 * SQ * DM];
__device__ __align__(1024) bf16 g_h[SQ * DM];
__device__ __align__(1024) bf16 g_hn[SQ * DM];
__device__ uint8_t g_xraw[12 << 20];
#define XPG 0
__device__ __forceinline__ uint64_t xpage() { return (((uint64_t)g_xraw + (2 << 20) - 1) & ~(uint64_t)((2 << 20) - 1)) + ((uint64_t)XPG << 21); }
constexpr uint32_t XR3 = (1u << 20) | (1u << 19) | (1u << 12);
__device__ __forceinline__ uint32_t aslot(uint32_t s) { return ((s & 1) << 18) | ((s & 2) << 19) | ((s & 4) * 0xc000u); }
__device__ __forceinline__ uint32_t acc_base(uint32_t W) { return ((W & 2) ? 0x3000u : 0u) + ((W & 4) << 12) + (W & 1) * 2048; }
__device__ __forceinline__ uint32_t ext_base(uint32_t W) { return 0x8000u + ((W & 4) << 12) + (W & 3) * 1024; }
#define XHS 256
#define XSS 32
__device__ __forceinline__ uint32_t zero_off(uint32_t c, uint32_t ln) {
    return ln < 8 ? acc_base(c >> 3) + (c & 7) * 256 + ln * 16 : ext_base(c >> 3) + ((c >> 2) & 1) * XHS + ((c >> 1) & 1) * XSS + (c & 1) * 16;
}
struct Flags {
    uint32_t kv[NT][NH][2];
    uint32_t o[NT][8][32];
    uint32_t rec[64];
    uint32_t xn[128];
    uint32_t rload[64];
    uint32_t p[NT][32];
    uint32_t rows[2][128];
    uint4 cand[2][128];
    uint4 norm[64];
};
__device__ __align__(1024) Flags g_f;
__device__ __align__(1024) uint4 g_yp[2][FF / 32][DM];
__device__ __align__(1024) uint32_t g_table[66 * 8];
__device__ __align__(256) uint32_t g_ticket[64];
__device__ uint32_t g_epoch;
#define HOLD 6
#define HSPLIT 24
#define EREL 0
#define PFK 2
#define PFO 0
#define PFS 0
#define NWAITLN 8
#define WGA 0
#define WGB 1
#define WGC (3 - WGA - WGB)
#define NPROBE 3
constexpr int NCTA = 132;
constexpr int NFW = 112;
__device__ uint32_t g_abort;
__device__ long long g_dbg[4096];
#define TR(slot, v)

__device__ __forceinline__ uint32_t smem_u32(const void* p) { return (uint32_t)__cvta_generic_to_shared(p); }
__device__ __forceinline__ void mbar_init(uint32_t a, uint32_t c) { asm volatile("mbarrier.init.shared::cta.b64 [%0], %1;" :: "r"(a), "r"(c) : "memory"); }
__device__ __forceinline__ void mbar_expect_tx(uint32_t a, uint32_t tx) { asm volatile("mbarrier.arrive.expect_tx.shared::cta.b64 _, [%0], %1;" :: "r"(a), "r"(tx) : "memory"); }
__device__ __forceinline__ void mbar_arrive(uint32_t a) { asm volatile("mbarrier.arrive.shared::cta.b64 _, [%0];" :: "r"(a) : "memory"); }
__device__ __forceinline__ void mbar_arrive_if(uint32_t a, uint32_t pred) {
    asm volatile("{\n.reg .pred p;\nsetp.ne.u32 p, %1, 0;\n@p mbarrier.arrive.shared::cta.b64 _, [%0];\n}" :: "r"(a), "r"(pred) : "memory");
}
__device__ __forceinline__ bool mbar_try(uint32_t a, uint32_t ph) {
    uint32_t ok;
    asm volatile("{\n.reg .pred p;\nmbarrier.try_wait.parity.shared::cta.b64 p, [%1], %2;\nselp.u32 %0, 1, 0, p;\n}" : "=r"(ok) : "r"(a), "r"(ph) : "memory");
    return ok != 0;
}
#define SPINLOG 20
constexpr uint32_t SPIN_LIMIT = 1u << SPINLOG;
#define ABORT(code_) atomicCAS(&g_abort, 0u, (code_))
__device__ __forceinline__ void mbar_wait(uint32_t a, uint32_t ph) {
    uint32_t n = 0;
#pragma unroll 1
    while (!mbar_try(a, ph)) { if (++n > SPIN_LIMIT) { ABORT(1); break; } }
}
__device__ __forceinline__ void bar_sync(int id, int n) { asm volatile("bar.sync %0, %1;" :: "r"(id), "r"(n) : "memory"); }
__device__ __forceinline__ void bar_arrive(int id, int n) { asm volatile("bar.arrive %0, %1;" :: "r"(id), "r"(n) : "memory"); }

__device__ __forceinline__ void ldsm4(uint32_t* r, uint32_t a) {
    asm volatile("ldmatrix.sync.aligned.m8n8.x4.shared.b16 {%0,%1,%2,%3}, [%4];" : "=r"(r[0]), "=r"(r[1]), "=r"(r[2]), "=r"(r[3]) : "r"(a) : "memory");
}
__device__ __forceinline__ void ldsm4t(uint32_t* r, uint32_t a) {
    asm volatile("ldmatrix.sync.aligned.m8n8.x4.trans.shared.b16 {%0,%1,%2,%3}, [%4];" : "=r"(r[0]), "=r"(r[1]), "=r"(r[2]), "=r"(r[3]) : "r"(a) : "memory");
}
__device__ __forceinline__ void stsm4t(uint32_t a, uint32_t r0, uint32_t r1, uint32_t r2, uint32_t r3) {
    asm volatile("stmatrix.sync.aligned.m8n8.x4.trans.shared.b16 [%0], {%1,%2,%3,%4};" :: "r"(a), "r"(r0), "r"(r1), "r"(r2), "r"(r3) : "memory");
}
__device__ __forceinline__ void stsm4(uint32_t a, uint32_t r0, uint32_t r1, uint32_t r2, uint32_t r3) {
    asm volatile("stmatrix.sync.aligned.m8n8.x4.shared.b16 [%0], {%1,%2,%3,%4};" :: "r"(a), "r"(r0), "r"(r1), "r"(r2), "r"(r3) : "memory");
}
__device__ __forceinline__ uint32_t movm(uint32_t a) { uint32_t d; asm volatile("movmatrix.sync.aligned.m8n8.trans.b16 %0, %1;" : "=r"(d) : "r"(a)); return d; }
__device__ __forceinline__ void mma16816(float* d, uint32_t a0, uint32_t a1, uint32_t a2, uint32_t a3, uint32_t b0, uint32_t b1) {
    asm volatile("mma.sync.aligned.m16n8k16.row.col.f32.bf16.bf16.f32 {%0,%1,%2,%3}, {%4,%5,%6,%7}, {%8,%9}, {%0,%1,%2,%3};"
        : "+f"(d[0]), "+f"(d[1]), "+f"(d[2]), "+f"(d[3]) : "r"(a0), "r"(a1), "r"(a2), "r"(a3), "r"(b0), "r"(b1));
}
__device__ __forceinline__ void mma1688(float* d, uint32_t a0, uint32_t a1, uint32_t b0) {
    asm volatile("mma.sync.aligned.m16n8k8.row.col.f32.bf16.bf16.f32 {%0,%1,%2,%3}, {%4,%5}, {%6}, {%0,%1,%2,%3};"
        : "+f"(d[0]), "+f"(d[1]), "+f"(d[2]), "+f"(d[3]) : "r"(a0), "r"(a1), "r"(b0));
}
__device__ __forceinline__ uint32_t pack2(float a, float b) { uint32_t d; asm("cvt.rn.bf16x2.f32 %0, %1, %2;" : "=r"(d) : "f"(b), "f"(a)); return d; }
__device__ __forceinline__ float bf_lo(uint32_t w) { return __uint_as_float(w << 16); }
__device__ __forceinline__ float bf_hi(uint32_t w) { return __uint_as_float(w & 0xffff0000u); }
__device__ __forceinline__ float rbf(float x) { return __bfloat162float(__float2bfloat16_rn(x)); }

__device__ __forceinline__ void sts128(uint32_t a, float x, float y, float z, float w) { asm volatile("st.shared.v4.f32 [%0], {%1,%2,%3,%4};" :: "r"(a), "f"(x), "f"(y), "f"(z), "f"(w) : "memory"); }
__device__ __forceinline__ void sts128u(uint32_t a, uint32_t x, uint32_t y, uint32_t z, uint32_t w) { asm volatile("st.shared.v4.b32 [%0], {%1,%2,%3,%4};" :: "r"(a), "r"(x), "r"(y), "r"(z), "r"(w) : "memory"); }
__device__ __forceinline__ void sts64(uint32_t a, float x, float y) { asm volatile("st.shared.v2.f32 [%0], {%1,%2};" :: "r"(a), "f"(x), "f"(y) : "memory"); }
__device__ __forceinline__ float4 lds128(uint32_t a) { float4 v; asm volatile("ld.shared.v4.f32 {%0,%1,%2,%3}, [%4];" : "=f"(v.x), "=f"(v.y), "=f"(v.z), "=f"(v.w) : "r"(a) : "memory"); return v; }
__device__ __forceinline__ float2 lds64(uint32_t a) { float2 v; asm volatile("ld.shared.v2.f32 {%0,%1}, [%2];" : "=f"(v.x), "=f"(v.y) : "r"(a) : "memory"); return v; }
__device__ __forceinline__ uint2 lds64u(uint32_t a) { uint2 v; asm volatile("ld.shared.v2.b32 {%0,%1}, [%2];" : "=r"(v.x), "=r"(v.y) : "r"(a) : "memory"); return v; }
__device__ __forceinline__ float4 lds128v(uint32_t a) { float4 v; asm volatile("ld.volatile.shared.v4.f32 {%0,%1,%2,%3}, [%4];" : "=f"(v.x), "=f"(v.y), "=f"(v.z), "=f"(v.w) : "r"(a) : "memory"); return v; }
__device__ __forceinline__ float2 lds64v(uint32_t a) { float2 v; asm volatile("ld.volatile.shared.v2.f32 {%0,%1}, [%2];" : "=f"(v.x), "=f"(v.y) : "r"(a) : "memory"); return v; }
__device__ __forceinline__ uint4 lds128uv(uint32_t a) { uint4 v; asm volatile("ld.volatile.shared.v4.b32 {%0,%1,%2,%3}, [%4];" : "=r"(v.x), "=r"(v.y), "=r"(v.z), "=r"(v.w) : "r"(a) : "memory"); return v; }
__device__ __forceinline__ void st_async4(uint32_t a, float x, float y, float z, float w, uint32_t mb) {
    asm volatile("st.async.weak.shared::cluster.mbarrier::complete_tx::bytes.v4.f32 [%0], {%1,%2,%3,%4}, [%5];" :: "r"(a), "f"(x), "f"(y), "f"(z), "f"(w), "r"(mb) : "memory");
}
__device__ __forceinline__ void st_async2(uint32_t a, uint32_t x, uint32_t y, uint32_t mb) {
    asm volatile("st.async.weak.shared::cluster.mbarrier::complete_tx::bytes.v2.b32 [%0], {%1,%2}, [%3];" :: "r"(a), "r"(x), "r"(y), "r"(mb) : "memory");
}
__device__ __forceinline__ uint32_t ldg_rlx(const uint32_t* p) { uint32_t v; asm volatile("ld.relaxed.gpu.global.b32 %0, [%1];" : "=r"(v) : "l"(p) : "memory"); return v; }
__device__ __forceinline__ uint4 ldg_rlx4(const uint32_t* p) { uint4 v; asm volatile("ld.relaxed.gpu.global.v4.b32 {%0,%1,%2,%3}, [%4];" : "=r"(v.x), "=r"(v.y), "=r"(v.z), "=r"(v.w) : "l"(p) : "memory"); return v; }
__device__ __forceinline__ uint4 ldg_rlx4_if(const uint32_t* p, bool c) {
    uint4 v;
    asm volatile("{\n.reg .pred p;\nsetp.ne.u32 p, %5, 0;\nmov.b32 %0, 0;\nmov.b32 %1, 0;\nmov.b32 %2, 0;\nmov.b32 %3, 0;\n@p ld.relaxed.gpu.global.v4.b32 {%0,%1,%2,%3}, [%4];\n}"
                 : "=r"(v.x), "=r"(v.y), "=r"(v.z), "=r"(v.w) : "l"(p), "r"((uint32_t)c) : "memory");
    return v;
}
__device__ __forceinline__ void stg_rlx(uint32_t* p, uint32_t v) { asm volatile("st.relaxed.gpu.global.b32 [%0], %1;" :: "l"(p), "r"(v) : "memory"); }
__device__ __forceinline__ void tma2d(uint32_t dst, const CUtensorMap* tm, int c0, int c1, uint32_t mb) {
    asm volatile("cp.async.bulk.tensor.2d.shared::cluster.global.mbarrier::complete_tx::bytes [%0], [%1, {%3, %4}], [%2];"
        :: "r"(dst), "l"((uint64_t)tm), "r"(mb), "r"(c0), "r"(c1) : "memory");
}

__device__ __forceinline__ void tma3d(uint32_t dst, const CUtensorMap* tm, int row, int chunk, uint32_t mb) {
    asm volatile("cp.async.bulk.tensor.3d.shared::cluster.global.mbarrier::complete_tx::bytes [%0], [%1, {%3, %4, %5}], [%2];"
        :: "r"(dst), "l"((uint64_t)tm), "r"(mb), "r"(0), "r"(row), "r"(chunk) : "memory");
}
__device__ __forceinline__ void tma2d_mc(uint32_t dst, const CUtensorMap* tm, int c0, int c1, uint32_t mb) {
    asm volatile("cp.async.bulk.tensor.2d.shared::cluster.global.mbarrier::complete_tx::bytes.multicast::cluster [%0], [%1, {%3, %4}], [%2], %5;"
        :: "r"(dst), "l"((uint64_t)tm), "r"(mb), "r"(c0), "r"(c1), "h"((uint16_t)3) : "memory");
}
__device__ __forceinline__ void mbar_arrive2_if(uint32_t a, uint32_t pred) {
    asm volatile("{\n.reg .pred p;\nsetp.ne.u32 p, %1, 0;\n@p mbarrier.arrive.shared::cta.b64 _, [%0];\n@p mbarrier.arrive.shared::cluster.b64 _, [%2];\n}"
                 :: "r"(a), "r"(pred), "r"(a ^ 0x01000000u) : "memory");
}
__device__ __forceinline__ void tma_pf3d(const CUtensorMap* tm, int row, int chunk) {
    asm volatile("cp.async.bulk.prefetch.tensor.3d.L2.global.tile [%0, {%1, %2, %3}];" :: "l"((uint64_t)tm), "r"(0), "r"(row), "r"(chunk) : "memory");
}
__device__ __forceinline__ void tma_pf2d(const CUtensorMap* tm, int c0, int c1) {
    asm volatile("cp.async.bulk.prefetch.tensor.2d.L2.global.tile [%0, {%1, %2}];" :: "l"((uint64_t)tm), "r"(c0), "r"(c1) : "memory");
}
__device__ __forceinline__ void tma_store3d(const CUtensorMap* tm, uint32_t src, int row, int chunk) {
    asm volatile("cp.async.bulk.tensor.3d.global.shared::cta.bulk_group [%0, {%2, %3, %4}], [%1];" :: "l"((uint64_t)tm), "r"(src), "r"(0), "r"(row), "r"(chunk) : "memory");
}
__device__ __forceinline__ void bulk_store(void* dst, uint32_t src, uint32_t bytes) {
    asm volatile("cp.async.bulk.global.shared::cta.bulk_group [%0], [%1], %2;" :: "l"(dst), "r"(src), "r"(bytes) : "memory");
}
#define GT(slot)
#define CNT(k)
#define CNT2(k, c)
#define TS(i, dep)
#define TSACC()
#define TSDECL
struct Maps { CUtensorMap wq, wk, wv, wo, wo2, kx, ox2, kx3, vx3, xn2, wg, wu; };
typedef Maps RecMaps;
__device__ __forceinline__ void st_rel(uint32_t* p, uint32_t v) { asm volatile("st.release.gpu.global.u32 [%0], %1;" :: "l"(p), "r"(v) : "memory"); }
#define PUBLISH(p, v) st_rel(p, v)
__device__ __forceinline__ uint2 ldg_rlx2(const uint32_t* p) { uint2 v; asm volatile("ld.relaxed.gpu.global.v2.b32 {%0,%1}, [%2];" : "=r"(v.x), "=r"(v.y) : "l"(p) : "memory"); return v; }
__device__ __forceinline__ void wait_eq2(const uint32_t* p, uint32_t e, int code) {
    uint32_t n = 0;
#pragma unroll 1
    while (true) { uint2 v = ldg_rlx2(p); if (v.x == e && v.y == e) break; __nanosleep(64); if (++n > SPIN_LIMIT) { ABORT(code); break; } }
}
__device__ __forceinline__ void wait_eq4(const uint32_t* p, uint32_t e, int code) {
    uint32_t n = 0;
#pragma unroll 1
    while (true) { uint4 v = ldg_rlx4(p); if (v.x == e && v.y == e && v.z == e && v.w == e) break; __nanosleep(64); if (++n > SPIN_LIMIT) { ABORT(code); break; } }
}
__device__ __forceinline__ void wait_rec(const uint32_t* p, uint32_t e, uint32_t steps) {
    uint32_t n = 0;
#pragma unroll 1
    while (true) {
        uint2 v = ldg_rlx2(p);
        if (__all_sync(0xffffffffu, (v.x >> 8) == e && (v.y >> 8) == e && (v.x & 255) >= steps && (v.y & 255) >= steps)) break;
        __nanosleep(64); if (++n > SPIN_LIMIT) { ABORT(8); break; }
    }
}

constexpr int R_QK1 = 0;
constexpr int R_WO = 65536;
constexpr int R_T = 131072;
constexpr int R_SLOT1 = R_T;
constexpr int R_MEMB = R_T + 24576;
constexpr int R_QP = R_MEMB + 8192;
constexpr int R_VRED = R_QP + 4096;
constexpr int R_STG = R_VRED + 2048;
constexpr int R_AX = R_STG + 2048;
constexpr int R_SLOT0 = 196608;
constexpr int R_SLOC = R_SLOT0 + 24576;
constexpr int R_SREM = R_SLOC + 1536;
constexpr int R_VB = R_SREM + 1536;
constexpr int R_MISC = R_VB + 2048;
constexpr int R_LT = R_MISC + 128;
constexpr int R_BAR = 229888;
constexpr int R_TS = 229888 + 128;
static_assert(R_AX + 24576 <= R_SLOT0 && R_LT + 2560 <= 229376, "smem map");
enum { MB_W0 = 0, MB_W1, MB_WV, MB_WO, MB_S, MB_FULL0, MB_FULL1, MB_V, MB_N };

__device__ __forceinline__ float ex2(float x) { float y; asm("ex2.approx.ftz.f32 %0, %1;" : "=f"(y) : "f"(x)); return y; }
__device__ __forceinline__ float rcpf(float x) { float y; asm("rcp.approx.ftz.f32 %0, %1;" : "=f"(y) : "f"(x)); return y; }
__device__ __forceinline__ void mma16816z(float* d, uint32_t a0, uint32_t a1, uint32_t a2, uint32_t a3, uint32_t b0, uint32_t b1) {
    asm volatile("mma.sync.aligned.m16n8k16.row.col.f32.bf16.bf16.f32 {%0,%1,%2,%3}, {%4,%5,%6,%7}, {%8,%9}, {%10,%10,%10,%10};"
        : "=f"(d[0]), "=f"(d[1]), "=f"(d[2]), "=f"(d[3]) : "r"(a0), "r"(a1), "r"(a2), "r"(a3), "r"(b0), "r"(b1), "f"(0.f));
}
__device__ __forceinline__ void mma1688hz(float* d, uint32_t a0, uint32_t a1, uint32_t b0) {
    asm volatile("mma.sync.aligned.m16n8k8.row.col.f32.f16.f16.f32 {%0,%1,%2,%3}, {%4,%5}, {%6}, {%7,%7,%7,%7};"
        : "=f"(d[0]), "=f"(d[1]), "=f"(d[2]), "=f"(d[3]) : "r"(a0), "r"(a1), "r"(b0), "f"(0.f));
}
#define MMA(d, a, b0, b1) mma16816(d, a[0], a[1], a[2], a[3], b0, b1)
#define MMAZ(d, a, b0, b1) mma16816z(d, a[0], a[1], a[2], a[3], b0, b1)
#define MMAF(first, d, a, b0, b1) do { if (first) MMAZ(d, a, b0, b1); else MMA(d, a, b0, b1); } while (0)

__device__ __forceinline__ uint32_t uni(uint32_t x) { return __reduce_max_sync(0xffffffffu, x); }
__device__ __forceinline__ void mbar_wait_u(uint32_t a, uint32_t ph) {
    uint32_t n = 0;
#pragma unroll 1
    while (!__all_sync(0xffffffffu, mbar_try(a, ph))) { if (++n > SPIN_LIMIT) { ABORT(1); break; } }
}
__device__ __forceinline__ void mbar_wait_p(uint32_t a, uint32_t ph) {
    asm volatile("{\n.reg .pred p, q;\n.reg .u32 n;\nmov.u32 n, 0;\nWL: mbarrier.try_wait.parity.shared::cta.b64 p, [%0], %1;\nadd.u32 n, n, 1;\n"
                 "setp.lt.and.u32 q, n, %2, !p;\n@q bra.uni WL;\n}" :: "r"(a), "r"(ph), "n"(SPIN_LIMIT) : "memory");
}
__device__ __forceinline__ uint32_t mbar_test(uint32_t a, uint32_t ph) {
    uint32_t ok;
    asm volatile("{\n.reg .pred p;\nmbarrier.test_wait.parity.shared::cta.b64 p, [%1], %2;\nselp.u32 %0, 1, 0, p;\n}" : "=r"(ok) : "r"(a), "r"(ph) : "memory");
    return ok;
}
__device__ __forceinline__ uint32_t opaque(uint32_t x) { return __shfl_sync(0xffffffffu, x, threadIdx.x & 31); }
__device__ __forceinline__ const uint32_t* mkptr(uint32_t lo, uint32_t hi) { uint64_t r; asm("mov.b64 %0, {%1, %2};" : "=l"(r) : "r"(lo), "r"(hi)); return (const uint32_t*)r; }
__device__ __forceinline__ uint32_t prmt(uint32_t a, uint32_t b, uint32_t s) { uint32_t d; asm("prmt.b32 %0, %1, %2, %3;" : "=r"(d) : "r"(a), "r"(b), "r"(s)); return d; }
__device__ __forceinline__ uint32_t packh2(float a, float b) { uint32_t d; asm("cvt.rn.f16x2.f32 %0, %1, %2;" : "=r"(d) : "f"(b), "f"(a)); return d; }
__device__ __forceinline__ uint32_t hadd2b(uint32_t a, uint32_t b) { uint32_t d; asm("add.rn.bf16x2 %0, %1, %2;" : "=r"(d) : "r"(a), "r"(b)); return d; }
__device__ __forceinline__ uint32_t hmul2b(uint32_t a, uint32_t b) { uint32_t d; asm("mul.rn.bf16x2 %0, %1, %2;" : "=r"(d) : "r"(a), "r"(b)); return d; }
__device__ __forceinline__ uint32_t amax2b(uint32_t a, uint32_t b) { uint32_t d; asm("max.xorsign.abs.bf16x2 %0, %1, %2;" : "=r"(d) : "r"(a), "r"(b)); return d; }
__device__ __forceinline__ uint32_t amax2h(uint32_t a, uint32_t b) { uint32_t d; asm("max.xorsign.abs.f16x2 %0, %1, %2;" : "=r"(d) : "r"(a), "r"(b)); return d; }
__device__ __forceinline__ void sts32(uint32_t a, uint32_t x) { asm volatile("st.shared.b32 [%0], %1;" :: "r"(a), "r"(x) : "memory"); }
__device__ __forceinline__ uint32_t lds32v_(uint32_t a) { uint32_t v; asm volatile("ld.volatile.shared.b32 %0, [%1];" : "=r"(v) : "r"(a) : "memory"); return v; }
__device__ __forceinline__ void stg4(void* p, uint4 v) { asm volatile("st.relaxed.gpu.global.v4.b32 [%0], {%1,%2,%3,%4};" :: "l"(p), "r"(v.x), "r"(v.y), "r"(v.z), "r"(v.w) : "memory"); }
__device__ __forceinline__ void lds_frag(uint32_t* r, uint32_t a) {
    asm volatile("ld.shared.v4.b32 {%0,%1,%2,%3}, [%4];" : "=r"(r[0]), "=r"(r[1]), "=r"(r[2]), "=r"(r[3]) : "r"(a) : "memory");
}
__device__ __forceinline__ void lds_fragv(uint32_t* r, uint32_t a) {
    asm volatile("ld.volatile.shared.v4.b32 {%0,%1,%2,%3}, [%4];" : "=r"(r[0]), "=r"(r[1]), "=r"(r[2]), "=r"(r[3]) : "r"(a) : "memory");
}
__device__ __forceinline__ uint32_t xorv(uint32_t a, uint32_t b) { uint32_t d; asm volatile("xor.b32 %0, %1, %2;" : "=r"(d) : "r"(a), "r"(b)); return d; }
#define SCHED(k) asm volatile("{\n.reg .pred p;\nsetp.ne.u32 p, %0, %1;\n@p bra.uni SD;\nSL: nanosleep.u32 64;\nbra.uni SL;\nSD:\n}" :: "r"(sbu - s), "n"(k) : "memory")
#define PINM() asm volatile("{\n.reg .pred p;\nsetp.eq.u32 p, %0, 1;\n@p st.shared.u32 [%0], %0;\n}" :: "r"(sbu) : "memory")
__device__ __forceinline__ uint32_t or_and(uint32_t a, uint32_t b, uint32_t c) { uint32_t d; asm("lop3.b32 %0, %1, %2, %3, 0xF8;" : "=r"(d) : "r"(a), "r"(b), "r"(c)); return d; }
__device__ __forceinline__ uint32_t pack2v(float a, float b) { uint32_t d; asm volatile("cvt.rn.bf16x2.f32 %0, %1, %2;" : "=r"(d) : "f"(b), "f"(a)); return d; }
#define FU(x) __float_as_uint(x)
__device__ __forceinline__ uint32_t clk32() { uint32_t t; asm volatile("mov.u32 %0, %%clock;" : "=r"(t) :: "memory"); return t; }
__device__ __forceinline__ void spin_until(uint32_t t0, uint32_t d) {
    if (d) {
#pragma unroll 1
        while (__any_sync(0xffffffffu, clk32() - t0 < d)) {}
    }
}
constexpr int SH_OFF = 229376 + 384;
constexpr uint32_t HONE2 = 0x3c003c00u, HCNT2 = 0x50005000u;

__device__ __forceinline__ uint64_t desc_sw128(uint32_t addr, uint32_t lbo, uint32_t sbo) {
    return (uint64_t)((addr & 0x3FFFF) >> 4) | ((uint64_t)(lbo >> 4) << 16) | ((uint64_t)(sbo >> 4) << 32) | (1ull << 62);
}
#define DP 320
#define NAX 4
#define NXL 0
#define NCX 2
#define NCL 1
#define DC 100
#define FLIP 1
#define KXB 4
#define KXI 5
#define ANB 3
#define BNB 3
#define CNB 3
#define SMA 0
#define SMB 0
#define SMC 0x01
#define IVA 0
#define RGA 160
#define RGC 160
#define RGB (504 - RGA - RGC)
#define NRW 8
#define NBR 14
#define E0 0
#define E1 6
#define E2 4
#define E3 10
#define IV 2
#define DEX 0
#define G2K 2
#define VDEP 0
#define AEARLY 0
#define VTP 1
#define LORD 1
#define TRK 1
#define TW 0
#define T2N 14
#define TEARLY 1
#define DT 0
#define NB0 0
#define NB1 8
#define DB2 80
#define DITHER 0
#define DA 40
#define DB 40
#define DS 200

__device__ __forceinline__ uint32_t wrow_off(int kk, int ch) {
    const int lane = threadIdx.x & 31, r = lane & 7;
    const int row = 64 * (kk >> 2) + 32 * (r & 1) + 16 * (kk & 1) + 8 * (lane >> 4) + 4 * ((kk >> 1) & 1) + (r >> 1);
    return row * 128 + ((ch ^ (row & 7)) << 4);
}
template <int K> __device__ __forceinline__ void sched(uint32_t key) {
    asm volatile("{\n.reg .pred p;\nsetp.ne.u32 p, %0, %1;\n@p bra.uni SD;\nSL: nanosleep.u32 64;\nbra.uni SL;\nSD:\n}" :: "r"(key), "n"(K) : "memory");
}
__device__ __forceinline__ void sched_i(int i, uint32_t key) {
    if (i == -1) sched<20>(key); if (i == 0) sched<21>(key); if (i == 1) sched<22>(key); if (i == 2) sched<23>(key);
    if (i == 3) sched<24>(key); if (i == 4) sched<25>(key); if (i == 5) sched<26>(key); if (i == 6) sched<27>(key);
}
template <int NB, int SM, class F>
__device__ __forceinline__ void g1(float* q0, float* k0, uint32_t (*wq)[4], uint32_t (*wk)[4], uint32_t ga, uint32_t key, F&& hook) {
    float q1[4], k1[4];
    uint32_t b[NB][4];
#pragma unroll
    for (int i = 0; i < NB; i++) ldsm4(b[i], ga + i * 512);
    hook(-1, b[0]);
    if (SM & 1) sched_i(-1, key);
#pragma unroll
    for (int i = 0; i < 8; i++) {
        uint32_t* c = b[i % NB];
        MMAF(i == 0, q0, wq[2 * i], c[0], c[1]); MMAF(i == 0, k0, wk[2 * i], c[0], c[1]);
        MMAF(i == 0, q1, wq[2 * i + 1], c[2], c[3]); MMAF(i == 0, k1, wk[2 * i + 1], c[2], c[3]);
        const uint32_t cc_[4] = {c[0], c[1], c[2], c[3]};
        if (i + NB < 8) ldsm4(b[i % NB], ga + (i + NB) * 512);
        hook(i, cc_);
        if ((SM >> (i + 1)) & 1) sched_i(i, key);
    }
#pragma unroll
    for (int i = 0; i < 4; i++) { q0[i] += q1[i]; k0[i] += k1[i]; }
}
__device__ __forceinline__ float frag_norm2(uint32_t (*w)[4]) {
    float d0[4], d1[4];
#pragma unroll
    for (int i = 0; i < 32; i++) { MMAF(i == 0, d0, w[i], w[i][0], w[i][2]); MMAF(i == 0, d1, w[i], w[i][1], w[i][3]); }
    const int lane = threadIdx.x & 31, g = lane >> 2, t = lane & 3;
    float v = g == 2 * t ? d0[0] + d1[2] : (g == 2 * t + 1 ? d0[1] + d1[3] : 0.f);
#pragma unroll
    for (int o = 16; o; o >>= 1) v += __shfl_xor_sync(0xffffffffu, v, o);
    return v;
}
__device__ __forceinline__ void load_slot(uint32_t sb, int c, int tile, const Maps& maps) {
    const uint32_t dst = sb + ((tile & 1) ? R_SLOT1 : R_SLOT0), mb = sb + R_BAR + 8 * (MB_FULL0 + (tile & 1));
    mbar_expect_tx(mb, 24576);
    tma2d(dst + 16384, &maps.kx, c * 64, tile * 64, mb);
    tma3d(dst, &maps.vx3, tile * 64, (c >> 1) * 2, mb);
}
__device__ __forceinline__ uint32_t put_mem0(uint32_t sb, int W, const bf16* __restrict__ mem0) {
    const int lane = threadIdx.x & 31;
    const uint4 a = *(const uint4*)(mem0 + (lane & 7) * DM + W * 64 + (lane >> 3) * 8), b = *(const uint4*)(mem0 + (lane & 7) * DM + W * 64 + 32 + (lane >> 3) * 8);
    const uint4 m0 = make_uint4(prmt(a.x, b.x, 0x5410u), prmt(a.x, b.x, 0x7632u), prmt(a.y, b.y, 0x5410u), prmt(a.y, b.y, 0x7632u));
    const uint4 m1 = make_uint4(prmt(a.z, b.z, 0x5410u), prmt(a.z, b.z, 0x7632u), prmt(a.w, b.w, 0x5410u), prmt(a.w, b.w, 0x7632u));
    bar_sync(3, 256);
    sts128u(sb + R_MEMB + W * 1024 + lane * 16, m0.x, m0.y, m0.z, m0.w);
    sts128u(sb + R_MEMB + W * 1024 + 512 + lane * 16, m1.x, m1.y, m1.z, m1.w);
    return amax2b(amax2b(amax2b(m0.x, m0.y), amax2b(m0.z, m0.w)), amax2b(amax2b(m1.x, m1.y), amax2b(m1.z, m1.w)));
}
#define PUT_MAX(W, dep) { uint32_t m_ = amax2b(amax2b(mx, my), mz | (dep)); sts32(sbu + R_MISC + (W) * 4, __reduce_max_sync(0xffffffffu, amax2b(m_, m_ << 16) & 0x7f800000u)); }
__device__ __forceinline__ uint32_t h2b(uint32_t w) {
    uint32_t d;
    asm("{\n.reg .f16 l, h;\n.reg .f32 a, b;\nmov.b32 {l, h}, %1;\ncvt.f32.f16 a, l;\ncvt.f32.f16 b, h;\ncvt.rn.bf16x2.f32 %0, b, a;\n}" : "=r"(d) : "r"(w));
    return d;
}
#define GATHER1(HALF)                                                                                           \
        {                                                                                                       \
            const uint4 x0 = ldg_rlx4(pm), x1 = ldg_rlx4(pm + 256); const uint2 y = ldg_rlx2(px);                 \
            cw = (sel & 0x4000u) ? prmt(x0.w, x1.w, 0x7632u) : prmt(y.x, y.y, 0x5410u);                         \
            const uint32_t p0 = h2b(x0.x), p1 = h2b(x0.y), p2 = h2b(x0.z), p3 = h2b(prmt(x0.w, y.x, sel));      \
            stsm4t(rG + R_MEMB + HALF * 4096, p0, p1, p2, p3);                                                  \
            const uint32_t p4 = h2b(x1.x), p5 = h2b(x1.y), p6 = h2b(x1.z), p7 = h2b(prmt(x1.w, y.y, sel));      \
            stsm4t(rG + R_MEMB + HALF * 4096 + 512, p4, p5, p6, p7);                                            \
            mx = amax2b(amax2b(p0, p1), amax2b(p2, p3)); my = amax2b(p4, p5); mz = amax2b(p6, p7);              \
        }
#define GATHER(HALF, PRE, SYNC, AFTER)                                                                                      \
        {                                                                                                       \
            const uint32_t so = aslot(s);                                                                       \
            const uint32_t ua = (glo + acc_base(HALF * 4 + fo)) ^ so, ux = (glo + ext_base(HALF * 4 + fo)) ^ so; \
            uint2 lt;                                                                                           \
            lt.x = lds32v_(rL + R_LT); lt.y = lds32v_(rL + R_LT + 4);                                           \
            const uint32_t sel = 0x3210u + (lt.x & 16) * 0x440u;                                                \
            const uint32_t* pm = mkptr(ua + lt.x, ghi);                                                         \
            const uint32_t* px = mkptr(ux + lt.y, ghi);                                                         \
            PRE                                                                                                 \
            bar_sync(5, 384);                                                                                   \
            const uint32_t t0 = clk32();                                                                        \
            TSACC();                                                                        \
            SYNC                                                                                                \
            spin_until(t0, DP + DITHER);                                                                                 \
            \
            TS(10, 0);                                                                                          \
            uint32_t cw, nr = 0;                                                                                \
            _Pragma("unroll 1") do {                                                                            \
                GATHER1(HALF)                                                                                   \
                nr++;                                                                                           \
            } while (__any_sync(0xffffffffu, cw != HCNT2 && nr < SPIN_LIMIT));                                  \
            TS(11, cw);                                                                                         \
            AFTER                                                                                               \
            CNT2(HALF * 4 + (s & 1) * 2 + (nr > 2), nr > 1);                                                    \
            \
        }
#define GOBAR (fo == 3 ? 14 : 10 + fo)

__device__ __forceinline__ void rec_a(uint32_t sb, int c, const bf16* __restrict__ mem0, uint32_t epoch) {
    const int tid = threadIdx.x - WGA * 128, lane = tid & 31, f = tid >> 5;
    uint32_t wq[16][4], wk[16][4], mx, my = 0, mz = 0;
    const int lrow = ((lane >> 4) << 3) + (lane & 7), lsel = (lane >> 3) & 1;
    {
        mbar_wait(sb + R_BAR + 8 * MB_W0, 0);
        if (c == 7 && tid == 0) GT(1421);
#pragma unroll
        for (int kk = 0; kk < 16; kk++) { const uint32_t a = sb + R_T + wrow_off(kk, 2 * f + lsel); ldsm4t(wq[kk], a); ldsm4t(wk[kk], a + 32768); }
        __syncwarp();
        mx = put_mem0(sb, f, mem0);
    }
    const uint32_t rL = opaque(sb + lane * 16), rG = opaque(sb + lane * 16 + f * 1024);
    const uint32_t sbu = uni(sb), fo = uni(f), cc = uni(c);
    const uint64_t gx = xpage();
    const uint32_t ghi = uni((uint32_t)(gx >> 32)), glo = uni((uint32_t)gx);
#pragma unroll
    for (int i = 0; i < NAX; i++) {
        sts128u(rG + R_AX + 4096 * i, wq[i][0], wq[i][1], wq[i][2], wq[i][3]);
        sts128u(rG + R_AX + 4096 * i + 512, wk[i][0], wk[i][1], wk[i][2], wk[i][3]);
    }
    sts128u(rL + R_LT + 512 + f * 512, (sb + R_SREM + (f >= 2 ? lane * 8 + f * 256 : lane * 16 + f * 1024)) ^ 0x01000000u, (sb + R_BAR + 8 * MB_S) ^ 0x01000000u,
            sb + R_QP + (lane >> 4) * 128 + lsel * 512 + (lane & 7) * 16 + (f == 3 ? 2048 : 0), sb + lrow * 128 + ((lsel ^ (lane & 7)) << 4));
    __syncwarp();
    if (tid == 0) GT(c * 8 + 1);
    TSDECL;
    const float cexp = 0.08838834764831845f * 1.4426950408889634f;
    float cs = cexp;
    auto step = [&](int s, bool first) -> bool {
        bar_sync(1, 128);
        float q0[4], k0[4];
        uint4 ta;
        const uint32_t ro = ((s & 2) ? R_SLOT1 : R_SLOT0) + (s & 1) * 4096;
        g1<ANB, SMA>(q0, k0, wq, wk, rL + R_MEMB, sbu - s, [&](int i, const uint32_t* c_) {
            if (i == 0) TS(0, c_[0]);
            if (i == -1) {
#pragma unroll
                for (int n = NAX - NXL; n < NAX; n++) { lds_fragv(wq[n], rG + R_AX + 4096 * n); lds_fragv(wk[n], rG + R_AX + 4096 * n + 512); }
                ta = lds128uv(rL + R_LT + 512 + fo * 512);
            }
            if (i == IVA) bar_arrive(GOBAR, 96);
        });
        stsm4t(rG + R_QP, pack2(q0[0], q0[1]), pack2(q0[2], q0[3]), pack2(k0[0], k0[1]), pack2(k0[2], k0[3]));
        TS(1, FU(k0[3]));
        if (first) mbar_wait_p(sbu + R_BAR + 8 * MB_FULL0, 0);
        if (__builtin_expect(fo < 2, FLIP)) {
            uint32_t qa[4][4], kx[4][4];
#pragma unroll
            for (int kk = 0; kk < KXB; kk++) ldsm4(kx[kk], (ta.w ^ (kk * 32)) + (ro + 16384 + fo * 2048));
            bar_sync(3, 256);
#pragma unroll
            for (int kk = 0; kk < 4; kk++) {
                if (kk == 2 && (!TRK || TW)) bar_arrive(13, 256);
                if (kk >= KXB) ldsm4(kx[kk], (ta.w ^ (kk * 32)) + (ro + 16384 + fo * 2048));
                ldsm4(qa[kk], ta.z + kk * 1024);
            }
            float s0[4], s1[4], s2[4], s3[4];
            MMAZ(s0, qa[0], kx[0][0], kx[0][1]); MMAZ(s1, qa[0], kx[0][2], kx[0][3]);
            MMAZ(s2, qa[1], kx[1][0], kx[1][1]); MMAZ(s3, qa[1], kx[1][2], kx[1][3]);
            MMA(s0, qa[2], kx[2][0], kx[2][1]); MMA(s1, qa[2], kx[2][2], kx[2][3]);
            MMA(s2, qa[3], kx[3][0], kx[3][1]); MMA(s3, qa[3], kx[3][2], kx[3][3]);
            const float x = ((s0[0] + s0[2]) + (s2[0] + s2[2])) * cs, y = ((s0[1] + s0[3]) + (s2[1] + s2[3])) * cs;
            const float z = ((s1[0] + s1[2]) + (s3[0] + s3[2])) * cs, w = ((s1[1] + s1[3]) + (s3[1] + s3[3])) * cs;
            st_async4(ta.x, x, y, z, w, ta.y);
            TS(2, qa[0][0]); TS(3, FU(w));
            sts128(rG + R_SLOC, x, y, z, w);
        } else {
            bar_sync(3, 256);
            uint32_t kb[4], kc[4], qa[4], qc[4];
            ldsm4(kb, ta.z + 256); ldsm4(qa, ta.z); if (!TRK || TW) bar_arrive(13, 256);
            ldsm4(kc, ta.z + 1280); ldsm4(qc, ta.z + 1024);
            const uint32_t k0_ = hadd2b(kb[0], kb[1]), k1_ = hadd2b(kb[2], kb[3]), k2_ = hadd2b(kc[0], kc[1]), k3_ = hadd2b(kc[2], kc[3]);
            float s0[4], s2[4];
            MMAZ(s0, qa, k0_, k1_); MMAZ(s2, qc, k2_, k3_);
            const float x = ((s0[0] + s0[2]) + (s2[0] + s2[2])) * cs, y = ((s0[1] + s0[3]) + (s2[1] + s2[3])) * cs;
            st_async2(ta.x, FU(x), FU(y), ta.y);
            TS(2, kb[0]); TS(3, FU(y));
            sts64((ta.x ^ 0x01000000u) + (R_SLOC - R_SREM), x, y);
            sts128u(rL + R_STG + (fo & 1) * 512, k0_, k1_, k2_, k3_);
        }
        const uint32_t r8 = (rL + sbu) >> 1;
        uint32_t vt00[4], vt01[4], vt10[4], vt11[4];
        const uint32_t rV = ta.w ^ ((fo & 1) * 64), vo = ro + (fo >> 1) * 8192;
        if (VTP < 2) { ldsm4t(vt00, rV + vo); ldsm4t(vt10, (rV ^ 32) + vo); }
        if (VTP < 1) { ldsm4t(vt01, rV + vo + 2048); ldsm4t(vt11, (rV ^ 32) + vo + 2048); }
        bar_sync(4, 128);
        const float4 l0 = lds128v(rL + R_SLOC), l1 = lds128v(rL + R_SLOC + 1024);
        const float2 l2 = lds64v(r8 + R_SLOC + 512), l3 = lds64v(r8 + R_SLOC + 768);
        if (E2 && !TRK) bar_arrive(15, 256);
        PUT_MAX(fo, 0)
        bar_arrive(9, 256);
        if (s == NSEG - 1) { mbar_wait_u(sbu + R_BAR + 8 * MB_S, 1); mbar_wait_u(sbu + R_BAR + 8 * MB_V, 1); return true; }
        mbar_wait_p(sbu + R_BAR + 8 * MB_S, s & 1);
        {
            const float4 r0 = lds128v(rL + R_SREM), r1 = lds128v(rL + R_SREM + 1024);
            const float2 r2 = lds64v(r8 + R_SREM + 512), r3 = lds64v(r8 + R_SREM + 768);
            if (VTP >= 1) PINM();
            if (VTP >= 2) { ldsm4t(vt00, rV + vo); ldsm4t(vt10, (rV ^ 32) + vo); }
            if (VTP >= 1) { ldsm4t(vt01, rV + vo + 2048); ldsm4t(vt11, (rV ^ 32) + vo + 2048); }
            float sv[10];
            sv[0] = l0.x + r0.x; sv[1] = l0.y + r0.y; sv[2] = l0.z + r0.z; sv[3] = l0.w + r0.w;
            sv[4] = l1.x + r1.x; sv[5] = l1.y + r1.y; sv[6] = l1.z + r1.z; sv[7] = l1.w + r1.w;
            sv[8] = ((l2.x + l3.x) + r2.x) + r3.x; sv[9] = ((l2.y + l3.y) + r2.y) + r3.y;
            float m = fmaxf(fmaxf(fmaxf(sv[0], sv[1]), fmaxf(sv[2], sv[3])), fmaxf(fmaxf(sv[4], sv[5]), fmaxf(sv[6], sv[7])));
            m = fmaxf(m, fmaxf(sv[8], sv[9]));
            {
                const float m1 = __shfl_xor_sync(0xffffffffu, m, 1), m2 = __shfl_xor_sync(0xffffffffu, m, 2), m3 = __shfl_xor_sync(0xffffffffu, m, 3);
                m = fmaxf(fmaxf(m, m1), fmaxf(m2, m3));
            }
            TS(4, FU(r0.x)); TS(5, FU(m));
            const uint32_t ONE2 = 0x3f803f80u;
            float o0[4], o1[4], sm[4];
            const uint32_t pb0 = pack2(ex2(sv[0] - m), ex2(sv[1] - m)), pb1 = pack2(ex2(sv[2] - m), ex2(sv[3] - m));
            mma16816z(sm, ONE2, ONE2, ONE2, ONE2, pb0, pb1);
            MMAZ(o0, vt00, pb0, pb1); MMAZ(o1, vt10, pb0, pb1);
            const uint32_t z = (VDEP == 0 ? FU(m) : pb0) & (sbu & 8);
            const uint32_t vok = mbar_test(sbu + R_BAR + 8 * MB_V + z, s & 1);
            const uint32_t rv = r8 + vok * 8;
            float2 va = lds64v(rv + R_VB - 8 + fo * 512);
            if (!TRK) bar_arrive(13, 256);
            float2 vb = lds64v(rv + R_VB - 8 + fo * 512 + 256);
            float sig = __uint_as_float(lds32v_(sbu + R_MISC + 40));
            const uint32_t pb2 = pack2(ex2(sv[4] - m), ex2(sv[5] - m)), pb3 = pack2(ex2(sv[6] - m), ex2(sv[7] - m));
            mma16816(sm, ONE2, ONE2, ONE2, ONE2, pb2, pb3);
            const uint32_t pb4 = pack2(ex2(sv[8] - m), ex2(sv[9] - m));
            MMA(o0, vt01, pb2, pb3); MMA(o1, vt11, pb2, pb3);
            mma1688(sm, ONE2, ONE2, pb4);
            const float z0 = rcpf(sm[0]), z1 = rcpf(sm[1]);
#define PUT_O()                                                                                                   \
            {                                                                                                     \
                float a0[4] = {o0[0], o0[1], o0[2], o0[3]}, a1[4] = {o1[0], o1[1], o1[2], o1[3]};                 \
                mma1688(a0, FU(va.x), FU(va.y), pb4); mma1688(a1, FU(vb.x), FU(vb.y), pb4);                       \
                const float i0 = z0 * sig, i1 = z1 * sig;                                                         \
                stsm4t(rG + R_QP, pack2(a0[0] * i0, a0[1] * i1), pack2(a0[2] * i0, a0[3] * i1), pack2(a1[0] * i0, a1[1] * i1), pack2(a1[2] * i0, a1[3] * i1)); \
            }
            PUT_O()
            asm volatile("{\n.reg .pred p;\nsetp.ne.u32 p, %0, 0;\n@p bar.arrive 8, 256;\n}" :: "r"(vok) : "memory");
            if (__builtin_expect(__any_sync(0xffffffffu, vok == 0), 0)) {
                mbar_wait_p(sbu + R_BAR + 8 * MB_V, s & 1);
                va = lds64v(r8 + R_VB + fo * 512); vb = lds64v(r8 + R_VB + fo * 512 + 256);
                sig = __uint_as_float(lds32v_(sbu + R_MISC + 40));
                PUT_O()
                bar_arrive(8, 256);
                CNT(8);
            }
            TS(6, 0);
            const float r = __uint_as_float(0x7f000000u - FU(sig));
            cs = cexp * r * (fo >= 2 ? r : 1.f);
        }
        return false;
    };
    step(0, true);
#pragma unroll 1
    for (int s = 0;; s++) {
        if (s & 1) mbar_wait_p(sbu + R_BAR + 8 * (MB_FULL0 + (((s + 1) >> 1) & 1)), ((s + 1) >> 2) & 1);
        auto early = [&]() {
            SCHED(13);
#pragma unroll
            for (int i = 0; i < NAX - NXL; i++) { lds_fragv(wq[i], rG + R_AX + 4096 * i); lds_fragv(wk[i], rG + R_AX + 4096 * i + 512); }
        };
        GATHER(0, , early();, )
        if (step(s + 1, false)) break;
    }
    CNT(9);
    if (rG == sbu) GT(cc * 8 + 4);
}

__device__ __forceinline__ void rec_b(uint32_t sb, int c, uint32_t epoch) {
    const int tid = threadIdx.x - WGB * 128, lane = tid & 31, f = tid >> 5;
    uint32_t wq[16][4], wk[16][4], wo[32][4];
    const int lrow = ((lane >> 4) << 3) + (lane & 7), lsel = (lane >> 3) & 1;
    const uint32_t rL = opaque(sb + lane * 16), rW = opaque(sb + lane * 16 + f * 16384);
    const uint32_t sbu = uni(sb), fo = uni(f), cc = uni(c), po = cc & 1, ep = uni(epoch);
    {
        mbar_wait(sb + R_BAR + 8 * MB_WO, 0);
        if (c == 7 && tid == 0) GT(1426);
        const uint32_t aO = sb + R_WO + f * 16384 + lrow * 128 + ((lsel ^ (lane & 7)) << 4);
#pragma unroll
        for (int i = 0; i < 32; i++) {
            const int tile = (i >> 4) * 2 + (i & 1), kk = (i >> 1) & 7;
            ldsm4t(wo[i], (aO ^ (32 * tile)) + kk * 2048);
        }
        const float no = frag_norm2(wo);
        if (lane == 0) sts32(sb + R_MISC + 80 + f * 4, FU(no));
        __syncwarp();
        bar_sync(15, 256);
        if (tid == 0) {
            const float4 a = lds128(sb + R_MISC + 64), b = lds128(sb + R_MISC + 80);
            stg4(&g_f.norm[c], make_uint4(FU((a.x + a.y) + (a.z + a.w)), epoch, FU((b.x + b.y) + (b.z + b.w)), epoch));
        }
        __syncwarp();
#pragma unroll
        for (int i = NRW; i < 32; i++) sts128u(rW + R_WO + i * 512, wo[i][0], wo[i][1], wo[i][2], wo[i][3]);
        mbar_wait(sb + R_BAR + 8 * MB_W1, 0);
        if (c == 7 && tid == 0) GT(1422);
        if (tid == 0) stg_rlx(&g_f.rload[c], epoch);
        __syncwarp();
#pragma unroll
        for (int kk = 0; kk < 16; kk++) { const uint32_t a = sb + R_QK1 + wrow_off(kk, 2 * f + lsel); ldsm4t(wq[kk], a); ldsm4t(wk[kk], a + 32768); }
        bar_sync(13, 128);
#pragma unroll
        for (int i = 0; i < 16; i++) {
            sts128u(rW + R_QK1 + i * 1024, wq[i][0], wq[i][1], wq[i][2], wq[i][3]);
            sts128u(rW + R_QK1 + i * 1024 + 512, wk[i][0], wk[i][1], wk[i][2], wk[i][3]);
        }
        __syncwarp();
    }
    const uint64_t gx = xpage();
    const uint32_t ghi = uni((uint32_t)(gx >> 32)), glo = uni((uint32_t)gx);
    TSDECL;
#pragma unroll 1
    for (int s = 0;; s++) {
        bar_sync(2, 256);
        float q0[4], k0[4];
        g1<BNB, SMB>(q0, k0, wq, wk, rL + R_MEMB + 4096, sbu - s, [&](int i, const uint32_t* c_) {
            if (i == 0) TS(0, c_[0]);
            if (i >= 2 && i < 6) {
#pragma unroll
                for (int n = NRW + (i - 2) * E0 / 4; n < NRW + (i - 1) * E0 / 4; n++) lds_fragv(wo[n], rW + R_WO + n * 512);
            }
            if (i == IV) bar_arrive(GOBAR, 96);
        });
        stsm4t(rL + fo * 1024 + R_QP + 512, pack2(q0[0], q0[1]), pack2(q0[2], q0[3]), pack2(k0[0], k0[1]), pack2(k0[2], k0[3]));
        bar_arrive(3, 256);
        TS(1, FU(k0[3]));
        const uint32_t so = aslot(s);
        uint2 lt;
        { const float2 t = lds64v(rL + R_LT + 8); lt.x = FU(t.x); lt.y = FU(t.y); }
        const uint32_t sel = 0x3210u + (lt.x & 16) * 0x440u;
        uint32_t* pm = (uint32_t*)mkptr(((glo + acc_base(po * 4 + fo)) ^ so) + lt.x, ghi);
        uint32_t* px = (uint32_t*)mkptr(((glo + ext_base(po * 4 + fo)) ^ so) + lt.y, ghi);
        if (TW) bar_sync(13, 256);
        if (s == NSEG - 1) break;
        {
            const uint32_t z = lt.x & 1;
#pragma unroll
            for (int n = NRW; n < NRW + E0 + E1 + E2 + E3; n++) {
                const int d = n - (n < NRW + T2N ? TRK + 1 : TRK);
                lds_fragv(wo[n], (d >= NRW ? or_and(rW, wo[d][0], z) : rW) + R_WO + n * 512);
            }
        }
        TS(2, wo[NRW + E0 + E1 + E2 + E3 - 1][0]);
        SCHED(4);
        bar_sync(8, 256);
        {
            float o[4][4];
            uint32_t b[4][4];
#pragma unroll
            for (int i = 0; i < 4; i++) ldsm4(b[i], rL + R_QP + i * 1024);
            PINM();
#pragma unroll
            for (int n = NRW + E0 + E1 + E2 + E3; n < 32; n++) lds_fragv(wo[n], rW + R_WO + n * 512);
            float p[4][4];
#define G2_STEP(o, hf, kk) _Pragma("unroll") for (int i = 0; i < 2; i++) MMAF((kk) < 2, o[((kk) & 1) * 2 + i], wo[(hf) * 16 + (kk) * 2 + i], b[(kk) >> 1][((kk) & 1) * 2], b[(kk) >> 1][((kk) & 1) * 2 + 1])
#define G2_RED(o, wl, h) const uint32_t wl = packh2(o[1][2] + o[3][2], o[1][3] + o[3][3]);                            \
                asm volatile("red.relaxed.gpu.global.add.noftz.v4.f16x2 [%0], {%1,%2,%3,%4};" :: "l"(pm + (h) * 16),  \
                    "r"(packh2(o[0][0] + o[2][0], o[0][1] + o[2][1])), "r"(packh2(o[0][2] + o[2][2], o[0][3] + o[2][3])), \
                    "r"(packh2(o[1][0] + o[3][0], o[1][1] + o[3][1])), "r"(prmt(wl, HONE2, sel)) : "memory");          \
                asm volatile("{\n.reg .pred p;\nsetp.ne.u32 p, %2, 0x3210;\n@p red.relaxed.gpu.global.add.noftz.f16x2 [%0], %1;\n}" \
                    :: "l"(px + (h) * (XHS / 4)), "r"((wl & 0xffff0000u) | 0x3c00u), "r"(sel) : "memory")
#pragma unroll
            for (int kk = 0; kk < 8; kk++) { G2_STEP(o, 0, kk); }
            TS(7, b[0][0]);
            SCHED(11);
#pragma unroll
            for (int kk = 0; kk < G2K; kk++) { G2_STEP(p, 1, kk); }
#pragma unroll
            for (int i = 0; i < NB0; i++) { lds_fragv(wq[i], rW + R_QK1 + i * 1024); lds_fragv(wk[i], rW + R_QK1 + i * 1024 + 512); }
            G2_RED(o, w3, 0);
            TS(8, w3);
#pragma unroll
            for (int kk = G2K; kk < 8; kk++) { G2_STEP(p, 1, kk); }
            G2_RED(p, w7, 1);
            TS(9, w7);
        }
        bar_arrive(5, 384);
        asm volatile("{\n.reg .pred p;\nsetp.eq.u32 p, %0, %1;\n@p mbarrier.arrive.expect_tx.shared::cta.b64 _, [%2], 1536;\n}"
                     :: "r"(rW), "r"(sbu), "r"(sbu + R_BAR + 8 * MB_S) : "memory");
        const uint32_t tb = clk32();
        TSACC();
        spin_until(tb, DB);
#pragma unroll
        for (int i = NB0; i < NBR; i++) {
            if (i == NB1) spin_until(tb, DP + DB2);
            lds_fragv(wq[i], rW + R_QK1 + i * 1024); lds_fragv(wk[i], rW + R_QK1 + i * 1024 + 512);
        }
    }
}

#undef lds_fragv
__device__ __forceinline__ void rec_first_loads(uint32_t sb, int c, const Maps& maps) {
    const uint32_t bar = sb + R_BAR;
    const int F0 = c * 64;
    mbar_expect_tx(bar + 8 * MB_W0, 65536); mbar_expect_tx(bar + 8 * MB_WO, 65536); mbar_expect_tx(bar + 8 * MB_WV, 65536);
    tma2d(sb + R_QK1, &maps.wv, F0, 0, bar + 8 * MB_WV); tma2d(sb + R_QK1 + 32768, &maps.wv, F0, 256, bar + 8 * MB_WV);
    tma2d(sb + R_T + 32768, &maps.wk, F0, 0, bar + 8 * MB_W0);
    if (!LORD) {
        for (int i = 0; i < 4; i++) tma2d(sb + R_WO + i * 16384, &maps.wo, (c & 1) * 256 + i * 64, (c >> 1) * 128, bar + 8 * MB_WO);
        tma2d(sb + R_T, &maps.wq, F0, 0, bar + 8 * MB_W0);
    }
    mbar_expect_tx(bar + 8 * MB_S, 1536);
}
__device__ __forceinline__ void rec_c(uint32_t sb, int c, const bf16* __restrict__ mem0, const Maps& maps, uint32_t epoch) {
    const int tid = threadIdx.x - WGC * 128, lane = tid & 31, u = tid >> 5;
    const uint32_t bar = sb + R_BAR;
    const int lrow = ((lane >> 4) << 3) + (lane & 7), lsel = (lane >> 3) & 1;
    const int kh = u >> 1, j = u & 1;
    uint32_t wv[32][4], mx, my = 0, mz = 0;
    {
        if (u == 0) {
            sts128u(sb + lane * 16 + R_LT, (lane >> 3) * 256 + (lane & 7) * 16, ((lane >> 2) & 1) * XHS + (lane >> 4) * XSS + (lane & 8) * 2 + (lane & 2) * 4,
                    (lane >> 2) * 256 + (lane & 3) * 16, ((lane >> 3) & 1) * XSS + (lane & 6) * 4 + (lane >> 4) * 4);
        }
        mbar_wait(bar + 8 * MB_WV, 0);
        if (c == 7 && tid == 0) GT(1425);
        if (LORD && tid == 32) {
            for (int i = 0; i < 4; i++) tma2d(sb + R_WO + i * 16384, &maps.wo, (c & 1) * 256 + i * 64, (c >> 1) * 128, bar + 8 * MB_WO);
            tma2d(sb + R_T, &maps.wq, c * 64, 0, bar + 8 * MB_W0);
        }
        __syncwarp();
#pragma unroll
        for (int kk = 0; kk < 16; kk++) {
            const uint32_t aa = sb + R_QK1 + kh * 32768 + wrow_off(kk, 4 * j + 2 * kh + lsel);
            ldsm4t(wv[kk], aa); ldsm4t(wv[16 + kk], aa ^ 32);
        }
        bar_sync(9, 128);
        if (c == 7 && tid == 0) GT(1423);
        if (tid == 0) {
            mbar_expect_tx(bar + 8 * MB_W1, 65536);
            tma2d(sb + R_QK1 + 32768, &maps.wk, c * 64, 256, bar + 8 * MB_W1); tma2d(sb + R_QK1, &maps.wq, c * 64, 256, bar + 8 * MB_W1);
        }
        __syncwarp();
        const float nv = frag_norm2(wv);
        if (lane == 0) sts32(sb + R_MISC + 64 + u * 4, FU(nv));
        __syncwarp();
        bar_arrive(15, 256);
        mx = put_mem0(sb, 4 + u, mem0);
    }
    const uint32_t rL = opaque(sb + lane * 16), rG = opaque(sb + lane * 16 + u * 1024);
    const uint32_t sbu = uni(sb), fo = uni(u), cc = uni(c), ep = uni(epoch);
    const uint64_t gx = xpage();
    const uint32_t ghi = uni((uint32_t)(gx >> 32)), glo = uni((uint32_t)gx);
    constexpr int CX = R_AX + NAX * 4096;
    static_assert(NAX + NCX <= 6, "AX");
#pragma unroll
    for (int i = 0; i < NCX; i++) {
        sts128u(rG + CX + 4096 * i, wv[i][0], wv[i][1], wv[i][2], wv[i][3]);
        sts128u(rG + CX + 4096 * i + 512, wv[16 + i][0], wv[16 + i][1], wv[16 + i][2], wv[16 + i][3]);
    }
    __syncwarp();
    TSDECL;
    uint32_t rpb = 0x3f800000u;
    bar_arrive(2, 256);
    if (fo == 3) {
        uint32_t n = 0;
#pragma unroll 1
        while (true) {
            const uint2 v = ldg_rlx2(&g_f.kv[0][cc >> 1][0]);
            if (__all_sync(0xffffffffu, v.x == ep && v.y == ep)) break;
            __nanosleep(32);
            if (++n > SPIN_LIMIT) { ABORT(6); break; }
        }
        if (rL == sbu) load_slot(sbu, cc, 0, maps);
        __syncwarp();
        if (cc == 7 && rL == sbu) GT(1427);
    }
#pragma unroll 1
    for (int s = 0;; s++) {
        if (TEARLY && fo == 3 && !(s & 1) && s > 0 && s + 2 < NSEG) {
            if (rL == sbu) load_slot(sbu, cc, (s + 2) >> 1, maps);
            __syncwarp();
        } else spin_until(clk32(), DC);
#pragma unroll
        for (int i = NCX - NCL; i < NCX; i++) { lds_fragv(wv[i], rG + CX + 4096 * i); lds_fragv(wv[16 + i], rG + CX + 4096 * i + 512); }
        PUT_MAX(4 + fo, 0)
        bar_sync(GOBAR, 96);
        float v0[4], v1[4];
        g1<CNB, SMC>(v0, v1, wv, wv + 16, rL + R_MEMB + (fo >> 1) * 4096, sbu - s, [&](int i, const uint32_t* c_) { if (i == 0) TS(0, c_[0]); });
        TS(1, FU(v1[3]));
        const uint32_t l16 = (rL ^ sbu) | (lds32v_(rL + R_LT + 4) & 1);
        const uint32_t r8 = sbu + (l16 >> 1);
        {
            sts128(rL + R_VRED + fo * 512, v1[0], v1[1], v1[2], v1[3]);
            const uint32_t d = r8 + R_VB + ((cc & 1) * 4 + (fo & 1) * 2 + (fo >> 1)) * 256;
            const uint32_t dr = xorv(d, 0x01000000u), br = xorv(sbu + R_BAR + 8 * MB_V, 0x01000000u);
            bar_sync(6 + (fo & 1), 64);
            const float4 a0 = lds128(rL + R_VRED + (fo ^ 2) * 512);
            const float rp = __uint_as_float(rpb);
            const uint32_t w0 = pack2((v0[0] + a0.x) * rp, (v0[1] + a0.y) * rp), w1 = pack2((v0[2] + a0.z) * rp, (v0[3] + a0.w) * rp);
            st_async2(dr, w0, w1, br);
            TS(3, w1);
            sts64(d, __uint_as_float(w0), __uint_as_float(w1));
            __syncwarp();
            asm volatile("{\n.reg .pred p;\nsetp.eq.u32 p, %0, %1;\n@p mbarrier.arrive.expect_tx.shared::cta.b64 _, [%2], 256;\n}"
                         :: "r"(rL), "r"(sbu), "r"(sbu + R_BAR + 8 * MB_V) : "memory");
        }
        if (fo == 1) {
            bar_sync(9, 256);
            {
                if (s == 0) {
                    const uint32_t* np = (const uint32_t*)&g_f.norm[0] + (l16 >> 2);
                    uint4 r, q; uint32_t n = 0;
#pragma unroll 1
                    while (true) {
                        r = ldg_rlx4(np); q = ldg_rlx4(np + 128);
                        const uint2 z = ldg_rlx2(&g_f.xn[l16 >> 3]);
                        if (__all_sync(0xffffffffu, r.y == ep && r.w == ep && q.y == ep && q.w == ep && z.x == ep && z.y == ep)) break;
                        if (++n > SPIN_LIMIT) { ABORT(5); break; }
                    }
                    float nv = __uint_as_float(r.x) + __uint_as_float(q.x), no = __uint_as_float(r.z) + __uint_as_float(q.z);
#pragma unroll
                    for (int o = 16; o; o >>= 1) { nv += __shfl_xor_sync(0xffffffffu, nv, o); no += __shfl_xor_sync(0xffffffffu, no, o); }
                    const int lc = ((int)(FU(nv) >> 23) + (int)(FU(no) >> 23) - 252 + 9 + 1) >> 1;
                    sts32(sbu + R_MISC + 32, 140 - lc);
                    __syncwarp();
                }
                const uint4 ma = lds128uv(sbu + R_MISC), mb = lds128uv(sbu + R_MISC + 16);
                const int em = (int)(max(max(max(ma.x, ma.y), max(ma.z, ma.w)), max(max(mb.x, mb.y), max(mb.z, mb.w))) >> 23) + (int)(rpb >> 23) - 127;
                const int es = min(max((int)lds32v_(sbu + R_MISC + 32) - max(em, 127), -60), 60);
                sts32(sbu + R_MISC + 40, (127 + es) << 23);
                mbar_arrive_if(sbu + R_BAR + 8 * MB_V, l16 == 0);
                TS(4, es);
            }
            uint8_t* dst = (uint8_t*)&g_KVf[s][cc >> 1][(cc & 1) * 256] + l16;
            const uint32_t r2 = prmt(rpb, 0, 0x3232u);
#pragma unroll
            for (int i = 0; i < 2; i++) {
                const uint4 a = lds128uv(rL + R_STG + i * 512);
                stg4(dst + i * 512, make_uint4(~hmul2b(a.x, r2), ~hmul2b(a.y, r2), ~hmul2b(a.z, r2), ~hmul2b(a.w, r2)));
                const float2 b0 = lds64v(r8 + R_VB + (cc & 1) * 1024 + i * 512), b1 = lds64v(r8 + R_VB + (cc & 1) * 1024 + i * 512 + 256);
                stg4(dst + 2048 + i * 512, make_uint4(~FU(b0.x), ~FU(b0.y), ~FU(b1.x), ~FU(b1.y)));
            }
            __syncwarp();
            if (l16 == 0) { stg_rlx(&g_f.rec[cc], (ep << 8) | (s + 1)); if (s == NSEG - 1) GT(1500 + cc); }
            __syncwarp();
        } else {
            bar_arrive(9, 256);
            if (fo == 2) {
                if (l16 < 144) stg4((void*)mkptr((glo + zero_off(cc, l16 >> 4)) ^ aslot(s + 4), ghi), make_uint4(0, 0, 0, 0));
                __syncwarp();
            } else if (fo == 3) {
                if (((s & 1) || s == 0) && s + 3 < NSEG) {
                    const uint32_t* fp = &g_f.kv[(s + 3) >> 1][cc >> 1][0];
                    uint32_t n = 0;
#pragma unroll 1
                    while (true) {
                        const uint2 v = ldg_rlx2(fp);
                        if (__all_sync(0xffffffffu, v.x == ep && v.y == ep)) break;
                        __nanosleep(64);
                        if (++n > SPIN_LIMIT) { ABORT(6); break; }
                    }
                }
                if (!(s & 1) && s + 2 < NSEG && (!TEARLY || s == 0)) {
                    spin_until(clk32(), DT);
                    if (l16 == 0) load_slot(sbu, cc, (s + 2) >> 1, maps);
                    __syncwarp();
                }
            }
        }
        if (s == NSEG - 1) break;
        auto early = [&]() {
#pragma unroll
            for (int i = 0; i < NCX - NCL; i++) { lds_fragv(wv[i], rG + CX + 4096 * i); lds_fragv(wv[16 + i], rG + CX + 4096 * i + 512); }
        };
        GATHER(1, , early(); rpb = 0x7f000000u - lds32v_(sbu + R_MISC + 40);, bar_arrive(2, 256);)
    }
}

__device__ __forceinline__ bool cand_better(float v, int i, float bv, int bi) { return v > bv || (v == bv && i < bi); }
constexpr int F_WG = 0, F_WU = 32768, F_WD = 65536, F_X = 98304, F_RED = F_X + 4096, F_ACT = F_RED + 8192, F_SEL = F_ACT + 256;

__device__ __noinline__ void ffn_phase(const Maps& maps, const bf16* __restrict__ wd, bf16* __restrict__ out) {
    extern __shared__ __align__(1024) uint8_t smem[];
    const uint32_t sb = smem_u32(smem);
    const int c = ((volatile int*)(smem + SH_OFF))[8];
    const uint32_t epoch = ((volatile uint32_t*)(smem + SH_OFF))[9];
    const int tid = threadIdx.x;
    constexpr int NWK = FF / 32;
    const bool worker = c < NWK;
    bar_sync(0, 384);
    const uint32_t mb = sb + R_BAR + 8 * MB_W0;
    if (tid == 32 && worker) {
        asm volatile("fence.proxy.async.shared::cta;" ::: "memory");
        mbar_expect_tx(mb, 98304);
        tma2d(sb + F_WG, &maps.wg, c * 32, 0, mb); tma2d(sb + F_WG + 16384, &maps.wg, c * 32, 256, mb);
        tma2d(sb + F_WU, &maps.wu, c * 32, 0, mb); tma2d(sb + F_WU + 16384, &maps.wu, c * 32, 256, mb);
        asm volatile("cp.async.bulk.shared::cluster.global.mbarrier::complete_tx::bytes [%0], [%1], %2, [%3];"
            :: "r"(sb + F_WD), "l"(wd + (size_t)c * 32 * DM), "r"(32768), "r"(mb) : "memory");
    }
    int p0 = -1, p1 = -1;
#pragma unroll 1
    for (int pass = 0; pass < 2; pass++) {
        if (tid < 32) {
            const uint32_t tag = epoch & 0xfffffu;
            uint4 r[4]; uint32_t n = 0;
            const int t3 = tid + 96 < NFW ? tid + 96 : tid;
#pragma unroll 1
            while (true) {
                bool ok = true;
#pragma unroll
                for (int i = 0; i < 4; i++) r[i] = ldg_rlx4((const uint32_t*)&g_f.cand[pass][i < 3 ? tid + 32 * i : t3]);
#pragma unroll
                for (int i = 0; i < 4; i++) ok = ok && (r[i].y >> 12) == tag && (r[i].w >> 12) == tag;
                if (__all_sync(0xffffffffu, ok)) break;
                __nanosleep(32);
                if (++n > SPIN_LIMIT) { ABORT(7); break; }
            }
            float b0 = __uint_as_float(r[0].x), b1 = __uint_as_float(r[0].z); int i0 = r[0].y & 4095, i1 = r[0].w & 4095;
#pragma unroll
            for (int i = 1; i < 4; i++) {
                if (i < 3 || t3 != tid) {
                    float c0 = __uint_as_float(r[i].x), c1 = __uint_as_float(r[i].z); int j0 = r[i].y & 4095, j1 = r[i].w & 4095;
                    if (cand_better(c0, j0, b0, i0)) {
                        if (cand_better(c1, j1, b0, i0)) { b1 = c1; i1 = j1; } else { b1 = b0; i1 = i0; }
                        b0 = c0; i0 = j0;
                    } else if (cand_better(c0, j0, b1, i1)) { b1 = c0; i1 = j0; }
                }
            }
#pragma unroll
            for (int o = 16; o; o >>= 1) {
                float c0 = __shfl_xor_sync(0xffffffffu, b0, o), c1 = __shfl_xor_sync(0xffffffffu, b1, o);
                int j0 = __shfl_xor_sync(0xffffffffu, i0, o), j1 = __shfl_xor_sync(0xffffffffu, i1, o);
                if (cand_better(c0, j0, b0, i0)) {
                    if (cand_better(c1, j1, b0, i0)) { b1 = c1; i1 = j1; } else { b1 = b0; i1 = i0; }
                    b0 = c0; i0 = j0;
                } else if (cand_better(c0, j0, b1, i1)) { b1 = c0; i1 = j0; }
            }
            i0 = min(i0, SQ - 1); i1 = min(i1, SQ - 1);
            if (i0 != p0 || i1 != p1) {
                n = 0;
#pragma unroll 1
                while (!__all_sync(0xffffffffu, (ldg_rlx(&g_f.rows[pass][tid]) == epoch) & (ldg_rlx(&g_f.rows[pass][tid + 32]) == epoch) &
                                                   (ldg_rlx(&g_f.rows[pass][tid + 64]) == epoch) & (ldg_rlx(&g_f.rows[pass][t3]) == epoch))) { __nanosleep(32); if (++n > SPIN_LIMIT) { ABORT(7); break; } }
            }
            int* sel = (int*)(smem + F_SEL);
            if (pass && tid == 0) GT(c * 8 + 5);
            if (tid == 0) { sel[0] = i0; sel[1] = i1; ((float*)sel)[2] = b0; ((float*)sel)[3] = b1; }
        }
        bar_sync(0, 384);
        const int t0 = ((int*)(smem + F_SEL))[0], t1 = ((int*)(smem + F_SEL))[1];
        if (c == 3 && tid == 0 && pass == 0) GT(1430);
        if (t0 == p0 && t1 == p1) break;
        const uint32_t ytag = epoch * 2 + pass + 1;
        if (worker) {
            float2* xs = (float2*)(smem + F_X);
            if (tid < 256) {
                uint32_t a = __ldcg((const uint32_t*)(g_hn + (size_t)t0 * DM) + tid), b = __ldcg((const uint32_t*)(g_hn + (size_t)t1 * DM) + tid);
                *(float4*)(xs + tid * 2) = make_float4(bf_lo(a), bf_lo(b), bf_hi(a), bf_hi(b));
            }
            mbar_wait(mb, 1);
            if (c == 3 && tid == 0 && pass == 0) GT(1431);
            bar_sync(0, 384);
            float4* red = (float4*)(smem + F_RED);
            if (tid < 256) {
                const int cp = tid & 31, kg = tid >> 5;
                const uint32_t* wp = (const uint32_t*)(smem + (cp < 16 ? F_WG : F_WU)) + (cp & 15);
                float a0 = 0.f, a1 = 0.f, b0 = 0.f, b1 = 0.f;
#pragma unroll 16
                for (int k = kg * 64; k < kg * 64 + 64; k++) {
                    uint32_t w = wp[k * 16]; float2 x = xs[k];
                    a0 = fmaf(x.x, bf_lo(w), a0); a1 = fmaf(x.x, bf_hi(w), a1); b0 = fmaf(x.y, bf_lo(w), b0); b1 = fmaf(x.y, bf_hi(w), b1);
                }
                red[kg * 32 + cp] = make_float4(a0, a1, b0, b1);
            }
            bar_sync(0, 384);
            float2* act = (float2*)(smem + F_ACT);
            if (tid < 64) {
                const int f = tid & 31, tk = tid >> 5;
                const float* r = (const float*)red + (f >> 1) * 4 + tk * 2 + (f & 1);
                float gsum = 0.f, usum = 0.f;
#pragma unroll
                for (int kg = 0; kg < 8; kg++) { gsum += r[kg * 128]; usum += r[kg * 128 + 64]; }
                gsum = rbf(gsum); usum = rbf(usum);
                float sg = rbf(gsum / (1.f + __expf(-gsum)));
                ((float*)act)[f * 2 + tk] = rbf(sg * usum);
            }
            bar_sync(0, 384);
            if (tid < 256) {
                const uint32_t* wp = (const uint32_t*)(smem + F_WD) + tid;
                float a0 = 0.f, a1 = 0.f, b0 = 0.f, b1 = 0.f;
#pragma unroll 16
                for (int f = 0; f < 32; f++) {
                    uint32_t w = wp[f * 256]; float2 x = act[f];
                    a0 = fmaf(x.x, bf_lo(w), a0); a1 = fmaf(x.x, bf_hi(w), a1); b0 = fmaf(x.y, bf_lo(w), b0); b1 = fmaf(x.y, bf_hi(w), b1);
                }
                asm volatile("st.relaxed.gpu.global.v4.b32 [%0], {%1,%2,%3,%2};" :: "l"(&g_yp[pass][c][tid]), "r"(FU(a0)), "r"(ytag), "r"(FU(a1)) : "memory");
                asm volatile("st.relaxed.gpu.global.v4.b32 [%0], {%1,%2,%3,%2};" :: "l"(&g_yp[pass][c][256 + tid]), "r"(FU(b0)), "r"(ytag), "r"(FU(b1)) : "memory");
            }
            if (c == 3 && tid == 0 && pass == 0) GT(1432);
        } else {
            const int r = c - NWK, j = tid & 63, part = tid >> 6, tk = r >> 2, dp = (r & 3) * 64 + j;
            const int tok = tk ? t1 : t0, old = tk ? p1 : p0;
            uint32_t hw = 0, nw = 0;
            if (part == 0) {
                hw = __ldcg((const uint32_t*)(g_h + (size_t)tok * DM) + dp); nw = __ldcg((const uint32_t*)(g_hn + (size_t)tok * DM) + dp);
                if (old >= 0 && old != t0 && old != t1) {
                    uint32_t ho = __ldcg((const uint32_t*)(g_h + (size_t)old * DM) + dp), no = __ldcg((const uint32_t*)(g_hn + (size_t)old * DM) + dp);
                    ((uint32_t*)(out + (size_t)old * DM))[dp] = pack2(bf_lo(ho) + bf_lo(no), bf_hi(ho) + bf_hi(no));
                }
            }
            float s0 = 0.f, s1 = 0.f;
            uint4 v[10]; uint32_t n = 0;
            bool ok;
#pragma unroll 1
            do {
                ok = true;
#pragma unroll
                for (int i = 0; i < 10; i++) {
                    const int src = part + 6 * i;
                    v[i] = src < NWK ? ldg_rlx4((const uint32_t*)&g_yp[pass][src][tk * 256 + dp]) : make_uint4(0, ytag, 0, ytag);
                }
#pragma unroll
                for (int i = 0; i < 10; i++) ok = ok && v[i].y == ytag && v[i].w == ytag;
                if (!ok) __nanosleep(100);
                if (++n > SPIN_LIMIT) { ABORT(7); break; }
            } while (!ok);
#pragma unroll
            for (int i = 0; i < 10; i++) { s0 += __uint_as_float(v[i].x); s1 += __uint_as_float(v[i].z); }
            float2* red = (float2*)(smem + F_RED);
            red[part * 64 + j] = make_float2(s0, s1);
            bar_sync(0, 384);
            if (part == 0) {
#pragma unroll
                for (int i = 1; i < 6; i++) { float2 q = red[i * 64 + j]; s0 += q.x; s1 += q.y; }
                const float rs = rbf(1.f / (1.f + __expf(-((float*)(smem + F_SEL))[2 + tk])));
                const float y0 = rbf(rbf(s0) * rs), y1 = rbf(rbf(s1) * rs);
                ((uint32_t*)(out + (size_t)tok * DM))[dp] = pack2(bf_lo(hw) + rbf(bf_lo(nw) + y0), bf_hi(hw) + rbf(bf_hi(nw) + y1));
            }
            if (tid == 0 && pass == 0 && r == 0) GT(1434);
        }
        p0 = t0; p1 = t1;
        if (c == 3 && tid == 0 && pass == 0) GT(1433);
        bar_sync(0, 384);
    }
}

constexpr int G_W = 0;
constexpr int G_RING = 131072;
constexpr int G_BUF = 163840;
constexpr int G_BAR = 229376;
constexpr int G_SMEM = G_BAR + 512;
enum { GB_W0 = 0, GB_W1, GB_WFREE, GB_FULL, GB_EMPTY = GB_FULL + 8, GB_KV = GB_EMPTY + 8, GB_STG = GB_KV + 2, GB_FREE = GB_STG + 2, GB_XN = GB_FREE + 2, GB_RL, GB_T1D, GB_VV, GB_KVF = GB_VV + 2, GB_VF, GB_N };
constexpr int SMEM_TOTAL = 232448;

__device__ __forceinline__ void wgmma_n128(float* d, uint64_t da, uint64_t db, int scale_d) {
    asm volatile("{\n.reg .pred p;\nsetp.ne.b32 p, %66, 0;\n"
        "wgmma.mma_async.sync.aligned.m64n128k16.f32.bf16.bf16 "
        "{%0,%1,%2,%3,%4,%5,%6,%7,%8,%9,%10,%11,%12,%13,%14,%15,%16,%17,%18,%19,%20,%21,%22,%23,%24,%25,%26,%27,%28,%29,%30,%31,"
        "%32,%33,%34,%35,%36,%37,%38,%39,%40,%41,%42,%43,%44,%45,%46,%47,%48,%49,%50,%51,%52,%53,%54,%55,%56,%57,%58,%59,%60,%61,%62,%63}, "
        "%64, %65, p, 1, 1, 0, 1;\n}"
        : "+f"(d[0]), "+f"(d[1]), "+f"(d[2]), "+f"(d[3]), "+f"(d[4]), "+f"(d[5]), "+f"(d[6]), "+f"(d[7]), "+f"(d[8]), "+f"(d[9]), "+f"(d[10]), "+f"(d[11]),
          "+f"(d[12]), "+f"(d[13]), "+f"(d[14]), "+f"(d[15]), "+f"(d[16]), "+f"(d[17]), "+f"(d[18]), "+f"(d[19]), "+f"(d[20]), "+f"(d[21]), "+f"(d[22]), "+f"(d[23]),
          "+f"(d[24]), "+f"(d[25]), "+f"(d[26]), "+f"(d[27]), "+f"(d[28]), "+f"(d[29]), "+f"(d[30]), "+f"(d[31]), "+f"(d[32]), "+f"(d[33]), "+f"(d[34]), "+f"(d[35]),
          "+f"(d[36]), "+f"(d[37]), "+f"(d[38]), "+f"(d[39]), "+f"(d[40]), "+f"(d[41]), "+f"(d[42]), "+f"(d[43]), "+f"(d[44]), "+f"(d[45]), "+f"(d[46]), "+f"(d[47]),
          "+f"(d[48]), "+f"(d[49]), "+f"(d[50]), "+f"(d[51]), "+f"(d[52]), "+f"(d[53]), "+f"(d[54]), "+f"(d[55]), "+f"(d[56]), "+f"(d[57]), "+f"(d[58]), "+f"(d[59]),
          "+f"(d[60]), "+f"(d[61]), "+f"(d[62]), "+f"(d[63])
        : "l"(da), "l"(db), "r"(scale_d));
}

__device__ __forceinline__ constexpr uint32_t slot_off(int slot) {
    return slot < 2 ? G_RING + slot * 16384 : G_BUF + (slot - 2) * 32768 + 16384;
}
template <int NSLOT>
__device__ __forceinline__ void gemm_tile(float* acc, uint32_t sb, int tile, int it, bool first, uint32_t wpar, int wg, bool pass, uint32_t l0) {
    const uint32_t bar = sb + G_BAR;
    bar_sync(3 + wg, 256);
    int prev = 0;
#pragma unroll
    for (int k = 0; k < 4; k++) {
        const int n = tile * 4 + k, slot = NSLOT == 4 ? k : n % 3;
        const uint32_t sz = sb + (((it + k) << 4) & sb & 0x3f0);
        const uint64_t da = desc_sw128(sz + slot_off(slot), 16, 1024), db0 = desc_sw128(sz + G_W, 65536, 1024);
        if ((k & 1) == 0 && first) mbar_wait_p(bar + 8 * (GB_W0 + (k >> 1)), wpar);
        bool rel = false;
        if (EREL && k > 0 && !__all_sync(0xffffffffu, mbar_test(bar + 8 * (GB_FULL + slot), tile & 1))) {
            asm volatile("wgmma.wait_group.sync.aligned 0;" ::: "memory");
            mbar_arrive2_if(bar + 8 * (GB_EMPTY + prev), l0);
            rel = true;
        }
        mbar_wait_p(bar + 8 * (GB_FULL + slot), NSLOT == 4 ? (tile & 1) : ((n / 3) & 1));
        if (k == 3 && pass) bar_arrive(3 + (wg ^ 1), 256);
        asm volatile("wgmma.fence.sync.aligned;" ::: "memory");
#pragma unroll
        for (int kk = 0; kk < 4; kk++) wgmma_n128(acc, da + kk * 2, db0 + k * 1024 + kk * 128, (k | kk) != 0);
        asm volatile("wgmma.commit_group.sync.aligned;" ::: "memory");
        if (k > 0) {
            asm volatile("wgmma.wait_group.sync.aligned 1;" ::: "memory");
            mbar_arrive2_if(bar + 8 * (GB_EMPTY + prev), rel ? 0 : l0);
        }
#pragma unroll
        for (int kk = 0; kk < 4; kk++) wgmma_n128(acc, da + 512 + kk * 2, db0 + k * 1024 + 512 + kk * 128, 1);
        asm volatile("wgmma.commit_group.sync.aligned;" ::: "memory");
        prev = slot;
    }
    asm volatile("wgmma.wait_group.sync.aligned 0;" ::: "memory");
    mbar_arrive2_if(bar + 8 * (GB_EMPTY + prev), l0);
}
__device__ __forceinline__ void stage_bf16(const float* acc, uint32_t buf, float s0, float s1) {
    const int lane = threadIdx.x & 31, wq = (threadIdx.x >> 5) & 3;
    const int row = wq * 16 + (lane & 7) + ((lane >> 3) & 1) * 8;
    const uint32_t base = buf + row * 128;
#pragma unroll
    for (int j = 0; j < 16; j += 2) {
        const int ch = (j & 7) + (lane >> 4);
        stsm4(base + (j >> 3) * 8192 + ((ch ^ (row & 7)) << 4),
              pack2(acc[4 * j] * s0, acc[4 * j + 1] * s0), pack2(acc[4 * j + 2] * s1, acc[4 * j + 3] * s1),
              pack2(acc[4 * j + 4] * s0, acc[4 * j + 5] * s0), pack2(acc[4 * j + 6] * s1, acc[4 * j + 7] * s1));
    }
}

__device__ __forceinline__ void store_perm(const float* acc, bf16* dst, int ld, float s0, float s1) {
#pragma unroll
    for (int i = 0; i < 4; i++) {
        const float* a = acc + 16 * i;
        *(uint4*)(dst + i * 32) = make_uint4(pack2(a[0] * s0, a[1] * s0), pack2(a[4] * s0, a[5] * s0), pack2(a[8] * s0, a[9] * s0), pack2(a[12] * s0, a[13] * s0));
        *(uint4*)(dst + 8 * ld + i * 32) = make_uint4(pack2(a[2] * s1, a[3] * s1), pack2(a[6] * s1, a[7] * s1), pack2(a[10] * s1, a[11] * s1), pack2(a[14] * s1, a[15] * s1));
    }
}
template <int ACC>
__device__ __forceinline__ void wgmma_rs64(float* d, const uint32_t* a, uint64_t db) {
    asm volatile("{\n.reg .pred p;\nsetp.ne.b32 p, %37, 0;\n"
        "wgmma.mma_async.sync.aligned.m64n64k16.f32.bf16.bf16 {%0,%1,%2,%3,%4,%5,%6,%7,%8,%9,%10,%11,%12,%13,%14,%15,%16,%17,%18,%19,%20,%21,%22,%23,%24,%25,%26,%27,%28,%29,%30,%31}, {%32,%33,%34,%35}, %36, p, 1, 1, 0;\n}"
        : "+f"(d[0]), "+f"(d[1]), "+f"(d[2]), "+f"(d[3]), "+f"(d[4]), "+f"(d[5]), "+f"(d[6]), "+f"(d[7]), "+f"(d[8]), "+f"(d[9]), "+f"(d[10]), "+f"(d[11]), "+f"(d[12]), "+f"(d[13]), "+f"(d[14]), "+f"(d[15]), "+f"(d[16]), "+f"(d[17]), "+f"(d[18]), "+f"(d[19]), "+f"(d[20]), "+f"(d[21]), "+f"(d[22]), "+f"(d[23]), "+f"(d[24]), "+f"(d[25]), "+f"(d[26]), "+f"(d[27]), "+f"(d[28]), "+f"(d[29]), "+f"(d[30]), "+f"(d[31])
        : "r"(a[0]), "r"(a[1]), "r"(a[2]), "r"(a[3]), "l"(db), "n"(ACC));
}
template <int ACC>
__device__ __forceinline__ void wgmma_rs128t(float* d, const uint32_t* a, uint64_t db) {
    asm volatile("{\n.reg .pred p;\nsetp.ne.b32 p, %69, 0;\n"
        "wgmma.mma_async.sync.aligned.m64n128k16.f32.bf16.bf16 {%0,%1,%2,%3,%4,%5,%6,%7,%8,%9,%10,%11,%12,%13,%14,%15,%16,%17,%18,%19,%20,%21,%22,%23,%24,%25,%26,%27,%28,%29,%30,%31,%32,%33,%34,%35,%36,%37,%38,%39,%40,%41,%42,%43,%44,%45,%46,%47,%48,%49,%50,%51,%52,%53,%54,%55,%56,%57,%58,%59,%60,%61,%62,%63}, {%64,%65,%66,%67}, %68, p, 1, 1, 1;\n}"
        : "+f"(d[0]), "+f"(d[1]), "+f"(d[2]), "+f"(d[3]), "+f"(d[4]), "+f"(d[5]), "+f"(d[6]), "+f"(d[7]), "+f"(d[8]), "+f"(d[9]), "+f"(d[10]), "+f"(d[11]), "+f"(d[12]), "+f"(d[13]), "+f"(d[14]), "+f"(d[15]), "+f"(d[16]), "+f"(d[17]), "+f"(d[18]), "+f"(d[19]), "+f"(d[20]), "+f"(d[21]), "+f"(d[22]), "+f"(d[23]), "+f"(d[24]), "+f"(d[25]), "+f"(d[26]), "+f"(d[27]), "+f"(d[28]), "+f"(d[29]), "+f"(d[30]), "+f"(d[31]), "+f"(d[32]), "+f"(d[33]), "+f"(d[34]), "+f"(d[35]), "+f"(d[36]), "+f"(d[37]), "+f"(d[38]), "+f"(d[39]), "+f"(d[40]), "+f"(d[41]), "+f"(d[42]), "+f"(d[43]), "+f"(d[44]), "+f"(d[45]), "+f"(d[46]), "+f"(d[47]), "+f"(d[48]), "+f"(d[49]), "+f"(d[50]), "+f"(d[51]), "+f"(d[52]), "+f"(d[53]), "+f"(d[54]), "+f"(d[55]), "+f"(d[56]), "+f"(d[57]), "+f"(d[58]), "+f"(d[59]), "+f"(d[60]), "+f"(d[61]), "+f"(d[62]), "+f"(d[63])
        : "r"(a[0]), "r"(a[1]), "r"(a[2]), "r"(a[3]), "l"(db), "n"(ACC));
}
__device__ __forceinline__ void attention_tile(float* acc, uint32_t sb, int tile, int h, int wg, int wq, uint32_t l0, uint32_t epoch, uint2 rec) {
    const uint32_t buf = sb + G_BUF + ((tile << 4) & sb & 0x3f0);
    const int lane = threadIdx.x & 31, g = lane >> 2, t = lane & 3;
    const int sg = wq >> 1, hf = wq & 1, seg = tile * 2 + sg;
    uint32_t qf[8][4];
#pragma unroll
    for (int kk = 0; kk < 8; kk++) {
        qf[kk][0] = pack2(acc[8 * kk], acc[8 * kk + 1]); qf[kk][1] = pack2(acc[8 * kk + 2], acc[8 * kk + 3]);
        qf[kk][2] = pack2(acc[8 * kk + 4], acc[8 * kk + 5]); qf[kk][3] = pack2(acc[8 * kk + 6], acc[8 * kk + 7]);
    }
    uint32_t* kvf = &g_KVf[seg][h][lane * 4];
    uint4 km[4], vm[4];
    const bool early = __all_sync(0xffffffffu, (rec.x >> 8) == epoch && (rec.y >> 8) == epoch && (rec.x & 255) > seg && (rec.y & 255) > seg);
#pragma unroll
    for (int i = 0; i < 4; i++) { km[i] = ldg_rlx4_if(kvf + i * 128, early); vm[i] = ldg_rlx4_if(kvf + 512 + i * 128, early); }
    mbar_wait_p(sb + G_BAR + 8 * (GB_KV + wg), (tile >> 1) & 1);
    if (h == 5 && (threadIdx.x & 127) == 0 && tile < 6) GT(1750 + tile * 8 + 2);
    float sc[5][4];
    {
        const uint64_t dk = desc_sw128(buf, 16, 1024);
        asm volatile("wgmma.fence.sync.aligned;" ::: "memory");
#pragma unroll
        for (int kk = 0; kk < 8; kk++) {
            if (kk == 0) wgmma_rs64<0>(acc, qf[kk], dk); else wgmma_rs64<1>(acc, qf[kk], dk + (kk >> 2) * 512 + (kk & 3) * 2);
        }
        asm volatile("wgmma.commit_group.sync.aligned;" ::: "memory");
        asm volatile("wgmma.wait_group.sync.aligned 0;" ::: "memory");
        mbar_arrive_if(sb + G_BAR + 8 * GB_KVF, l0);
#pragma unroll
        for (int i = 0; i < 32; i++) asm volatile("" : "+f"(acc[i]) :: "memory");
#pragma unroll
        for (int b = 0; b < 4; b++)
#pragma unroll
            for (int i = 0; i < 4; i++) sc[b][i] = sg ? acc[16 + 4 * b + i] : acc[4 * b + i];
        sc[4][0] = sc[4][1] = sc[4][2] = sc[4][3] = 0.f;
    }
    const float cexp = 0.08838834764831845f * 1.4426950408889634f;
    const int r0 = hf * 16 + g, r1 = r0 + 8;
#pragma unroll
    for (int b = 0; b < 4; b++) {
        const int j = b * 8 + 2 * t;
        if (j > r0) sc[b][0] = -INFINITY;
        if (j + 1 > r0) sc[b][1] = -INFINITY;
        if (j > r1) sc[b][2] = -INFINITY;
        if (j + 1 > r1) sc[b][3] = -INFINITY;
    }
    float m0 = -INFINITY, m1 = -INFINITY;
#pragma unroll
    for (int b = 0; b < 4; b++) { m0 = fmaxf(m0, fmaxf(sc[b][0], sc[b][1])); m1 = fmaxf(m1, fmaxf(sc[b][2], sc[b][3])); }
    m0 = fmaxf(m0, __shfl_xor_sync(0xffffffffu, m0, 1)); m0 = fmaxf(m0, __shfl_xor_sync(0xffffffffu, m0, 2));
    m1 = fmaxf(m1, __shfl_xor_sync(0xffffffffu, m1, 1)); m1 = fmaxf(m1, __shfl_xor_sync(0xffffffffu, m1, 2));
    float z0 = 0.f, z1 = 0.f;
    {
        const float c0 = -m0 * cexp, c1 = -m1 * cexp;
        uint32_t pf[4][2];
#pragma unroll
        for (int b = 0; b < 4; b++) {
            pf[b][0] = pack2(ex2(fmaf(sc[b][0], cexp, c0)), ex2(fmaf(sc[b][1], cexp, c0)));
            pf[b][1] = pack2(ex2(fmaf(sc[b][2], cexp, c1)), ex2(fmaf(sc[b][3], cexp, c1)));
            z0 += bf_lo(pf[b][0]) + bf_hi(pf[b][0]); z1 += bf_lo(pf[b][1]) + bf_hi(pf[b][1]);
        }
        uint32_t pa[4][4];
#pragma unroll
        for (int kk = 0; kk < 4; kk++)
#pragma unroll
            for (int i = 0; i < 4; i++) pa[kk][i] = (kk >> 1) == sg ? pf[(kk & 1) * 2 + (i >> 1)][i & 1] : 0u;
        const uint64_t dv = desc_sw128(buf + 32768, 8192, 1024);
        mbar_wait_p(sb + G_BAR + 8 * (GB_VV + wg), (tile >> 1) & 1);
        asm volatile("wgmma.fence.sync.aligned;" ::: "memory");
#pragma unroll
        for (int kk = 0; kk < 4; kk++) { if (kk == 0) wgmma_rs128t<0>(acc, pa[kk], dv); else wgmma_rs128t<1>(acc, pa[kk], dv + kk * 128); }
        asm volatile("wgmma.commit_group.sync.aligned;" ::: "memory");
        asm volatile("wgmma.wait_group.sync.aligned 0;" ::: "memory");
#pragma unroll
        for (int i = 0; i < 64; i++) asm volatile("" : "+f"(acc[i]) :: "memory");
    }
    mbar_arrive_if(sb + G_BAR + 8 * GB_VF, l0);
    if (h == 5 && (threadIdx.x & 127) == 0 && tile < 6) GT(1750 + tile * 8 + 3);
    if (!early) wait_rec(&g_f.rec[2 * h], epoch, seg + 1);
    if (seg == 63 && (threadIdx.x & 63) == 0) GT(1570 + h);
    if (h == 5 && (threadIdx.x & 127) == 0 && tile < 6) GT(1750 + tile * 8 + 4);
    __syncwarp();
    {
        uint32_t n = 0;
#pragma unroll 1
        while (true) {
            uint32_t mn = 0xffffffffu;
#pragma unroll
            for (int i = 0; i < 4; i++) mn = min(min(min(mn, min(km[i].x, km[i].y)), min(km[i].z, km[i].w)), min(min(vm[i].x, vm[i].y), min(vm[i].z, vm[i].w)));
            if (__all_sync(0xffffffffu, mn != 0)) break;
            if (++n > SPIN_LIMIT) { ABORT(4); break; }
#pragma unroll
            for (int i = 0; i < 4; i++) { km[i] = ldg_rlx4(kvf + i * 128); vm[i] = ldg_rlx4(kvf + 512 + i * 128); }
        }
#pragma unroll
        for (int i = 0; i < 4; i++) {
            km[i] = make_uint4(~km[i].x, ~km[i].y, ~km[i].z, ~km[i].w); vm[i] = make_uint4(~vm[i].x, ~vm[i].y, ~vm[i].z, ~vm[i].w);
        }
        if (hf) bar_arrive(5 + wg * 2 + sg, 64);
        float sb_[4] = {0.f, 0.f, 0.f, 0.f};
#pragma unroll
        for (int i = 0; i < 4; i++) { MMA(sc[4], qf[2 * i], km[i].x, km[i].y); MMA(sb_, qf[2 * i + 1], km[i].z, km[i].w); }
#pragma unroll
        for (int i = 0; i < 4; i++) sc[4][i] += sb_[i];
        float n0 = fmaxf(sc[4][0], sc[4][1]), n1 = fmaxf(sc[4][2], sc[4][3]);
        n0 = fmaxf(n0, __shfl_xor_sync(0xffffffffu, n0, 1)); n1 = fmaxf(n1, __shfl_xor_sync(0xffffffffu, n1, 1));
        n0 = fmaxf(n0, __shfl_xor_sync(0xffffffffu, n0, 2)); n1 = fmaxf(n1, __shfl_xor_sync(0xffffffffu, n1, 2));
        n0 = fmaxf(n0, m0); n1 = fmaxf(n1, m1);
        const float a0 = ex2((m0 - n0) * cexp), a1 = ex2((m1 - n1) * cexp);
        const float c0 = -n0 * cexp, c1 = -n1 * cexp;
        const uint32_t p0 = pack2(ex2(fmaf(sc[4][0], cexp, c0)), ex2(fmaf(sc[4][1], cexp, c0)));
        const uint32_t p1 = pack2(ex2(fmaf(sc[4][2], cexp, c1)), ex2(fmaf(sc[4][3], cexp, c1)));
        z0 = fmaf(z0, a0, bf_lo(p0) + bf_hi(p0)); z1 = fmaf(z1, a1, bf_lo(p1) + bf_hi(p1));
        const uint32_t* vmw = (const uint32_t*)vm;
#pragma unroll
        for (int j = 0; j < 16; j++) {
            float* o = acc + 4 * j;
            o[0] *= a0; o[1] *= a0; o[2] *= a1; o[3] *= a1;
            mma1688(o, p0, p1, vmw[j]);
        }
        z0 += __shfl_xor_sync(0xffffffffu, z0, 1); z1 += __shfl_xor_sync(0xffffffffu, z1, 1);
        z0 += __shfl_xor_sync(0xffffffffu, z0, 2); z1 += __shfl_xor_sync(0xffffffffu, z1, 2);
    }
    if (h == 5 && (threadIdx.x & 127) == 0 && tile < 6) GT(1750 + tile * 8 + 5);
    store_perm(acc, g_O + (size_t)(tile * 64 + wq * 16 + g) * HD + h * 128 + t * 8, HD, rcpf(z0), rcpf(z1));
    if (tile >= 2) mbar_wait_p(sb + G_BAR + 8 * (GB_FREE + wg), ((tile >> 1) - 1) & 1);
    mbar_arrive(sb + G_BAR + 8 * (GB_STG + wg));
    if (!hf) {
        bar_sync(5 + wg * 2 + sg, 64);
#pragma unroll
        for (int i = 0; i < 8; i++) stg4(kvf + i * 128, make_uint4(0, 0, 0, 0));
    }
}

__device__ __forceinline__ void g_consumer(uint32_t sb_, int g_, int wg_, uint32_t epoch) {
    const uint32_t sb = uni(sb_);
    const int g = uni(g_), wg = uni(wg_), wq = uni((threadIdx.x >> 5) & 3);
    const uint32_t l0 = opaque((threadIdx.x & 31) == 0);
    const uint32_t bar = sb + G_BAR, buf = sb + G_BUF + wg * 32768;
    const int lane = threadIdx.x & 31;
    float acc[64];
    if (wg == 1) bar_arrive(3, 256);
    const int n1 = g < 32 ? HSPLIT / 2 : NT - HSPLIT / 2;
#pragma unroll 1
    for (int i = 0; i < n1; i++) {
        gemm_tile<4>(acc, sb, wg, i, i == 0 || i == NT / 2, i >= NT / 2, wg, true, l0);
        if (i == n1 - 1 || i == NT / 2 - 1) mbar_arrive_if(bar + 8 * GB_WFREE, l0);
        if (threadIdx.x == 0 && i == 0) GT((64 + g) * 8 + 1);
        if (threadIdx.x == 128 && i == 3) GT((64 + g) * 8 + 2);
        if (i > 0) mbar_wait_p(bar + 8 * (GB_FREE + wg), (i - 1) & 1);
        stage_bf16(acc, buf, 1.f, 1.f);
        asm volatile("fence.proxy.async.shared::cta;" ::: "memory");
        mbar_arrive(bar + 8 * (GB_STG + wg));
    }
    if (threadIdx.x == 128) GT((64 + g) * 8 + 3);
    if (g < 32) {
#pragma unroll 1
        for (int i = 0; i < NT / 2; i++) {
            const int tile = 2 * i + wg;
            const uint2 rec = ldg_rlx2(&g_f.rec[2 * g]);
            gemm_tile<4>(acc, sb, tile, i, i == 0, 1, wg, tile != NT - 1, l0);
            if (threadIdx.x == 0 && i == 0) GT((64 + g) * 8 + 4);
            if (threadIdx.x == 128 && i == 3) GT((64 + g) * 8 + 5);
            if (g == 5 && (threadIdx.x & 127) == 0 && tile < 6) GT(1750 + tile * 8 + 1);
            attention_tile(acc, sb, tile, g, wg, wq, l0, epoch, rec);
            if (g == 5 && (threadIdx.x & 127) == 0 && tile < 6) GT(1750 + tile * 8 + 6);
        }
    } else {
#pragma unroll 1
        for (int i = 0; i < NT / 2; i++) {
            const int tile = 2 * i + wg;
            gemm_tile<4>(acc, sb, tile, i, i == 0, 0, wg, tile != NT - 1, l0);
            if (threadIdx.x == 0 && i == 0) GT((64 + g) * 8 + 4);
            if (threadIdx.x == 128 && i == 3) GT((64 + g) * 8 + 5);
            store_perm(acc, g_P + (size_t)(((g - 32) >> 2) * SQ + tile * 64 + wq * 16 + (lane >> 2)) * DM + ((g - 32) & 3) * 128 + (lane & 3) * 8, DM, 1.f, 1.f);
            mbar_wait_p(bar + 8 * (GB_FREE + wg), (i - 1) & 1);
            mbar_arrive(bar + 8 * (GB_STG + wg));
        }
    }
}

__device__ __forceinline__ void load_w(uint32_t sb, const CUtensorMap* tm, int col, int row, int k0 = 0, int k1 = 2) {
    const uint32_t bar = sb + G_BAR;
#pragma unroll
    for (int kh = k0; kh < k1; kh++) {
        mbar_expect_tx(bar + 8 * (GB_W0 + kh), 65536);
        tma2d(sb + G_W + kh * 32768, tm, col, row + kh * 256, bar + 8 * (GB_W0 + kh));
        tma2d(sb + G_W + 65536 + kh * 32768, tm, col + 64, row + kh * 256, bar + 8 * (GB_W0 + kh));
    }
}

__device__ __forceinline__ void rbf2(float& a, float& b) { uint32_t w = pack2(a, b); a = bf_lo(w); b = bf_hi(w); }
__device__ __forceinline__ void warp_sum2(float& a, float& b) {
#pragma unroll
    for (int o = 16; o; o >>= 1) { float c = __shfl_xor_sync(0xffffffffu, a, o), d = __shfl_xor_sync(0xffffffffu, b, o); a += c; b += d; }
}
__device__ __forceinline__ float sum16(const float* v) {
    return (((v[0] + v[1]) + (v[2] + v[3])) + ((v[4] + v[5]) + (v[6] + v[7]))) + (((v[8] + v[9]) + (v[10] + v[11])) + ((v[12] + v[13]) + (v[14] + v[15])));
}
__device__ __forceinline__ void ln_row2(float* v, float* u) {
    float sv = sum16(v), su = sum16(u);
    warp_sum2(sv, su);
    const float mv = sv * (1.f / DM), mu = su * (1.f / DM);
    float qv = 0.f, qu = 0.f, qv2 = 0.f, qu2 = 0.f;
#pragma unroll
    for (int i = 0; i < 16; i += 2) {
        float d0 = v[i] - mv, d1 = v[i + 1] - mv, e0 = u[i] - mu, e1 = u[i + 1] - mu;
        qv = fmaf(d0, d0, qv); qv2 = fmaf(d1, d1, qv2); qu = fmaf(e0, e0, qu); qu2 = fmaf(e1, e1, qu2);
    }
    qv += qv2; qu += qu2;
    warp_sum2(qv, qu);
    const float rv = rbf(mv), ru = rbf(mu);
    const float iv = __frcp_rn(rbf(sqrtf(rbf(rbf(qv * (1.f / DM)) + 1e-5f)))), iu = __frcp_rn(rbf(sqrtf(rbf(rbf(qu * (1.f / DM)) + 1e-5f))));
#pragma unroll
    for (int i = 0; i < 16; i += 2) {
        float a = v[i] - rv, b = v[i + 1] - rv, c = u[i] - ru, d = u[i + 1] - ru;
        rbf2(a, b); rbf2(c, d);
        a *= iv; b *= iv; c *= iu; d *= iu;
        rbf2(a, b); rbf2(c, d);
        v[i] = a; v[i + 1] = b; u[i] = c; u[i + 1] = d;
    }
}

__device__ __forceinline__ void ln_row1(float* v) {
    float sv = sum16(v);
#pragma unroll
    for (int o = 16; o; o >>= 1) sv += __shfl_xor_sync(0xffffffffu, sv, o);
    const float mv = sv * (1.f / DM);
    float qv = 0.f, qv2 = 0.f;
#pragma unroll
    for (int i = 0; i < 16; i += 2) { float d0 = v[i] - mv, d1 = v[i + 1] - mv; qv = fmaf(d0, d0, qv); qv2 = fmaf(d1, d1, qv2); }
    qv += qv2;
#pragma unroll
    for (int o = 16; o; o >>= 1) qv += __shfl_xor_sync(0xffffffffu, qv, o);
    const float rv = rbf(mv);
    float sq, iv;
    asm("sqrt.approx.f32 %0, %1;" : "=f"(sq) : "f"(rbf(rbf(qv * (1.f / DM)) + 1e-5f)));
    asm("rcp.approx.f32 %0, %1;" : "=f"(iv) : "f"(rbf(sq)));
#pragma unroll
    for (int i = 0; i < 16; i += 2) {
        float a = v[i] - rv, b = v[i + 1] - rv;
        rbf2(a, b);
        a *= iv; b *= iv;
        rbf2(a, b);
        v[i] = a; v[i + 1] = b;
    }
}
constexpr int FSPLIT = 28;
__device__ __forceinline__ int fin_row(int id, int i) {
    if (id < 64) { const int tile = i < FSPLIT / 2 ? 2 * i : i + FSPLIT / 2; return tile < NT ? tile * 64 + id : -1; }
    const int j = id - 64 + i * 48;
    return j < FSPLIT * 32 ? (j >> 6) * 128 + 64 + (j & 63) : -1;
}
__device__ __forceinline__ void finalizer(int id, const bf16* __restrict__ x, const bf16* __restrict__ wr, bf16* __restrict__ out, uint32_t epoch) {
    const int lane = threadIdx.x & 31;
    float b0 = -INFINITY, b1 = -INFINITY; int i0 = 0x7fffffff, i1 = 0x7fffffff;
    const uint32_t tag = (epoch & 0xfffffu) << 12;
    uint32_t fl = ~epoch;
    int row = fin_row(id, 0);
    const uint4 ra = *(const uint4*)(wr + lane * 8), rb = *(const uint4*)(wr + 256 + lane * 8);
    uint4 xa = *(const uint4*)(x + (size_t)row * DM + lane * 8), xb = *(const uint4*)(x + (size_t)row * DM + lane * 8 + 256);
#pragma unroll 1
    for (int it = 0; row >= 0; it++) {
        const int tile = row >> 6, nxt = fin_row(id, it + 1);
        const size_t o0 = (size_t)row * DM + lane * 8;
        uint32_t n = 0;
#pragma unroll 1
        while (!__all_sync(0xffffffffu, fl == epoch)) {
            if (n) __nanosleep(it ? 64 : 1000);
            fl = ldg_rlx(&g_f.p[tile][lane]);
            if (++n > SPIN_LIMIT) { ABORT(12); break; }
        }
        if (tile == NT - 1 && id == 63 && lane == 0) GT(1438);
        if ((id == 63 || id == 3 || id == 70) && lane == 0) GT(1800 + (id == 3) * 32 + tile);
        float v[16];
        {
            uint4 pa[8][2];
#pragma unroll
            for (int k = 0; k < 8; k++) {
                pa[k][0] = ldg_rlx4((const uint32_t*)(g_P + (size_t)k * SQ * DM + o0));
                pa[k][1] = ldg_rlx4((const uint32_t*)(g_P + (size_t)k * SQ * DM + o0 + 256));
            }
            fl = ldg_rlx(&g_f.p[max(nxt, 0) >> 6][lane]);
#pragma unroll
            for (int j = 0; j < 2; j++) {
#pragma unroll
                for (int i = 0; i < 4; i++) {
                    uint32_t w[8];
#pragma unroll
                    for (int k = 0; k < 8; k++) w[k] = i == 0 ? pa[k][j].x : (i == 1 ? pa[k][j].y : (i == 2 ? pa[k][j].z : pa[k][j].w));
                    v[j * 8 + 2 * i] = ((bf_lo(w[0]) + bf_lo(w[1])) + (bf_lo(w[2]) + bf_lo(w[3]))) + ((bf_lo(w[4]) + bf_lo(w[5])) + (bf_lo(w[6]) + bf_lo(w[7])));
                    v[j * 8 + 2 * i + 1] = ((bf_hi(w[0]) + bf_hi(w[1])) + (bf_hi(w[2]) + bf_hi(w[3]))) + ((bf_hi(w[4]) + bf_hi(w[5])) + (bf_hi(w[6]) + bf_hi(w[7])));
                }
            }
        }
        uint32_t hw[8];
        {
            const uint32_t xw[8] = {xa.x, xa.y, xa.z, xa.w, xb.x, xb.y, xb.z, xb.w};
            uint32_t aw[8];
#pragma unroll
            for (int i = 0; i < 8; i++) aw[i] = pack2(v[2 * i], v[2 * i + 1]);
#pragma unroll
            for (int d = 1; d <= 2; d++) {
                const bool up = lane & d;
#pragma unroll
                for (int i = 0; i < 8; i++) {
                    if (!(i & d)) {
                        const uint32_t r = __shfl_xor_sync(0xffffffffu, up ? aw[i] : aw[i | d], d);
                        if (up) aw[i] = r; else aw[i | d] = r;
                    }
                }
            }
#pragma unroll
            for (int i = 0; i < 8; i++) {
                hw[i] = pack2(bf_lo(aw[i]) + bf_lo(xw[i]), bf_hi(aw[i]) + bf_hi(xw[i]));
                v[2 * i] = bf_lo(hw[i]); v[2 * i + 1] = bf_hi(hw[i]);
            }
        }
        xa = *(const uint4*)(x + (size_t)max(nxt, 0) * DM + lane * 8); xb = *(const uint4*)(x + (size_t)max(nxt, 0) * DM + lane * 8 + 256);
        ln_row1(v);
        float r0 = 0.f, r1 = 0.f;
        {
            const uint32_t ww[8] = {ra.x, ra.y, ra.z, ra.w, rb.x, rb.y, rb.z, rb.w};
#pragma unroll
            for (int i = 0; i < 8; i++) { r0 = fmaf(v[2 * i], bf_lo(ww[i]), r0); r1 = fmaf(v[2 * i + 1], bf_hi(ww[i]), r1); }
        }
        r0 += r1;
#pragma unroll
        for (int o = 16; o; o >>= 1) r0 += __shfl_xor_sync(0xffffffffu, r0, o);
        r0 = rbf(r0);
        if (cand_better(r0, row, b0, i0)) { b1 = b0; i1 = i0; b0 = r0; i0 = row; }
        else if (cand_better(r0, row, b1, i1)) { b1 = r0; i1 = row; }
        if (tile == NT - 1 && id == 63 && lane == 0) GT(1439);
        const bool last = nxt < 0, spec = tile < SPEC_TILES && (last || (nxt >> 6) >= SPEC_TILES);
        const bool pub = (lane == 0 && spec) || (lane == 1 && last);
        if (pub)
            asm volatile("st.relaxed.gpu.global.v4.b32 [%0], {%1,%2,%3,%4};" :: "l"(&g_f.cand[lane][id]),
                         "r"(FU(b0)), "r"(tag | (uint32_t)min(i0, 4095)), "r"(FU(b1)), "r"(tag | (uint32_t)min(i1, 4095)) : "memory");
#pragma unroll
        for (int j = 0; j < 2; j++) {
            const uint32_t* hh = hw + j * 4; const float* nn = v + j * 8;
            *(uint4*)(out + o0 + j * 256) = make_uint4(pack2(bf_lo(hh[0]) + nn[0], bf_hi(hh[0]) + nn[1]), pack2(bf_lo(hh[1]) + nn[2], bf_hi(hh[1]) + nn[3]),
                                                       pack2(bf_lo(hh[2]) + nn[4], bf_hi(hh[2]) + nn[5]), pack2(bf_lo(hh[3]) + nn[6], bf_hi(hh[3]) + nn[7]));
            *(uint4*)(g_h + o0 + j * 256) = make_uint4(hh[0], hh[1], hh[2], hh[3]);
            *(uint4*)(g_hn + o0 + j * 256) = make_uint4(pack2(nn[0], nn[1]), pack2(nn[2], nn[3]), pack2(nn[4], nn[5]), pack2(nn[6], nn[7]));
        }
        if (last || spec) {
            __threadfence();
            __syncwarp();
            if (pub) stg_rlx(&g_f.rows[lane][id], epoch);
        }
        row = nxt;
    }
    if (id == 0 && lane == 0) { g_epoch = epoch; if (epoch == 0xffffffu) { g_ticket[0] = 0; g_ticket[32] = 0; } }
}

__device__ __forceinline__ void g_producer(uint32_t sb, int g, const Maps& maps, uint32_t epoch, const bf16* __restrict__ x, const bf16* __restrict__ wr, bf16* __restrict__ out) {
    const uint32_t bar = sb + G_BAR;
    const int warp = (threadIdx.x >> 5) - 8;
    if (threadIdx.x == 256 && g == 5) GT(1410);
    if (threadIdx.x == 256 && g == 5) GT(1411);
    if (warp == 3) {
        wait_eq4(&g_f.xn[(threadIdx.x & 31) * 4], epoch, 13);
        __syncwarp();
        if ((threadIdx.x & 31) == 0) mbar_arrive(bar + 8 * GB_XN);
        wait_eq2(&g_f.rload[(threadIdx.x & 31) * 2], epoch, 13);
        __syncwarp();
        if ((threadIdx.x & 31) == 0) mbar_arrive(bar + 8 * GB_RL);
        finalizer(g, x, wr, out, epoch);
        if (g == 63 && (threadIdx.x & 31) == 0) GT(128 * 8 + 6);
    }
    if ((threadIdx.x & 31) != 0) return;
    if (threadIdx.x == 256 && g == 5) GT(1412);
    if (warp == 0) {
        wait_eq4(&g_f.xn[0], epoch, 13);
        const int rk = g & 1;
        const int m1 = g < 32 ? HSPLIT : 2 * NT - HSPLIT;
#pragma unroll 1
        for (int it = 0; it < m1; it++) {
            const int tile = it < NT ? it : it - NT + HSPLIT;
            if (it == HOLD) mbar_wait(bar + 8 * GB_RL, 0);
            if (it == 1) wait_eq4(&g_f.xn[4], epoch, 13);
            if (it == 2) mbar_wait(bar + 8 * GB_XN, 0);
            if (it == NT) {
                mbar_wait(bar + 8 * GB_WFREE, 0);
                load_w(sb, (g & 1) ? &maps.wv : &maps.wk, ((g - 32) >> 1) * 128, 0);
            }
#pragma unroll
            for (int k = 0; k < 4; k++) {
                if (k == 2 && it == 0) load_w(sb, (g & 1) ? &maps.wv : &maps.wk, (g >> 1) * 128, 0, 1, 2);
                mbar_wait(bar + 8 * (GB_EMPTY + k), (it & 1) ^ 1);
                mbar_expect_tx(bar + 8 * (GB_FULL + k), 16384);
                tma2d_mc(sb + slot_off(k) + rk * 8192, &maps.xn2, (k * 2 + rk) * 64, tile * 64, bar + 8 * (GB_FULL + k));
            }
        }
        mbar_wait(bar + 8 * GB_WFREE, g >= 32);
        const int u = g - 32, ks = u >> 2, ns = u & 3;
        if (g < 32) load_w(sb, &maps.wq, g * 128, 0);
        else {
#pragma unroll
            for (int kh = 0; kh < 2; kh++) {
                mbar_expect_tx(bar + 8 * (GB_W0 + kh), 65536);
#pragma unroll
                for (int nh = 0; nh < 2; nh++)
                    asm volatile("cp.async.bulk.tensor.5d.shared::cluster.global.mbarrier::complete_tx::bytes [%0], [%1, {%3, %4, %4, %4, %5}], [%2];"
                        :: "r"(sb + G_W + nh * 65536 + kh * 32768), "l"((uint64_t)&maps.wo2), "r"(bar + 8 * (GB_W0 + kh)), "r"(ns * 128 + nh * 64), "r"(0), "r"(ks * 16 + kh * 8) : "memory");
            }
        }
        if (g < 32) {
#pragma unroll 1
            for (int n = 0; n < NT * 4; n++) {
                const int slot = n & 3;
                mbar_wait(bar + 8 * (GB_EMPTY + slot), ((n >> 2) & 1) ^ 1);
                mbar_expect_tx(bar + 8 * (GB_FULL + slot), 16384);
                tma2d_mc(sb + slot_off(slot) + rk * 8192, &maps.xn2, (slot * 2 + rk) * 64, (n >> 2) * 64, bar + 8 * (GB_FULL + slot));
            }
        } else {
#pragma unroll 1
            for (int tile = 0; tile < NT; tile++) {
                wait_eq4(&g_f.o[tile][ks][0], epoch, 9);
                if (g == 40 && tile == NT - 1) GT(1437);
                if (tile == NT - 1) GT(1690 + g - 32);
#pragma unroll
                for (int k = 0; k < 4; k++) {
                    mbar_wait(bar + 8 * (GB_EMPTY + k), (tile & 1) ^ 1);
                    mbar_expect_tx(bar + 8 * (GB_FULL + k), 16384);
                    tma2d_mc(sb + slot_off(k) + rk * 8192, &maps.ox2, (ks * 8 + k * 2 + rk) * 64, tile * 64, bar + 8 * (GB_FULL + k));
                }
            }
        }
    } else if (warp < 3) {
        const int wg = warp - 1;
        const uint32_t buf = sb + G_BUF + wg * 32768;
        const CUtensorMap* tkv = (g & 1) ? &maps.vx3 : &maps.kx3;
        const int n1 = g < 32 ? HSPLIT / 2 : NT - HSPLIT / 2;
#pragma unroll 1
        for (int i = 0; i < n1; i++) {
            const int tile = (i < NT / 2 ? 2 * i : 2 * i - NT + HSPLIT) + wg, hd = (i < NT / 2 ? g : g - 32) >> 1;
            mbar_wait(bar + 8 * (GB_STG + wg), i & 1);
            tma_store3d(tkv, buf, tile * 64, hd * 2);
            asm volatile("cp.async.bulk.commit_group;" ::: "memory");
            asm volatile("cp.async.bulk.wait_group.read 0;" ::: "memory");
            mbar_arrive(bar + 8 * (GB_FREE + wg));
            asm volatile("cp.async.bulk.wait_group 0;" ::: "memory");
            PUBLISH(&g_f.kv[tile][hd][g & 1], epoch);
        }
        if (wg == 0) mbar_arrive(bar + 8 * GB_T1D);
        if (g < 32 && wg == 1) {
            mbar_wait(bar + 8 * GB_T1D, 0);
#pragma unroll 1
            for (int tile = 0; tile < NT; tile++) {
                wait_eq2(&g_f.kv[tile][g][0], epoch, 10);
                if (tile > 0) mbar_wait(bar + 8 * GB_KVF, (tile - 1) & 1);
                mbar_expect_tx(bar + 8 * (GB_KV + (tile & 1)), 16384);
                tma3d(sb + G_BUF, &maps.kx3, tile * 64, g * 2, bar + 8 * (GB_KV + (tile & 1)));
                if (tile > 0) mbar_wait(bar + 8 * GB_VF, (tile - 1) & 1);
                mbar_expect_tx(bar + 8 * (GB_VV + (tile & 1)), 16384);
                tma3d(sb + G_BUF + 32768, &maps.vx3, tile * 64, g * 2, bar + 8 * (GB_VV + (tile & 1)));
                if (PFK && tile + PFK < NT) {
                    const uint2 v = ldg_rlx2(&g_f.kv[tile + PFK][g][0]);
                    if (v.x == epoch && v.y == epoch) { tma_pf3d(&maps.kx3, (tile + PFK) * 64, g * 2); tma_pf3d(&maps.vx3, (tile + PFK) * 64, g * 2); }
                }
            }
        } else {
#pragma unroll 1
            for (int tile = g < 32 ? 0 : wg; tile < NT; tile += g < 32 ? 1 : 2) {
                mbar_wait(bar + 8 * (GB_STG + (tile & 1)), (tile >> 1) & 1);
                mbar_arrive(bar + 8 * (GB_FREE + (tile & 1)));
                PUBLISH(g < 32 ? &g_f.o[tile][g >> 2][g & 3] : &g_f.p[tile][g - 32], epoch);
                if (g == 3 && tile == NT - 1) GT(1436);
                if (g == 3) GT(1896 + tile);
                if (g < 32 && tile == NT - 1) GT(1610 + g);
                if (g == 40 && tile == NT - 1) GT(1435);
                if (g == 40) GT(1864 + tile);
                if (g >= 32 && tile == NT - 1) GT(1650 + g - 32);
            }
        }
    }
}

struct WPtr { const bf16 *q, *k, *v, *o; };
__device__ __forceinline__ int startup(uint8_t* smem, const bf16* __restrict__ x, const Maps& maps, uint32_t& epoch, const WPtr& pw) {
    const int tid = threadIdx.x, lane = tid & 31, w = tid >> 5, cta = blockIdx.x;
    volatile uint32_t* sh = (volatile uint32_t*)(smem + SH_OFF);
    if (cta == 4 && tid == 0) GT(1399);
    epoch = (ldg_rlx(&g_epoch) + 1) & 0x00ffffffu;
    if (w < 4) {
        if (!(cta & 1)) {
            uint32_t* pp = (uint32_t*)(xpage() + ((XR3 ^ 0x3000u) ^ ((w == 1 || w == 2) ? 0x1000u : 0u) ^ ((w & 2) << 13))) + (cta >> 1) * 8;
            if (lane < 8) stg_rlx(pp + lane, 0u);
            __syncwarp();
            if (lane == 0) {
                uint32_t best = 0xffffffffu, a = 0;
#pragma unroll 1
                for (int r = 0; r < NPROBE; r++) {
                    uint32_t t0 = clk32();
                    asm volatile("atom.relaxed.gpu.global.add.u32 %0, [%1], %2;" : "=r"(a) : "l"(pp), "r"(a + 1) : "memory");
                    if (a == 0x7fffffffu) ABORT(15);
                    uint32_t t1 = clk32();
                    if (r > 0) best = min(best, t1 - t0);
                    else if (w == 0) {
                        asm volatile("red.relaxed.gpu.global.max.u32 [%0], %1;" :: "l"(&g_ticket[0]), "r"(epoch << 8) : "memory");
                        asm volatile("red.relaxed.gpu.global.max.u32 [%0], %1;" :: "l"(&g_ticket[32]), "r"(epoch << 8) : "memory");
                    }
                }
                sh[w] = best;
            }
        }
        if (!(cta & 1)) bar_sync(1, 128);
        if (cta == 4 && tid == 0) GT(1400);
        if (w == 0) {
            if (lane == 0) {
                uint32_t rp;
                if (!(cta & 1)) {
                    uint32_t a = sh[0], b = sh[1], c = sh[2], d = sh[3];
                    uint32_t mid = (min(min(a, b), min(c, d)) + max(max(a, b), max(c, d))) >> 1;
                    const int dd = (int)min(a, d) - (int)min(b, c);
                    uint32_t cls = abs(dd) > 60 ? dd > 0 : a > mid;
                    uint32_t t = atomicAdd(&g_ticket[cls * 32], 1u) & 255;
                    if (t >= (cls ? 34u : 32u)) { cls ^= 1; t = atomicAdd(&g_ticket[cls * 32], 1u) & 255; }
                    rp = min(cls ? 32 + t : t, 65u);
                    stg_rlx(&g_table[(cta >> 1) * 8], (epoch << 8) | rp);
                } else {
                    uint32_t v, n = 0;
#pragma unroll 1
                    while (((v = ldg_rlx(&g_table[(cta >> 1) * 8])) >> 8) != epoch) { if (++n > SPIN_LIMIT) { ABORT(14); break; } }
                    rp = v & 255;
                }
                const int role = rp * 2 + (cta & 1);
                sh[8] = role; sh[9] = epoch;
                while (sh[10] != epoch + 1 && cta < NWAITLN) {}
                if (role < 64) rec_first_loads(smem_u32(smem), role, maps);
                else if (role < 128) load_w(smem_u32(smem), (role & 1) ? &maps.wv : &maps.wk, ((role - 64) >> 1) * 128, 0, 0, 1);
                if (cta == 4) GT(1401);
            }
        }
    } else if (cta < 128) {
        uint4 u[2][2];
        const int row0 = cta * 16 + (w - 4) * 2;
#pragma unroll
        for (int r = 0; r < 2; r++)
#pragma unroll
            for (int j = 0; j < 2; j++) u[r][j] = *(const uint4*)(x + (size_t)(row0 + r) * DM + j * 256 + lane * 8);
        if (cta < 48) {
            const uint32_t b = cta >> 3, off = (b >= 4 ? 0x8000u + (b & 1) * 0x4000u : ((b & 1) ? 0x3000u : 0u) + ((b & 2) << 13)) ^ aslot(cta & 7);
            *(uint4*)(xpage() + off + (tid - 128) * 16) = make_uint4(0, 0, 0, 0);
        }
        float v[2][16];
#pragma unroll
        for (int r = 0; r < 2; r++)
#pragma unroll
            for (int j = 0; j < 2; j++) {
                uint32_t ww[4] = {u[r][j].x, u[r][j].y, u[r][j].z, u[r][j].w};
#pragma unroll
                for (int i = 0; i < 4; i++) { v[r][j * 8 + 2 * i] = bf_lo(ww[i]); v[r][j * 8 + 2 * i + 1] = bf_hi(ww[i]); }
            }
        ln_row2(v[0], v[1]);
#pragma unroll
        for (int r = 0; r < 2; r++)
#pragma unroll
            for (int j = 0; j < 2; j++)
                *(uint4*)(g_xn + (size_t)(row0 + r) * DM + j * 256 + lane * 8) =
                    make_uint4(pack2(v[r][j * 8], v[r][j * 8 + 1]), pack2(v[r][j * 8 + 2], v[r][j * 8 + 3]), pack2(v[r][j * 8 + 4], v[r][j * 8 + 5]), pack2(v[r][j * 8 + 6], v[r][j * 8 + 7]));
        bar_sync(2, 256);
        if (tid == 160 && cta < NWAITLN) { st_rel(&g_f.xn[cta], epoch); sh[10] = epoch + 1; }
        if (cta == 4 && tid == 160) GT(1403);
        __syncwarp();
    }
    if (cta == 4 && tid == 128) GT(1402);
    __syncthreads();
    if (tid == 160 && cta >= NWAITLN && cta < 128) st_rel(&g_f.xn[cta], epoch);
    __syncwarp();
    const int role = sh[8];
    return role;
}

__global__ void __cluster_dims__(2, 1, 1) __launch_bounds__(384, 1)
main_kernel(const __grid_constant__ Maps maps, const bf16* __restrict__ x, const bf16* __restrict__ mem0, const bf16* __restrict__ wr,
            const bf16* __restrict__ wd, bf16* __restrict__ out, const WPtr pw) {
    extern __shared__ __align__(1024) uint8_t smem[];
    const uint32_t sb = smem_u32(smem);
    if (threadIdx.x == 0) {
        for (int i = 0; i < MB_N; i++) mbar_init(sb + R_BAR + 8 * i, i == MB_V ? 5 : 1);
        for (int i = 0; i < GB_N; i++)
            mbar_init(sb + G_BAR + 8 * i, i == GB_WFREE || (i >= GB_EMPTY && i < GB_KV) ? 8 : (i >= GB_KVF ? 4 : (i >= GB_STG && i < GB_FREE ? 128 : 1)));
        asm volatile("fence.mbarrier_init.release.cluster;" ::: "memory");
    }
    __syncwarp();
    asm volatile("barrier.cluster.arrive.relaxed.aligned;" ::: "memory");
    if (threadIdx.x >= 352 && threadIdx.x < 352 + (int)(sizeof(Maps) / sizeof(CUtensorMap)))
        asm volatile("prefetch.tensormap [%0];" :: "l"((const CUtensorMap*)&maps + (threadIdx.x - 352)) : "memory");
    uint32_t epoch;
    asm volatile("fence.proxy.async.shared::cta;" ::: "memory");
    const int role = uni(startup(smem, x, maps, epoch, pw));
    asm volatile("barrier.cluster.wait.aligned;" ::: "memory");
    const int wg = uni(threadIdx.x >> 7);
    if (role < 64) {
#define SETREG(n) do { if ((n) < 168) asm volatile("setmaxnreg.dec.sync.aligned.u32 %0;" :: "n"(n)); if ((n) > 168) asm volatile("setmaxnreg.inc.sync.aligned.u32 %0;" :: "n"(n)); } while (0)
#define RESREG(n) do { if ((n) < 168) asm volatile("setmaxnreg.inc.sync.aligned.u32 168;"); if ((n) > 168) asm volatile("setmaxnreg.dec.sync.aligned.u32 168;"); } while (0)
        if (wg == WGA) {
            SETREG(RGA);
            rec_a(sb, role, mem0, epoch);
            RESREG(RGA);
        } else if (wg == WGB) {
            SETREG(RGB);
            rec_b(sb, role, epoch);
            RESREG(RGB);
        } else {
            SETREG(RGC);
            rec_c(sb, role, mem0, maps, epoch);
            RESREG(RGC);
        }
        ffn_phase(maps, wd, out);
        if (threadIdx.x == 0) GT(((volatile int*)(smem + SH_OFF))[8] * 8 + 6);
    } else if (role < 128) {
        if (wg < 2) {
            asm volatile("setmaxnreg.inc.sync.aligned.u32 192;");
            g_consumer(sb, role - 64, wg, epoch);
            if (threadIdx.x == 128) GT(role * 8 + 6);
        } else {
            asm volatile("setmaxnreg.dec.sync.aligned.u32 120;");
            g_producer(sb, role - 64, maps, epoch, x, wr, out);
        }
    } else {
        finalizer(64 + (threadIdx.x >> 5) * 4 + role - 128, x, wr, out, epoch);
    }
}

typedef CUresult (*EncodeFn)(CUtensorMap*, CUtensorMapDataType, cuuint32_t, void*, const cuuint64_t*, const cuuint64_t*, const cuuint32_t*, const cuuint32_t*,
                             CUtensorMapInterleave, CUtensorMapSwizzle, CUtensorMapL2promotion, CUtensorMapFloatOOBfill);
static void make_map3(EncodeFn fn, CUtensorMap* m, const void* ptr, uint64_t cols, uint64_t rows) {
    cuuint64_t dims[3] = {64, rows, cols / 64};
    cuuint64_t strides[2] = {cols * 2, 128};
    cuuint32_t box[3] = {64, 64, 2};
    cuuint32_t es[3] = {1, 1, 1};
    fn(m, CU_TENSOR_MAP_DATA_TYPE_BFLOAT16, 3, (void*)ptr, dims, strides, box, es, CU_TENSOR_MAP_INTERLEAVE_NONE, CU_TENSOR_MAP_SWIZZLE_128B,
       CU_TENSOR_MAP_L2_PROMOTION_L2_256B, CU_TENSOR_MAP_FLOAT_OOB_FILL_NONE);
}
static void make_map(EncodeFn fn, CUtensorMap* m, const void* ptr, uint64_t cols, uint64_t rows, uint32_t bcols, uint32_t brows,
                     bool f32 = false, CUtensorMapSwizzle sw = CU_TENSOR_MAP_SWIZZLE_128B) {
    cuuint64_t dims[2] = {cols, rows};
    cuuint64_t strides[1] = {cols * (f32 ? 4 : 2)};
    cuuint32_t box[2] = {bcols, brows};
    cuuint32_t es[2] = {1, 1};
    fn(m, f32 ? CU_TENSOR_MAP_DATA_TYPE_FLOAT32 : CU_TENSOR_MAP_DATA_TYPE_BFLOAT16, 2, (void*)ptr, dims, strides, box, es, CU_TENSOR_MAP_INTERLEAVE_NONE, sw,
       CU_TENSOR_MAP_L2_PROMOTION_L2_256B, CU_TENSOR_MAP_FLOAT_OOB_FILL_NONE);
}

extern "C" void kernel_launch(void* const* d_in, const int* in_sizes, int n_in, void* d_out, int out_size) {
    const bf16* x = (const bf16*)d_in[0];
    const bf16* mem0 = (const bf16*)d_in[1];
    const bf16* Wq = (const bf16*)d_in[2];
    const bf16* Wk = (const bf16*)d_in[3];
    const bf16* Wv = (const bf16*)d_in[4];
    const bf16* Wo = (const bf16*)d_in[5];
    const bf16* wr = (const bf16*)d_in[8];
    const bf16* wg = (const bf16*)d_in[9];
    const bf16* wu = (const bf16*)d_in[10];
    const bf16* wd = (const bf16*)d_in[11];
    bf16* out = (bf16*)d_out;

    static EncodeFn enc = nullptr;
    static void *pxn, *pK, *pV, *pO, *pacc;
    if (!enc) {
        cudaDriverEntryPointQueryResult qr;
        void* fn = nullptr;
        cudaGetDriverEntryPoint("cuTensorMapEncodeTiled", &fn, cudaEnableDefault, &qr);
        enc = (EncodeFn)fn;
        cudaGetSymbolAddress(&pxn, g_xn); cudaGetSymbolAddress(&pK, g_K); cudaGetSymbolAddress(&pV, g_V);
        cudaGetSymbolAddress(&pO, g_O); cudaGetSymbolAddress(&pacc, g_P);
        cudaFuncSetAttribute(main_kernel, cudaFuncAttributeMaxDynamicSharedMemorySize, SMEM_TOTAL);
    }
    Maps m;
    make_map(enc, &m.wq, Wq, HD, DM, 64, 256);
    make_map(enc, &m.wk, Wk, HD, DM, 64, 256);
    make_map(enc, &m.wv, Wv, HD, DM, 64, 256);
    make_map(enc, &m.wo, Wo, DM, HD, 64, 128);
    {
        cuuint64_t dims[5] = {DM, 2, 4, 4, HD / 32};
        cuuint64_t strides[4] = {DM * 2, 8 * DM * 2, 2 * DM * 2, 32 * DM * 2};
        cuuint32_t box[5] = {64, 2, 4, 4, 8};
        cuuint32_t es[5] = {1, 1, 1, 1, 1};
        enc(&m.wo2, CU_TENSOR_MAP_DATA_TYPE_BFLOAT16, 5, (void*)Wo, dims, strides, box, es, CU_TENSOR_MAP_INTERLEAVE_NONE, CU_TENSOR_MAP_SWIZZLE_128B,
            CU_TENSOR_MAP_L2_PROMOTION_L2_256B, CU_TENSOR_MAP_FLOAT_OOB_FILL_NONE);
    }
    make_map(enc, &m.kx, pK, HD, SQ, 64, 64);
    make_map(enc, &m.ox2, pO, HD, SQ, 64, 64);
    make_map(enc, &m.xn2, pxn, DM, SQ, 64, 64);
    make_map3(enc, &m.kx3, pK, HD, SQ); make_map3(enc, &m.vx3, pV, HD, SQ);
    make_map(enc, &m.wg, wg, FF, DM, 32, 256, false, CU_TENSOR_MAP_SWIZZLE_NONE);
    make_map(enc, &m.wu, wu, FF, DM, 32, 256, false, CU_TENSOR_MAP_SWIZZLE_NONE);

    cudaStream_t st = cudaStreamPerThread;
    main_kernel<<<NCTA, 384, SMEM_TOTAL, st>>>(m, x, mem0, wr, wd, out, WPtr{Wq, Wk, Wv, Wo});
}
```

```cpp
#include <cuda_runtime.h>
#include <cuda_bf16.h>
#include <cuda.h>
#include <stdint.h>
#include <stddef.h>

typedef __nv_bfloat16 bf16;

constexpr int SQ = 2048, DM = 512, NH = 32, DH = 128, NSEG = 64, HD = 4096, FF = 1792;

constexpr int NT = 32;
#define SPEC_TILES 30
__device__ __align__(1024) bf16 g_xn[SQ * DM];
__device__ __align__(1024) bf16 g_K[SQ * HD];
__device__ __align__(1024) bf16 g_V[SQ * HD];
__device__ __align__(1024) bf16 g_O[SQ * HD];
__device__ __align__(1024) uint32_t g_KVf[NSEG][NH][1024];
__device__ __align__(1024) bf16 g_P[8 * SQ * DM];
__device__ __align__(1024) bf16 g_h[SQ * DM];
__device__ __align__(1024) bf16 g_hn[SQ * DM];
__device__ uint8_t g_xraw[12 << 20];
#define XPG 0
__device__ __forceinline__ uint64_t xpage() { return (((uint64_t)g_xraw + (2 << 20) - 1) & ~(uint64_t)((2 << 20) - 1)) + ((uint64_t)XPG << 21); }
constexpr uint32_t XR3 = (1u << 20) | (1u << 19) | (1u << 12);
__device__ __forceinline__ uint32_t aslot(uint32_t s) { return ((s & 1) << 18) | ((s & 2) << 19) | ((s & 4) * 0xc000u); }
__device__ __forceinline__ uint32_t acc_base(uint32_t W) { return ((W & 2) ? 0x3000u : 0u) + ((W & 4) << 12) + (W & 1) * 2048; }
__device__ __forceinline__ uint32_t ext_base(uint32_t W) { return 0x8000u + ((W & 4) << 12) + (W & 3) * 1024; }
#define XHS 256
#define XSS 32
__device__ __forceinline__ uint32_t zero_off(uint32_t c, uint32_t ln) {
    return ln < 8 ? acc_base(c >> 3) + (c & 7) * 256 + ln * 16 : ext_base(c >> 3) + ((c >> 2) & 1) * XHS + ((c >> 1) & 1) * XSS + (c & 1) * 16;
}
struct Flags {
    uint32_t kv[NT][NH][2];
    uint32_t o[NT][8][32];
    uint32_t rec[64];
    uint32_t xn[128];
    uint32_t rload[64];
    uint32_t p[NT][32];
    uint32_t rows[2][128];
    uint4 cand[2][128];
    uint4 norm[64];
};
__device__ __align__(1024) Flags g_f;
__device__ __align__(1024) uint4 g_yp[2][FF / 32][DM];
__device__ __align__(1024) uint32_t g_table[66 * 8];
__device__ __align__(256) uint32_t g_ticket[64];
__device__ uint32_t g_epoch;
#define HOLD 6
#define HSPLIT 24
#define EREL 0
#define PFK 2
#define PFO 0
#define PFS 0
#define NWAITLN 8
#define WGA 0
#define WGB 1
#define WGC (3 - WGA - WGB)
#define NPROBE 3
constexpr int NCTA = 132;
constexpr int NFW = 112;
__device__ uint32_t g_abort;
__device__ long long g_dbg[4096];
#define TR(slot, v)

__device__ __forceinline__ uint32_t smem_u32(const void* p) { return (uint32_t)__cvta_generic_to_shared(p); }
__device__ __forceinline__ void mbar_init(uint32_t a, uint32_t c) { asm volatile("mbarrier.init.shared::cta.b64 [%0], %1;" :: "r"(a), "r"(c) : "memory"); }
__device__ __forceinline__ void mbar_expect_tx(uint32_t a, uint32_t tx) { asm volatile("mbarrier.arrive.expect_tx.shared::cta.b64 _, [%0], %1;" :: "r"(a), "r"(tx) : "memory"); }
__device__ __forceinline__ void mbar_arrive(uint32_t a) { asm volatile("mbarrier.arrive.shared::cta.b64 _, [%0];" :: "r"(a) : "memory"); }
__device__ __forceinline__ void mbar_arrive_if(uint32_t a, uint32_t pred) {
    asm volatile("{\n.reg .pred p;\nsetp.ne.u32 p, %1, 0;\n@p mbarrier.arrive.shared::cta.b64 _, [%0];\n}" :: "r"(a), "r"(pred) : "memory");
}
__device__ __forceinline__ bool mbar_try(uint32_t a, uint32_t ph) {
    uint32_t ok;
    asm volatile("{\n.reg .pred p;\nmbarrier.try_wait.parity.shared::cta.b64 p, [%1], %2;\nselp.u32 %0, 1, 0, p;\n}" : "=r"(ok) : "r"(a), "r"(ph) : "memory");
    return ok != 0;
}
#define SPINLOG 20
constexpr uint32_t SPIN_LIMIT = 1u << SPINLOG;
#define ABORT(code_) atomicCAS(&g_abort, 0u, (code_))
__device__ __forceinline__ void mbar_wait(uint32_t a, uint32_t ph) {
    uint32_t n = 0;
#pragma unroll 1
    while (!mbar_try(a, ph)) { if (++n > SPIN_LIMIT) { ABORT(1); break; } }
}
__device__ __forceinline__ void bar_sync(int id, int n) { asm volatile("bar.sync %0, %1;" :: "r"(id), "r"(n) : "memory"); }
__device__ __forceinline__ void bar_arrive(int id, int n) { asm volatile("bar.arrive %0, %1;" :: "r"(id), "r"(n) : "memory"); }

__device__ __forceinline__ void ldsm4(uint32_t* r, uint32_t a) {
    asm volatile("ldmatrix.sync.aligned.m8n8.x4.shared.b16 {%0,%1,%2,%3}, [%4];" : "=r"(r[0]), "=r"(r[1]), "=r"(r[2]), "=r"(r[3]) : "r"(a) : "memory");
}
__device__ __forceinline__ void ldsm4t(uint32_t* r, uint32_t a) {
    asm volatile("ldmatrix.sync.aligned.m8n8.x4.trans.shared.b16 {%0,%1,%2,%3}, [%4];" : "=r"(r[0]), "=r"(r[1]), "=r"(r[2]), "=r"(r[3]) : "r"(a) : "memory");
}
__device__ __forceinline__ void stsm4t(uint32_t a, uint32_t r0, uint32_t r1, uint32_t r2, uint32_t r3) {
    asm volatile("stmatrix.sync.aligned.m8n8.x4.trans.shared.b16 [%0], {%1,%2,%3,%4};" :: "r"(a), "r"(r0), "r"(r1), "r"(r2), "r"(r3) : "memory");
}
__device__ __forceinline__ void stsm4(uint32_t a, uint32_t r0, uint32_t r1, uint32_t r2, uint32_t r3) {
    asm volatile("stmatrix.sync.aligned.m8n8.x4.shared.b16 [%0], {%1,%2,%3,%4};" :: "r"(a), "r"(r0), "r"(r1), "r"(r2), "r"(r3) : "memory");
}
__device__ __forceinline__ uint32_t movm(uint32_t a) { uint32_t d; asm volatile("movmatrix.sync.aligned.m8n8.trans.b16 %0, %1;" : "=r"(d) : "r"(a)); return d; }
__device__ __forceinline__ void mma16816(float* d, uint32_t a0, uint32_t a1, uint32_t a2, uint32_t a3, uint32_t b0, uint32_t b1) {
    asm volatile("mma.sync.aligned.m16n8k16.row.col.f32.bf16.bf16.f32 {%0,%1,%2,%3}, {%4,%5,%6,%7}, {%8,%9}, {%0,%1,%2,%3};"
        : "+f"(d[0]), "+f"(d[1]), "+f"(d[2]), "+f"(d[3]) : "r"(a0), "r"(a1), "r"(a2), "r"(a3), "r"(b0), "r"(b1));
}
__device__ __forceinline__ void mma1688(float* d, uint32_t a0, uint32_t a1, uint32_t b0) {
    asm volatile("mma.sync.aligned.m16n8k8.row.col.f32.bf16.bf16.f32 {%0,%1,%2,%3}, {%4,%5}, {%6}, {%0,%1,%2,%3};"
        : "+f"(d[0]), "+f"(d[1]), "+f"(d[2]), "+f"(d[3]) : "r"(a0), "r"(a1), "r"(b0));
}
__device__ __forceinline__ uint32_t pack2(float a, float b) { uint32_t d; asm("cvt.rn.bf16x2.f32 %0, %1, %2;" : "=r"(d) : "f"(b), "f"(a)); return d; }
__device__ __forceinline__ float bf_lo(uint32_t w) { return __uint_as_float(w << 16); }
__device__ __forceinline__ float bf_hi(uint32_t w) { return __uint_as_float(w & 0xffff0000u); }
__device__ __forceinline__ float rbf(float x) { return __bfloat162float(__float2bfloat16_rn(x)); }

__device__ __forceinline__ void sts128(uint32_t a, float x, float y, float z, float w) { asm volatile("st.shared.v4.f32 [%0], {%1,%2,%3,%4};" :: "r"(a), "f"(x), "f"(y), "f"(z), "f"(w) : "memory"); }
__device__ __forceinline__ void sts128u(uint32_t a, uint32_t x, uint32_t y, uint32_t z, uint32_t w) { asm volatile("st.shared.v4.b32 [%0], {%1,%2,%3,%4};" :: "r"(a), "r"(x), "r"(y), "r"(z), "r"(w) : "memory"); }
__device__ __forceinline__ void sts64(uint32_t a, float x, float y) { asm volatile("st.shared.v2.f32 [%0], {%1,%2};" :: "r"(a), "f"(x), "f"(y) : "memory"); }
__device__ __forceinline__ float4 lds128(uint32_t a) { float4 v; asm volatile("ld.shared.v4.f32 {%0,%1,%2,%3}, [%4];" : "=f"(v.x), "=f"(v.y), "=f"(v.z), "=f"(v.w) : "r"(a) : "memory"); return v; }
__device__ __forceinline__ float2 lds64(uint32_t a) { float2 v; asm volatile("ld.shared.v2.f32 {%0,%1}, [%2];" : "=f"(v.x), "=f"(v.y) : "r"(a) : "memory"); return v; }
__device__ __forceinline__ uint2 lds64u(uint32_t a) { uint2 v; asm volatile("ld.shared.v2.b32 {%0,%1}, [%2];" : "=r"(v.x), "=r"(v.y) : "r"(a) : "memory"); return v; }
__device__ __forceinline__ float4 lds128v(uint32_t a) { float4 v; asm volatile("ld.volatile.shared.v4.f32 {%0,%1,%2,%3}, [%4];" : "=f"(v.x), "=f"(v.y), "=f"(v.z), "=f"(v.w) : "r"(a) : "memory"); return v; }
__device__ __forceinline__ float2 lds64v(uint32_t a) { float2 v; asm volatile("ld.volatile.shared.v2.f32 {%0,%1}, [%2];" : "=f"(v.x), "=f"(v.y) : "r"(a) : "memory"); return v; }
__device__ __forceinline__ uint4 lds128uv(uint32_t a) { uint4 v; asm volatile("ld.volatile.shared.v4.b32 {%0,%1,%2,%3}, [%4];" : "=r"(v.x), "=r"(v.y), "=r"(v.z), "=r"(v.w) : "r"(a) : "memory"); return v; }
__device__ __forceinline__ void st_async4(uint32_t a, float x, float y, float z, float w, uint32_t mb) {
    asm volatile("st.async.weak.shared::cluster.mbarrier::complete_tx::bytes.v4.f32 [%0], {%1,%2,%3,%4}, [%5];" :: "r"(a), "f"(x), "f"(y), "f"(z), "f"(w), "r"(mb) : "memory");
}
__device__ __forceinline__ void st_async2(uint32_t a, uint32_t x, uint32_t y, uint32_t mb) {
    asm volatile("st.async.weak.shared::cluster.mbarrier::complete_tx::bytes.v2.b32 [%0], {%1,%2}, [%3];" :: "r"(a), "r"(x), "r"(y), "r"(mb) : "memory");
}
__device__ __forceinline__ uint32_t ldg_rlx(const uint32_t* p) { uint32_t v; asm volatile("ld.relaxed.gpu.global.b32 %0, [%1];" : "=r"(v) : "l"(p) : "memory"); return v; }
__device__ __forceinline__ uint4 ldg_rlx4(const uint32_t* p) { uint4 v; asm volatile("ld.relaxed.gpu.global.v4.b32 {%0,%1,%2,%3}, [%4];" : "=r"(v.x), "=r"(v.y), "=r"(v.z), "=r"(v.w) : "l"(p) : "memory"); return v; }
__device__ __forceinline__ uint4 ldg_rlx4_if(const uint32_t* p, bool c) {
    uint4 v;
    asm volatile("{\n.reg .pred p;\nsetp.ne.u32 p, %5, 0;\nmov.b32 %0, 0;\nmov.b32 %1, 0;\nmov.b32 %2, 0;\nmov.b32 %3, 0;\n@p ld.relaxed.gpu.global.v4.b32 {%0,%1,%2,%3}, [%4];\n}"
                 : "=r"(v.x), "=r"(v.y), "=r"(v.z), "=r"(v.w) : "l"(p), "r"((uint32_t)c) : "memory");
    return v;
}
__device__ __forceinline__ void stg_rlx(uint32_t* p, uint32_t v) { asm volatile("st.relaxed.gpu.global.b32 [%0], %1;" :: "l"(p), "r"(v) : "memory"); }
__device__ __forceinline__ void tma2d(uint32_t dst, const CUtensorMap* tm, int c0, int c1, uint32_t mb) {
    asm volatile("cp.async.bulk.tensor.2d.shared::cluster.global.mbarrier::complete_tx::bytes [%0], [%1, {%3, %4}], [%2];"
        :: "r"(dst), "l"((uint64_t)tm), "r"(mb), "r"(c0), "r"(c1) : "memory");
}

__device__ __forceinline__ void tma3d(uint32_t dst, const CUtensorMap* tm, int row, int chunk, uint32_t mb) {
    asm volatile("cp.async.bulk.tensor.3d.shared::cluster.global.mbarrier::complete_tx::bytes [%0], [%1, {%3, %4, %5}], [%2];"
        :: "r"(dst), "l"((uint64_t)tm), "r"(mb), "r"(0), "r"(row), "r"(chunk) : "memory");
}
__device__ __forceinline__ void tma2d_mc(uint32_t dst, const CUtensorMap* tm, int c0, int c1, uint32_t mb) {
    asm volatile("cp.async.bulk.tensor.2d.shared::cluster.global.mbarrier::complete_tx::bytes.multicast::cluster [%0], [%1, {%3, %4}], [%2], %5;"
        :: "r"(dst), "l"((uint64_t)tm), "r"(mb), "r"(c0), "r"(c1), "h"((uint16_t)3) : "memory");
}
__device__ __forceinline__ void mbar_arrive2_if(uint32_t a, uint32_t pred) {
    asm volatile("{\n.reg .pred p;\nsetp.ne.u32 p, %1, 0;\n@p mbarrier.arrive.shared::cta.b64 _, [%0];\n@p mbarrier.arrive.shared::cluster.b64 _, [%2];\n}"
                 :: "r"(a), "r"(pred), "r"(a ^ 0x01000000u) : "memory");
}
__device__ __forceinline__ void tma_pf3d(const CUtensorMap* tm, int row, int chunk) {
    asm volatile("cp.async.bulk.prefetch.tensor.3d.L2.global.tile [%0, {%1, %2, %3}];" :: "l"((uint64_t)tm), "r"(0), "r"(row), "r"(chunk) : "memory");
}
__device__ __forceinline__ void tma_pf2d(const CUtensorMap* tm, int c0, int c1) {
    asm volatile("cp.async.bulk.prefetch.tensor.2d.L2.global.tile [%0, {%1, %2}];" :: "l"((uint64_t)tm), "r"(c0), "r"(c1) : "memory");
}
__device__ __forceinline__ void tma_store3d(const CUtensorMap* tm, uint32_t src, int row, int chunk) {
    asm volatile("cp.async.bulk.tensor.3d.global.shared::cta.bulk_group [%0, {%2, %3, %4}], [%1];" :: "l"((uint64_t)tm), "r"(src), "r"(0), "r"(row), "r"(chunk) : "memory");
}
__device__ __forceinline__ void bulk_store(void* dst, uint32_t src, uint32_t bytes) {
    asm volatile("cp.async.bulk.global.shared::cta.bulk_group [%0], [%1], %2;" :: "l"(dst), "r"(src), "r"(bytes) : "memory");
}
#define GT(slot)
#define CNT(k)
#define CNT2(k, c)
#define TS(i, dep)
#define TSACC()
#define TSDECL
struct Maps { CUtensorMap wq, wk, wv, wo, wo2, kx, ox2, kx3, vx3, xn2, wg, wu; };
typedef Maps RecMaps;
__device__ __forceinline__ void st_rel(uint32_t* p, uint32_t v) { asm volatile("st.release.gpu.global.u32 [%0], %1;" :: "l"(p), "r"(v) : "memory"); }
#define PUBLISH(p, v) st_rel(p, v)
__device__ __forceinline__ uint2 ldg_rlx2(const uint32_t* p) { uint2 v; asm volatile("ld.relaxed.gpu.global.v2.b32 {%0,%1}, [%2];" : "=r"(v.x), "=r"(v.y) : "l"(p) : "memory"); return v; }
__device__ __forceinline__ void wait_eq2(const uint32_t* p, uint32_t e, int code) {
    uint32_t n = 0;
#pragma unroll 1
    while (true) { uint2 v = ldg_rlx2(p); if (v.x == e && v.y == e) break; __nanosleep(64); if (++n > SPIN_LIMIT) { ABORT(code); break; } }
}
__device__ __forceinline__ void wait_eq4(const uint32_t* p, uint32_t e, int code) {
    uint32_t n = 0;
#pragma unroll 1
    while (true) { uint4 v = ldg_rlx4(p); if (v.x == e && v.y == e && v.z == e && v.w == e) break; __nanosleep(64); if (++n > SPIN_LIMIT) { ABORT(code); break; } }
}
__device__ __forceinline__ void wait_rec(const uint32_t* p, uint32_t e, uint32_t steps) {
    uint32_t n = 0;
#pragma unroll 1
    while (true) {
        uint2 v = ldg_rlx2(p);
        if (__all_sync(0xffffffffu, (v.x >> 8) == e && (v.y >> 8) == e && (v.x & 255) >= steps && (v.y & 255) >= steps)) break;
        __nanosleep(64); if (++n > SPIN_LIMIT) { ABORT(8); break; }
    }
}

constexpr int R_QK1 = 0;
constexpr int R_WO = 65536;
constexpr int R_T = 131072;
constexpr int R_SLOT1 = R_T;
constexpr int R_MEMB = R_T + 24576;
constexpr int R_QP = R_MEMB + 8192;
constexpr int R_VRED = R_QP + 4096;
constexpr int R_STG = R_VRED + 2048;
constexpr int R_AX = R_STG + 2048;
constexpr int R_SLOT0 = 196608;
constexpr int R_SLOC = R_SLOT0 + 24576;
constexpr int R_SREM = R_SLOC + 1536;
constexpr int R_VB = R_SREM + 1536;
constexpr int R_MISC = R_VB + 2048;
constexpr int R_LT = R_MISC + 128;
constexpr int R_BAR = 229888;
constexpr int R_TS = 229888 + 128;
static_assert(R_AX + 24576 <= R_SLOT0 && R_LT + 2560 <= 229376, "smem map");
enum { MB_W0 = 0, MB_W1, MB_WV, MB_WO, MB_S, MB_FULL0, MB_FULL1, MB_V, MB_N };

__device__ __forceinline__ float ex2(float x) { float y; asm("ex2.approx.ftz.f32 %0, %1;" : "=f"(y) : "f"(x)); return y; }
__device__ __forceinline__ float rcpf(float x) { float y; asm("rcp.approx.ftz.f32 %0, %1;" : "=f"(y) : "f"(x)); return y; }
__device__ __forceinline__ void mma16816z(float* d, uint32_t a0, uint32_t a1, uint32_t a2, uint32_t a3, uint32_t b0, uint32_t b1) {
    asm volatile("mma.sync.aligned.m16n8k16.row.col.f32.bf16.bf16.f32 {%0,%1,%2,%3}, {%4,%5,%6,%7}, {%8,%9}, {%10,%10,%10,%10};"
        : "=f"(d[0]), "=f"(d[1]), "=f"(d[2]), "=f"(d[3]) : "r"(a0), "r"(a1), "r"(a2), "r"(a3), "r"(b0), "r"(b1), "f"(0.f));
}
__device__ __forceinline__ void mma1688hz(float* d, uint32_t a0, uint32_t a1, uint32_t b0) {
    asm volatile("mma.sync.aligned.m16n8k8.row.col.f32.f16.f16.f32 {%0,%1,%2,%3}, {%4,%5}, {%6}, {%7,%7,%7,%7};"
        : "=f"(d[0]), "=f"(d[1]), "=f"(d[2]), "=f"(d[3]) : "r"(a0), "r"(a1), "r"(b0), "f"(0.f));
}
#define MMA(d, a, b0, b1) mma16816(d, a[0], a[1], a[2], a[3], b0, b1)
#define MMAZ(d, a, b0, b1) mma16816z(d, a[0], a[1], a[2], a[3], b0, b1)
#define MMAF(first, d, a, b0, b1) do { if (first) MMAZ(d, a, b0, b1); else MMA(d, a, b0, b1); } while (0)

__device__ __forceinline__ uint32_t uni(uint32_t x) { return __reduce_max_sync(0xffffffffu, x); }
__device__ __forceinline__ void mbar_wait_u(uint32_t a, uint32_t ph) {
    uint32_t n = 0;
#pragma unroll 1
    while (!__all_sync(0xffffffffu, mbar_try(a, ph))) { if (++n > SPIN_LIMIT) { ABORT(1); break; } }
}
__device__ __forceinline__ void mbar_wait_p(uint32_t a, uint32_t ph) {
    asm volatile("{\n.reg .pred p, q;\n.reg .u32 n;\nmov.u32 n, 0;\nWL: mbarrier.try_wait.parity.shared::cta.b64 p, [%0], %1;\nadd.u32 n, n, 1;\n"
                 "setp.lt.and.u32 q, n, %2, !p;\n@q bra.uni WL;\n}" :: "r"(a), "r"(ph), "n"(SPIN_LIMIT) : "memory");
}
__device__ __forceinline__ uint32_t mbar_test(uint32_t a, uint32_t ph) {
    uint32_t ok;
    asm volatile("{\n.reg .pred p;\nmbarrier.test_wait.parity.shared::cta.b64 p, [%1], %2;\nselp.u32 %0, 1, 0, p;\n}" : "=r"(ok) : "r"(a), "r"(ph) : "memory");
    return ok;
}
__device__ __forceinline__ uint32_t opaque(uint32_t x) { return __shfl_sync(0xffffffffu, x, threadIdx.x & 31); }
__device__ __forceinline__ const uint32_t* mkptr(uint32_t lo, uint32_t hi) { uint64_t r; asm("mov.b64 %0, {%1, %2};" : "=l"(r) : "r"(lo), "r"(hi)); return (const uint32_t*)r; }
__device__ __forceinline__ uint32_t prmt(uint32_t a, uint32_t b, uint32_t s) { uint32_t d; asm("prmt.b32 %0, %1, %2, %3;" : "=r"(d) : "r"(a), "r"(b), "r"(s)); return d; }
__device__ __forceinline__ uint32_t packh2(float a, float b) { uint32_t d; asm("cvt.rn.f16x2.f32 %0, %1, %2;" : "=r"(d) : "f"(b), "f"(a)); return d; }
__device__ __forceinline__ uint32_t hadd2b(uint32_t a, uint32_t b) { uint32_t d; asm("add.rn.bf16x2 %0, %1, %2;" : "=r"(d) : "r"(a), "r"(b)); return d; }
__device__ __forceinline__ uint32_t hmul2b(uint32_t a, uint32_t b) { uint32_t d; asm("mul.rn.bf16x2 %0, %1, %2;" : "=r"(d) : "r"(a), "r"(b)); return d; }
__device__ __forceinline__ uint32_t amax2b(uint32_t a, uint32_t b) { uint32_t d; asm("max.xorsign.abs.bf16x2 %0, %1, %2;" : "=r"(d) : "r"(a), "r"(b)); return d; }
__device__ __forceinline__ uint32_t amax2h(uint32_t a, uint32_t b) { uint32_t d; asm("max.xorsign.abs.f16x2 %0, %1, %2;" : "=r"(d) : "r"(a), "r"(b)); return d; }
__device__ __forceinline__ void sts32(uint32_t a, uint32_t x) { asm volatile("st.shared.b32 [%0], %1;" :: "r"(a), "r"(x) : "memory"); }
__device__ __forceinline__ uint32_t lds32v_(uint32_t a) { uint32_t v; asm volatile("ld.volatile.shared.b32 %0, [%1];" : "=r"(v) : "r"(a) : "memory"); return v; }
__device__ __forceinline__ void stg4(void* p, uint4 v) { asm volatile("st.relaxed.gpu.global.v4.b32 [%0], {%1,%2,%3,%4};" :: "l"(p), "r"(v.x), "r"(v.y), "r"(v.z), "r"(v.w) : "memory"); }
__device__ __forceinline__ void lds_frag(uint32_t* r, uint32_t a) {
    asm volatile("ld.shared.v4.b32 {%0,%1,%2,%3}, [%4];" : "=r"(r[0]), "=r"(r[1]), "=r"(r[2]), "=r"(r[3]) : "r"(a) : "memory");
}
__device__ __forceinline__ void lds_fragv(uint32_t* r, uint32_t a) {
    asm volatile("ld.volatile.shared.v4.b32 {%0,%1,%2,%3}, [%4];" : "=r"(r[0]), "=r"(r[1]), "=r"(r[2]), "=r"(r[3]) : "r"(a) : "memory");
}
__device__ __forceinline__ uint32_t xorv(uint32_t a, uint32_t b) { uint32_t d; asm volatile("xor.b32 %0, %1, %2;" : "=r"(d) : "r"(a), "r"(b)); return d; }
#define SCHED(k) asm volatile("{\n.reg .pred p;\nsetp.ne.u32 p, %0, %1;\n@p bra.uni SD;\nSL: nanosleep.u32 64;\nbra.uni SL;\nSD:\n}" :: "r"(sbu - s), "n"(k) : "memory")
#define PINM() asm volatile("{\n.reg .pred p;\nsetp.eq.u32 p, %0, 1;\n@p st.shared.u32 [%0], 0;\n}" :: "r"(sbu) : "memory")
__device__ __forceinline__ uint32_t or_and(uint32_t a, uint32_t b, uint32_t c) { uint32_t d; asm("lop3.b32 %0, %1, %2, %3, 0xF8;" : "=r"(d) : "r"(a), "r"(b), "r"(c)); return d; }
__device__ __forceinline__ uint32_t pack2v(float a, float b) { uint32_t d; asm volatile("cvt.rn.bf16x2.f32 %0, %1, %2;" : "=r"(d) : "f"(b), "f"(a)); return d; }
#define FU(x) __float_as_uint(x)
__device__ __forceinline__ uint32_t clk32() { uint32_t t; asm volatile("mov.u32 %0, %%clock;" : "=r"(t) :: "memory"); return t; }
__device__ __forceinline__ void spin_until(uint32_t t0, uint32_t d) {
    if (d) {
#pragma unroll 1
        while (__any_sync(0xffffffffu, clk32() - t0 < d)) {}
    }
}
constexpr int SH_OFF = 229376 + 384;
constexpr uint32_t HONE2 = 0x3c003c00u, HCNT2 = 0x50005000u;

__device__ __forceinline__ uint64_t desc_sw128(uint32_t addr, uint32_t lbo, uint32_t sbo) {
    return (uint64_t)((addr & 0x3FFFF) >> 4) | ((uint64_t)(lbo >> 4) << 16) | ((uint64_t)(sbo >> 4) << 32) | (1ull << 62);
}
#define DP 390
#define NAX 3
#define NXL 0
#define NCX 2
#define NCL 1
#define DC 0
#define FLIP 1
#define VTA 1
#define KXB 4
#define KXI 5
#define ANB 3
#define BNB 3
#define CNB 3
#define SMA 0
#define SMB 0
#define SMC 0x01
#define IVA 0
#define RGA 160
#define RGC 160
#define RGB (504 - RGA - RGC)
#define NRW 8
#define NBR 14
#define E0 0
#define E1 6
#define E2 4
#define E3 8
#define IV 2
#define DEX 0
#define G2V 0
#define G2K 2
#define VDEP 0
#define AEARLY 0
#define VTP 2
#define LORD 1
#define TRK 1
#define TW 0
#define T2N 14
#define TEARLY 1
#define DT 0
#define NB0 0
#define NB1 8
#define DB2 80
#define DITHER 0
#define DA 40
#define DB 40
#define DS 200

__device__ __forceinline__ uint32_t wrow_off(int kk, int ch) {
    const int lane = threadIdx.x & 31, r = lane & 7;
    const int row = 64 * (kk >> 2) + 32 * (r & 1) + 16 * (kk & 1) + 8 * (lane >> 4) + 4 * ((kk >> 1) & 1) + (r >> 1);
    return row * 128 + ((ch ^ (row & 7)) << 4);
}
template <int K> __device__ __forceinline__ void sched(uint32_t key) {
    asm volatile("{\n.reg .pred p;\nsetp.ne.u32 p, %0, %1;\n@p bra.uni SD;\nSL: nanosleep.u32 64;\nbra.uni SL;\nSD:\n}" :: "r"(key), "n"(K) : "memory");
}
__device__ __forceinline__ void sched_i(int i, uint32_t key) {
    if (i == -1) sched<20>(key); if (i == 0) sched<21>(key); if (i == 1) sched<22>(key); if (i == 2) sched<23>(key);
    if (i == 3) sched<24>(key); if (i == 4) sched<25>(key); if (i == 5) sched<26>(key); if (i == 6) sched<27>(key);
}
template <int NB, int SM, class F>
__device__ __forceinline__ void g1(float* q0, float* k0, uint32_t (*wq)[4], uint32_t (*wk)[4], uint32_t ga, uint32_t key, F&& hook) {
    float q1[4], k1[4];
    uint32_t b[NB][4];
#pragma unroll
    for (int i = 0; i < NB; i++) ldsm4(b[i], ga + i * 512);
    hook(-1, b[0]);
    if (SM & 1) sched_i(-1, key);
#pragma unroll
    for (int i = 0; i < 8; i++) {
        uint32_t* c = b[i % NB];
        MMAF(i == 0, q0, wq[2 * i], c[0], c[1]); MMAF(i == 0, k0, wk[2 * i], c[0], c[1]);
        MMAF(i == 0, q1, wq[2 * i + 1], c[2], c[3]); MMAF(i == 0, k1, wk[2 * i + 1], c[2], c[3]);
        const uint32_t cc_[4] = {c[0], c[1], c[2], c[3]};
        if (i + NB < 8) ldsm4(b[i % NB], ga + (i + NB) * 512);
        hook(i, cc_);
        if ((SM >> (i + 1)) & 1) sched_i(i, key);
    }
#pragma unroll
    for (int i = 0; i < 4; i++) { q0[i] += q1[i]; k0[i] += k1[i]; }
}
__device__ __forceinline__ float frag_norm2(uint32_t (*w)[4]) {
    float d0[4], d1[4];
#pragma unroll
    for (int i = 0; i < 32; i++) { MMAF(i == 0, d0, w[i], w[i][0], w[i][2]); MMAF(i == 0, d1, w[i], w[i][1], w[i][3]); }
    const int lane = threadIdx.x & 31, g = lane >> 2, t = lane & 3;
    float v = g == 2 * t ? d0[0] + d1[2] : (g == 2 * t + 1 ? d0[1] + d1[3] : 0.f);
#pragma unroll
    for (int o = 16; o; o >>= 1) v += __shfl_xor_sync(0xffffffffu, v, o);
    return v;
}
__device__ __forceinline__ void load_slot(uint32_t sb, int c, int tile, const Maps& maps) {
    const uint32_t dst = sb + ((tile & 1) ? R_SLOT1 : R_SLOT0), mb = sb + R_BAR + 8 * (MB_FULL0 + (tile & 1));
    mbar_expect_tx(mb, 24576);
    tma2d(dst + 16384, &maps.kx, c * 64, tile * 64, mb);
    tma3d(dst, &maps.vx3, tile * 64, (c >> 1) * 2, mb);
}
__device__ __forceinline__ uint32_t put_mem0(uint32_t sb, int W, const bf16* __restrict__ mem0) {
    const int lane = threadIdx.x & 31;
    const uint4 a = *(const uint4*)(mem0 + (lane & 7) * DM + W * 64 + (lane >> 3) * 8), b = *(const uint4*)(mem0 + (lane & 7) * DM + W * 64 + 32 + (lane >> 3) * 8);
    const uint4 m0 = make_uint4(prmt(a.x, b.x, 0x5410u), prmt(a.x, b.x, 0x7632u), prmt(a.y, b.y, 0x5410u), prmt(a.y, b.y, 0x7632u));
    const uint4 m1 = make_uint4(prmt(a.z, b.z, 0x5410u), prmt(a.z, b.z, 0x7632u), prmt(a.w, b.w, 0x5410u), prmt(a.w, b.w, 0x7632u));
    bar_sync(3, 256);
    sts128u(sb + R_MEMB + W * 1024 + lane * 16, m0.x, m0.y, m0.z, m0.w);
    sts128u(sb + R_MEMB + W * 1024 + 512 + lane * 16, m1.x, m1.y, m1.z, m1.w);
    return amax2b(amax2b(amax2b(m0.x, m0.y), amax2b(m0.z, m0.w)), amax2b(amax2b(m1.x, m1.y), amax2b(m1.z, m1.w)));
}
#define PUT_MAX(rL, W) sts32(rL + R_STG + 1024 + ((W) >> 2) * 512 + ((W) & 3) * 4, amax2b(amax2b(mx, my), mz));
__device__ __forceinline__ uint32_t h2b(uint32_t w) {
    uint32_t d;
    asm("{\n.reg .f16 l, h;\n.reg .f32 a, b;\nmov.b32 {l, h}, %1;\ncvt.f32.f16 a, l;\ncvt.f32.f16 b, h;\ncvt.rn.bf16x2.f32 %0, b, a;\n}" : "=r"(d) : "r"(w));
    return d;
}
#define GATHER1(HALF)                                                                                           \
        {                                                                                                       \
            const uint4 x0 = ldg_rlx4(pm), x1 = ldg_rlx4(pm + 256); const uint2 y = ldg_rlx2(px);                 \
            cw = (sel & 0x4000u) ? prmt(x0.w, x1.w, 0x7632u) : prmt(y.x, y.y, 0x5410u);                         \
            const uint32_t p0 = h2b(x0.x), p1 = h2b(x0.y), p2 = h2b(x0.z), p3 = h2b(prmt(x0.w, y.x, sel));      \
            stsm4t(rG + R_MEMB + HALF * 4096, p0, p1, p2, p3);                                                  \
            const uint32_t p4 = h2b(x1.x), p5 = h2b(x1.y), p6 = h2b(x1.z), p7 = h2b(prmt(x1.w, y.y, sel));      \
            stsm4t(rG + R_MEMB + HALF * 4096 + 512, p4, p5, p6, p7);                                            \
            mx = amax2b(amax2b(p0, p1), amax2b(p2, p3)); my = amax2b(p4, p5); mz = amax2b(p6, p7);              \
        }
#define GATHER(HALF, PRE, SYNC, AFTER)                                                                                      \
        {                                                                                                       \
            const uint32_t so = aslot(s);                                                                       \
            const uint32_t ua = (glo + acc_base(HALF * 4 + fo)) ^ so, ux = (glo + ext_base(HALF * 4 + fo)) ^ so; \
            uint2 lt;                                                                                           \
            lt.x = lds32v_(rL + R_LT); lt.y = lds32v_(rL + R_LT + 4);                                           \
            const uint32_t sel = 0x7610u - ((lt.x ^ (lt.x >> 2)) & 16) * 0x440u;                                \
            const uint32_t* pm = mkptr(ua + lt.x, ghi);                                                         \
            const uint32_t* px = mkptr(ux + lt.y, ghi);                                                         \
            PRE                                                                                                 \
            bar_sync(5, 384);                                                                                   \
            const uint32_t t0 = clk32();                                                                        \
            TSACC();                                                                        \
            SYNC                                                                                                \
            spin_until(t0, DP + DITHER);                                                                                 \
            \
            TS(10, 0);                                                                                          \
            uint32_t cw, nr = 0;                                                                                \
            _Pragma("unroll 1") do {                                                                            \
                GATHER1(HALF)                                                                                   \
                nr++;                                                                                           \
            } while (__any_sync(0xffffffffu, cw != HCNT2 && nr < SPIN_LIMIT));                                  \
            TS(11, cw);                                                                                         \
            AFTER                                                                                               \
            CNT2(HALF * 4 + (s & 1) * 2 + (nr > 2), nr > 1);                                                    \
            \
        }
#define GOBAR (fo == 3 ? 14 : 10 + fo)

__device__ __forceinline__ void rec_a(uint32_t sb, int c, const bf16* __restrict__ mem0, uint32_t epoch) {
    const int tid = threadIdx.x - WGA * 128, lane = tid & 31, f = tid >> 5;
    uint32_t wq[16][4], wk[16][4], mx, my = 0, mz = 0;
    const int lrow = ((lane >> 4) << 3) + (lane & 7), lsel = (lane >> 3) & 1;
    {
        mbar_wait(sb + R_BAR + 8 * MB_W0, 0);
        if (c == 7 && tid == 0) GT(1421);
#pragma unroll
        for (int kk = 0; kk < 16; kk++) { const uint32_t a = sb + R_T + wrow_off(kk, 2 * f + lsel); ldsm4t(wq[kk], a); ldsm4t(wk[kk], a + 32768); }
        __syncwarp();
        mx = put_mem0(sb, f, mem0);
    }
    const uint32_t rL = opaque(sb + lane * 16), rG = opaque(sb + lane * 16 + f * 1024);
    const uint32_t sbu = uni(sb), fo = uni(f), cc = uni(c);
    const uint64_t gx = xpage();
    const uint32_t ghi = uni((uint32_t)(gx >> 32)), glo = uni((uint32_t)gx);
#pragma unroll
    for (int i = 0; i < NAX; i++) {
        sts128u(rG + R_AX + 4096 * i, wq[i][0], wq[i][1], wq[i][2], wq[i][3]);
        sts128u(rG + R_AX + 4096 * i + 512, wk[i][0], wk[i][1], wk[i][2], wk[i][3]);
    }
    sts128u(rL + R_LT + 512 + f * 512, (sb + R_SREM + (f >= 2 ? lane * 8 + f * 256 : lane * 16 + f * 1024)) ^ 0x01000000u, (sb + R_BAR + 8 * MB_S) ^ 0x01000000u,
            sb + R_QP + (lane >> 4) * 128 + lsel * 512 + (lane & 7) * 16 + (f == 3 ? 2048 : 0), sb + R_SLOT0 + lrow * 128 + ((lsel ^ (lane & 7)) << 4));
    __syncwarp();
    if (tid == 0) GT(c * 8 + 1);
    TSDECL;
    const float cexp = 0.08838834764831845f * 1.4426950408889634f;
    float cs = cexp;
    auto step = [&](int s, bool first) -> bool {
        bar_sync(1, 128);
        float q0[4], k0[4];
        uint4 ta;
        uint32_t zr, rl2;
        g1<ANB, SMA>(q0, k0, wq, wk, rL + R_MEMB, sbu - s, [&](int i, const uint32_t* c_) {
            if (i == 0) TS(0, c_[0]);
            if (i == -1) {
#pragma unroll
                for (int n = NAX - NXL; n < NAX; n++) { lds_fragv(wq[n], rG + R_AX + 4096 * n); lds_fragv(wk[n], rG + R_AX + 4096 * n + 512); }
                ta = lds128uv(rL + R_LT + 512 + fo * 512);
                zr = ta.w & 1; rl2 = rL | zr;
            }
            if (i == IVA) { PUT_MAX(rl2, fo) bar_arrive(15, 256); bar_arrive(GOBAR, 96); }
        });
        stsm4t(rG + R_QP, pack2(q0[0], q0[1]), pack2(q0[2], q0[3]), pack2(k0[0], k0[1]), pack2(k0[2], k0[3]));
        TS(1, FU(k0[3]));
        if (first) mbar_wait_p(sbu + R_BAR + 8 * MB_FULL0, 0);
        if (fo >= 2) {
            bar_sync(3, 256);
            uint32_t kb[4], kc[4], qa[4], qc[4];
            ldsm4(kb, ta.z + 256); ldsm4(qa, ta.z);
            ldsm4(kc, ta.z + 1280); ldsm4(qc, ta.z + 1024);
            const uint32_t k0_ = hadd2b(kb[0], kb[1]), k1_ = hadd2b(kb[2], kb[3]), k2_ = hadd2b(kc[0], kc[1]), k3_ = hadd2b(kc[2], kc[3]);
            float s0[4], s2[4];
            MMAZ(s0, qa, k0_, k1_); MMAZ(s2, qc, k2_, k3_);
            const float x = ((s0[0] + s0[2]) + (s2[0] + s2[2])) * cs, y = ((s0[1] + s0[3]) + (s2[1] + s2[3])) * cs;
            st_async2(ta.x, FU(x), FU(y), ta.y);
            TS(3, FU(y));
            sts64((ta.x ^ 0x01000000u) + (R_SLOC - R_SREM), x, y);
            sts128u(rl2 + R_STG + (fo & 1) * 512, k0_, k1_, k2_, k3_);
            bar_arrive(9, 192);
        } else {
            uint32_t qa[4][4], kx[4][4];
#pragma unroll
            for (int kk = 0; kk < KXB; kk++) ldsm4(kx[kk], (ta.w ^ (kk * 32)) + (16384 + fo * 2048));
            bar_sync(3, 256);
#pragma unroll
            for (int kk = 0; kk < 4; kk++) {
                if (kk >= KXB) ldsm4(kx[kk], (ta.w ^ (kk * 32)) + (16384 + fo * 2048));
                ldsm4(qa[kk], ta.z + kk * 1024);
            }
            float s0[4], s1[4], s2[4], s3[4];
            MMAZ(s0, qa[0], kx[0][0], kx[0][1]); MMAZ(s1, qa[0], kx[0][2], kx[0][3]);
            MMAZ(s2, qa[1], kx[1][0], kx[1][1]); MMAZ(s3, qa[1], kx[1][2], kx[1][3]);
            MMA(s0, qa[2], kx[2][0], kx[2][1]); MMA(s1, qa[2], kx[2][2], kx[2][3]);
            MMA(s2, qa[3], kx[3][0], kx[3][1]); MMA(s3, qa[3], kx[3][2], kx[3][3]);
            const float x = ((s0[0] + s0[2]) + (s2[0] + s2[2])) * cs, y = ((s0[1] + s0[3]) + (s2[1] + s2[3])) * cs;
            const float z = ((s1[0] + s1[2]) + (s3[0] + s3[2])) * cs, w = ((s1[1] + s1[3]) + (s3[1] + s3[3])) * cs;
            st_async4(ta.x, x, y, z, w, ta.y);
            TS(3, FU(w));
            sts128(rG + R_SLOC, x, y, z, w);
        }
        const uint32_t r8 = (rl2 + sbu) >> 1;
        uint32_t vt00[4], vt01[4], vt10[4], vt11[4];
        const uint32_t rV = ta.w ^ ((fo & 1) * 64), vo = (fo >> 1) * 8192;
        if (!VTA && VTP < 2) { ldsm4t(vt00, rV + vo); ldsm4t(vt10, (rV ^ 32) + vo); }
        if (!VTA && VTP < 1) { ldsm4t(vt01, rV + vo + 2048); ldsm4t(vt11, (rV ^ 32) + vo + 2048); }
        bar_sync(4, 128);
        const float2 l2 = lds64v(r8 + R_SLOC + 512), l3 = lds64v(r8 + R_SLOC + 768);
        const float4 l0 = lds128v(rL + R_SLOC), l1 = lds128v(rL + R_SLOC + 1024);
        if (VTA && VTP < 2) { ldsm4t(vt00, rV + vo); ldsm4t(vt10, (rV ^ 32) + vo); }
        if (VTA && VTP < 1) { ldsm4t(vt01, rV + vo + 2048); ldsm4t(vt11, (rV ^ 32) + vo + 2048); }

        if (s == NSEG - 1) { mbar_wait_u(sbu + R_BAR + 8 * MB_S, 1); mbar_wait_u(sbu + R_BAR + 8 * MB_V, 1); return true; }
        TS(2, FU(l3.y));
        mbar_wait_p(sbu + R_BAR + 8 * MB_S, s & 1);
        TS(4, 0);
        {
            const float2 r2 = lds64v(r8 + R_SREM + 512), r3 = lds64v(r8 + R_SREM + 768);
            const float4 r0 = lds128v(rL + R_SREM), r1 = lds128v(rL + R_SREM + 1024);
            if (VTP >= 1) PINM();
            if (VTP >= 2) { ldsm4t(vt00, rV + vo); ldsm4t(vt10, (rV ^ 32) + vo); }
            if (VTP >= 1) { ldsm4t(vt01, rV + vo + 2048); ldsm4t(vt11, (rV ^ 32) + vo + 2048); }
            float sv[10];
            sv[0] = l0.x + r0.x; sv[1] = l0.y + r0.y; sv[2] = l0.z + r0.z; sv[3] = l0.w + r0.w;
            sv[4] = l1.x + r1.x; sv[5] = l1.y + r1.y; sv[6] = l1.z + r1.z; sv[7] = l1.w + r1.w;
            sv[8] = ((l2.x + l3.x) + r2.x) + r3.x; sv[9] = ((l2.y + l3.y) + r2.y) + r3.y;
            float m = fmaxf(fmaxf(fmaxf(fmaxf(sv[8], sv[9]), sv[0]), fmaxf(fmaxf(sv[2], sv[3]), sv[1])), fmaxf(fmaxf(sv[4], sv[5]), fmaxf(sv[6], sv[7])));
            {
                const float m1 = __shfl_xor_sync(0xffffffffu, m, 1), m2 = __shfl_xor_sync(0xffffffffu, m, 2), m3 = __shfl_xor_sync(0xffffffffu, m, 3);
                m = fmaxf(fmaxf(m, m1), fmaxf(m2, m3));
            }
            TS(5, FU(m));
            const uint32_t ONE2 = 0x3f803f80u;
            float o0[4], o1[4], sm[4];
            const uint32_t pb0 = pack2(ex2(sv[0] - m), ex2(sv[1] - m)), pb1 = pack2(ex2(sv[2] - m), ex2(sv[3] - m));
            mma16816z(sm, ONE2, ONE2, ONE2, ONE2, pb0, pb1);
            MMAZ(o0, vt00, pb0, pb1); MMAZ(o1, vt10, pb0, pb1);
            const uint32_t z = (VDEP == 0 ? FU(m) : pb0) & zr;
            const uint32_t vok = mbar_test(sbu + R_BAR + 8 * MB_V + z, s & 1);
            const uint32_t rv = r8 + vok * 8;
            float2 va = lds64v(rv + R_VB - 8 + fo * 512);
            float2 vb = lds64v(rv + R_VB - 8 + fo * 512 + 256);
            float sig = __uint_as_float(lds32v_(sbu + R_MISC + 40));
            const uint32_t pb2 = pack2(ex2(sv[4] - m), ex2(sv[5] - m)), pb3 = pack2(ex2(sv[6] - m), ex2(sv[7] - m));
            mma16816(sm, ONE2, ONE2, ONE2, ONE2, pb2, pb3);
            const uint32_t pb4 = pack2(ex2(sv[8] - m), ex2(sv[9] - m));
            MMA(o0, vt01, pb2, pb3); MMA(o1, vt11, pb2, pb3);
            mma1688(sm, ONE2, ONE2, pb4);
            const float z0 = rcpf(sm[0]), z1 = rcpf(sm[1]);
#define PUT_O()                                                                                                   \
            {                                                                                                     \
                float a0[4] = {o0[0], o0[1], o0[2], o0[3]}, a1[4] = {o1[0], o1[1], o1[2], o1[3]};                 \
                mma1688(a0, FU(va.x), FU(va.y), pb4); mma1688(a1, FU(vb.x), FU(vb.y), pb4);                       \
                const float i0 = z0 * sig, i1 = z1 * sig;                                                         \
                stsm4t(rG + R_QP, pack2(a0[0] * i0, a0[1] * i1), pack2(a0[2] * i0, a0[3] * i1), pack2(a1[0] * i0, a1[1] * i1), pack2(a1[2] * i0, a1[3] * i1)); \
            }
            PUT_O()
            asm volatile("{\n.reg .pred p;\nsetp.ne.u32 p, %0, 0;\n@p bar.arrive 8, 256;\n}" :: "r"(vok) : "memory");
            if (__builtin_expect(__any_sync(0xffffffffu, vok == 0), 0)) {
                mbar_wait_p(sbu + R_BAR + 8 * MB_V, s & 1);
                va = lds64v(r8 + R_VB + fo * 512); vb = lds64v(r8 + R_VB + fo * 512 + 256);
                sig = __uint_as_float(lds32v_(sbu + R_MISC + 40));
                PUT_O()
                bar_arrive(8, 256);
                CNT(8);
            }
            TS(6, 0);
            const float r = __uint_as_float(0x7f000000u - FU(sig));
            cs = cexp * r * (fo >= 2 ? r : 1.f);
        }
        return false;
    };
    step(0, true);
#pragma unroll 1
    for (int s = 0;; s++) {
        if (s & 1) mbar_wait_p(sbu + R_BAR + 8 * (MB_FULL0 + (((s + 1) >> 1) & 1)), ((s + 1) >> 2) & 1);
        {
            const uint32_t a = rL + R_LT + 512 + 12 + fo * 512;
            sts32(a, lds32v_(a) + ((s & 1) ? ((s & 2) ? R_SLOT0 - R_SLOT1 - 4096 : R_SLOT1 - R_SLOT0 - 4096) : 4096));
        }
        auto early = [&]() {
            SCHED(13);
#pragma unroll
            for (int i = 0; i < NAX - NXL; i++) { lds_fragv(wq[i], rG + R_AX + 4096 * i); lds_fragv(wk[i], rG + R_AX + 4096 * i + 512); }
        };
        GATHER(0, , early();, )
        if (step(s + 1, false)) break;
    }
    CNT(9);
    if (rG == sbu) GT(cc * 8 + 4);
}

__device__ __forceinline__ void rec_b(uint32_t sb, int c, uint32_t epoch) {
    const int tid = threadIdx.x - WGB * 128, lane = tid & 31, f = tid >> 5;
    uint32_t wq[16][4], wk[16][4], wo[32][4];
    const int lrow = ((lane >> 4) << 3) + (lane & 7), lsel = (lane >> 3) & 1;
    const uint32_t rL = opaque(sb + lane * 16), rW = opaque(sb + lane * 16 + f * 16384);
    const uint32_t sbu = uni(sb), fo = uni(f), cc = uni(c), po = cc & 1, ep = uni(epoch);
    {
        mbar_wait(sb + R_BAR + 8 * MB_WO, 0);
        if (c == 7 && tid == 0) GT(1426);
        const uint32_t aO = sb + R_WO + f * 16384 + lrow * 128 + ((lsel ^ (lane & 7)) << 4);
#pragma unroll
        for (int i = 0; i < 32; i++) {
            const int tile = (i >> 4) * 2 + (i & 1), kk = (i >> 1) & 7;
            ldsm4t(wo[i], (aO ^ (32 * tile)) + kk * 2048);
        }
        const float no = frag_norm2(wo);
        if (lane == 0) sts32(sb + R_MISC + 80 + f * 4, FU(no));
        __syncwarp();
        bar_sync(0, 256);
        if (tid == 0) {
            const float4 a = lds128(sb + R_MISC + 64), b = lds128(sb + R_MISC + 80);
            stg4(&g_f.norm[c], make_uint4(FU((a.x + a.y) + (a.z + a.w)), epoch, FU((b.x + b.y) + (b.z + b.w)), epoch));
        }
        __syncwarp();
#pragma unroll
        for (int i = NRW; i < 32; i++) sts128u(rW + R_WO + i * 512, wo[i][0], wo[i][1], wo[i][2], wo[i][3]);
        mbar_wait(sb + R_BAR + 8 * MB_W1, 0);
        if (c == 7 && tid == 0) GT(1422);
        if (tid == 0) stg_rlx(&g_f.rload[c], epoch);
        __syncwarp();
#pragma unroll
        for (int kk = 0; kk < 16; kk++) { const uint32_t a = sb + R_QK1 + wrow_off(kk, 2 * f + lsel); ldsm4t(wq[kk], a); ldsm4t(wk[kk], a + 32768); }
        bar_sync(13, 128);
#pragma unroll
        for (int i = 0; i < 16; i++) {
            sts128u(rW + R_QK1 + i * 1024, wq[i][0], wq[i][1], wq[i][2], wq[i][3]);
            sts128u(rW + R_QK1 + i * 1024 + 512, wk[i][0], wk[i][1], wk[i][2], wk[i][3]);
        }
        __syncwarp();
    }
    const uint64_t gx = xpage();
    const uint32_t ghi = uni((uint32_t)(gx >> 32)), glo = uni((uint32_t)gx);
    TSDECL;
#pragma unroll 1
    for (int s = 0;; s++) {
        bar_sync(2, 256);
        float q0[4], k0[4];
        g1<BNB, SMB>(q0, k0, wq, wk, rL + R_MEMB + 4096, sbu - s, [&](int i, const uint32_t* c_) {
            if (i == 0) TS(0, c_[0]);
            if (i >= 2 && i < 6) {
#pragma unroll
                for (int n = NRW + (i - 2) * E0 / 4; n < NRW + (i - 1) * E0 / 4; n++) lds_fragv(wo[n], rW + R_WO + n * 512);
            }
            if (i == IV) bar_arrive(GOBAR, 96);
        });
        stsm4t(rL + fo * 1024 + R_QP + 512, pack2(q0[0], q0[1]), pack2(q0[2], q0[3]), pack2(k0[0], k0[1]), pack2(k0[2], k0[3]));
        bar_arrive(3, 256);
        TS(1, FU(k0[3]));
        const uint32_t so = aslot(s);
        uint2 lt;
        { const float2 t = lds64v(rL + R_LT + 8); lt.x = FU(t.x); lt.y = FU(t.y); }
        const uint32_t sel = 0x3210u + (lt.x & 16) * 0x440u;
        uint32_t* pm = (uint32_t*)mkptr(((glo + acc_base(po * 4 + fo)) ^ so) + lt.x, ghi);
        uint32_t* px = (uint32_t*)mkptr(((glo + ext_base(po * 4 + fo)) ^ so) + lt.y, ghi);
        if (s == NSEG - 1) break;
        {
            const uint32_t z = lt.x & 1;
#pragma unroll
            for (int n = NRW; n < NRW + E0 + E1 + E2 + E3; n++) {
                const int d = n - (n < NRW + T2N ? TRK + 1 : TRK);
                lds_fragv(wo[n], (d >= NRW ? or_and(rW, wo[d][0], z) : rW) + R_WO + n * 512);
            }
        }
        TS(2, wo[NRW + E0 + E1 + E2 + E3 - 1][0]);
        SCHED(4);
        bar_sync(8, 256);
        {
            float o[4][4];
            uint32_t b[4][4];
#pragma unroll
            for (int i = 0; i < 4; i++) ldsm4(b[i], rL + R_QP + i * 1024);
            PINM();
#pragma unroll
            for (int n = NRW + E0 + E1 + E2 + E3; n < 32; n++) lds_fragv(wo[n], rW + R_WO + n * 512);
            float p[4][4];
#define G2_STEP(o, hf, kk) _Pragma("unroll") for (int i = 0; i < 2; i++) MMAF((kk) < 2, o[((kk) & 1) * 2 + i], wo[(hf) * 16 + (kk) * 2 + i], b[(kk) >> 1][((kk) & 1) * 2], b[(kk) >> 1][((kk) & 1) * 2 + 1])
#define G2_RED(o, wl, h) const uint32_t wl = packh2(o[1][2] + o[3][2], o[1][3] + o[3][3]);                            \
                asm volatile("red.relaxed.gpu.global.add.noftz.v4.f16x2 [%0], {%1,%2,%3,%4};" :: "l"(pm + (h) * 16),  \
                    "r"(packh2(o[0][0] + o[2][0], o[0][1] + o[2][1])), "r"(packh2(o[0][2] + o[2][2], o[0][3] + o[2][3])), \
                    "r"(packh2(o[1][0] + o[3][0], o[1][1] + o[3][1])), "r"(prmt(wl, HONE2, (h) ? sel : sel ^ 0x4400u)) : "memory")
            if (G2V == 1) SCHED(11);
#pragma unroll
            for (int kk = 0; kk < 8; kk++) { G2_STEP(o, 0, kk); }
            TS(7, b[0][0]);
            if (G2V == 0) SCHED(11);
            else {
#pragma unroll
                for (int i = 0; i < 4; i++) wo[16 + i][0] = or_and(wo[16 + i][0], FU(o[i][0]), lt.x & 1);
            }
#pragma unroll
            for (int kk = 0; kk < G2K; kk++) { G2_STEP(p, 1, kk); }
#pragma unroll
            for (int i = 0; i < NB0; i++) { lds_fragv(wq[i], rW + R_QK1 + i * 1024); lds_fragv(wk[i], rW + R_QK1 + i * 1024 + 512); }
            G2_RED(o, w3, 0);
            TS(8, w3);
            if (G2V == 0) SCHED(12);
#pragma unroll
            for (int kk = G2K; kk < 8; kk++) { G2_STEP(p, 1, kk); }
            G2_RED(p, w7, 1);
            asm volatile("red.relaxed.gpu.global.add.noftz.f16x2 [%0], %1;" :: "l"(px), "r"(prmt((w3 & 0xffff0000u) | 0x3c00u, w7, sel)) : "memory");
            TS(9, w7);
        }
        bar_arrive(5, 384);
        asm volatile("{\n.reg .pred p;\nsetp.eq.u32 p, %0, %1;\n@p mbarrier.arrive.expect_tx.shared::cta.b64 _, [%2], 1536;\n}"
                     :: "r"(rW), "r"(sbu), "r"(sbu + R_BAR + 8 * MB_S) : "memory");
        const uint32_t tb = clk32();
        TSACC();
        spin_until(tb, DB);
#pragma unroll
        for (int i = NB0; i < NBR; i++) {
            if (i == NB1) spin_until(tb, DP + DB2);
            lds_fragv(wq[i], rW + R_QK1 + i * 1024); lds_fragv(wk[i], rW + R_QK1 + i * 1024 + 512);
        }
    }
}

#undef lds_fragv
__device__ __forceinline__ void rec_first_loads(uint32_t sb, int c, const Maps& maps) {
    const uint32_t bar = sb + R_BAR;
    const int F0 = c * 64;
    mbar_expect_tx(bar + 8 * MB_W0, 65536); mbar_expect_tx(bar + 8 * MB_WO, 65536); mbar_expect_tx(bar + 8 * MB_WV, 65536);
    tma2d(sb + R_QK1, &maps.wv, F0, 0, bar + 8 * MB_WV); tma2d(sb + R_QK1 + 32768, &maps.wv, F0, 256, bar + 8 * MB_WV);
    tma2d(sb + R_T + 32768, &maps.wk, F0, 0, bar + 8 * MB_W0);
    if (!LORD) {
        for (int i = 0; i < 4; i++) tma2d(sb + R_WO + i * 16384, &maps.wo, (c & 1) * 256 + i * 64, (c >> 1) * 128, bar + 8 * MB_WO);
        tma2d(sb + R_T, &maps.wq, F0, 0, bar + 8 * MB_W0);
    }
    mbar_expect_tx(bar + 8 * MB_S, 1536);
}
__device__ __forceinline__ void rec_c(uint32_t sb, int c, const bf16* __restrict__ mem0, const Maps& maps, uint32_t epoch) {
    const int tid = threadIdx.x - WGC * 128, lane = tid & 31, u = tid >> 5;
    const uint32_t bar = sb + R_BAR;
    const int lrow = ((lane >> 4) << 3) + (lane & 7), lsel = (lane >> 3) & 1;
    const int kh = u >> 1, j = u & 1;
    uint32_t wv[32][4], mx, my = 0, mz = 0;
    {
        if (u == 0) {
            sts128u(sb + lane * 16 + R_LT, (lane >> 3) * 256 + (lane & 7) * 16, ((lane >> 2) & 1) * XHS + (lane >> 4) * XSS + (lane & 8) * 2 + (lane & 2) * 4,
                    (lane >> 2) * 256 + (lane & 3) * 16, (lane & 1) * XHS + ((lane >> 3) & 1) * XSS + (lane & 6) * 4 + (lane >> 4) * 4);
        }
        mbar_wait(bar + 8 * MB_WV, 0);
        if (c == 7 && tid == 0) GT(1425);
        if (LORD && tid == 32) {
            for (int i = 0; i < 4; i++) tma2d(sb + R_WO + i * 16384, &maps.wo, (c & 1) * 256 + i * 64, (c >> 1) * 128, bar + 8 * MB_WO);
            tma2d(sb + R_T, &maps.wq, c * 64, 0, bar + 8 * MB_W0);
        }
        __syncwarp();
#pragma unroll
        for (int kk = 0; kk < 16; kk++) {
            const uint32_t aa = sb + R_QK1 + kh * 32768 + wrow_off(kk, 4 * j + 2 * kh + lsel);
            ldsm4t(wv[kk], aa); ldsm4t(wv[16 + kk], aa ^ 32);
        }
        bar_sync(9, 128);
        if (c == 7 && tid == 0) GT(1423);
        if (tid == 0) {
            mbar_expect_tx(bar + 8 * MB_W1, 65536);
            tma2d(sb + R_QK1 + 32768, &maps.wk, c * 64, 256, bar + 8 * MB_W1); tma2d(sb + R_QK1, &maps.wq, c * 64, 256, bar + 8 * MB_W1);
        }
        __syncwarp();
        const float nv = frag_norm2(wv);
        if (lane == 0) sts32(sb + R_MISC + 64 + u * 4, FU(nv));
        __syncwarp();
        bar_arrive(0, 256);
        mx = put_mem0(sb, 4 + u, mem0);
    }
    const uint32_t rL = opaque(sb + lane * 16), rG = opaque(sb + lane * 16 + u * 1024);
    const uint32_t sbu = uni(sb), fo = uni(u), cc = uni(c), ep = uni(epoch);
    const uint64_t gx = xpage();
    const uint32_t ghi = uni((uint32_t)(gx >> 32)), glo = uni((uint32_t)gx);
    constexpr int CX = R_AX + NAX * 4096;
    static_assert(NAX + NCX <= 6, "AX");
#pragma unroll
    for (int i = 0; i < NCX; i++) {
        sts128u(rG + CX + 4096 * i, wv[i][0], wv[i][1], wv[i][2], wv[i][3]);
        sts128u(rG + CX + 4096 * i + 512, wv[16 + i][0], wv[16 + i][1], wv[16 + i][2], wv[16 + i][3]);
    }
    __syncwarp();
    TSDECL;
    uint32_t rpb = 0x3f800000u;
    bar_arrive(2, 256);
    if (fo == 3) {
        uint32_t n = 0;
#pragma unroll 1
        while (true) {
            const uint2 v = ldg_rlx2(&g_f.kv[0][cc >> 1][0]);
            if (__all_sync(0xffffffffu, v.x == ep && v.y == ep)) break;
            __nanosleep(32);
            if (++n > SPIN_LIMIT) { ABORT(6); break; }
        }
        if (rL == sbu) load_slot(sbu, cc, 0, maps);
        __syncwarp();
        if (cc == 7 && rL == sbu) GT(1427);
    }
#pragma unroll 1
    for (int s = 0;; s++) {
        if (TEARLY && fo == 3 && !(s & 1) && s > 0 && s + 2 < NSEG) {
            if (rL == sbu) load_slot(sbu, cc, (s + 2) >> 1, maps);
            __syncwarp();
        } else spin_until(clk32(), DC);
#pragma unroll
        for (int i = NCX - NCL; i < NCX; i++) { lds_fragv(wv[i], rG + CX + 4096 * i); lds_fragv(wv[16 + i], rG + CX + 4096 * i + 512); }
        PUT_MAX(rL, 4 + fo)
        if (fo == 0) {
                bar_sync(15, 256);
                if (s == 0) {
                    const uint32_t* np = (const uint32_t*)&g_f.norm[0] + ((rL ^ sbu) >> 2);
                    uint4 r, q; uint32_t n = 0;
#pragma unroll 1
                    while (true) {
                        r = ldg_rlx4(np); q = ldg_rlx4(np + 128);
                        const uint2 z = ldg_rlx2(&g_f.xn[(rL ^ sbu) >> 3]);
                        if (__all_sync(0xffffffffu, r.y == ep && r.w == ep && q.y == ep && q.w == ep && z.x == ep && z.y == ep)) break;
                        if (++n > SPIN_LIMIT) { ABORT(5); break; }
                    }
                    float nv = __uint_as_float(r.x) + __uint_as_float(q.x), no = __uint_as_float(r.z) + __uint_as_float(q.z);
#pragma unroll
                    for (int o = 16; o; o >>= 1) { nv += __shfl_xor_sync(0xffffffffu, nv, o); no += __shfl_xor_sync(0xffffffffu, no, o); }
                    const int lc = ((int)(FU(nv) >> 23) + (int)(FU(no) >> 23) - 252 + 9 + 1) >> 1;
                    sts32(sbu + R_MISC + 32, 140 - lc);
                    __syncwarp();
                }
                const uint4 ma = lds128uv(rL + R_STG + 1024), mb = lds128uv(rL + R_STG + 1536);
                const uint32_t m_ = amax2b(amax2b(amax2b(ma.x, ma.y), amax2b(ma.z, ma.w)), amax2b(amax2b(mb.x, mb.y), amax2b(mb.z, mb.w)));
                const int em = (int)(__reduce_max_sync(0xffffffffu, amax2b(m_, m_ << 16) & 0x7f800000u) >> 23) + (int)(rpb >> 23) - 127;
                const int es = min(max((int)lds32v_(sbu + R_MISC + 32) - max(em, 127), -60), 60);
                sts32(sbu + R_MISC + 40, (127 + es) << 23);
                TS(4, es);
        } else bar_arrive(15, 256);
        bar_sync(GOBAR, 96);
        float v0[4], v1[4];
        g1<CNB, SMC>(v0, v1, wv, wv + 16, rL + R_MEMB + (fo >> 1) * 4096, sbu - s, [&](int i, const uint32_t* c_) { if (i == 0) TS(0, c_[0]); });
        TS(1, FU(v1[3]));
        const uint32_t l16 = (rL ^ sbu) | (lds32v_(rL + R_LT + 4) & 1);
        const uint32_t r8 = sbu + (l16 >> 1);
        {
            sts128(rL + R_VRED + fo * 512, v1[0], v1[1], v1[2], v1[3]);
            const uint32_t d = r8 + R_VB + ((cc & 1) * 4 + (fo & 1) * 2 + (fo >> 1)) * 256;
            const uint32_t dr = xorv(d, 0x01000000u), br = xorv(sbu + R_BAR + 8 * MB_V, 0x01000000u);
            bar_sync(6 + (fo & 1), 64);
            const float4 a0 = lds128(rL + R_VRED + (fo ^ 2) * 512);
            const float rp = __uint_as_float(rpb);
            const uint32_t w0 = pack2((v0[0] + a0.x) * rp, (v0[1] + a0.y) * rp), w1 = pack2((v0[2] + a0.z) * rp, (v0[3] + a0.w) * rp);
            st_async2(dr, w0, w1, br);
            TS(3, w1);
            sts64(d, __uint_as_float(w0), __uint_as_float(w1));
            __syncwarp();
            asm volatile("{\n.reg .pred p;\nsetp.eq.u32 p, %0, %1;\n@p mbarrier.arrive.expect_tx.shared::cta.b64 _, [%2], 256;\n}"
                         :: "r"(rL), "r"(sbu), "r"(sbu + R_BAR + 8 * MB_V) : "memory");
        }
        if (fo == 1) {
            bar_sync(9, 192);
            uint8_t* dst = (uint8_t*)&g_KVf[s][cc >> 1][(cc & 1) * 256] + l16;
            const uint32_t r2 = prmt(rpb, 0, 0x3232u);
#pragma unroll
            for (int i = 0; i < 2; i++) {
                const uint4 a = lds128uv(rL + R_STG + i * 512);
                stg4(dst + i * 512, make_uint4(~hmul2b(a.x, r2), ~hmul2b(a.y, r2), ~hmul2b(a.z, r2), ~hmul2b(a.w, r2)));
                const float2 b0 = lds64v(r8 + R_VB + (cc & 1) * 1024 + i * 512), b1 = lds64v(r8 + R_VB + (cc & 1) * 1024 + i * 512 + 256);
                stg4(dst + 2048 + i * 512, make_uint4(~FU(b0.x), ~FU(b0.y), ~FU(b1.x), ~FU(b1.y)));
            }
            __syncwarp();
            if (l16 == 0) { stg_rlx(&g_f.rec[cc], (ep << 8) | (s + 1)); if (s == NSEG - 1) GT(1500 + cc); }
            __syncwarp();
        } else {
            bar_arrive(9, 192);
            if (fo == 2) {
                if (l16 < 144) stg4((void*)mkptr((glo + zero_off(cc, l16 >> 4)) ^ aslot(s + 4), ghi), make_uint4(0, 0, 0, 0));
                __syncwarp();
            } else if (fo == 3) {
                if (((s & 1) || s == 0) && s + 3 < NSEG) {
                    const uint32_t* fp = &g_f.kv[(s + 3) >> 1][cc >> 1][0];
                    uint32_t n = 0;
#pragma unroll 1
                    while (true) {
                        const uint2 v = ldg_rlx2(fp);
                        if (__all_sync(0xffffffffu, v.x == ep && v.y == ep)) break;
                        __nanosleep(64);
                        if (++n > SPIN_LIMIT) { ABORT(6); break; }
                    }
                }
                if (!(s & 1) && s + 2 < NSEG && (!TEARLY || s == 0)) {
                    spin_until(clk32(), DT);
                    if (l16 == 0) load_slot(sbu, cc, (s + 2) >> 1, maps);
                    __syncwarp();
                }
            }
        }
        if (s == NSEG - 1) break;
        auto early = [&]() {
#pragma unroll
            for (int i = 0; i < NCX - NCL; i++) { lds_fragv(wv[i], rG + CX + 4096 * i); lds_fragv(wv[16 + i], rG + CX + 4096 * i + 512); }
        };
        GATHER(1, , early(); rpb = 0x7f000000u - lds32v_(sbu + R_MISC + 40);, bar_arrive(2, 256);)
    }
}

__device__ __forceinline__ bool cand_better(float v, int i, float bv, int bi) { return v > bv || (v == bv && i < bi); }
constexpr int F_WG = 0, F_WU = 32768, F_WD = 65536, F_X = 98304, F_RED = F_X + 4096, F_ACT = F_RED + 8192, F_SEL = F_ACT + 256;

__device__ __noinline__ void ffn_phase(const Maps& maps, const bf16* __restrict__ wd, bf16* __restrict__ out) {
    extern __shared__ __align__(1024) uint8_t smem[];
    const uint32_t sb = smem_u32(smem);
    const int c = ((volatile int*)(smem + SH_OFF))[8];
    const uint32_t epoch = ((volatile uint32_t*)(smem + SH_OFF))[9];
    const int tid = threadIdx.x;
    constexpr int NWK = FF / 32;
    const bool worker = c < NWK;
    bar_sync(0, 384);
    const uint32_t mb = sb + R_BAR + 8 * MB_W0;
    if (tid == 32 && worker) {
        asm volatile("fence.proxy.async.shared::cta;" ::: "memory");
        mbar_expect_tx(mb, 98304);
        tma2d(sb + F_WG, &maps.wg, c * 32, 0, mb); tma2d(sb + F_WG + 16384, &maps.wg, c * 32, 256, mb);
        tma2d(sb + F_WU, &maps.wu, c * 32, 0, mb); tma2d(sb + F_WU + 16384, &maps.wu, c * 32, 256, mb);
        asm volatile("cp.async.bulk.shared::cluster.global.mbarrier::complete_tx::bytes [%0], [%1], %2, [%3];"
            :: "r"(sb + F_WD), "l"(wd + (size_t)c * 32 * DM), "r"(32768), "r"(mb) : "memory");
    }
    int p0 = -1, p1 = -1;
#pragma unroll 1
    for (int pass = 0; pass < 2; pass++) {
        if (tid < 32) {
            const uint32_t tag = epoch & 0xfffffu;
            uint4 r[4]; uint32_t n = 0;
            const int t3 = tid + 96 < NFW ? tid + 96 : tid;
#pragma unroll 1
            while (true) {
                bool ok = true;
#pragma unroll
                for (int i = 0; i < 4; i++) r[i] = ldg_rlx4((const uint32_t*)&g_f.cand[pass][i < 3 ? tid + 32 * i : t3]);
#pragma unroll
                for (int i = 0; i < 4; i++) ok = ok && (r[i].y >> 12) == tag && (r[i].w >> 12) == tag;
                if (__all_sync(0xffffffffu, ok)) break;
                __nanosleep(32);
                if (++n > SPIN_LIMIT) { ABORT(7); break; }
            }
            float b0 = __uint_as_float(r[0].x), b1 = __uint_as_float(r[0].z); int i0 = r[0].y & 4095, i1 = r[0].w & 4095;
#pragma unroll
            for (int i = 1; i < 4; i++) {
                if (i < 3 || t3 != tid) {
                    float c0 = __uint_as_float(r[i].x), c1 = __uint_as_float(r[i].z); int j0 = r[i].y & 4095, j1 = r[i].w & 4095;
                    if (cand_better(c0, j0, b0, i0)) {
                        if (cand_better(c1, j1, b0, i0)) { b1 = c1; i1 = j1; } else { b1 = b0; i1 = i0; }
                        b0 = c0; i0 = j0;
                    } else if (cand_better(c0, j0, b1, i1)) { b1 = c0; i1 = j0; }
                }
            }
#pragma unroll
            for (int o = 16; o; o >>= 1) {
                float c0 = __shfl_xor_sync(0xffffffffu, b0, o), c1 = __shfl_xor_sync(0xffffffffu, b1, o);
                int j0 = __shfl_xor_sync(0xffffffffu, i0, o), j1 = __shfl_xor_sync(0xffffffffu, i1, o);
                if (cand_better(c0, j0, b0, i0)) {
                    if (cand_better(c1, j1, b0, i0)) { b1 = c1; i1 = j1; } else { b1 = b0; i1 = i0; }
                    b0 = c0; i0 = j0;
                } else if (cand_better(c0, j0, b1, i1)) { b1 = c0; i1 = j0; }
            }
            i0 = min(i0, SQ - 1); i1 = min(i1, SQ - 1);
            if (i0 != p0 || i1 != p1) {
                n = 0;
#pragma unroll 1
                while (!__all_sync(0xffffffffu, (ldg_rlx(&g_f.rows[pass][tid]) == epoch) & (ldg_rlx(&g_f.rows[pass][tid + 32]) == epoch) &
                                                   (ldg_rlx(&g_f.rows[pass][tid + 64]) == epoch) & (ldg_rlx(&g_f.rows[pass][t3]) == epoch))) { __nanosleep(32); if (++n > SPIN_LIMIT) { ABORT(7); break; } }
            }
            int* sel = (int*)(smem + F_SEL);
            if (pass && tid == 0) GT(c * 8 + 5);
            if (tid == 0) { sel[0] = i0; sel[1] = i1; ((float*)sel)[2] = b0; ((float*)sel)[3] = b1; }
        }
        bar_sync(0, 384);
        const int t0 = ((int*)(smem + F_SEL))[0], t1 = ((int*)(smem + F_SEL))[1];
        if (c == 3 && tid == 0 && pass == 0) GT(1430);
        if (t0 == p0 && t1 == p1) break;
        const uint32_t ytag = epoch * 2 + pass + 1;
        if (worker) {
            float2* xs = (float2*)(smem + F_X);
            if (tid < 256) {
                uint32_t a = __ldcg((const uint32_t*)(g_hn + (size_t)t0 * DM) + tid), b = __ldcg((const uint32_t*)(g_hn + (size_t)t1 * DM) + tid);
                *(float4*)(xs + tid * 2) = make_float4(bf_lo(a), bf_lo(b), bf_hi(a), bf_hi(b));
            }
            mbar_wait(mb, 1);
            if (c == 3 && tid == 0 && pass == 0) GT(1431);
            bar_sync(0, 384);
            float4* red = (float4*)(smem + F_RED);
            if (tid < 256) {
                const int cp = tid & 31, kg = tid >> 5;
                const uint32_t* wp = (const uint32_t*)(smem + (cp < 16 ? F_WG : F_WU)) + (cp & 15);
                float a0 = 0.f, a1 = 0.f, b0 = 0.f, b1 = 0.f;
#pragma unroll 16
                for (int k = kg * 64; k < kg * 64 + 64; k++) {
                    uint32_t w = wp[k * 16]; float2 x = xs[k];
                    a0 = fmaf(x.x, bf_lo(w), a0); a1 = fmaf(x.x, bf_hi(w), a1); b0 = fmaf(x.y, bf_lo(w), b0); b1 = fmaf(x.y, bf_hi(w), b1);
                }
                red[kg * 32 + cp] = make_float4(a0, a1, b0, b1);
            }
            bar_sync(0, 384);
            float2* act = (float2*)(smem + F_ACT);
            if (tid < 64) {
                const int f = tid & 31, tk = tid >> 5;
                const float* r = (const float*)red + (f >> 1) * 4 + tk * 2 + (f & 1);
                float gsum = 0.f, usum = 0.f;
#pragma unroll
                for (int kg = 0; kg < 8; kg++) { gsum += r[kg * 128]; usum += r[kg * 128 + 64]; }
                gsum = rbf(gsum); usum = rbf(usum);
                float sg = rbf(gsum / (1.f + __expf(-gsum)));
                ((float*)act)[f * 2 + tk] = rbf(sg * usum);
            }
            bar_sync(0, 384);
            if (tid < 256) {
                const uint32_t* wp = (const uint32_t*)(smem + F_WD) + tid;
                float a0 = 0.f, a1 = 0.f, b0 = 0.f, b1 = 0.f;
#pragma unroll 16
                for (int f = 0; f < 32; f++) {
                    uint32_t w = wp[f * 256]; float2 x = act[f];
                    a0 = fmaf(x.x, bf_lo(w), a0); a1 = fmaf(x.x, bf_hi(w), a1); b0 = fmaf(x.y, bf_lo(w), b0); b1 = fmaf(x.y, bf_hi(w), b1);
                }
                asm volatile("st.relaxed.gpu.global.v4.b32 [%0], {%1,%2,%3,%2};" :: "l"(&g_yp[pass][c][tid]), "r"(FU(a0)), "r"(ytag), "r"(FU(a1)) : "memory");
                asm volatile("st.relaxed.gpu.global.v4.b32 [%0], {%1,%2,%3,%2};" :: "l"(&g_yp[pass][c][256 + tid]), "r"(FU(b0)), "r"(ytag), "r"(FU(b1)) : "memory");
            }
            if (c == 3 && tid == 0 && pass == 0) GT(1432);
        } else {
            const int r = c - NWK, j = tid & 63, part = tid >> 6, tk = r >> 2, dp = (r & 3) * 64 + j;
            const int tok = tk ? t1 : t0, old = tk ? p1 : p0;
            uint32_t hw = 0, nw = 0;
            if (part == 0) {
                hw = __ldcg((const uint32_t*)(g_h + (size_t)tok * DM) + dp); nw = __ldcg((const uint32_t*)(g_hn + (size_t)tok * DM) + dp);
                if (old >= 0 && old != t0 && old != t1) {
                    uint32_t ho = __ldcg((const uint32_t*)(g_h + (size_t)old * DM) + dp), no = __ldcg((const uint32_t*)(g_hn + (size_t)old * DM) + dp);
                    ((uint32_t*)(out + (size_t)old * DM))[dp] = pack2(bf_lo(ho) + bf_lo(no), bf_hi(ho) + bf_hi(no));
                }
            }
            float s0 = 0.f, s1 = 0.f;
            uint4 v[10]; uint32_t n = 0;
            bool ok;
#pragma unroll 1
            do {
                ok = true;
#pragma unroll
                for (int i = 0; i < 10; i++) {
                    const int src = part + 6 * i;
                    v[i] = src < NWK ? ldg_rlx4((const uint32_t*)&g_yp[pass][src][tk * 256 + dp]) : make_uint4(0, ytag, 0, ytag);
                }
#pragma unroll
                for (int i = 0; i < 10; i++) ok = ok && v[i].y == ytag && v[i].w == ytag;
                if (!ok) __nanosleep(100);
                if (++n > SPIN_LIMIT) { ABORT(7); break; }
            } while (!ok);
#pragma unroll
            for (int i = 0; i < 10; i++) { s0 += __uint_as_float(v[i].x); s1 += __uint_as_float(v[i].z); }
            float2* red = (float2*)(smem + F_RED);
            red[part * 64 + j] = make_float2(s0, s1);
            bar_sync(0, 384);
            if (part == 0) {
#pragma unroll
                for (int i = 1; i < 6; i++) { float2 q = red[i * 64 + j]; s0 += q.x; s1 += q.y; }
                const float rs = rbf(1.f / (1.f + __expf(-((float*)(smem + F_SEL))[2 + tk])));
                const float y0 = rbf(rbf(s0) * rs), y1 = rbf(rbf(s1) * rs);
                ((uint32_t*)(out + (size_t)tok * DM))[dp] = pack2(bf_lo(hw) + rbf(bf_lo(nw) + y0), bf_hi(hw) + rbf(bf_hi(nw) + y1));
            }
            if (tid == 0 && pass == 0 && r == 0) GT(1434);
        }
        p0 = t0; p1 = t1;
        if (c == 3 && tid == 0 && pass == 0) GT(1433);
        bar_sync(0, 384);
    }
}

constexpr int G_W = 0;
constexpr int G_RING = 131072;
constexpr int G_BUF = 163840;
constexpr int G_BAR = 229376;
constexpr int G_SMEM = G_BAR + 512;
enum { GB_W0 = 0, GB_W1, GB_WFREE, GB_FULL, GB_EMPTY = GB_FULL + 8, GB_KV = GB_EMPTY + 8, GB_STG = GB_KV + 2, GB_FREE = GB_STG + 2, GB_XN = GB_FREE + 2, GB_RL, GB_T1D, GB_VV, GB_KVF = GB_VV + 2, GB_VF, GB_N };
constexpr int SMEM_TOTAL = 232448;

__device__ __forceinline__ void wgmma_n128(float* d, uint64_t da, uint64_t db, int scale_d) {
    asm volatile("{\n.reg .pred p;\nsetp.ne.b32 p, %66, 0;\n"
        "wgmma.mma_async.sync.aligned.m64n128k16.f32.bf16.bf16 "
        "{%0,%1,%2,%3,%4,%5,%6,%7,%8,%9,%10,%11,%12,%13,%14,%15,%16,%17,%18,%19,%20,%21,%22,%23,%24,%25,%26,%27,%28,%29,%30,%31,"
        "%32,%33,%34,%35,%36,%37,%38,%39,%40,%41,%42,%43,%44,%45,%46,%47,%48,%49,%50,%51,%52,%53,%54,%55,%56,%57,%58,%59,%60,%61,%62,%63}, "
        "%64, %65, p, 1, 1, 0, 1;\n}"
        : "+f"(d[0]), "+f"(d[1]), "+f"(d[2]), "+f"(d[3]), "+f"(d[4]), "+f"(d[5]), "+f"(d[6]), "+f"(d[7]), "+f"(d[8]), "+f"(d[9]), "+f"(d[10]), "+f"(d[11]),
          "+f"(d[12]), "+f"(d[13]), "+f"(d[14]), "+f"(d[15]), "+f"(d[16]), "+f"(d[17]), "+f"(d[18]), "+f"(d[19]), "+f"(d[20]), "+f"(d[21]), "+f"(d[22]), "+f"(d[23]),
          "+f"(d[24]), "+f"(d[25]), "+f"(d[26]), "+f"(d[27]), "+f"(d[28]), "+f"(d[29]), "+f"(d[30]), "+f"(d[31]), "+f"(d[32]), "+f"(d[33]), "+f"(d[34]), "+f"(d[35]),
          "+f"(d[36]), "+f"(d[37]), "+f"(d[38]), "+f"(d[39]), "+f"(d[40]), "+f"(d[41]), "+f"(d[42]), "+f"(d[43]), "+f"(d[44]), "+f"(d[45]), "+f"(d[46]), "+f"(d[47]),
          "+f"(d[48]), "+f"(d[49]), "+f"(d[50]), "+f"(d[51]), "+f"(d[52]), "+f"(d[53]), "+f"(d[54]), "+f"(d[55]), "+f"(d[56]), "+f"(d[57]), "+f"(d[58]), "+f"(d[59]),
          "+f"(d[60]), "+f"(d[61]), "+f"(d[62]), "+f"(d[63])
        : "l"(da), "l"(db), "r"(scale_d));
}

__device__ __forceinline__ constexpr uint32_t slot_off(int slot) {
    return slot < 2 ? G_RING + slot * 16384 : G_BUF + (slot - 2) * 32768 + 16384;
}
template <int NSLOT>
__device__ __forceinline__ void gemm_tile(float* acc, uint32_t sb, int tile, int it, bool first, uint32_t wpar, int wg, bool pass, uint32_t l0) {
    const uint32_t bar = sb + G_BAR;
    bar_sync(3 + wg, 256);
    int prev = 0;
#pragma unroll
    for (int k = 0; k < 4; k++) {
        const int n = tile * 4 + k, slot = NSLOT == 4 ? k : n % 3;
        const uint32_t sz = sb + (((it + k) << 4) & sb & 0x3f0);
        const uint64_t da = desc_sw128(sz + slot_off(slot), 16, 1024), db0 = desc_sw128(sz + G_W, 65536, 1024);
        if ((k & 1) == 0 && first) mbar_wait_p(bar + 8 * (GB_W0 + (k >> 1)), wpar);
        bool rel = false;
        if (EREL && k > 0 && !__all_sync(0xffffffffu, mbar_test(bar + 8 * (GB_FULL + slot), tile & 1))) {
            asm volatile("wgmma.wait_group.sync.aligned 0;" ::: "memory");
            mbar_arrive2_if(bar + 8 * (GB_EMPTY + prev), l0);
            rel = true;
        }
        mbar_wait_p(bar + 8 * (GB_FULL + slot), NSLOT == 4 ? (tile & 1) : ((n / 3) & 1));
        if (k == 3 && pass) bar_arrive(3 + (wg ^ 1), 256);
        asm volatile("wgmma.fence.sync.aligned;" ::: "memory");
#pragma unroll
        for (int kk = 0; kk < 4; kk++) wgmma_n128(acc, da + kk * 2, db0 + k * 1024 + kk * 128, (k | kk) != 0);
        asm volatile("wgmma.commit_group.sync.aligned;" ::: "memory");
        if (k > 0) {
            asm volatile("wgmma.wait_group.sync.aligned 1;" ::: "memory");
            mbar_arrive2_if(bar + 8 * (GB_EMPTY + prev), rel ? 0 : l0);
        }
#pragma unroll
        for (int kk = 0; kk < 4; kk++) wgmma_n128(acc, da + 512 + kk * 2, db0 + k * 1024 + 512 + kk * 128, 1);
        asm volatile("wgmma.commit_group.sync.aligned;" ::: "memory");
        prev = slot;
    }
    asm volatile("wgmma.wait_group.sync.aligned 0;" ::: "memory");
    mbar_arrive2_if(bar + 8 * (GB_EMPTY + prev), l0);
}
__device__ __forceinline__ void stage_bf16(const float* acc, uint32_t buf, float s0, float s1) {
    const int lane = threadIdx.x & 31, wq = (threadIdx.x >> 5) & 3;
    const int row = wq * 16 + (lane & 7) + ((lane >> 3) & 1) * 8;
    const uint32_t base = buf + row * 128;
#pragma unroll
    for (int j = 0; j < 16; j += 2) {
        const int ch = (j & 7) + (lane >> 4);
        stsm4(base + (j >> 3) * 8192 + ((ch ^ (row & 7)) << 4),
              pack2(acc[4 * j] * s0, acc[4 * j + 1] * s0), pack2(acc[4 * j + 2] * s1, acc[4 * j + 3] * s1),
              pack2(acc[4 * j + 4] * s0, acc[4 * j + 5] * s0), pack2(acc[4 * j + 6] * s1, acc[4 * j + 7] * s1));
    }
}

__device__ __forceinline__ void store_perm(const float* acc, bf16* dst, int ld, float s0, float s1) {
#pragma unroll
    for (int i = 0; i < 4; i++) {
        const float* a = acc + 16 * i;
        *(uint4*)(dst + i * 32) = make_uint4(pack2(a[0] * s0, a[1] * s0), pack2(a[4] * s0, a[5] * s0), pack2(a[8] * s0, a[9] * s0), pack2(a[12] * s0, a[13] * s0));
        *(uint4*)(dst + 8 * ld + i * 32) = make_uint4(pack2(a[2] * s1, a[3] * s1), pack2(a[6] * s1, a[7] * s1), pack2(a[10] * s1, a[11] * s1), pack2(a[14] * s1, a[15] * s1));
    }
}
template <int ACC>
__device__ __forceinline__ void wgmma_rs64(float* d, const uint32_t* a, uint64_t db) {
    asm volatile("{\n.reg .pred p;\nsetp.ne.b32 p, %37, 0;\n"
        "wgmma.mma_async.sync.aligned.m64n64k16.f32.bf16.bf16 {%0,%1,%2,%3,%4,%5,%6,%7,%8,%9,%10,%11,%12,%13,%14,%15,%16,%17,%18,%19,%20,%21,%22,%23,%24,%25,%26,%27,%28,%29,%30,%31}, {%32,%33,%34,%35}, %36, p, 1, 1, 0;\n}"
        : "+f"(d[0]), "+f"(d[1]), "+f"(d[2]), "+f"(d[3]), "+f"(d[4]), "+f"(d[5]), "+f"(d[6]), "+f"(d[7]), "+f"(d[8]), "+f"(d[9]), "+f"(d[10]), "+f"(d[11]), "+f"(d[12]), "+f"(d[13]), "+f"(d[14]), "+f"(d[15]), "+f"(d[16]), "+f"(d[17]), "+f"(d[18]), "+f"(d[19]), "+f"(d[20]), "+f"(d[21]), "+f"(d[22]), "+f"(d[23]), "+f"(d[24]), "+f"(d[25]), "+f"(d[26]), "+f"(d[27]), "+f"(d[28]), "+f"(d[29]), "+f"(d[30]), "+f"(d[31])
        : "r"(a[0]), "r"(a[1]), "r"(a[2]), "r"(a[3]), "l"(db), "n"(ACC));
}
template <int ACC>
__device__ __forceinline__ void wgmma_rs128t(float* d, const uint32_t* a, uint64_t db) {
    asm volatile("{\n.reg .pred p;\nsetp.ne.b32 p, %69, 0;\n"
        "wgmma.mma_async.sync.aligned.m64n128k16.f32.bf16.bf16 {%0,%1,%2,%3,%4,%5,%6,%7,%8,%9,%10,%11,%12,%13,%14,%15,%16,%17,%18,%19,%20,%21,%22,%23,%24,%25,%26,%27,%28,%29,%30,%31,%32,%33,%34,%35,%36,%37,%38,%39,%40,%41,%42,%43,%44,%45,%46,%47,%48,%49,%50,%51,%52,%53,%54,%55,%56,%57,%58,%59,%60,%61,%62,%63}, {%64,%65,%66,%67}, %68, p, 1, 1, 1;\n}"
        : "+f"(d[0]), "+f"(d[1]), "+f"(d[2]), "+f"(d[3]), "+f"(d[4]), "+f"(d[5]), "+f"(d[6]), "+f"(d[7]), "+f"(d[8]), "+f"(d[9]), "+f"(d[10]), "+f"(d[11]), "+f"(d[12]), "+f"(d[13]), "+f"(d[14]), "+f"(d[15]), "+f"(d[16]), "+f"(d[17]), "+f"(d[18]), "+f"(d[19]), "+f"(d[20]), "+f"(d[21]), "+f"(d[22]), "+f"(d[23]), "+f"(d[24]), "+f"(d[25]), "+f"(d[26]), "+f"(d[27]), "+f"(d[28]), "+f"(d[29]), "+f"(d[30]), "+f"(d[31]), "+f"(d[32]), "+f"(d[33]), "+f"(d[34]), "+f"(d[35]), "+f"(d[36]), "+f"(d[37]), "+f"(d[38]), "+f"(d[39]), "+f"(d[40]), "+f"(d[41]), "+f"(d[42]), "+f"(d[43]), "+f"(d[44]), "+f"(d[45]), "+f"(d[46]), "+f"(d[47]), "+f"(d[48]), "+f"(d[49]), "+f"(d[50]), "+f"(d[51]), "+f"(d[52]), "+f"(d[53]), "+f"(d[54]), "+f"(d[55]), "+f"(d[56]), "+f"(d[57]), "+f"(d[58]), "+f"(d[59]), "+f"(d[60]), "+f"(d[61]), "+f"(d[62]), "+f"(d[63])
        : "r"(a[0]), "r"(a[1]), "r"(a[2]), "r"(a[3]), "l"(db), "n"(ACC));
}
__device__ __forceinline__ void attention_tile(float* acc, uint32_t sb, int tile, int h, int wg, int wq, uint32_t l0, uint32_t epoch, uint2 rec) {
    const uint32_t buf = sb + G_BUF + ((tile << 4) & sb & 0x3f0);
    const int lane = threadIdx.x & 31, g = lane >> 2, t = lane & 3;
    const int sg = wq >> 1, hf = wq & 1, seg = tile * 2 + sg;
    uint32_t qf[8][4];
#pragma unroll
    for (int kk = 0; kk < 8; kk++) {
        qf[kk][0] = pack2(acc[8 * kk], acc[8 * kk + 1]); qf[kk][1] = pack2(acc[8 * kk + 2], acc[8 * kk + 3]);
        qf[kk][2] = pack2(acc[8 * kk + 4], acc[8 * kk + 5]); qf[kk][3] = pack2(acc[8 * kk + 6], acc[8 * kk + 7]);
    }
    uint32_t* kvf = &g_KVf[seg][h][lane * 4];
    uint4 km[4], vm[4];
    const bool early = __all_sync(0xffffffffu, (rec.x >> 8) == epoch && (rec.y >> 8) == epoch && (rec.x & 255) > seg && (rec.y & 255) > seg);
#pragma unroll
    for (int i = 0; i < 4; i++) { km[i] = ldg_rlx4_if(kvf + i * 128, early); vm[i] = ldg_rlx4_if(kvf + 512 + i * 128, early); }
    mbar_wait_p(sb + G_BAR + 8 * (GB_KV + wg), (tile >> 1) & 1);
    if (h == 5 && (threadIdx.x & 127) == 0 && tile < 6) GT(1750 + tile * 8 + 2);
    float sc[5][4];
    {
        const uint64_t dk = desc_sw128(buf, 16, 1024);
        asm volatile("wgmma.fence.sync.aligned;" ::: "memory");
#pragma unroll
        for (int kk = 0; kk < 8; kk++) {
            if (kk == 0) wgmma_rs64<0>(acc, qf[kk], dk); else wgmma_rs64<1>(acc, qf[kk], dk + (kk >> 2) * 512 + (kk & 3) * 2);
        }
        asm volatile("wgmma.commit_group.sync.aligned;" ::: "memory");
        asm volatile("wgmma.wait_group.sync.aligned 0;" ::: "memory");
        mbar_arrive_if(sb + G_BAR + 8 * GB_KVF, l0);
#pragma unroll
        for (int i = 0; i < 32; i++) asm volatile("" : "+f"(acc[i]) :: "memory");
#pragma unroll
        for (int b = 0; b < 4; b++)
#pragma unroll
            for (int i = 0; i < 4; i++) sc[b][i] = sg ? acc[16 + 4 * b + i] : acc[4 * b + i];
        sc[4][0] = sc[4][1] = sc[4][2] = sc[4][3] = 0.f;
    }
    const float cexp = 0.08838834764831845f * 1.4426950408889634f;
    const int r0 = hf * 16 + g, r1 = r0 + 8;
#pragma unroll
    for (int b = 0; b < 4; b++) {
        const int j = b * 8 + 2 * t;
        if (j > r0) sc[b][0] = -INFINITY;
        if (j + 1 > r0) sc[b][1] = -INFINITY;
        if (j > r1) sc[b][2] = -INFINITY;
        if (j + 1 > r1) sc[b][3] = -INFINITY;
    }
    float m0 = -INFINITY, m1 = -INFINITY;
#pragma unroll
    for (int b = 0; b < 4; b++) { m0 = fmaxf(m0, fmaxf(sc[b][0], sc[b][1])); m1 = fmaxf(m1, fmaxf(sc[b][2], sc[b][3])); }
    m0 = fmaxf(m0, __shfl_xor_sync(0xffffffffu, m0, 1)); m0 = fmaxf(m0, __shfl_xor_sync(0xffffffffu, m0, 2));
    m1 = fmaxf(m1, __shfl_xor_sync(0xffffffffu, m1, 1)); m1 = fmaxf(m1, __shfl_xor_sync(0xffffffffu, m1, 2));
    float z0 = 0.f, z1 = 0.f;
    {
        const float c0 = -m0 * cexp, c1 = -m1 * cexp;
        uint32_t pf[4][2];
#pragma unroll
        for (int b = 0; b < 4; b++) {
            pf[b][0] = pack2(ex2(fmaf(sc[b][0], cexp, c0)), ex2(fmaf(sc[b][1], cexp, c0)));
            pf[b][1] = pack2(ex2(fmaf(sc[b][2], cexp, c1)), ex2(fmaf(sc[b][3], cexp, c1)));
            z0 += bf_lo(pf[b][0]) + bf_hi(pf[b][0]); z1 += bf_lo(pf[b][1]) + bf_hi(pf[b][1]);
        }
        uint32_t pa[4][4];
#pragma unroll
        for (int kk = 0; kk < 4; kk++)
#pragma unroll
            for (int i = 0; i < 4; i++) pa[kk][i] = (kk >> 1) == sg ? pf[(kk & 1) * 2 + (i >> 1)][i & 1] : 0u;
        const uint64_t dv = desc_sw128(buf + 32768, 8192, 1024);
        mbar_wait_p(sb + G_BAR + 8 * (GB_VV + wg), (tile >> 1) & 1);
        asm volatile("wgmma.fence.sync.aligned;" ::: "memory");
#pragma unroll
        for (int kk = 0; kk < 4; kk++) { if (kk == 0) wgmma_rs128t<0>(acc, pa[kk], dv); else wgmma_rs128t<1>(acc, pa[kk], dv + kk * 128); }
        asm volatile("wgmma.commit_group.sync.aligned;" ::: "memory");
        asm volatile("wgmma.wait_group.sync.aligned 0;" ::: "memory");
#pragma unroll
        for (int i = 0; i < 64; i++) asm volatile("" : "+f"(acc[i]) :: "memory");
    }
    mbar_arrive_if(sb + G_BAR + 8 * GB_VF, l0);
    if (h == 5 && (threadIdx.x & 127) == 0 && tile < 6) GT(1750 + tile * 8 + 3);
    if (!early) wait_rec(&g_f.rec[2 * h], epoch, seg + 1);
    if (seg == 63 && (threadIdx.x & 63) == 0) GT(1570 + h);
    if (h == 5 && (threadIdx.x & 127) == 0 && tile < 6) GT(1750 + tile * 8 + 4);
    __syncwarp();
    {
        uint32_t n = 0;
#pragma unroll 1
        while (true) {
            uint32_t mn = 0xffffffffu;
#pragma unroll
            for (int i = 0; i < 4; i++) mn = min(min(min(mn, min(km[i].x, km[i].y)), min(km[i].z, km[i].w)), min(min(vm[i].x, vm[i].y), min(vm[i].z, vm[i].w)));
            if (__all_sync(0xffffffffu, mn != 0)) break;
            if (++n > SPIN_LIMIT) { ABORT(4); break; }
#pragma unroll
            for (int i = 0; i < 4; i++) { km[i] = ldg_rlx4(kvf + i * 128); vm[i] = ldg_rlx4(kvf + 512 + i * 128); }
        }
#pragma unroll
        for (int i = 0; i < 4; i++) {
            km[i] = make_uint4(~km[i].x, ~km[i].y, ~km[i].z, ~km[i].w); vm[i] = make_uint4(~vm[i].x, ~vm[i].y, ~vm[i].z, ~vm[i].w);
        }
        if (hf) bar_arrive(5 + wg * 2 + sg, 64);
        float sb_[4] = {0.f, 0.f, 0.f, 0.f};
#pragma unroll
        for (int i = 0; i < 4; i++) { MMA(sc[4], qf[2 * i], km[i].x, km[i].y); MMA(sb_, qf[2 * i + 1], km[i].z, km[i].w); }
#pragma unroll
        for (int i = 0; i < 4; i++) sc[4][i] += sb_[i];
        float n0 = fmaxf(sc[4][0], sc[4][1]), n1 = fmaxf(sc[4][2], sc[4][3]);
        n0 = fmaxf(n0, __shfl_xor_sync(0xffffffffu, n0, 1)); n1 = fmaxf(n1, __shfl_xor_sync(0xffffffffu, n1, 1));
        n0 = fmaxf(n0, __shfl_xor_sync(0xffffffffu, n0, 2)); n1 = fmaxf(n1, __shfl_xor_sync(0xffffffffu, n1, 2));
        n0 = fmaxf(n0, m0); n1 = fmaxf(n1, m1);
        const float a0 = ex2((m0 - n0) * cexp), a1 = ex2((m1 - n1) * cexp);
        const float c0 = -n0 * cexp, c1 = -n1 * cexp;
        const uint32_t p0 = pack2(ex2(fmaf(sc[4][0], cexp, c0)), ex2(fmaf(sc[4][1], cexp, c0)));
        const uint32_t p1 = pack2(ex2(fmaf(sc[4][2], cexp, c1)), ex2(fmaf(sc[4][3], cexp, c1)));
        z0 = fmaf(z0, a0, bf_lo(p0) + bf_hi(p0)); z1 = fmaf(z1, a1, bf_lo(p1) + bf_hi(p1));
        const uint32_t* vmw = (const uint32_t*)vm;
#pragma unroll
        for (int j = 0; j < 16; j++) {
            float* o = acc + 4 * j;
            o[0] *= a0; o[1] *= a0; o[2] *= a1; o[3] *= a1;
            mma1688(o, p0, p1, vmw[j]);
        }
        z0 += __shfl_xor_sync(0xffffffffu, z0, 1); z1 += __shfl_xor_sync(0xffffffffu, z1, 1);
        z0 += __shfl_xor_sync(0xffffffffu, z0, 2); z1 += __shfl_xor_sync(0xffffffffu, z1, 2);
    }
    if (h == 5 && (threadIdx.x & 127) == 0 && tile < 6) GT(1750 + tile * 8 + 5);
    store_perm(acc, g_O + (size_t)(tile * 64 + wq * 16 + g) * HD + h * 128 + t * 8, HD, rcpf(z0), rcpf(z1));
    if (tile >= 2) mbar_wait_p(sb + G_BAR + 8 * (GB_FREE + wg), ((tile >> 1) - 1) & 1);
    mbar_arrive(sb + G_BAR + 8 * (GB_STG + wg));
    if (!hf) {
        bar_sync(5 + wg * 2 + sg, 64);
#pragma unroll
        for (int i = 0; i < 8; i++) stg4(kvf + i * 128, make_uint4(0, 0, 0, 0));
    }
}

__device__ __forceinline__ void g_consumer(uint32_t sb_, int g_, int wg_, uint32_t epoch) {
    const uint32_t sb = uni(sb_);
    const int g = uni(g_), wg = uni(wg_), wq = uni((threadIdx.x >> 5) & 3);
    const uint32_t l0 = opaque((threadIdx.x & 31) == 0);
    const uint32_t bar = sb + G_BAR, buf = sb + G_BUF + wg * 32768;
    const int lane = threadIdx.x & 31;
    float acc[64];
    if (wg == 1) bar_arrive(3, 256);
    const int n1 = g < 32 ? HSPLIT / 2 : NT - HSPLIT / 2;
#pragma unroll 1
    for (int i = 0; i < n1; i++) {
        gemm_tile<4>(acc, sb, wg, i, i == 0 || i == NT / 2, i >= NT / 2, wg, true, l0);
        if (i == n1 - 1 || i == NT / 2 - 1) mbar_arrive_if(bar + 8 * GB_WFREE, l0);
        if (threadIdx.x == 0 && i == 0) GT((64 + g) * 8 + 1);
        if (threadIdx.x == 128 && i == 3) GT((64 + g) * 8 + 2);
        if (i > 0) mbar_wait_p(bar + 8 * (GB_FREE + wg), (i - 1) & 1);
        stage_bf16(acc, buf, 1.f, 1.f);
        asm volatile("fence.proxy.async.shared::cta;" ::: "memory");
        mbar_arrive(bar + 8 * (GB_STG + wg));
    }
    if (threadIdx.x == 128) GT((64 + g) * 8 + 3);
    if (g < 32) {
#pragma unroll 1
        for (int i = 0; i < NT / 2; i++) {
            const int tile = 2 * i + wg;
            const uint2 rec = ldg_rlx2(&g_f.rec[2 * g]);
            gemm_tile<4>(acc, sb, tile, i, i == 0, 1, wg, tile != NT - 1, l0);
            if (threadIdx.x == 0 && i == 0) GT((64 + g) * 8 + 4);
            if (threadIdx.x == 128 && i == 3) GT((64 + g) * 8 + 5);
            if (g == 5 && (threadIdx.x & 127) == 0 && tile < 6) GT(1750 + tile * 8 + 1);
            attention_tile(acc, sb, tile, g, wg, wq, l0, epoch, rec);
            if (g == 5 && (threadIdx.x & 127) == 0 && tile < 6) GT(1750 + tile * 8 + 6);
        }
    } else {
#pragma unroll 1
        for (int i = 0; i < NT / 2; i++) {
            const int tile = 2 * i + wg;
            gemm_tile<4>(acc, sb, tile, i, i == 0, 0, wg, tile != NT - 1, l0);
            if (threadIdx.x == 0 && i == 0) GT((64 + g) * 8 + 4);
            if (threadIdx.x == 128 && i == 3) GT((64 + g) * 8 + 5);
            store_perm(acc, g_P + (size_t)(((g - 32) >> 2) * SQ + tile * 64 + wq * 16 + (lane >> 2)) * DM + ((g - 32) & 3) * 128 + (lane & 3) * 8, DM, 1.f, 1.f);
            mbar_wait_p(bar + 8 * (GB_FREE + wg), (i - 1) & 1);
            mbar_arrive(bar + 8 * (GB_STG + wg));
        }
    }
}

__device__ __forceinline__ void load_w(uint32_t sb, const CUtensorMap* tm, int col, int row, int k0 = 0, int k1 = 2) {
    const uint32_t bar = sb + G_BAR;
#pragma unroll
    for (int kh = k0; kh < k1; kh++) {
        mbar_expect_tx(bar + 8 * (GB_W0 + kh), 65536);
        tma2d(sb + G_W + kh * 32768, tm, col, row + kh * 256, bar + 8 * (GB_W0 + kh));
        tma2d(sb + G_W + 65536 + kh * 32768, tm, col + 64, row + kh * 256, bar + 8 * (GB_W0 + kh));
    }
}

__device__ __forceinline__ void rbf2(float& a, float& b) { uint32_t w = pack2(a, b); a = bf_lo(w); b = bf_hi(w); }
__device__ __forceinline__ void warp_sum2(float& a, float& b) {
#pragma unroll
    for (int o = 16; o; o >>= 1) { float c = __shfl_xor_sync(0xffffffffu, a, o), d = __shfl_xor_sync(0xffffffffu, b, o); a += c; b += d; }
}
__device__ __forceinline__ float sum16(const float* v) {
    return (((v[0] + v[1]) + (v[2] + v[3])) + ((v[4] + v[5]) + (v[6] + v[7]))) + (((v[8] + v[9]) + (v[10] + v[11])) + ((v[12] + v[13]) + (v[14] + v[15])));
}
__device__ __forceinline__ void ln_row2(float* v, float* u) {
    float sv = sum16(v), su = sum16(u);
    warp_sum2(sv, su);
    const float mv = sv * (1.f / DM), mu = su * (1.f / DM);
    float qv = 0.f, qu = 0.f, qv2 = 0.f, qu2 = 0.f;
#pragma unroll
    for (int i = 0; i < 16; i += 2) {
        float d0 = v[i] - mv, d1 = v[i + 1] - mv, e0 = u[i] - mu, e1 = u[i + 1] - mu;
        qv = fmaf(d0, d0, qv); qv2 = fmaf(d1, d1, qv2); qu = fmaf(e0, e0, qu); qu2 = fmaf(e1, e1, qu2);
    }
    qv += qv2; qu += qu2;
    warp_sum2(qv, qu);
    const float rv = rbf(mv), ru = rbf(mu);
    const float iv = __frcp_rn(rbf(sqrtf(rbf(rbf(qv * (1.f / DM)) + 1e-5f)))), iu = __frcp_rn(rbf(sqrtf(rbf(rbf(qu * (1.f / DM)) + 1e-5f))));
#pragma unroll
    for (int i = 0; i < 16; i += 2) {
        float a = v[i] - rv, b = v[i + 1] - rv, c = u[i] - ru, d = u[i + 1] - ru;
        rbf2(a, b); rbf2(c, d);
        a *= iv; b *= iv; c *= iu; d *= iu;
        rbf2(a, b); rbf2(c, d);
        v[i] = a; v[i + 1] = b; u[i] = c; u[i + 1] = d;
    }
}

__device__ __forceinline__ void ln_row1(float* v) {
    float sv = sum16(v);
#pragma unroll
    for (int o = 16; o; o >>= 1) sv += __shfl_xor_sync(0xffffffffu, sv, o);
    const float mv = sv * (1.f / DM);
    float qv = 0.f, qv2 = 0.f;
#pragma unroll
    for (int i = 0; i < 16; i += 2) { float d0 = v[i] - mv, d1 = v[i + 1] - mv; qv = fmaf(d0, d0, qv); qv2 = fmaf(d1, d1, qv2); }
    qv += qv2;
#pragma unroll
    for (int o = 16; o; o >>= 1) qv += __shfl_xor_sync(0xffffffffu, qv, o);
    const float rv = rbf(mv);
    float sq, iv;
    asm("sqrt.approx.f32 %0, %1;" : "=f"(sq) : "f"(rbf(rbf(qv * (1.f / DM)) + 1e-5f)));
    asm("rcp.approx.f32 %0, %1;" : "=f"(iv) : "f"(rbf(sq)));
#pragma unroll
    for (int i = 0; i < 16; i += 2) {
        float a = v[i] - rv, b = v[i + 1] - rv;
        rbf2(a, b);
        a *= iv; b *= iv;
        rbf2(a, b);
        v[i] = a; v[i + 1] = b;
    }
}
constexpr int FSPLIT = 28;
__device__ __forceinline__ int fin_row(int id, int i) {
    if (id < 64) { const int tile = i < FSPLIT / 2 ? 2 * i : i + FSPLIT / 2; return tile < NT ? tile * 64 + id : -1; }
    const int j = id - 64 + i * 48;
    return j < FSPLIT * 32 ? (j >> 6) * 128 + 64 + (j & 63) : -1;
}
__device__ __forceinline__ void finalizer(int id, const bf16* __restrict__ x, const bf16* __restrict__ wr, bf16* __restrict__ out, uint32_t epoch) {
    const int lane = threadIdx.x & 31;
    float b0 = -INFINITY, b1 = -INFINITY; int i0 = 0x7fffffff, i1 = 0x7fffffff;
    const uint32_t tag = (epoch & 0xfffffu) << 12;
    uint32_t fl = ~epoch;
    int row = fin_row(id, 0);
    const uint4 ra = *(const uint4*)(wr + lane * 8), rb = *(const uint4*)(wr + 256 + lane * 8);
    uint4 xa = *(const uint4*)(x + (size_t)row * DM + lane * 8), xb = *(const uint4*)(x + (size_t)row * DM + lane * 8 + 256);
#pragma unroll 1
    for (int it = 0; row >= 0; it++) {
        const int tile = row >> 6, nxt = fin_row(id, it + 1);
        const size_t o0 = (size_t)row * DM + lane * 8;
        uint32_t n = 0;
#pragma unroll 1
        while (!__all_sync(0xffffffffu, fl == epoch)) {
            if (n) __nanosleep(it ? 64 : 1000);
            fl = ldg_rlx(&g_f.p[tile][lane]);
            if (++n > SPIN_LIMIT) { ABORT(12); break; }
        }
        if (tile == NT - 1 && id == 63 && lane == 0) GT(1438);
        if ((id == 63 || id == 3 || id == 70) && lane == 0) GT(1800 + (id == 3) * 32 + tile);
        float v[16];
        {
            uint4 pa[8][2];
#pragma unroll
            for (int k = 0; k < 8; k++) {
                pa[k][0] = ldg_rlx4((const uint32_t*)(g_P + (size_t)k * SQ * DM + o0));
                pa[k][1] = ldg_rlx4((const uint32_t*)(g_P + (size_t)k * SQ * DM + o0 + 256));
            }
            fl = ldg_rlx(&g_f.p[max(nxt, 0) >> 6][lane]);
#pragma unroll
            for (int j = 0; j < 2; j++) {
#pragma unroll
                for (int i = 0; i < 4; i++) {
                    uint32_t w[8];
#pragma unroll
                    for (int k = 0; k < 8; k++) w[k] = i == 0 ? pa[k][j].x : (i == 1 ? pa[k][j].y : (i == 2 ? pa[k][j].z : pa[k][j].w));
                    v[j * 8 + 2 * i] = ((bf_lo(w[0]) + bf_lo(w[1])) + (bf_lo(w[2]) + bf_lo(w[3]))) + ((bf_lo(w[4]) + bf_lo(w[5])) + (bf_lo(w[6]) + bf_lo(w[7])));
                    v[j * 8 + 2 * i + 1] = ((bf_hi(w[0]) + bf_hi(w[1])) + (bf_hi(w[2]) + bf_hi(w[3]))) + ((bf_hi(w[4]) + bf_hi(w[5])) + (bf_hi(w[6]) + bf_hi(w[7])));
                }
            }
        }
        uint32_t hw[8];
        {
            const uint32_t xw[8] = {xa.x, xa.y, xa.z, xa.w, xb.x, xb.y, xb.z, xb.w};
            uint32_t aw[8];
#pragma unroll
            for (int i = 0; i < 8; i++) aw[i] = pack2(v[2 * i], v[2 * i + 1]);
#pragma unroll
            for (int d = 1; d <= 2; d++) {
                const bool up = lane & d;
#pragma unroll
                for (int i = 0; i < 8; i++) {
                    if (!(i & d)) {
                        const uint32_t r = __shfl_xor_sync(0xffffffffu, up ? aw[i] : aw[i | d], d);
                        if (up) aw[i] = r; else aw[i | d] = r;
                    }
                }
            }
#pragma unroll
            for (int i = 0; i < 8; i++) {
                hw[i] = pack2(bf_lo(aw[i]) + bf_lo(xw[i]), bf_hi(aw[i]) + bf_hi(xw[i]));
                v[2 * i] = bf_lo(hw[i]); v[2 * i + 1] = bf_hi(hw[i]);
            }
        }
        xa = *(const uint4*)(x + (size_t)max(nxt, 0) * DM + lane * 8); xb = *(const uint4*)(x + (size_t)max(nxt, 0) * DM + lane * 8 + 256);
        ln_row1(v);
        float r0 = 0.f, r1 = 0.f;
        {
            const uint32_t ww[8] = {ra.x, ra.y, ra.z, ra.w, rb.x, rb.y, rb.z, rb.w};
#pragma unroll
            for (int i = 0; i < 8; i++) { r0 = fmaf(v[2 * i], bf_lo(ww[i]), r0); r1 = fmaf(v[2 * i + 1], bf_hi(ww[i]), r1); }
        }
        r0 += r1;
#pragma unroll
        for (int o = 16; o; o >>= 1) r0 += __shfl_xor_sync(0xffffffffu, r0, o);
        r0 = rbf(r0);
        if (cand_better(r0, row, b0, i0)) { b1 = b0; i1 = i0; b0 = r0; i0 = row; }
        else if (cand_better(r0, row, b1, i1)) { b1 = r0; i1 = row; }
        if (tile == NT - 1 && id == 63 && lane == 0) GT(1439);
        const bool last = nxt < 0, spec = tile < SPEC_TILES && (last || (nxt >> 6) >= SPEC_TILES);
        const bool pub = (lane == 0 && spec) || (lane == 1 && last);
        if (pub)
            asm volatile("st.relaxed.gpu.global.v4.b32 [%0], {%1,%2,%3,%4};" :: "l"(&g_f.cand[lane][id]),
                         "r"(FU(b0)), "r"(tag | (uint32_t)min(i0, 4095)), "r"(FU(b1)), "r"(tag | (uint32_t)min(i1, 4095)) : "memory");
#pragma unroll
        for (int j = 0; j < 2; j++) {
            const uint32_t* hh = hw + j * 4; const float* nn = v + j * 8;
            *(uint4*)(out + o0 + j * 256) = make_uint4(pack2(bf_lo(hh[0]) + nn[0], bf_hi(hh[0]) + nn[1]), pack2(bf_lo(hh[1]) + nn[2], bf_hi(hh[1]) + nn[3]),
                                                       pack2(bf_lo(hh[2]) + nn[4], bf_hi(hh[2]) + nn[5]), pack2(bf_lo(hh[3]) + nn[6], bf_hi(hh[3]) + nn[7]));
            *(uint4*)(g_h + o0 + j * 256) = make_uint4(hh[0], hh[1], hh[2], hh[3]);
            *(uint4*)(g_hn + o0 + j * 256) = make_uint4(pack2(nn[0], nn[1]), pack2(nn[2], nn[3]), pack2(nn[4], nn[5]), pack2(nn[6], nn[7]));
        }
        if (last || spec) {
            __threadfence();
            __syncwarp();
            if (pub) stg_rlx(&g_f.rows[lane][id], epoch);
        }
        row = nxt;
    }
    if (id == 0 && lane == 0) { g_epoch = epoch; if (epoch == 0xffffffu) { g_ticket[0] = 0; g_ticket[32] = 0; } }
}

__device__ __forceinline__ void g_producer(uint32_t sb, int g, const Maps& maps, uint32_t epoch, const bf16* __restrict__ x, const bf16* __restrict__ wr, bf16* __restrict__ out) {
    const uint32_t bar = sb + G_BAR;
    const int warp = (threadIdx.x >> 5) - 8;
    if (threadIdx.x == 256 && g == 5) GT(1410);
    if (threadIdx.x == 256 && g == 5) GT(1411);
    if (warp == 3) {
        wait_eq4(&g_f.xn[(threadIdx.x & 31) * 4], epoch, 13);
        __syncwarp();
        if ((threadIdx.x & 31) == 0) mbar_arrive(bar + 8 * GB_XN);
        wait_eq2(&g_f.rload[(threadIdx.x & 31) * 2], epoch, 13);
        __syncwarp();
        if ((threadIdx.x & 31) == 0) mbar_arrive(bar + 8 * GB_RL);
        finalizer(g, x, wr, out, epoch);
        if (g == 63 && (threadIdx.x & 31) == 0) GT(128 * 8 + 6);
    }
    if ((threadIdx.x & 31) != 0) return;
    if (threadIdx.x == 256 && g == 5) GT(1412);
    if (warp == 0) {
        wait_eq4(&g_f.xn[0], epoch, 13);
        const int rk = g & 1;
        const int m1 = g < 32 ? HSPLIT : 2 * NT - HSPLIT;
#pragma unroll 1
        for (int it = 0; it < m1; it++) {
            const int tile = it < NT ? it : it - NT + HSPLIT;
            if (it == HOLD) mbar_wait(bar + 8 * GB_RL, 0);
            if (it == 1) wait_eq4(&g_f.xn[4], epoch, 13);
            if (it == 2) mbar_wait(bar + 8 * GB_XN, 0);
            if (it == NT) {
                mbar_wait(bar + 8 * GB_WFREE, 0);
                load_w(sb, (g & 1) ? &maps.wv : &maps.wk, ((g - 32) >> 1) * 128, 0);
            }
#pragma unroll
            for (int k = 0; k < 4; k++) {
                if (k == 2 && it == 0) load_w(sb, (g & 1) ? &maps.wv : &maps.wk, (g >> 1) * 128, 0, 1, 2);
                mbar_wait(bar + 8 * (GB_EMPTY + k), (it & 1) ^ 1);
                mbar_expect_tx(bar + 8 * (GB_FULL + k), 16384);
                tma2d_mc(sb + slot_off(k) + rk * 8192, &maps.xn2, (k * 2 + rk) * 64, tile * 64, bar + 8 * (GB_FULL + k));
            }
        }
        mbar_wait(bar + 8 * GB_WFREE, g >= 32);
        const int u = g - 32, ks = u >> 2, ns = u & 3;
        if (g < 32) load_w(sb, &maps.wq, g * 128, 0);
        else {
#pragma unroll
            for (int kh = 0; kh < 2; kh++) {
                mbar_expect_tx(bar + 8 * (GB_W0 + kh), 65536);
#pragma unroll
                for (int nh = 0; nh < 2; nh++)
                    asm volatile("cp.async.bulk.tensor.5d.shared::cluster.global.mbarrier::complete_tx::bytes [%0], [%1, {%3, %4, %4, %4, %5}], [%2];"
                        :: "r"(sb + G_W + nh * 65536 + kh * 32768), "l"((uint64_t)&maps.wo2), "r"(bar + 8 * (GB_W0 + kh)), "r"(ns * 128 + nh * 64), "r"(0), "r"(ks * 16 + kh * 8) : "memory");
            }
        }
        if (g < 32) {
#pragma unroll 1
            for (int n = 0; n < NT * 4; n++) {
                const int slot = n & 3;
                mbar_wait(bar + 8 * (GB_EMPTY + slot), ((n >> 2) & 1) ^ 1);
                mbar_expect_tx(bar + 8 * (GB_FULL + slot), 16384);
                tma2d_mc(sb + slot_off(slot) + rk * 8192, &maps.xn2, (slot * 2 + rk) * 64, (n >> 2) * 64, bar + 8 * (GB_FULL + slot));
            }
        } else {
#pragma unroll 1
            for (int tile = 0; tile < NT; tile++) {
                wait_eq4(&g_f.o[tile][ks][0], epoch, 9);
                if (g == 40 && tile == NT - 1) GT(1437);
                if (tile == NT - 1) GT(1690 + g - 32);
#pragma unroll
                for (int k = 0; k < 4; k++) {
                    mbar_wait(bar + 8 * (GB_EMPTY + k), (tile & 1) ^ 1);
                    mbar_expect_tx(bar + 8 * (GB_FULL + k), 16384);
                    tma2d_mc(sb + slot_off(k) + rk * 8192, &maps.ox2, (ks * 8 + k * 2 + rk) * 64, tile * 64, bar + 8 * (GB_FULL + k));
                }
            }
        }
    } else if (warp < 3) {
        const int wg = warp - 1;
        const uint32_t buf = sb + G_BUF + wg * 32768;
        const CUtensorMap* tkv = (g & 1) ? &maps.vx3 : &maps.kx3;
        const int n1 = g < 32 ? HSPLIT / 2 : NT - HSPLIT / 2;
#pragma unroll 1
        for (int i = 0; i < n1; i++) {
            const int tile = (i < NT / 2 ? 2 * i : 2 * i - NT + HSPLIT) + wg, hd = (i < NT / 2 ? g : g - 32) >> 1;
            mbar_wait(bar + 8 * (GB_STG + wg), i & 1);
            tma_store3d(tkv, buf, tile * 64, hd * 2);
            asm volatile("cp.async.bulk.commit_group;" ::: "memory");
            asm volatile("cp.async.bulk.wait_group.read 0;" ::: "memory");
            mbar_arrive(bar + 8 * (GB_FREE + wg));
            asm volatile("cp.async.bulk.wait_group 0;" ::: "memory");
            PUBLISH(&g_f.kv[tile][hd][g & 1], epoch);
        }
        if (wg == 0) mbar_arrive(bar + 8 * GB_T1D);
        if (g < 32 && wg == 1) {
            mbar_wait(bar + 8 * GB_T1D, 0);
#pragma unroll 1
            for (int tile = 0; tile < NT; tile++) {
                wait_eq2(&g_f.kv[tile][g][0], epoch, 10);
                if (tile > 0) mbar_wait(bar + 8 * GB_KVF, (tile - 1) & 1);
                mbar_expect_tx(bar + 8 * (GB_KV + (tile & 1)), 16384);
                tma3d(sb + G_BUF, &maps.kx3, tile * 64, g * 2, bar + 8 * (GB_KV + (tile & 1)));
                if (tile > 0) mbar_wait(bar + 8 * GB_VF, (tile - 1) & 1);
                mbar_expect_tx(bar + 8 * (GB_VV + (tile & 1)), 16384);
                tma3d(sb + G_BUF + 32768, &maps.vx3, tile * 64, g * 2, bar + 8 * (GB_VV + (tile & 1)));
                if (PFK && tile + PFK < NT) {
                    const uint2 v = ldg_rlx2(&g_f.kv[tile + PFK][g][0]);
                    if (v.x == epoch && v.y == epoch) { tma_pf3d(&maps.kx3, (tile + PFK) * 64, g * 2); tma_pf3d(&maps.vx3, (tile + PFK) * 64, g * 2); }
                }
            }
        } else {
#pragma unroll 1
            for (int tile = g < 32 ? 0 : wg; tile < NT; tile += g < 32 ? 1 : 2) {
                mbar_wait(bar + 8 * (GB_STG + (tile & 1)), (tile >> 1) & 1);
                mbar_arrive(bar + 8 * (GB_FREE + (tile & 1)));
                PUBLISH(g < 32 ? &g_f.o[tile][g >> 2][g & 3] : &g_f.p[tile][g - 32], epoch);
                if (g == 3 && tile == NT - 1) GT(1436);
                if (g == 3) GT(1896 + tile);
                if (g < 32 && tile == NT - 1) GT(1610 + g);
                if (g == 40 && tile == NT - 1) GT(1435);
                if (g == 40) GT(1864 + tile);
                if (g >= 32 && tile == NT - 1) GT(1650 + g - 32);
            }
        }
    }
}

struct WPtr { const bf16 *q, *k, *v, *o; };
__device__ __forceinline__ int startup(uint8_t* smem, const bf16* __restrict__ x, const Maps& maps, uint32_t& epoch, const WPtr& pw) {
    const int tid = threadIdx.x, lane = tid & 31, w = tid >> 5, cta = blockIdx.x;
    volatile uint32_t* sh = (volatile uint32_t*)(smem + SH_OFF);
    if (cta == 4 && tid == 0) GT(1399);
    epoch = (ldg_rlx(&g_epoch) + 1) & 0x00ffffffu;
    if (w < 4) {
        if (!(cta & 1)) {
            uint32_t* pp = (uint32_t*)(xpage() + ((XR3 ^ 0x3000u) ^ ((w == 1 || w == 2) ? 0x1000u : 0u) ^ ((w & 2) << 13))) + (cta >> 1) * 8;
            if (lane < 8) stg_rlx(pp + lane, 0u);
            __syncwarp();
            if (lane == 0) {
                uint32_t best = 0xffffffffu, a = 0;
#pragma unroll 1
                for (int r = 0; r < NPROBE; r++) {
                    uint32_t t0 = clk32();
                    asm volatile("atom.relaxed.gpu.global.add.u32 %0, [%1], %2;" : "=r"(a) : "l"(pp), "r"(a + 1) : "memory");
                    if (a == 0x7fffffffu) ABORT(15);
                    uint32_t t1 = clk32();
                    if (r > 0) best = min(best, t1 - t0);
                    else if (w == 0) {
                        asm volatile("red.relaxed.gpu.global.max.u32 [%0], %1;" :: "l"(&g_ticket[0]), "r"(epoch << 8) : "memory");
                        asm volatile("red.relaxed.gpu.global.max.u32 [%0], %1;" :: "l"(&g_ticket[32]), "r"(epoch << 8) : "memory");
                    }
                }
                sh[w] = best;
            }
        }
        if (!(cta & 1)) bar_sync(1, 128);
        if (cta == 4 && tid == 0) GT(1400);
        if (w == 0) {
            if (lane == 0) {
                uint32_t rp;
                if (!(cta & 1)) {
                    uint32_t a = sh[0], b = sh[1], c = sh[2], d = sh[3];
                    uint32_t mid = (min(min(a, b), min(c, d)) + max(max(a, b), max(c, d))) >> 1;
                    const int dd = (int)min(a, d) - (int)min(b, c);
                    uint32_t cls = abs(dd) > 60 ? dd > 0 : a > mid;
                    uint32_t t = atomicAdd(&g_ticket[cls * 32], 1u) & 255;
                    if (t >= (cls ? 34u : 32u)) { cls ^= 1; t = atomicAdd(&g_ticket[cls * 32], 1u) & 255; }
                    rp = min(cls ? 32 + t : t, 65u);
                    stg_rlx(&g_table[(cta >> 1) * 8], (epoch << 8) | rp);
                } else {
                    uint32_t v, n = 0;
#pragma unroll 1
                    while (((v = ldg_rlx(&g_table[(cta >> 1) * 8])) >> 8) != epoch) { if (++n > SPIN_LIMIT) { ABORT(14); break; } }
                    rp = v & 255;
                }
                const int role = rp * 2 + (cta & 1);
                sh[8] = role; sh[9] = epoch;
                while (sh[10] != epoch + 1 && cta < NWAITLN) {}
                if (role < 64) rec_first_loads(smem_u32(smem), role, maps);
                else if (role < 128) load_w(smem_u32(smem), (role & 1) ? &maps.wv : &maps.wk, ((role - 64) >> 1) * 128, 0, 0, 1);
                if (cta == 4) GT(1401);
            }
        }
    } else if (cta < 128) {
        uint4 u[2][2];
        const int row0 = cta * 16 + (w - 4) * 2;
#pragma unroll
        for (int r = 0; r < 2; r++)
#pragma unroll
            for (int j = 0; j < 2; j++) u[r][j] = *(const uint4*)(x + (size_t)(row0 + r) * DM + j * 256 + lane * 8);
        if (cta < 48) {
            const uint32_t b = cta >> 3, off = (b >= 4 ? 0x8000u + (b & 1) * 0x4000u : ((b & 1) ? 0x3000u : 0u) + ((b & 2) << 13)) ^ aslot(cta & 7);
            *(uint4*)(xpage() + off + (tid - 128) * 16) = make_uint4(0, 0, 0, 0);
        }
        float v[2][16];
#pragma unroll
        for (int r = 0; r < 2; r++)
#pragma unroll
            for (int j = 0; j < 2; j++) {
                uint32_t ww[4] = {u[r][j].x, u[r][j].y, u[r][j].z, u[r][j].w};
#pragma unroll
                for (int i = 0; i < 4; i++) { v[r][j * 8 + 2 * i] = bf_lo(ww[i]); v[r][j * 8 + 2 * i + 1] = bf_hi(ww[i]); }
            }
        ln_row2(v[0], v[1]);
#pragma unroll
        for (int r = 0; r < 2; r++)
#pragma unroll
            for (int j = 0; j < 2; j++)
                *(uint4*)(g_xn + (size_t)(row0 + r) * DM + j * 256 + lane * 8) =
                    make_uint4(pack2(v[r][j * 8], v[r][j * 8 + 1]), pack2(v[r][j * 8 + 2], v[r][j * 8 + 3]), pack2(v[r][j * 8 + 4], v[r][j * 8 + 5]), pack2(v[r][j * 8 + 6], v[r][j * 8 + 7]));
        bar_sync(2, 256);
        if (tid == 160 && cta < NWAITLN) { st_rel(&g_f.xn[cta], epoch); sh[10] = epoch + 1; }
        if (cta == 4 && tid == 160) GT(1403);
        __syncwarp();
    }
    if (cta == 4 && tid == 128) GT(1402);
    __syncthreads();
    if (tid == 160 && cta >= NWAITLN && cta < 128) st_rel(&g_f.xn[cta], epoch);
    __syncwarp();
    const int role = sh[8];
    return role;
}

__global__ void __cluster_dims__(2, 1, 1) __launch_bounds__(384, 1)
main_kernel(const __grid_constant__ Maps maps, const bf16* __restrict__ x, const bf16* __restrict__ mem0, const bf16* __restrict__ wr,
            const bf16* __restrict__ wd, bf16* __restrict__ out, const WPtr pw) {
    extern __shared__ __align__(1024) uint8_t smem[];
    const uint32_t sb = smem_u32(smem);
    if (threadIdx.x == 0) {
        for (int i = 0; i < MB_N; i++) mbar_init(sb + R_BAR + 8 * i, i == MB_V ? 4 : 1);
        for (int i = 0; i < GB_N; i++)
            mbar_init(sb + G_BAR + 8 * i, i == GB_WFREE || (i >= GB_EMPTY && i < GB_KV) ? 8 : (i >= GB_KVF ? 4 : (i >= GB_STG && i < GB_FREE ? 128 : 1)));
        asm volatile("fence.mbarrier_init.release.cluster;" ::: "memory");
    }
    __syncwarp();
    asm volatile("barrier.cluster.arrive.relaxed.aligned;" ::: "memory");
    if (threadIdx.x >= 352 && threadIdx.x < 352 + (int)(sizeof(Maps) / sizeof(CUtensorMap)))
        asm volatile("prefetch.tensormap [%0];" :: "l"((const CUtensorMap*)&maps + (threadIdx.x - 352)) : "memory");
    uint32_t epoch;
    asm volatile("fence.proxy.async.shared::cta;" ::: "memory");
    const int role = uni(startup(smem, x, maps, epoch, pw));
    asm volatile("barrier.cluster.wait.aligned;" ::: "memory");
    const int wg = uni(threadIdx.x >> 7);
    if (role < 64) {
#define SETREG(n) do { if ((n) < 168) asm volatile("setmaxnreg.dec.sync.aligned.u32 %0;" :: "n"(n)); if ((n) > 168) asm volatile("setmaxnreg.inc.sync.aligned.u32 %0;" :: "n"(n)); } while (0)
#define RESREG(n) do { if ((n) < 168) asm volatile("setmaxnreg.inc.sync.aligned.u32 168;"); if ((n) > 168) asm volatile("setmaxnreg.dec.sync.aligned.u32 168;"); } while (0)
        if (wg == WGA) {
            SETREG(RGA);
            rec_a(sb, role, mem0, epoch);
            RESREG(RGA);
        } else if (wg == WGB) {
            SETREG(RGB);
            rec_b(sb, role, epoch);
            RESREG(RGB);
        } else {
            SETREG(RGC);
            rec_c(sb, role, mem0, maps, epoch);
            RESREG(RGC);
        }
        ffn_phase(maps, wd, out);
        if (threadIdx.x == 0) GT(((volatile int*)(smem + SH_OFF))[8] * 8 + 6);
    } else if (role < 128) {
        if (wg < 2) {
            asm volatile("setmaxnreg.inc.sync.aligned.u32 192;");
            g_consumer(sb, role - 64, wg, epoch);
            if (threadIdx.x == 128) GT(role * 8 + 6);
        } else {
            asm volatile("setmaxnreg.dec.sync.aligned.u32 120;");
            g_producer(sb, role - 64, maps, epoch, x, wr, out);
        }
    } else {
        finalizer(64 + (threadIdx.x >> 5) * 4 + role - 128, x, wr, out, epoch);
    }
}

typedef CUresult (*EncodeFn)(CUtensorMap*, CUtensorMapDataType, cuuint32_t, void*, const cuuint64_t*, const cuuint64_t*, const cuuint32_t*, const cuuint32_t*,
                             CUtensorMapInterleave, CUtensorMapSwizzle, CUtensorMapL2promotion, CUtensorMapFloatOOBfill);
static void make_map3(EncodeFn fn, CUtensorMap* m, const void* ptr, uint64_t cols, uint64_t rows) {
    cuuint64_t dims[3] = {64, rows, cols / 64};
    cuuint64_t strides[2] = {cols * 2, 128};
    cuuint32_t box[3] = {64, 64, 2};
    cuuint32_t es[3] = {1, 1, 1};
    fn(m, CU_TENSOR_MAP_DATA_TYPE_BFLOAT16, 3, (void*)ptr, dims, strides, box, es, CU_TENSOR_MAP_INTERLEAVE_NONE, CU_TENSOR_MAP_SWIZZLE_128B,
       CU_TENSOR_MAP_L2_PROMOTION_L2_256B, CU_TENSOR_MAP_FLOAT_OOB_FILL_NONE);
}
static void make_map(EncodeFn fn, CUtensorMap* m, const void* ptr, uint64_t cols, uint64_t rows, uint32_t bcols, uint32_t brows,
                     bool f32 = false, CUtensorMapSwizzle sw = CU_TENSOR_MAP_SWIZZLE_128B) {
    cuuint64_t dims[2] = {cols, rows};
    cuuint64_t strides[1] = {cols * (f32 ? 4 : 2)};
    cuuint32_t box[2] = {bcols, brows};
    cuuint32_t es[2] = {1, 1};
    fn(m, f32 ? CU_TENSOR_MAP_DATA_TYPE_FLOAT32 : CU_TENSOR_MAP_DATA_TYPE_BFLOAT16, 2, (void*)ptr, dims, strides, box, es, CU_TENSOR_MAP_INTERLEAVE_NONE, sw,
       CU_TENSOR_MAP_L2_PROMOTION_L2_256B, CU_TENSOR_MAP_FLOAT_OOB_FILL_NONE);
}

extern "C" void kernel_launch(void* const* d_in, const int* in_sizes, int n_in, void* d_out, int out_size) {
    const bf16* x = (const bf16*)d_in[0];
    const bf16* mem0 = (const bf16*)d_in[1];
    const bf16* Wq = (const bf16*)d_in[2];
    const bf16* Wk = (const bf16*)d_in[3];
    const bf16* Wv = (const bf16*)d_in[4];
    const bf16* Wo = (const bf16*)d_in[5];
    const bf16* wr = (const bf16*)d_in[8];
    const bf16* wg = (const bf16*)d_in[9];
    const bf16* wu = (const bf16*)d_in[10];
    const bf16* wd = (const bf16*)d_in[11];
    bf16* out = (bf16*)d_out;

    static EncodeFn enc = nullptr;
    static void *pxn, *pK, *pV, *pO, *pacc;
    if (!enc) {
        cudaDriverEntryPointQueryResult qr;
        void* fn = nullptr;
        cudaGetDriverEntryPoint("cuTensorMapEncodeTiled", &fn, cudaEnableDefault, &qr);
        enc = (EncodeFn)fn;
        cudaGetSymbolAddress(&pxn, g_xn); cudaGetSymbolAddress(&pK, g_K); cudaGetSymbolAddress(&pV, g_V);
        cudaGetSymbolAddress(&pO, g_O); cudaGetSymbolAddress(&pacc, g_P);
        cudaFuncSetAttribute(main_kernel, cudaFuncAttributeMaxDynamicSharedMemorySize, SMEM_TOTAL);
    }
    Maps m;
    make_map(enc, &m.wq, Wq, HD, DM, 64, 256);
    make_map(enc, &m.wk, Wk, HD, DM, 64, 256);
    make_map(enc, &m.wv, Wv, HD, DM, 64, 256);
    make_map(enc, &m.wo, Wo, DM, HD, 64, 128);
    {
        cuuint64_t dims[5] = {DM, 2, 4, 4, HD / 32};
        cuuint64_t strides[4] = {DM * 2, 8 * DM * 2, 2 * DM * 2, 32 * DM * 2};
        cuuint32_t box[5] = {64, 2, 4, 4, 8};
        cuuint32_t es[5] = {1, 1, 1, 1, 1};
        enc(&m.wo2, CU_TENSOR_MAP_DATA_TYPE_BFLOAT16, 5, (void*)Wo, dims, strides, box, es, CU_TENSOR_MAP_INTERLEAVE_NONE, CU_TENSOR_MAP_SWIZZLE_128B,
            CU_TENSOR_MAP_L2_PROMOTION_L2_256B, CU_TENSOR_MAP_FLOAT_OOB_FILL_NONE);
    }
    make_map(enc, &m.kx, pK, HD, SQ, 64, 64);
    make_map(enc, &m.ox2, pO, HD, SQ, 64, 64);
    make_map(enc, &m.xn2, pxn, DM, SQ, 64, 64);
    make_map3(enc, &m.kx3, pK, HD, SQ); make_map3(enc, &m.vx3, pV, HD, SQ);
    make_map(enc, &m.wg, wg, FF, DM, 32, 256, false, CU_TENSOR_MAP_SWIZZLE_NONE);
    make_map(enc, &m.wu, wu, FF, DM, 32, 256, false, CU_TENSOR_MAP_SWIZZLE_NONE);

    cudaStream_t st = cudaStreamPerThread;
    main_kernel<<<NCTA, 384, SMEM_TOTAL, st>>>(m, x, mem0, wr, wd, out, WPtr{Wq, Wk, Wv, Wo});
}
```

```cpp
#include <cuda_runtime.h>
#include <cuda_bf16.h>
#include <cuda.h>
#include <stdint.h>
#include <stddef.h>

typedef __nv_bfloat16 bf16;

constexpr int SQ = 2048, DM = 512, NH = 32, DH = 128, NSEG = 64, HD = 4096, FF = 1792;

constexpr int NT = 32;
#define SPEC_TILES 30
__device__ __align__(1024) bf16 g_xn[SQ * DM];
__device__ __align__(1024) bf16 g_K[SQ * HD];
__device__ __align__(1024) bf16 g_V[SQ * HD];
__device__ __align__(1024) bf16 g_O[SQ * HD];
__device__ __align__(1024) uint32_t g_KVf[NSEG][NH][1024];
__device__ __align__(1024) bf16 g_P[8 * SQ * DM];
__device__ __align__(1024) bf16 g_h[SQ * DM];
__device__ __align__(1024) bf16 g_hn[SQ * DM];
__device__ uint8_t g_xraw[12 << 20];
#define XPG 0
__device__ __forceinline__ uint64_t xpage() { return (((uint64_t)g_xraw + (2 << 20) - 1) & ~(uint64_t)((2 << 20) - 1)) + ((uint64_t)XPG << 21); }
constexpr uint32_t XR3 = (1u << 20) | (1u << 19) | (1u << 12);
__device__ __forceinline__ uint32_t aslot(uint32_t s) { return ((s & 1) << 18) | ((s & 2) << 19) | ((s & 4) * 0xc000u); }
__device__ __forceinline__ uint32_t acc_base(uint32_t W) { return ((W & 2) ? 0x3000u : 0u) + ((W & 4) << 12) + (W & 1) * 2048; }
__device__ __forceinline__ uint32_t ext_base(uint32_t W) { return 0x8000u + ((W & 4) << 12) + (W & 3) * 1024; }
#define XHS 256
#define XSS 32
__device__ __forceinline__ uint32_t zero_off(uint32_t c, uint32_t ln) {
    return ln < 8 ? acc_base(c >> 3) + (c & 7) * 256 + ln * 16 : ext_base(c >> 3) + ((c >> 2) & 1) * XHS + ((c >> 1) & 1) * XSS + (c & 1) * 16;
}
struct Flags {
    uint32_t kv[NT][NH][2];
    uint32_t o[NT][8][32];
    uint32_t rec[64];
    uint32_t xn[128];
    uint32_t rload[64];
    uint32_t p[NT][32];
    uint32_t rows[2][128];
    uint4 cand[2][128];
    uint4 norm[64];
};
__device__ __align__(1024) Flags g_f;
__device__ __align__(1024) uint4 g_yp[2][FF / 32][DM];
__device__ __align__(1024) uint32_t g_table[66 * 8];
__device__ __align__(256) uint32_t g_ticket[64];
__device__ uint32_t g_epoch;
#define HOLD 6
#define HSPLIT 24
#define EREL 0
#define PFK 2
#define PFO 0
#define PFS 0
#define NWAITLN 8
#define WGA 0
#define WGB 1
#define WGC (3 - WGA - WGB)
#define NPROBE 3
constexpr int NCTA = 132;
constexpr int NFW = 112;
__device__ uint32_t g_abort;
__device__ long long g_dbg[4096];
#define TR(slot, v)

__device__ __forceinline__ uint32_t smem_u32(const void* p) { return (uint32_t)__cvta_generic_to_shared(p); }
__device__ __forceinline__ void mbar_init(uint32_t a, uint32_t c) { asm volatile("mbarrier.init.shared::cta.b64 [%0], %1;" :: "r"(a), "r"(c) : "memory"); }
__device__ __forceinline__ void mbar_expect_tx(uint32_t a, uint32_t tx) { asm volatile("mbarrier.arrive.expect_tx.shared::cta.b64 _, [%0], %1;" :: "r"(a), "r"(tx) : "memory"); }
__device__ __forceinline__ void mbar_arrive(uint32_t a) { asm volatile("mbarrier.arrive.shared::cta.b64 _, [%0];" :: "r"(a) : "memory"); }
__device__ __forceinline__ void mbar_arrive_if(uint32_t a, uint32_t pred) {
    asm volatile("{\n.reg .pred p;\nsetp.ne.u32 p, %1, 0;\n@p mbarrier.arrive.shared::cta.b64 _, [%0];\n}" :: "r"(a), "r"(pred) : "memory");
}
__device__ __forceinline__ bool mbar_try(uint32_t a, uint32_t ph) {
    uint32_t ok;
    asm volatile("{\n.reg .pred p;\nmbarrier.try_wait.parity.shared::cta.b64 p, [%1], %2;\nselp.u32 %0, 1, 0, p;\n}" : "=r"(ok) : "r"(a), "r"(ph) : "memory");
    return ok != 0;
}
#define SPINLOG 20
constexpr uint32_t SPIN_LIMIT = 1u << SPINLOG;
#define ABORT(code_) atomicCAS(&g_abort, 0u, (code_))
__device__ __forceinline__ void mbar_wait(uint32_t a, uint32_t ph) {
    uint32_t n = 0;
#pragma unroll 1
    while (!mbar_try(a, ph)) { if (++n > SPIN_LIMIT) { ABORT(1); break; } }
}
__device__ __forceinline__ void bar_sync(int id, int n) { asm volatile("bar.sync %0, %1;" :: "r"(id), "r"(n) : "memory"); }
__device__ __forceinline__ void bar_arrive(int id, int n) { asm volatile("bar.arrive %0, %1;" :: "r"(id), "r"(n) : "memory"); }

__device__ __forceinline__ void ldsm4(uint32_t* r, uint32_t a) {
    asm volatile("ldmatrix.sync.aligned.m8n8.x4.shared.b16 {%0,%1,%2,%3}, [%4];" : "=r"(r[0]), "=r"(r[1]), "=r"(r[2]), "=r"(r[3]) : "r"(a) : "memory");
}
__device__ __forceinline__ void ldsm4t(uint32_t* r, uint32_t a) {
    asm volatile("ldmatrix.sync.aligned.m8n8.x4.trans.shared.b16 {%0,%1,%2,%3}, [%4];" : "=r"(r[0]), "=r"(r[1]), "=r"(r[2]), "=r"(r[3]) : "r"(a) : "memory");
}
__device__ __forceinline__ void stsm4t(uint32_t a, uint32_t r0, uint32_t r1, uint32_t r2, uint32_t r3) {
    asm volatile("stmatrix.sync.aligned.m8n8.x4.trans.shared.b16 [%0], {%1,%2,%3,%4};" :: "r"(a), "r"(r0), "r"(r1), "r"(r2), "r"(r3) : "memory");
}
__device__ __forceinline__ void stsm4(uint32_t a, uint32_t r0, uint32_t r1, uint32_t r2, uint32_t r3) {
    asm volatile("stmatrix.sync.aligned.m8n8.x4.shared.b16 [%0], {%1,%2,%3,%4};" :: "r"(a), "r"(r0), "r"(r1), "r"(r2), "r"(r3) : "memory");
}
__device__ __forceinline__ uint32_t movm(uint32_t a) { uint32_t d; asm volatile("movmatrix.sync.aligned.m8n8.trans.b16 %0, %1;" : "=r"(d) : "r"(a)); return d; }
__device__ __forceinline__ void mma16816(float* d, uint32_t a0, uint32_t a1, uint32_t a2, uint32_t a3, uint32_t b0, uint32_t b1) {
    asm volatile("mma.sync.aligned.m16n8k16.row.col.f32.bf16.bf16.f32 {%0,%1,%2,%3}, {%4,%5,%6,%7}, {%8,%9}, {%0,%1,%2,%3};"
        : "+f"(d[0]), "+f"(d[1]), "+f"(d[2]), "+f"(d[3]) : "r"(a0), "r"(a1), "r"(a2), "r"(a3), "r"(b0), "r"(b1));
}
__device__ __forceinline__ void mma1688(float* d, uint32_t a0, uint32_t a1, uint32_t b0) {
    asm volatile("mma.sync.aligned.m16n8k8.row.col.f32.bf16.bf16.f32 {%0,%1,%2,%3}, {%4,%5}, {%6}, {%0,%1,%2,%3};"
        : "+f"(d[0]), "+f"(d[1]), "+f"(d[2]), "+f"(d[3]) : "r"(a0), "r"(a1), "r"(b0));
}
__device__ __forceinline__ uint32_t pack2(float a, float b) { uint32_t d; asm("cvt.rn.bf16x2.f32 %0, %1, %2;" : "=r"(d) : "f"(b), "f"(a)); return d; }
__device__ __forceinline__ float bf_lo(uint32_t w) { return __uint_as_float(w << 16); }
__device__ __forceinline__ float bf_hi(uint32_t w) { return __uint_as_float(w & 0xffff0000u); }
__device__ __forceinline__ float rbf(float x) { return __bfloat162float(__float2bfloat16_rn(x)); }

__device__ __forceinline__ void sts128(uint32_t a, float x, float y, float z, float w) { asm volatile("st.shared.v4.f32 [%0], {%1,%2,%3,%4};" :: "r"(a), "f"(x), "f"(y), "f"(z), "f"(w) : "memory"); }
__device__ __forceinline__ void sts128u(uint32_t a, uint32_t x, uint32_t y, uint32_t z, uint32_t w) { asm volatile("st.shared.v4.b32 [%0], {%1,%2,%3,%4};" :: "r"(a), "r"(x), "r"(y), "r"(z), "r"(w) : "memory"); }
__device__ __forceinline__ void sts64(uint32_t a, float x, float y) { asm volatile("st.shared.v2.f32 [%0], {%1,%2};" :: "r"(a), "f"(x), "f"(y) : "memory"); }
__device__ __forceinline__ float4 lds128(uint32_t a) { float4 v; asm volatile("ld.shared.v4.f32 {%0,%1,%2,%3}, [%4];" : "=f"(v.x), "=f"(v.y), "=f"(v.z), "=f"(v.w) : "r"(a) : "memory"); return v; }
__device__ __forceinline__ float2 lds64(uint32_t a) { float2 v; asm volatile("ld.shared.v2.f32 {%0,%1}, [%2];" : "=f"(v.x), "=f"(v.y) : "r"(a) : "memory"); return v; }
__device__ __forceinline__ uint2 lds64u(uint32_t a) { uint2 v; asm volatile("ld.shared.v2.b32 {%0,%1}, [%2];" : "=r"(v.x), "=r"(v.y) : "r"(a) : "memory"); return v; }
__device__ __forceinline__ float4 lds128v(uint32_t a) { float4 v; asm volatile("ld.volatile.shared.v4.f32 {%0,%1,%2,%3}, [%4];" : "=f"(v.x), "=f"(v.y), "=f"(v.z), "=f"(v.w) : "r"(a) : "memory"); return v; }
__device__ __forceinline__ float2 lds64v(uint32_t a) { float2 v; asm volatile("ld.volatile.shared.v2.f32 {%0,%1}, [%2];" : "=f"(v.x), "=f"(v.y) : "r"(a) : "memory"); return v; }
__device__ __forceinline__ uint4 lds128uv(uint32_t a) { uint4 v; asm volatile("ld.volatile.shared.v4.b32 {%0,%1,%2,%3}, [%4];" : "=r"(v.x), "=r"(v.y), "=r"(v.z), "=r"(v.w) : "r"(a) : "memory"); return v; }
__device__ __forceinline__ void st_async4(uint32_t a, float x, float y, float z, float w, uint32_t mb) {
    asm volatile("st.async.weak.shared::cluster.mbarrier::complete_tx::bytes.v4.f32 [%0], {%1,%2,%3,%4}, [%5];" :: "r"(a), "f"(x), "f"(y), "f"(z), "f"(w), "r"(mb) : "memory");
}
__device__ __forceinline__ void st_async2(uint32_t a, uint32_t x, uint32_t y, uint32_t mb) {
    asm volatile("st.async.weak.shared::cluster.mbarrier::complete_tx::bytes.v2.b32 [%0], {%1,%2}, [%3];" :: "r"(a), "r"(x), "r"(y), "r"(mb) : "memory");
}
__device__ __forceinline__ uint32_t ldg_rlx(const uint32_t* p) { uint32_t v; asm volatile("ld.relaxed.gpu.global.b32 %0, [%1];" : "=r"(v) : "l"(p) : "memory"); return v; }
__device__ __forceinline__ uint4 ldg_rlx4(const uint32_t* p) { uint4 v; asm volatile("ld.relaxed.gpu.global.v4.b32 {%0,%1,%2,%3}, [%4];" : "=r"(v.x), "=r"(v.y), "=r"(v.z), "=r"(v.w) : "l"(p) : "memory"); return v; }
__device__ __forceinline__ uint4 ldg_rlx4_if(const uint32_t* p, bool c) {
    uint4 v;
    asm volatile("{\n.reg .pred p;\nsetp.ne.u32 p, %5, 0;\nmov.b32 %0, 0;\nmov.b32 %1, 0;\nmov.b32 %2, 0;\nmov.b32 %3, 0;\n@p ld.relaxed.gpu.global.v4.b32 {%0,%1,%2,%3}, [%4];\n}"
                 : "=r"(v.x), "=r"(v.y), "=r"(v.z), "=r"(v.w) : "l"(p), "r"((uint32_t)c) : "memory");
    return v;
}
__device__ __forceinline__ void stg_rlx(uint32_t* p, uint32_t v) { asm volatile("st.relaxed.gpu.global.b32 [%0], %1;" :: "l"(p), "r"(v) : "memory"); }
__device__ __forceinline__ void tma2d(uint32_t dst, const CUtensorMap* tm, int c0, int c1, uint32_t mb) {
    asm volatile("cp.async.bulk.tensor.2d.shared::cluster.global.mbarrier::complete_tx::bytes [%0], [%1, {%3, %4}], [%2];"
        :: "r"(dst), "l"((uint64_t)tm), "r"(mb), "r"(c0), "r"(c1) : "memory");
}

__device__ __forceinline__ void tma3d(uint32_t dst, const CUtensorMap* tm, int row, int chunk, uint32_t mb) {
    asm volatile("cp.async.bulk.tensor.3d.shared::cluster.global.mbarrier::complete_tx::bytes [%0], [%1, {%3, %4, %5}], [%2];"
        :: "r"(dst), "l"((uint64_t)tm), "r"(mb), "r"(0), "r"(row), "r"(chunk) : "memory");
}
#define EF 0xff
__device__ __forceinline__ uint64_t pol_ef(int bit) {
    uint64_t p;
    if ((EF >> bit) & 1) asm("createpolicy.fractional.L2::evict_first.b64 %0, 1.0;" : "=l"(p));
    else asm("createpolicy.fractional.L2::evict_normal.b64 %0, 1.0;" : "=l"(p));
    return p;
}
__device__ __forceinline__ void tma3d_h(uint32_t dst, const CUtensorMap* tm, int row, int chunk, uint32_t mb, uint64_t pol) {
    asm volatile("cp.async.bulk.tensor.3d.shared::cluster.global.mbarrier::complete_tx::bytes.L2::cache_hint [%0], [%1, {%3, %4, %5}], [%2], %6;"
        :: "r"(dst), "l"((uint64_t)tm), "r"(mb), "r"(0), "r"(row), "r"(chunk), "l"(pol) : "memory");
}
__device__ __forceinline__ void tma2d_h(uint32_t dst, const CUtensorMap* tm, int c0, int c1, uint32_t mb, uint64_t pol) {
    asm volatile("cp.async.bulk.tensor.2d.shared::cluster.global.mbarrier::complete_tx::bytes.L2::cache_hint [%0], [%1, {%3, %4}], [%2], %5;"
        :: "r"(dst), "l"((uint64_t)tm), "r"(mb), "r"(c0), "r"(c1), "l"(pol) : "memory");
}
__device__ __forceinline__ void tma2d_mc_h(uint32_t dst, const CUtensorMap* tm, int c0, int c1, uint32_t mb, uint64_t pol) {
    asm volatile("cp.async.bulk.tensor.2d.shared::cluster.global.mbarrier::complete_tx::bytes.multicast::cluster.L2::cache_hint [%0], [%1, {%3, %4}], [%2], %5, %6;"
        :: "r"(dst), "l"((uint64_t)tm), "r"(mb), "r"(c0), "r"(c1), "h"((uint16_t)3), "l"(pol) : "memory");
}
__device__ __forceinline__ uint4 ldg4_h(const void* p, uint64_t pol) {
    uint4 v;
    asm volatile("ld.relaxed.gpu.global.L2::cache_hint.v4.b32 {%0,%1,%2,%3}, [%4], %5;" : "=r"(v.x), "=r"(v.y), "=r"(v.z), "=r"(v.w) : "l"(p), "l"(pol) : "memory");
    return v;
}
__device__ __forceinline__ void stg4_h(void* p, uint4 v, uint64_t pol) {
    asm volatile("st.relaxed.gpu.global.L2::cache_hint.v4.b32 [%0], {%1,%2,%3,%4}, %5;" :: "l"(p), "r"(v.x), "r"(v.y), "r"(v.z), "r"(v.w), "l"(pol) : "memory");
}
__device__ __forceinline__ void tma2d_mc(uint32_t dst, const CUtensorMap* tm, int c0, int c1, uint32_t mb) {
    asm volatile("cp.async.bulk.tensor.2d.shared::cluster.global.mbarrier::complete_tx::bytes.multicast::cluster [%0], [%1, {%3, %4}], [%2], %5;"
        :: "r"(dst), "l"((uint64_t)tm), "r"(mb), "r"(c0), "r"(c1), "h"((uint16_t)3) : "memory");
}
__device__ __forceinline__ void mbar_arrive2_if(uint32_t a, uint32_t pred) {
    asm volatile("{\n.reg .pred p;\nsetp.ne.u32 p, %1, 0;\n@p mbarrier.arrive.shared::cta.b64 _, [%0];\n@p mbarrier.arrive.shared::cluster.b64 _, [%2];\n}"
                 :: "r"(a), "r"(pred), "r"(a ^ 0x01000000u) : "memory");
}
__device__ __forceinline__ void tma_pf3d(const CUtensorMap* tm, int row, int chunk) {
    asm volatile("cp.async.bulk.prefetch.tensor.3d.L2.global.tile [%0, {%1, %2, %3}];" :: "l"((uint64_t)tm), "r"(0), "r"(row), "r"(chunk) : "memory");
}
__device__ __forceinline__ void tma_pf2d(const CUtensorMap* tm, int c0, int c1) {
    asm volatile("cp.async.bulk.prefetch.tensor.2d.L2.global.tile [%0, {%1, %2}];" :: "l"((uint64_t)tm), "r"(c0), "r"(c1) : "memory");
}
__device__ __forceinline__ void tma_store3d(const CUtensorMap* tm, uint32_t src, int row, int chunk) {
    asm volatile("cp.async.bulk.tensor.3d.global.shared::cta.bulk_group [%0, {%2, %3, %4}], [%1];" :: "l"((uint64_t)tm), "r"(src), "r"(0), "r"(row), "r"(chunk) : "memory");
}
__device__ __forceinline__ void bulk_store(void* dst, uint32_t src, uint32_t bytes) {
    asm volatile("cp.async.bulk.global.shared::cta.bulk_group [%0], [%1], %2;" :: "l"(dst), "r"(src), "r"(bytes) : "memory");
}
#define GT(slot)
#define CNT(k)
#define CNT2(k, c)
#define TS(i, dep)
#define TSACC()
#define TSDECL
struct Maps { CUtensorMap wq, wk, wv, wo, wo2, kx, ox2, kx3, vx3, xn2, wg, wu; };
typedef Maps RecMaps;
__device__ __forceinline__ void st_rel(uint32_t* p, uint32_t v) { asm volatile("st.release.gpu.global.u32 [%0], %1;" :: "l"(p), "r"(v) : "memory"); }
#define PUBLISH(p, v) st_rel(p, v)
__device__ __forceinline__ uint2 ldg_rlx2(const uint32_t* p) { uint2 v; asm volatile("ld.relaxed.gpu.global.v2.b32 {%0,%1}, [%2];" : "=r"(v.x), "=r"(v.y) : "l"(p) : "memory"); return v; }
__device__ __forceinline__ void wait_eq2(const uint32_t* p, uint32_t e, int code) {
    uint32_t n = 0;
#pragma unroll 1
    while (true) { uint2 v = ldg_rlx2(p); if (v.x == e && v.y == e) break; __nanosleep(64); if (++n > SPIN_LIMIT) { ABORT(code); break; } }
}
__device__ __forceinline__ void wait_eq4(const uint32_t* p, uint32_t e, int code) {
    uint32_t n = 0;
#pragma unroll 1
    while (true) { uint4 v = ldg_rlx4(p); if (v.x == e && v.y == e && v.z == e && v.w == e) break; __nanosleep(64); if (++n > SPIN_LIMIT) { ABORT(code); break; } }
}
__device__ __forceinline__ void wait_rec(const uint32_t* p, uint32_t e, uint32_t steps) {
    uint32_t n = 0;
#pragma unroll 1
    while (true) {
        uint2 v = ldg_rlx2(p);
        if (__all_sync(0xffffffffu, (v.x >> 8) == e && (v.y >> 8) == e && (v.x & 255) >= steps && (v.y & 255) >= steps)) break;
        __nanosleep(64); if (++n > SPIN_LIMIT) { ABORT(8); break; }
    }
}

constexpr int R_QK1 = 0;
constexpr int R_WO = 65536;
constexpr int R_T = 131072;
constexpr int R_SLOT1 = R_T;
constexpr int R_MEMB = R_T + 24576;
constexpr int R_QP = R_MEMB + 8192;
constexpr int R_VRED = R_QP + 4096;
constexpr int R_STG = R_VRED + 2048;
constexpr int R_AX = R_STG + 2048;
constexpr int R_SLOT0 = 196608;
constexpr int R_SLOC = R_SLOT0 + 24576;
constexpr int R_SREM = R_SLOC + 1536;
constexpr int R_VB = R_SREM + 1536;
constexpr int R_MISC = R_VB + 2048;
constexpr int R_LT = R_MISC + 128;
constexpr int R_BAR = 229888;
constexpr int R_TS = 229888 + 128;
static_assert(R_AX + 24576 <= R_SLOT0 && R_LT + 2560 <= 229376, "smem map");
enum { MB_W0 = 0, MB_W1, MB_WV, MB_WO, MB_S, MB_FULL0, MB_FULL1, MB_V, MB_N };

__device__ __forceinline__ float ex2(float x) { float y; asm("ex2.approx.ftz.f32 %0, %1;" : "=f"(y) : "f"(x)); return y; }
__device__ __forceinline__ float rcpf(float x) { float y; asm("rcp.approx.ftz.f32 %0, %1;" : "=f"(y) : "f"(x)); return y; }
__device__ __forceinline__ void mma16816z(float* d, uint32_t a0, uint32_t a1, uint32_t a2, uint32_t a3, uint32_t b0, uint32_t b1) {
    asm volatile("mma.sync.aligned.m16n8k16.row.col.f32.bf16.bf16.f32 {%0,%1,%2,%3}, {%4,%5,%6,%7}, {%8,%9}, {%10,%10,%10,%10};"
        : "=f"(d[0]), "=f"(d[1]), "=f"(d[2]), "=f"(d[3]) : "r"(a0), "r"(a1), "r"(a2), "r"(a3), "r"(b0), "r"(b1), "f"(0.f));
}
__device__ __forceinline__ void mma1688hz(float* d, uint32_t a0, uint32_t a1, uint32_t b0) {
    asm volatile("mma.sync.aligned.m16n8k8.row.col.f32.f16.f16.f32 {%0,%1,%2,%3}, {%4,%5}, {%6}, {%7,%7,%7,%7};"
        : "=f"(d[0]), "=f"(d[1]), "=f"(d[2]), "=f"(d[3]) : "r"(a0), "r"(a1), "r"(b0), "f"(0.f));
}
#define MMA(d, a, b0, b1) mma16816(d, a[0], a[1], a[2], a[3], b0, b1)
#define MMAZ(d, a, b0, b1) mma16816z(d, a[0], a[1], a[2], a[3], b0, b1)
#define MMAF(first, d, a, b0, b1) do { if (first) MMAZ(d, a, b0, b1); else MMA(d, a, b0, b1); } while (0)

__device__ __forceinline__ uint32_t uni(uint32_t x) { return __reduce_max_sync(0xffffffffu, x); }
__device__ __forceinline__ void mbar_wait_u(uint32_t a, uint32_t ph) {
    uint32_t n = 0;
#pragma unroll 1
    while (!__all_sync(0xffffffffu, mbar_try(a, ph))) { if (++n > SPIN_LIMIT) { ABORT(1); break; } }
}
__device__ __forceinline__ void mbar_wait_p(uint32_t a, uint32_t ph) {
    asm volatile("{\n.reg .pred p, q;\n.reg .u32 n;\nmov.u32 n, 0;\nWL: mbarrier.try_wait.parity.shared::cta.b64 p, [%0], %1;\nadd.u32 n, n, 1;\n"
                 "setp.lt.and.u32 q, n, %2, !p;\n@q bra.uni WL;\n}" :: "r"(a), "r"(ph), "n"(SPIN_LIMIT) : "memory");
}
__device__ __forceinline__ uint32_t mbar_test(uint32_t a, uint32_t ph) {
    uint32_t ok;
    asm volatile("{\n.reg .pred p;\nmbarrier.test_wait.parity.shared::cta.b64 p, [%1], %2;\nselp.u32 %0, 1, 0, p;\n}" : "=r"(ok) : "r"(a), "r"(ph) : "memory");
    return ok;
}
__device__ __forceinline__ uint32_t opaque(uint32_t x) { return __shfl_sync(0xffffffffu, x, threadIdx.x & 31); }
__device__ __forceinline__ const uint32_t* mkptr(uint32_t lo, uint32_t hi) { uint64_t r; asm("mov.b64 %0, {%1, %2};" : "=l"(r) : "r"(lo), "r"(hi)); return (const uint32_t*)r; }
__device__ __forceinline__ uint32_t prmt(uint32_t a, uint32_t b, uint32_t s) { uint32_t d; asm("prmt.b32 %0, %1, %2, %3;" : "=r"(d) : "r"(a), "r"(b), "r"(s)); return d; }
__device__ __forceinline__ uint32_t packh2(float a, float b) { uint32_t d; asm("cvt.rn.f16x2.f32 %0, %1, %2;" : "=r"(d) : "f"(b), "f"(a)); return d; }
__device__ __forceinline__ uint32_t hadd2b(uint32_t a, uint32_t b) { uint32_t d; asm("add.rn.bf16x2 %0, %1, %2;" : "=r"(d) : "r"(a), "r"(b)); return d; }
__device__ __forceinline__ uint32_t hmul2b(uint32_t a, uint32_t b) { uint32_t d; asm("mul.rn.bf16x2 %0, %1, %2;" : "=r"(d) : "r"(a), "r"(b)); return d; }
__device__ __forceinline__ uint32_t amax2b(uint32_t a, uint32_t b) { uint32_t d; asm("max.xorsign.abs.bf16x2 %0, %1, %2;" : "=r"(d) : "r"(a), "r"(b)); return d; }
__device__ __forceinline__ uint32_t amax2h(uint32_t a, uint32_t b) { uint32_t d; asm("max.xorsign.abs.f16x2 %0, %1, %2;" : "=r"(d) : "r"(a), "r"(b)); return d; }
__device__ __forceinline__ void sts32(uint32_t a, uint32_t x) { asm volatile("st.shared.b32 [%0], %1;" :: "r"(a), "r"(x) : "memory"); }
__device__ __forceinline__ uint32_t lds32v_(uint32_t a) { uint32_t v; asm volatile("ld.volatile.shared.b32 %0, [%1];" : "=r"(v) : "r"(a) : "memory"); return v; }
__device__ __forceinline__ void stg4(void* p, uint4 v) { asm volatile("st.relaxed.gpu.global.v4.b32 [%0], {%1,%2,%3,%4};" :: "l"(p), "r"(v.x), "r"(v.y), "r"(v.z), "r"(v.w) : "memory"); }
__device__ __forceinline__ void lds_frag(uint32_t* r, uint32_t a) {
    asm volatile("ld.shared.v4.b32 {%0,%1,%2,%3}, [%4];" : "=r"(r[0]), "=r"(r[1]), "=r"(r[2]), "=r"(r[3]) : "r"(a) : "memory");
}
__device__ __forceinline__ void lds_fragv(uint32_t* r, uint32_t a) {
    asm volatile("ld.volatile.shared.v4.b32 {%0,%1,%2,%3}, [%4];" : "=r"(r[0]), "=r"(r[1]), "=r"(r[2]), "=r"(r[3]) : "r"(a) : "memory");
}
__device__ __forceinline__ uint32_t xorv(uint32_t a, uint32_t b) { uint32_t d; asm volatile("xor.b32 %0, %1, %2;" : "=r"(d) : "r"(a), "r"(b)); return d; }
#define SCHED(k) asm volatile("{\n.reg .pred p;\nsetp.ne.u32 p, %0, %1;\n@p bra.uni SD;\nSL: nanosleep.u32 64;\nbra.uni SL;\nSD:\n}" :: "r"(sbu - s), "n"(k) : "memory")
#define PINM() asm volatile("{\n.reg .pred p;\nsetp.eq.u32 p, %0, 1;\n@p st.shared.u32 [%0], 0;\n}" :: "r"(sbu) : "memory")
__device__ __forceinline__ uint32_t or_and(uint32_t a, uint32_t b, uint32_t c) { uint32_t d; asm("lop3.b32 %0, %1, %2, %3, 0xF8;" : "=r"(d) : "r"(a), "r"(b), "r"(c)); return d; }
__device__ __forceinline__ uint32_t pack2v(float a, float b) { uint32_t d; asm volatile("cvt.rn.bf16x2.f32 %0, %1, %2;" : "=r"(d) : "f"(b), "f"(a)); return d; }
#define FU(x) __float_as_uint(x)
__device__ __forceinline__ uint32_t clk32() { uint32_t t; asm volatile("mov.u32 %0, %%clock;" : "=r"(t) :: "memory"); return t; }
__device__ __forceinline__ void spin_until(uint32_t t0, uint32_t d) {
    if (d) {
#pragma unroll 1
        while (__any_sync(0xffffffffu, clk32() - t0 < d)) {}
    }
}
constexpr int SH_OFF = 229376 + 384;
constexpr uint32_t HONE2 = 0x3c003c00u, HCNT2 = 0x50005000u;

__device__ __forceinline__ uint64_t desc_sw128(uint32_t addr, uint32_t lbo, uint32_t sbo) {
    return (uint64_t)((addr & 0x3FFFF) >> 4) | ((uint64_t)(lbo >> 4) << 16) | ((uint64_t)(sbo >> 4) << 32) | (1ull << 62);
}
#define DP 390
#define NAX 3
#define NXL 0
#define NCX 2
#define NCL 1
#define DC 0
#define FLIP 1
#define VTA 1
#define KXB 4
#define KXI 5
#define ANB 3
#define BNB 3
#define CNB 3
#define SMA 0
#define SMB 0
#define SMC 0x01
#define IVA 0
#define RGA 160
#define RGC 160
#define RGB (504 - RGA - RGC)
#define NRW 8
#define NBR 16
#define E0 0
#define E1 6
#define E2 4
#define E3 8
#define IV 2
#define DEX 0
#define G2V 0
#define G2K 2
#define VDEP 0
#define AEARLY 0
#define VTP 2
#define LORD 1
#define TRK 1
#define TW 0
#define T2N 14
#define TEARLY 1
#define DT 0
#define NB0 0
#define NB1 9
#define DB2 80
#define DITHER 0
#define DA 40
#define DB 40
#define DS 200

__device__ __forceinline__ uint32_t wrow_off(int kk, int ch) {
    const int lane = threadIdx.x & 31, r = lane & 7;
    const int row = 64 * (kk >> 2) + 32 * (r & 1) + 16 * (kk & 1) + 8 * (lane >> 4) + 4 * ((kk >> 1) & 1) + (r >> 1);
    return row * 128 + ((ch ^ (row & 7)) << 4);
}
template <int K> __device__ __forceinline__ void sched(uint32_t key) {
    asm volatile("{\n.reg .pred p;\nsetp.ne.u32 p, %0, %1;\n@p bra.uni SD;\nSL: nanosleep.u32 64;\nbra.uni SL;\nSD:\n}" :: "r"(key), "n"(K) : "memory");
}
__device__ __forceinline__ void sched_i(int i, uint32_t key) {
    if (i == -1) sched<20>(key); if (i == 0) sched<21>(key); if (i == 1) sched<22>(key); if (i == 2) sched<23>(key);
    if (i == 3) sched<24>(key); if (i == 4) sched<25>(key); if (i == 5) sched<26>(key); if (i == 6) sched<27>(key);
}
template <int NB, int SM, class F>
__device__ __forceinline__ void g1(float* q0, float* k0, uint32_t (*wq)[4], uint32_t (*wk)[4], uint32_t ga, uint32_t key, F&& hook) {
    float q1[4], k1[4];
    uint32_t b[NB][4];
#pragma unroll
    for (int i = 0; i < NB; i++) ldsm4(b[i], ga + i * 512);
    hook(-1, b[0]);
    if (SM & 1) sched_i(-1, key);
#pragma unroll
    for (int i = 0; i < 8; i++) {
        uint32_t* c = b[i % NB];
        MMAF(i == 0, q0, wq[2 * i], c[0], c[1]); MMAF(i == 0, k0, wk[2 * i], c[0], c[1]);
        MMAF(i == 0, q1, wq[2 * i + 1], c[2], c[3]); MMAF(i == 0, k1, wk[2 * i + 1], c[2], c[3]);
        const uint32_t cc_[4] = {c[0], c[1], c[2], c[3]};
        if (i + NB < 8) ldsm4(b[i % NB], ga + (i + NB) * 512);
        hook(i, cc_);
        if ((SM >> (i + 1)) & 1) sched_i(i, key);
    }
#pragma unroll
    for (int i = 0; i < 4; i++) { q0[i] += q1[i]; k0[i] += k1[i]; }
}
__device__ __forceinline__ float frag_norm2(uint32_t (*w)[4]) {
    float d0[4], d1[4];
#pragma unroll
    for (int i = 0; i < 32; i++) { MMAF(i == 0, d0, w[i], w[i][0], w[i][2]); MMAF(i == 0, d1, w[i], w[i][1], w[i][3]); }
    const int lane = threadIdx.x & 31, g = lane >> 2, t = lane & 3;
    float v = g == 2 * t ? d0[0] + d1[2] : (g == 2 * t + 1 ? d0[1] + d1[3] : 0.f);
#pragma unroll
    for (int o = 16; o; o >>= 1) v += __shfl_xor_sync(0xffffffffu, v, o);
    return v;
}
__device__ __forceinline__ void load_slot(uint32_t sb, int c, int tile, const Maps& maps) {
    const uint32_t dst = sb + ((tile & 1) ? R_SLOT1 : R_SLOT0), mb = sb + R_BAR + 8 * (MB_FULL0 + (tile & 1));
    mbar_expect_tx(mb, 24576);
    if ((EF >> 8) & 1) {
        tma2d_h(dst + 16384, &maps.kx, c * 64, tile * 64, mb, pol_ef(8));
        tma3d_h(dst, &maps.vx3, tile * 64, (c >> 1) * 2, mb, pol_ef(8));
    } else {
        tma2d(dst + 16384, &maps.kx, c * 64, tile * 64, mb);
        tma3d(dst, &maps.vx3, tile * 64, (c >> 1) * 2, mb);
    }
}
__device__ __forceinline__ uint32_t put_mem0(uint32_t sb, int W, const bf16* __restrict__ mem0) {
    const int lane = threadIdx.x & 31;
    const uint4 a = *(const uint4*)(mem0 + (lane & 7) * DM + W * 64 + (lane >> 3) * 8), b = *(const uint4*)(mem0 + (lane & 7) * DM + W * 64 + 32 + (lane >> 3) * 8);
    const uint4 m0 = make_uint4(prmt(a.x, b.x, 0x5410u), prmt(a.x, b.x, 0x7632u), prmt(a.y, b.y, 0x5410u), prmt(a.y, b.y, 0x7632u));
    const uint4 m1 = make_uint4(prmt(a.z, b.z, 0x5410u), prmt(a.z, b.z, 0x7632u), prmt(a.w, b.w, 0x5410u), prmt(a.w, b.w, 0x7632u));
    bar_sync(3, 256);
    sts128u(sb + R_MEMB + W * 1024 + lane * 16, m0.x, m0.y, m0.z, m0.w);
    sts128u(sb + R_MEMB + W * 1024 + 512 + lane * 16, m1.x, m1.y, m1.z, m1.w);
    return amax2b(amax2b(amax2b(m0.x, m0.y), amax2b(m0.z, m0.w)), amax2b(amax2b(m1.x, m1.y), amax2b(m1.z, m1.w)));
}
#define PUT_MAX(rL, W) sts32(rL + R_STG + 1024 + ((W) >> 2) * 512 + ((W) & 3) * 4, amax2b(amax2b(mx, my), mz));
__device__ __forceinline__ uint32_t h2b(uint32_t w) {
    uint32_t d;
    asm("{\n.reg .f16 l, h;\n.reg .f32 a, b;\nmov.b32 {l, h}, %1;\ncvt.f32.f16 a, l;\ncvt.f32.f16 b, h;\ncvt.rn.bf16x2.f32 %0, b, a;\n}" : "=r"(d) : "r"(w));
    return d;
}
#define GATHER1(HALF)                                                                                           \
        {                                                                                                       \
            const uint4 x0 = ldg_rlx4(pm), x1 = ldg_rlx4(pm + 256); const uint2 y = ldg_rlx2(px);                 \
            cw = (sel & 0x4000u) ? prmt(x0.w, x1.w, 0x7632u) : prmt(y.x, y.y, 0x5410u);                         \
            const uint32_t p0 = h2b(x0.x), p1 = h2b(x0.y), p2 = h2b(x0.z), p3 = h2b(prmt(x0.w, y.x, sel));      \
            stsm4t(rG + R_MEMB + HALF * 4096, p0, p1, p2, p3);                                                  \
            const uint32_t p4 = h2b(x1.x), p5 = h2b(x1.y), p6 = h2b(x1.z), p7 = h2b(prmt(x1.w, y.y, sel));      \
            stsm4t(rG + R_MEMB + HALF * 4096 + 512, p4, p5, p6, p7);                                            \
            mx = amax2b(amax2b(p0, p1), amax2b(p2, p3)); my = amax2b(p4, p5); mz = amax2b(p6, p7);              \
        }
#define GATHER(HALF, PRE, SYNC, AFTER)                                                                                      \
        {                                                                                                       \
            const uint32_t so = aslot(s);                                                                       \
            const uint32_t ua = (glo + acc_base(HALF * 4 + fo)) ^ so, ux = (glo + ext_base(HALF * 4 + fo)) ^ so; \
            uint2 lt;                                                                                           \
            lt.x = lds32v_(rL + R_LT); lt.y = lds32v_(rL + R_LT + 4);                                           \
            const uint32_t sel = 0x7610u - ((lt.x ^ (lt.x >> 2)) & 16) * 0x440u;                                \
            const uint32_t* pm = mkptr(ua + lt.x, ghi);                                                         \
            const uint32_t* px = mkptr(ux + lt.y, ghi);                                                         \
            PRE                                                                                                 \
            bar_sync(5, 384);                                                                                   \
            const uint32_t t0 = clk32();                                                                        \
            TSACC();                                                                        \
            SYNC                                                                                                \
            spin_until(t0, DP + DITHER);                                                                                 \
            \
            TS(10, 0);                                                                                          \
            uint32_t cw, nr = 0;                                                                                \
            _Pragma("unroll 1") do {                                                                            \
                GATHER1(HALF)                                                                                   \
                nr++;                                                                                           \
            } while (__any_sync(0xffffffffu, cw != HCNT2 && nr < SPIN_LIMIT));                                  \
            TS(11, cw);                                                                                         \
            AFTER                                                                                               \
            CNT2(HALF * 4 + (s & 1) * 2 + (nr > 2), nr > 1);                                                    \
            \
        }
#define GOBAR (fo == 3 ? 14 : 10 + fo)

__device__ __forceinline__ void rec_a(uint32_t sb, int c, const bf16* __restrict__ mem0, uint32_t epoch) {
    const int tid = threadIdx.x - WGA * 128, lane = tid & 31, f = tid >> 5;
    uint32_t wq[16][4], wk[16][4], mx, my = 0, mz = 0;
    const int lrow = ((lane >> 4) << 3) + (lane & 7), lsel = (lane >> 3) & 1;
    {
        mbar_wait(sb + R_BAR + 8 * MB_W0, 0);
        if (c == 7 && tid == 0) GT(1421);
#pragma unroll
        for (int kk = 0; kk < 16; kk++) { const uint32_t a = sb + R_T + wrow_off(kk, 2 * f + lsel); ldsm4t(wq[kk], a); ldsm4t(wk[kk], a + 32768); }
        __syncwarp();
        mx = put_mem0(sb, f, mem0);
    }
    const uint32_t rL = opaque(sb + lane * 16), rG = opaque(sb + lane * 16 + f * 1024);
    const uint32_t sbu = uni(sb), fo = uni(f), cc = uni(c);
    const uint64_t gx = xpage();
    const uint32_t ghi = uni((uint32_t)(gx >> 32)), glo = uni((uint32_t)gx);
#pragma unroll
    for (int i = 0; i < NAX; i++) {
        sts128u(rG + R_AX + 4096 * i, wq[i][0], wq[i][1], wq[i][2], wq[i][3]);
        sts128u(rG + R_AX + 4096 * i + 512, wk[i][0], wk[i][1], wk[i][2], wk[i][3]);
    }
    sts128u(rL + R_LT + 512 + f * 512, (sb + R_SREM + (f >= 2 ? lane * 8 + f * 256 : lane * 16 + f * 1024)) ^ 0x01000000u, (sb + R_BAR + 8 * MB_S) ^ 0x01000000u,
            sb + R_QP + (lane >> 4) * 128 + lsel * 512 + (lane & 7) * 16 + (f == 3 ? 2048 : 0), sb + R_SLOT0 + lrow * 128 + ((lsel ^ (lane & 7)) << 4));
    __syncwarp();
    if (tid == 0) GT(c * 8 + 1);
    TSDECL;
    const float cexp = 0.08838834764831845f * 1.4426950408889634f;
    float cs = cexp;
    auto step = [&](int s, bool first) -> bool {
        bar_sync(1, 128);
        float q0[4], k0[4];
        uint4 ta;
        uint32_t zr, rl2;
        g1<ANB, SMA>(q0, k0, wq, wk, rL + R_MEMB, sbu - s, [&](int i, const uint32_t* c_) {
            if (i == 0) TS(0, c_[0]);
            if (i == -1) {
#pragma unroll
                for (int n = NAX - NXL; n < NAX; n++) { lds_fragv(wq[n], rG + R_AX + 4096 * n); lds_fragv(wk[n], rG + R_AX + 4096 * n + 512); }
                ta = lds128uv(rL + R_LT + 512 + fo * 512);
                zr = ta.w & 1; rl2 = rL | zr;
            }
            if (i == IVA) { PUT_MAX(rl2, fo) bar_arrive(15, 256); bar_arrive(GOBAR, 96); }
        });
        stsm4t(rG + R_QP, pack2(q0[0], q0[1]), pack2(q0[2], q0[3]), pack2(k0[0], k0[1]), pack2(k0[2], k0[3]));
        TS(1, FU(k0[3]));
        if (first) mbar_wait_p(sbu + R_BAR + 8 * MB_FULL0, 0);
        if (fo >= 2) {
            bar_sync(3, 256);
            uint32_t kb[4], kc[4], qa[4], qc[4];
            ldsm4(kb, ta.z + 256); ldsm4(qa, ta.z);
            ldsm4(kc, ta.z + 1280); ldsm4(qc, ta.z + 1024);
            const uint32_t k0_ = hadd2b(kb[0], kb[1]), k1_ = hadd2b(kb[2], kb[3]), k2_ = hadd2b(kc[0], kc[1]), k3_ = hadd2b(kc[2], kc[3]);
            float s0[4], s2[4];
            MMAZ(s0, qa, k0_, k1_); MMAZ(s2, qc, k2_, k3_);
            const float x = ((s0[0] + s0[2]) + (s2[0] + s2[2])) * cs, y = ((s0[1] + s0[3]) + (s2[1] + s2[3])) * cs;
            st_async2(ta.x, FU(x), FU(y), ta.y);
            TS(3, FU(y));
            sts64((ta.x ^ 0x01000000u) + (R_SLOC - R_SREM), x, y);
            sts128u(rl2 + R_STG + (fo & 1) * 512, k0_, k1_, k2_, k3_);
            bar_arrive(9, 192);
        } else {
            uint32_t qa[4][4], kx[4][4];
#pragma unroll
            for (int kk = 0; kk < KXB; kk++) ldsm4(kx[kk], (ta.w ^ (kk * 32)) + (16384 + fo * 2048));
            bar_sync(3, 256);
#pragma unroll
            for (int kk = 0; kk < 4; kk++) {
                if (kk >= KXB) ldsm4(kx[kk], (ta.w ^ (kk * 32)) + (16384 + fo * 2048));
                ldsm4(qa[kk], ta.z + kk * 1024);
            }
            float s0[4], s1[4], s2[4], s3[4];
            MMAZ(s0, qa[0], kx[0][0], kx[0][1]); MMAZ(s1, qa[0], kx[0][2], kx[0][3]);
            MMAZ(s2, qa[1], kx[1][0], kx[1][1]); MMAZ(s3, qa[1], kx[1][2], kx[1][3]);
            MMA(s0, qa[2], kx[2][0], kx[2][1]); MMA(s1, qa[2], kx[2][2], kx[2][3]);
            MMA(s2, qa[3], kx[3][0], kx[3][1]); MMA(s3, qa[3], kx[3][2], kx[3][3]);
            const float x = ((s0[0] + s0[2]) + (s2[0] + s2[2])) * cs, y = ((s0[1] + s0[3]) + (s2[1] + s2[3])) * cs;
            const float z = ((s1[0] + s1[2]) + (s3[0] + s3[2])) * cs, w = ((s1[1] + s1[3]) + (s3[1] + s3[3])) * cs;
            st_async4(ta.x, x, y, z, w, ta.y);
            TS(3, FU(w));
            sts128(rG + R_SLOC, x, y, z, w);
        }
        const uint32_t r8 = (rl2 + sbu) >> 1;
        uint32_t vt00[4], vt01[4], vt10[4], vt11[4];
        const uint32_t rV = ta.w ^ ((fo & 1) * 64), vo = (fo >> 1) * 8192;
        if (!VTA && VTP < 2) { ldsm4t(vt00, rV + vo); ldsm4t(vt10, (rV ^ 32) + vo); }
        if (!VTA && VTP < 1) { ldsm4t(vt01, rV + vo + 2048); ldsm4t(vt11, (rV ^ 32) + vo + 2048); }
        bar_sync(4, 128);
        const float2 l2 = lds64v(r8 + R_SLOC + 512), l3 = lds64v(r8 + R_SLOC + 768);
        const float4 l0 = lds128v(rL + R_SLOC), l1 = lds128v(rL + R_SLOC + 1024);
        if (VTA && VTP < 2) { ldsm4t(vt00, rV + vo); ldsm4t(vt10, (rV ^ 32) + vo); }
        if (VTA && VTP < 1) { ldsm4t(vt01, rV + vo + 2048); ldsm4t(vt11, (rV ^ 32) + vo + 2048); }

        if (s == NSEG - 1) { mbar_wait_u(sbu + R_BAR + 8 * MB_S, 1); mbar_wait_u(sbu + R_BAR + 8 * MB_V, 1); return true; }
        TS(2, FU(l3.y));
        mbar_wait_p(sbu + R_BAR + 8 * MB_S, s & 1);
        TS(4, 0);
        {
            const float2 r2 = lds64v(r8 + R_SREM + 512), r3 = lds64v(r8 + R_SREM + 768);
            const float4 r0 = lds128v(rL + R_SREM), r1 = lds128v(rL + R_SREM + 1024);
            if (VTP >= 1) PINM();
            if (VTP >= 2) { ldsm4t(vt00, rV + vo); ldsm4t(vt10, (rV ^ 32) + vo); }
            if (VTP >= 1) { ldsm4t(vt01, rV + vo + 2048); ldsm4t(vt11, (rV ^ 32) + vo + 2048); }
            float sv[10];
            sv[0] = l0.x + r0.x; sv[1] = l0.y + r0.y; sv[2] = l0.z + r0.z; sv[3] = l0.w + r0.w;
            sv[4] = l1.x + r1.x; sv[5] = l1.y + r1.y; sv[6] = l1.z + r1.z; sv[7] = l1.w + r1.w;
            sv[8] = ((l2.x + l3.x) + r2.x) + r3.x; sv[9] = ((l2.y + l3.y) + r2.y) + r3.y;
            float m = fmaxf(fmaxf(fmaxf(fmaxf(sv[8], sv[9]), sv[0]), fmaxf(fmaxf(sv[2], sv[3]), sv[1])), fmaxf(fmaxf(sv[4], sv[5]), fmaxf(sv[6], sv[7])));
            {
                const float m1 = __shfl_xor_sync(0xffffffffu, m, 1), m2 = __shfl_xor_sync(0xffffffffu, m, 2), m3 = __shfl_xor_sync(0xffffffffu, m, 3);
                m = fmaxf(fmaxf(m, m1), fmaxf(m2, m3));
            }
            TS(5, FU(m));
            const uint32_t ONE2 = 0x3f803f80u;
            float o0[4], o1[4], sm[4];
            const uint32_t pb0 = pack2(ex2(sv[0] - m), ex2(sv[1] - m)), pb1 = pack2(ex2(sv[2] - m), ex2(sv[3] - m));
            mma16816z(sm, ONE2, ONE2, ONE2, ONE2, pb0, pb1);
            MMAZ(o0, vt00, pb0, pb1); MMAZ(o1, vt10, pb0, pb1);
            const uint32_t z = (VDEP == 0 ? FU(m) : pb0) & zr;
            const uint32_t vok = mbar_test(sbu + R_BAR + 8 * MB_V + z, s & 1);
            const uint32_t rv = r8 + vok * 8;
            float2 va = lds64v(rv + R_VB - 8 + fo * 512);
            float2 vb = lds64v(rv + R_VB - 8 + fo * 512 + 256);
            float sig = __uint_as_float(lds32v_(sbu + R_MISC + 40));
            const uint32_t pb2 = pack2(ex2(sv[4] - m), ex2(sv[5] - m)), pb3 = pack2(ex2(sv[6] - m), ex2(sv[7] - m));
            mma16816(sm, ONE2, ONE2, ONE2, ONE2, pb2, pb3);
            const uint32_t pb4 = pack2(ex2(sv[8] - m), ex2(sv[9] - m));
            MMA(o0, vt01, pb2, pb3); MMA(o1, vt11, pb2, pb3);
            mma1688(sm, ONE2, ONE2, pb4);
            const float z0 = rcpf(sm[0]), z1 = rcpf(sm[1]);
#define PUT_O()                                                                                                   \
            {                                                                                                     \
                float a0[4] = {o0[0], o0[1], o0[2], o0[3]}, a1[4] = {o1[0], o1[1], o1[2], o1[3]};                 \
                mma1688(a0, FU(va.x), FU(va.y), pb4); mma1688(a1, FU(vb.x), FU(vb.y), pb4);                       \
                const float i0 = z0 * sig, i1 = z1 * sig;                                                         \
                stsm4t(rG + R_QP, pack2(a0[0] * i0, a0[1] * i1), pack2(a0[2] * i0, a0[3] * i1), pack2(a1[0] * i0, a1[1] * i1), pack2(a1[2] * i0, a1[3] * i1)); \
            }
            PUT_O()
            asm volatile("{\n.reg .pred p;\nsetp.ne.u32 p, %0, 0;\n@p bar.arrive 8, 256;\n}" :: "r"(vok) : "memory");
            if (__builtin_expect(__any_sync(0xffffffffu, vok == 0), 0)) {
                mbar_wait_p(sbu + R_BAR + 8 * MB_V, s & 1);
                va = lds64v(r8 + R_VB + fo * 512); vb = lds64v(r8 + R_VB + fo * 512 + 256);
                sig = __uint_as_float(lds32v_(sbu + R_MISC + 40));
                PUT_O()
                bar_arrive(8, 256);
                CNT(8);
            }
            TS(6, 0);
            const float r = __uint_as_float(0x7f000000u - FU(sig));
            cs = cexp * r * (fo >= 2 ? r : 1.f);
        }
        return false;
    };
    step(0, true);
#pragma unroll 1
    for (int s = 0;; s++) {
        if (s & 1) mbar_wait_p(sbu + R_BAR + 8 * (MB_FULL0 + (((s + 1) >> 1) & 1)), ((s + 1) >> 2) & 1);
        {
            const uint32_t a = rL + R_LT + 512 + 12 + fo * 512;
            sts32(a, lds32v_(a) + ((s & 1) ? ((s & 2) ? R_SLOT0 - R_SLOT1 - 4096 : R_SLOT1 - R_SLOT0 - 4096) : 4096));
        }
        auto early = [&]() {
            SCHED(13);
#pragma unroll
            for (int i = 0; i < NAX - NXL; i++) { lds_fragv(wq[i], rG + R_AX + 4096 * i); lds_fragv(wk[i], rG + R_AX + 4096 * i + 512); }
        };
        GATHER(0, , early();, )
        if (step(s + 1, false)) break;
    }
    CNT(9);
    if (rG == sbu) GT(cc * 8 + 4);
}

__device__ __forceinline__ void rec_b(uint32_t sb, int c, uint32_t epoch) {
    const int tid = threadIdx.x - WGB * 128, lane = tid & 31, f = tid >> 5;
    uint32_t wq[16][4], wk[16][4], wo[32][4];
    const int lrow = ((lane >> 4) << 3) + (lane & 7), lsel = (lane >> 3) & 1;
    const uint32_t rL = opaque(sb + lane * 16), rW = opaque(sb + lane * 16 + f * 16384);
    const uint32_t sbu = uni(sb), fo = uni(f), cc = uni(c), po = cc & 1, ep = uni(epoch);
    {
        mbar_wait(sb + R_BAR + 8 * MB_WO, 0);
        if (c == 7 && tid == 0) GT(1426);
        const uint32_t aO = sb + R_WO + f * 16384 + lrow * 128 + ((lsel ^ (lane & 7)) << 4);
#pragma unroll
        for (int i = 0; i < 32; i++) {
            const int tile = (i >> 4) * 2 + (i & 1), kk = (i >> 1) & 7;
            ldsm4t(wo[i], (aO ^ (32 * tile)) + kk * 2048);
        }
        const float no = frag_norm2(wo);
        if (lane == 0) sts32(sb + R_MISC + 80 + f * 4, FU(no));
        __syncwarp();
        bar_sync(0, 256);
        if (tid == 0) {
            const float4 a = lds128(sb + R_MISC + 64), b = lds128(sb + R_MISC + 80);
            stg4(&g_f.norm[c], make_uint4(FU((a.x + a.y) + (a.z + a.w)), epoch, FU((b.x + b.y) + (b.z + b.w)), epoch));
        }
        __syncwarp();
#pragma unroll
        for (int i = NRW; i < 32; i++) sts128u(rW + R_WO + i * 512, wo[i][0], wo[i][1], wo[i][2], wo[i][3]);
        mbar_wait(sb + R_BAR + 8 * MB_W1, 0);
        if (c == 7 && tid == 0) GT(1422);
        if (tid == 0) stg_rlx(&g_f.rload[c], epoch);
        __syncwarp();
#pragma unroll
        for (int kk = 0; kk < 16; kk++) { const uint32_t a = sb + R_QK1 + wrow_off(kk, 2 * f + lsel); ldsm4t(wq[kk], a); ldsm4t(wk[kk], a + 32768); }
        bar_sync(13, 128);
#pragma unroll
        for (int i = 0; i < 16; i++) {
            sts128u(rW + R_QK1 + i * 1024, wq[i][0], wq[i][1], wq[i][2], wq[i][3]);
            sts128u(rW + R_QK1 + i * 1024 + 512, wk[i][0], wk[i][1], wk[i][2], wk[i][3]);
        }
        __syncwarp();
    }
    const uint64_t gx = xpage();
    const uint32_t ghi = uni((uint32_t)(gx >> 32)), glo = uni((uint32_t)gx);
    TSDECL;
#pragma unroll 1
    for (int s = 0;; s++) {
        bar_sync(2, 256);
        float q0[4], k0[4];
        g1<BNB, SMB>(q0, k0, wq, wk, rL + R_MEMB + 4096, sbu - s, [&](int i, const uint32_t* c_) {
            if (i == 0) TS(0, c_[0]);
            if (i >= 2 && i < 6) {
#pragma unroll
                for (int n = NRW + (i - 2) * E0 / 4; n < NRW + (i - 1) * E0 / 4; n++) lds_fragv(wo[n], rW + R_WO + n * 512);
            }
            if (i == IV) bar_arrive(GOBAR, 96);
        });
        stsm4t(rL + fo * 1024 + R_QP + 512, pack2(q0[0], q0[1]), pack2(q0[2], q0[3]), pack2(k0[0], k0[1]), pack2(k0[2], k0[3]));
        bar_arrive(3, 256);
        TS(1, FU(k0[3]));
        const uint32_t so = aslot(s);
        uint2 lt;
        { const float2 t = lds64v(rL + R_LT + 8); lt.x = FU(t.x); lt.y = FU(t.y); }
        const uint32_t sel = 0x3210u + (lt.x & 16) * 0x440u;
        uint32_t* pm = (uint32_t*)mkptr(((glo + acc_base(po * 4 + fo)) ^ so) + lt.x, ghi);
        uint32_t* px = (uint32_t*)mkptr(((glo + ext_base(po * 4 + fo)) ^ so) + lt.y, ghi);
        if (s == NSEG - 1) break;
        {
            const uint32_t z = lt.x & 1;
#pragma unroll
            for (int n = NRW; n < NRW + E0 + E1 + E2 + E3; n++) {
                const int d = n - (n < NRW + T2N ? TRK + 1 : TRK);
                lds_fragv(wo[n], (d >= NRW ? or_and(rW, wo[d][0], z) : rW) + R_WO + n * 512);
            }
        }
        TS(2, wo[NRW + E0 + E1 + E2 + E3 - 1][0]);
        SCHED(4);
        bar_sync(8, 256);
        {
            float o[4][4];
            uint32_t b[4][4];
#pragma unroll
            for (int i = 0; i < 4; i++) ldsm4(b[i], rL + R_QP + i * 1024);
            PINM();
#pragma unroll
            for (int n = NRW + E0 + E1 + E2 + E3; n < 32; n++) lds_fragv(wo[n], rW + R_WO + n * 512);
            float p[4][4];
#define G2_STEP(o, hf, kk) _Pragma("unroll") for (int i = 0; i < 2; i++) MMAF((kk) < 2, o[((kk) & 1) * 2 + i], wo[(hf) * 16 + (kk) * 2 + i], b[(kk) >> 1][((kk) & 1) * 2], b[(kk) >> 1][((kk) & 1) * 2 + 1])
#define G2_RED(o, wl, h) const uint32_t wl = packh2(o[1][2] + o[3][2], o[1][3] + o[3][3]);                            \
                asm volatile("red.relaxed.gpu.global.add.noftz.v4.f16x2 [%0], {%1,%2,%3,%4};" :: "l"(pm + (h) * 16),  \
                    "r"(packh2(o[0][0] + o[2][0], o[0][1] + o[2][1])), "r"(packh2(o[0][2] + o[2][2], o[0][3] + o[2][3])), \
                    "r"(packh2(o[1][0] + o[3][0], o[1][1] + o[3][1])), "r"(prmt(wl, HONE2, (h) ? sel : sel ^ 0x4400u)) : "memory")
            if (G2V == 1) SCHED(11);
#pragma unroll
            for (int kk = 0; kk < 8; kk++) { G2_STEP(o, 0, kk); }
            TS(7, b[0][0]);
            if (G2V == 0) SCHED(11);
            else {
#pragma unroll
                for (int i = 0; i < 4; i++) wo[16 + i][0] = or_and(wo[16 + i][0], FU(o[i][0]), lt.x & 1);
            }
#pragma unroll
            for (int kk = 0; kk < G2K; kk++) { G2_STEP(p, 1, kk); }
#pragma unroll
            for (int i = 0; i < NB0; i++) { lds_fragv(wq[i], rW + R_QK1 + i * 1024); lds_fragv(wk[i], rW + R_QK1 + i * 1024 + 512); }
            G2_RED(o, w3, 0);
            TS(8, w3);
            if (G2V == 0) SCHED(12);
#pragma unroll
            for (int kk = G2K; kk < 8; kk++) { G2_STEP(p, 1, kk); }
            G2_RED(p, w7, 1);
            asm volatile("red.relaxed.gpu.global.add.noftz.f16x2 [%0], %1;" :: "l"(px), "r"(prmt((w3 & 0xffff0000u) | 0x3c00u, w7, sel)) : "memory");
            TS(9, w7);
        }
        bar_arrive(5, 384);
        asm volatile("{\n.reg .pred p;\nsetp.eq.u32 p, %0, %1;\n@p mbarrier.arrive.expect_tx.shared::cta.b64 _, [%2], 1536;\n}"
                     :: "r"(rW), "r"(sbu), "r"(sbu + R_BAR + 8 * MB_S) : "memory");
        const uint32_t tb = clk32();
        TSACC();
        spin_until(tb, DB);
#pragma unroll
        for (int i = NB0; i < NBR; i++) {
            if (i == NB1) spin_until(tb, DP + DB2);
            lds_fragv(wq[i], rW + R_QK1 + i * 1024); lds_fragv(wk[i], rW + R_QK1 + i * 1024 + 512);
        }
    }
}

#undef lds_fragv
__device__ __forceinline__ void rec_first_loads(uint32_t sb, int c, const Maps& maps) {
    const uint32_t bar = sb + R_BAR;
    const int F0 = c * 64;
    mbar_expect_tx(bar + 8 * MB_W0, 65536); mbar_expect_tx(bar + 8 * MB_WO, 65536); mbar_expect_tx(bar + 8 * MB_WV, 65536);
    tma2d(sb + R_QK1, &maps.wv, F0, 0, bar + 8 * MB_WV); tma2d(sb + R_QK1 + 32768, &maps.wv, F0, 256, bar + 8 * MB_WV);
    tma2d(sb + R_T + 32768, &maps.wk, F0, 0, bar + 8 * MB_W0);
    if (!LORD) {
        for (int i = 0; i < 4; i++) tma2d(sb + R_WO + i * 16384, &maps.wo, (c & 1) * 256 + i * 64, (c >> 1) * 128, bar + 8 * MB_WO);
        tma2d(sb + R_T, &maps.wq, F0, 0, bar + 8 * MB_W0);
    }
    mbar_expect_tx(bar + 8 * MB_S, 1536);
}
__device__ __forceinline__ void rec_c(uint32_t sb, int c, const bf16* __restrict__ mem0, const Maps& maps, uint32_t epoch) {
    const int tid = threadIdx.x - WGC * 128, lane = tid & 31, u = tid >> 5;
    const uint32_t bar = sb + R_BAR;
    const int lrow = ((lane >> 4) << 3) + (lane & 7), lsel = (lane >> 3) & 1;
    const int kh = u >> 1, j = u & 1;
    uint32_t wv[32][4], mx, my = 0, mz = 0;
    {
        if (u == 0) {
            sts128u(sb + lane * 16 + R_LT, (lane >> 3) * 256 + (lane & 7) * 16, ((lane >> 2) & 1) * XHS + (lane >> 4) * XSS + (lane & 8) * 2 + (lane & 2) * 4,
                    (lane >> 2) * 256 + (lane & 3) * 16, (lane & 1) * XHS + ((lane >> 3) & 1) * XSS + (lane & 6) * 4 + (lane >> 4) * 4);
        }
        mbar_wait(bar + 8 * MB_WV, 0);
        if (c == 7 && tid == 0) GT(1425);
        if (LORD && tid == 32) {
            for (int i = 0; i < 4; i++) tma2d(sb + R_WO + i * 16384, &maps.wo, (c & 1) * 256 + i * 64, (c >> 1) * 128, bar + 8 * MB_WO);
            tma2d(sb + R_T, &maps.wq, c * 64, 0, bar + 8 * MB_W0);
        }
        __syncwarp();
#pragma unroll
        for (int kk = 0; kk < 16; kk++) {
            const uint32_t aa = sb + R_QK1 + kh * 32768 + wrow_off(kk, 4 * j + 2 * kh + lsel);
            ldsm4t(wv[kk], aa); ldsm4t(wv[16 + kk], aa ^ 32);
        }
        bar_sync(9, 128);
        if (c == 7 && tid == 0) GT(1423);
        if (tid == 0) {
            mbar_expect_tx(bar + 8 * MB_W1, 65536);
            tma2d(sb + R_QK1 + 32768, &maps.wk, c * 64, 256, bar + 8 * MB_W1); tma2d(sb + R_QK1, &maps.wq, c * 64, 256, bar + 8 * MB_W1);
        }
        __syncwarp();
        const float nv = frag_norm2(wv);
        if (lane == 0) sts32(sb + R_MISC + 64 + u * 4, FU(nv));
        __syncwarp();
        bar_arrive(0, 256);
        mx = put_mem0(sb, 4 + u, mem0);
    }
    const uint32_t rL = opaque(sb + lane * 16), rG = opaque(sb + lane * 16 + u * 1024);
    const uint32_t sbu = uni(sb), fo = uni(u), cc = uni(c), ep = uni(epoch);
    const uint64_t gx = xpage();
    const uint32_t ghi = uni((uint32_t)(gx >> 32)), glo = uni((uint32_t)gx);
    constexpr int CX = R_AX + NAX * 4096;
    static_assert(NAX + NCX <= 6, "AX");
#pragma unroll
    for (int i = 0; i < NCX; i++) {
        sts128u(rG + CX + 4096 * i, wv[i][0], wv[i][1], wv[i][2], wv[i][3]);
        sts128u(rG + CX + 4096 * i + 512, wv[16 + i][0], wv[16 + i][1], wv[16 + i][2], wv[16 + i][3]);
    }
    __syncwarp();
    TSDECL;
    uint32_t rpb = 0x3f800000u;
    bar_arrive(2, 256);
    if (fo == 3) {
        uint32_t n = 0;
#pragma unroll 1
        while (true) {
            const uint2 v = ldg_rlx2(&g_f.kv[0][cc >> 1][0]);
            if (__all_sync(0xffffffffu, v.x == ep && v.y == ep)) break;
            __nanosleep(32);
            if (++n > SPIN_LIMIT) { ABORT(6); break; }
        }
        if (rL == sbu) load_slot(sbu, cc, 0, maps);
        __syncwarp();
        if (cc == 7 && rL == sbu) GT(1427);
    }
#pragma unroll 1
    for (int s = 0;; s++) {
        if (TEARLY && fo == 3 && !(s & 1) && s > 0 && s + 2 < NSEG) {
            if (rL == sbu) load_slot(sbu, cc, (s + 2) >> 1, maps);
            __syncwarp();
        } else spin_until(clk32(), DC);
#pragma unroll
        for (int i = NCX - NCL; i < NCX; i++) { lds_fragv(wv[i], rG + CX + 4096 * i); lds_fragv(wv[16 + i], rG + CX + 4096 * i + 512); }
        PUT_MAX(rL, 4 + fo)
        if (fo == 0) {
                bar_sync(15, 256);
                if (s == 0) {
                    const uint32_t* np = (const uint32_t*)&g_f.norm[0] + ((rL ^ sbu) >> 2);
                    uint4 r, q; uint32_t n = 0;
#pragma unroll 1
                    while (true) {
                        r = ldg_rlx4(np); q = ldg_rlx4(np + 128);
                        const uint2 z = ldg_rlx2(&g_f.xn[(rL ^ sbu) >> 3]);
                        if (__all_sync(0xffffffffu, r.y == ep && r.w == ep && q.y == ep && q.w == ep && z.x == ep && z.y == ep)) break;
                        if (++n > SPIN_LIMIT) { ABORT(5); break; }
                    }
                    float nv = __uint_as_float(r.x) + __uint_as_float(q.x), no = __uint_as_float(r.z) + __uint_as_float(q.z);
#pragma unroll
                    for (int o = 16; o; o >>= 1) { nv += __shfl_xor_sync(0xffffffffu, nv, o); no += __shfl_xor_sync(0xffffffffu, no, o); }
                    const int lc = ((int)(FU(nv) >> 23) + (int)(FU(no) >> 23) - 252 + 9 + 1) >> 1;
                    sts32(sbu + R_MISC + 32, 140 - lc);
                    __syncwarp();
                }
                const uint4 ma = lds128uv(rL + R_STG + 1024), mb = lds128uv(rL + R_STG + 1536);
                const uint32_t m_ = amax2b(amax2b(amax2b(ma.x, ma.y), amax2b(ma.z, ma.w)), amax2b(amax2b(mb.x, mb.y), amax2b(mb.z, mb.w)));
                const int em = (int)(__reduce_max_sync(0xffffffffu, amax2b(m_, m_ << 16) & 0x7f800000u) >> 23) + (int)(rpb >> 23) - 127;
                const int es = min(max((int)lds32v_(sbu + R_MISC + 32) - max(em, 127), -60), 60);
                sts32(sbu + R_MISC + 40, (127 + es) << 23);
                TS(4, es);
        } else bar_arrive(15, 256);
        bar_sync(GOBAR, 96);
        float v0[4], v1[4];
        g1<CNB, SMC>(v0, v1, wv, wv + 16, rL + R_MEMB + (fo >> 1) * 4096, sbu - s, [&](int i, const uint32_t* c_) { if (i == 0) TS(0, c_[0]); });
        TS(1, FU(v1[3]));
        const uint32_t l16 = (rL ^ sbu) | (lds32v_(rL + R_LT + 4) & 1);
        const uint32_t r8 = sbu + (l16 >> 1);
        {
            sts128(rL + R_VRED + fo * 512, v1[0], v1[1], v1[2], v1[3]);
            const uint32_t d = r8 + R_VB + ((cc & 1) * 4 + (fo & 1) * 2 + (fo >> 1)) * 256;
            const uint32_t dr = xorv(d, 0x01000000u), br = xorv(sbu + R_BAR + 8 * MB_V, 0x01000000u);
            bar_sync(6 + (fo & 1), 64);
            const float4 a0 = lds128(rL + R_VRED + (fo ^ 2) * 512);
            const float rp = __uint_as_float(rpb);
            const uint32_t w0 = pack2((v0[0] + a0.x) * rp, (v0[1] + a0.y) * rp), w1 = pack2((v0[2] + a0.z) * rp, (v0[3] + a0.w) * rp);
            st_async2(dr, w0, w1, br);
            TS(3, w1);
            sts64(d, __uint_as_float(w0), __uint_as_float(w1));
            __syncwarp();
            asm volatile("{\n.reg .pred p;\nsetp.eq.u32 p, %0, %1;\n@p mbarrier.arrive.expect_tx.shared::cta.b64 _, [%2], 256;\n}"
                         :: "r"(rL), "r"(sbu), "r"(sbu + R_BAR + 8 * MB_V) : "memory");
        }
        if (fo == 1) {
            bar_sync(9, 192);
            uint8_t* dst = (uint8_t*)&g_KVf[s][cc >> 1][(cc & 1) * 256] + l16;
            const uint32_t r2 = prmt(rpb, 0, 0x3232u);
#pragma unroll
            for (int i = 0; i < 2; i++) {
                const uint4 a = lds128uv(rL + R_STG + i * 512);
                stg4(dst + i * 512, make_uint4(~hmul2b(a.x, r2), ~hmul2b(a.y, r2), ~hmul2b(a.z, r2), ~hmul2b(a.w, r2)));
                const float2 b0 = lds64v(r8 + R_VB + (cc & 1) * 1024 + i * 512), b1 = lds64v(r8 + R_VB + (cc & 1) * 1024 + i * 512 + 256);
                stg4(dst + 2048 + i * 512, make_uint4(~FU(b0.x), ~FU(b0.y), ~FU(b1.x), ~FU(b1.y)));
            }
            __syncwarp();
            if (l16 == 0) { stg_rlx(&g_f.rec[cc], (ep << 8) | (s + 1)); if (s == NSEG - 1) GT(1500 + cc); }
            __syncwarp();
        } else {
            bar_arrive(9, 192);
            if (fo == 2) {
                if (l16 < 144) stg4((void*)mkptr((glo + zero_off(cc, l16 >> 4)) ^ aslot(s + 4), ghi), make_uint4(0, 0, 0, 0));
                __syncwarp();
            } else if (fo == 3) {
                if (((s & 1) || s == 0) && s + 3 < NSEG) {
                    const uint32_t* fp = &g_f.kv[(s + 3) >> 1][cc >> 1][0];
                    uint32_t n = 0;
#pragma unroll 1
                    while (true) {
                        const uint2 v = ldg_rlx2(fp);
                        if (__all_sync(0xffffffffu, v.x == ep && v.y == ep)) break;
                        __nanosleep(64);
                        if (++n > SPIN_LIMIT) { ABORT(6); break; }
                    }
                }
                if (!(s & 1) && s + 2 < NSEG && (!TEARLY || s == 0)) {
                    spin_until(clk32(), DT);
                    if (l16 == 0) load_slot(sbu, cc, (s + 2) >> 1, maps);
                    __syncwarp();
                }
            }
        }
        if (s == NSEG - 1) break;
        auto early = [&]() {
#pragma unroll
            for (int i = 0; i < NCX - NCL; i++) { lds_fragv(wv[i], rG + CX + 4096 * i); lds_fragv(wv[16 + i], rG + CX + 4096 * i + 512); }
        };
        GATHER(1, , early(); rpb = 0x7f000000u - lds32v_(sbu + R_MISC + 40);, bar_arrive(2, 256);)
    }
}

__device__ __forceinline__ bool cand_better(float v, int i, float bv, int bi) { return v > bv || (v == bv && i < bi); }
constexpr int F_WG = 0, F_WU = 32768, F_WD = 65536, F_X = 98304, F_RED = F_X + 4096, F_ACT = F_RED + 8192, F_SEL = F_ACT + 256;

__device__ __noinline__ void ffn_phase(const Maps& maps, const bf16* __restrict__ wd, bf16* __restrict__ out) {
    extern __shared__ __align__(1024) uint8_t smem[];
    const uint32_t sb = smem_u32(smem);
    const int c = ((volatile int*)(smem + SH_OFF))[8];
    const uint32_t epoch = ((volatile uint32_t*)(smem + SH_OFF))[9];
    const int tid = threadIdx.x;
    constexpr int NWK = FF / 32;
    const bool worker = c < NWK;
    bar_sync(0, 384);
    const uint32_t mb = sb + R_BAR + 8 * MB_W0;
    if (tid == 32 && worker) {
        asm volatile("fence.proxy.async.shared::cta;" ::: "memory");
        mbar_expect_tx(mb, 98304);
        tma2d(sb + F_WG, &maps.wg, c * 32, 0, mb); tma2d(sb + F_WG + 16384, &maps.wg, c * 32, 256, mb);
        tma2d(sb + F_WU, &maps.wu, c * 32, 0, mb); tma2d(sb + F_WU + 16384, &maps.wu, c * 32, 256, mb);
        asm volatile("cp.async.bulk.shared::cluster.global.mbarrier::complete_tx::bytes [%0], [%1], %2, [%3];"
            :: "r"(sb + F_WD), "l"(wd + (size_t)c * 32 * DM), "r"(32768), "r"(mb) : "memory");
    }
    int p0 = -1, p1 = -1;
#pragma unroll 1
    for (int pass = 0; pass < 2; pass++) {
        if (tid < 32) {
            const uint32_t tag = epoch & 0xfffffu;
            uint4 r[4]; uint32_t n = 0;
            const int t3 = tid + 96 < NFW ? tid + 96 : tid;
#pragma unroll 1
            while (true) {
                bool ok = true;
#pragma unroll
                for (int i = 0; i < 4; i++) r[i] = ldg_rlx4((const uint32_t*)&g_f.cand[pass][i < 3 ? tid + 32 * i : t3]);
#pragma unroll
                for (int i = 0; i < 4; i++) ok = ok && (r[i].y >> 12) == tag && (r[i].w >> 12) == tag;
                if (__all_sync(0xffffffffu, ok)) break;
                __nanosleep(32);
                if (++n > SPIN_LIMIT) { ABORT(7); break; }
            }
            float b0 = __uint_as_float(r[0].x), b1 = __uint_as_float(r[0].z); int i0 = r[0].y & 4095, i1 = r[0].w & 4095;
#pragma unroll
            for (int i = 1; i < 4; i++) {
                if (i < 3 || t3 != tid) {
                    float c0 = __uint_as_float(r[i].x), c1 = __uint_as_float(r[i].z); int j0 = r[i].y & 4095, j1 = r[i].w & 4095;
                    if (cand_better(c0, j0, b0, i0)) {
                        if (cand_better(c1, j1, b0, i0)) { b1 = c1; i1 = j1; } else { b1 = b0; i1 = i0; }
                        b0 = c0; i0 = j0;
                    } else if (cand_better(c0, j0, b1, i1)) { b1 = c0; i1 = j0; }
                }
            }
#pragma unroll
            for (int o = 16; o; o >>= 1) {
                float c0 = __shfl_xor_sync(0xffffffffu, b0, o), c1 = __shfl_xor_sync(0xffffffffu, b1, o);
                int j0 = __shfl_xor_sync(0xffffffffu, i0, o), j1 = __shfl_xor_sync(0xffffffffu, i1, o);
                if (cand_better(c0, j0, b0, i0)) {
                    if (cand_better(c1, j1, b0, i0)) { b1 = c1; i1 = j1; } else { b1 = b0; i1 = i0; }
                    b0 = c0; i0 = j0;
                } else if (cand_better(c0, j0, b1, i1)) { b1 = c0; i1 = j0; }
            }
            i0 = min(i0, SQ - 1); i1 = min(i1, SQ - 1);
            if (i0 != p0 || i1 != p1) {
                n = 0;
#pragma unroll 1
                while (!__all_sync(0xffffffffu, (ldg_rlx(&g_f.rows[pass][tid]) == epoch) & (ldg_rlx(&g_f.rows[pass][tid + 32]) == epoch) &
                                                   (ldg_rlx(&g_f.rows[pass][tid + 64]) == epoch) & (ldg_rlx(&g_f.rows[pass][t3]) == epoch))) { __nanosleep(32); if (++n > SPIN_LIMIT) { ABORT(7); break; } }
            }
            int* sel = (int*)(smem + F_SEL);
            if (pass && tid == 0) GT(c * 8 + 5);
            if (tid == 0) { sel[0] = i0; sel[1] = i1; ((float*)sel)[2] = b0; ((float*)sel)[3] = b1; }
        }
        bar_sync(0, 384);
        const int t0 = ((int*)(smem + F_SEL))[0], t1 = ((int*)(smem + F_SEL))[1];
        if (c == 3 && tid == 0 && pass == 0) GT(1430);
        if (t0 == p0 && t1 == p1) break;
        const uint32_t ytag = epoch * 2 + pass + 1;
        if (worker) {
            float2* xs = (float2*)(smem + F_X);
            if (tid < 256) {
                uint32_t a = __ldcg((const uint32_t*)(g_hn + (size_t)t0 * DM) + tid), b = __ldcg((const uint32_t*)(g_hn + (size_t)t1 * DM) + tid);
                *(float4*)(xs + tid * 2) = make_float4(bf_lo(a), bf_lo(b), bf_hi(a), bf_hi(b));
            }
            mbar_wait(mb, 1);
            if (c == 3 && tid == 0 && pass == 0) GT(1431);
            bar_sync(0, 384);
            float4* red = (float4*)(smem + F_RED);
            if (tid < 256) {
                const int cp = tid & 31, kg = tid >> 5;
                const uint32_t* wp = (const uint32_t*)(smem + (cp < 16 ? F_WG : F_WU)) + (cp & 15);
                float a0 = 0.f, a1 = 0.f, b0 = 0.f, b1 = 0.f;
#pragma unroll 16
                for (int k = kg * 64; k < kg * 64 + 64; k++) {
                    uint32_t w = wp[k * 16]; float2 x = xs[k];
                    a0 = fmaf(x.x, bf_lo(w), a0); a1 = fmaf(x.x, bf_hi(w), a1); b0 = fmaf(x.y, bf_lo(w), b0); b1 = fmaf(x.y, bf_hi(w), b1);
                }
                red[kg * 32 + cp] = make_float4(a0, a1, b0, b1);
            }
            bar_sync(0, 384);
            float2* act = (float2*)(smem + F_ACT);
            if (tid < 64) {
                const int f = tid & 31, tk = tid >> 5;
                const float* r = (const float*)red + (f >> 1) * 4 + tk * 2 + (f & 1);
                float gsum = 0.f, usum = 0.f;
#pragma unroll
                for (int kg = 0; kg < 8; kg++) { gsum += r[kg * 128]; usum += r[kg * 128 + 64]; }
                gsum = rbf(gsum); usum = rbf(usum);
                float sg = rbf(gsum / (1.f + __expf(-gsum)));
                ((float*)act)[f * 2 + tk] = rbf(sg * usum);
            }
            bar_sync(0, 384);
            if (tid < 256) {
                const uint32_t* wp = (const uint32_t*)(smem + F_WD) + tid;
                float a0 = 0.f, a1 = 0.f, b0 = 0.f, b1 = 0.f;
#pragma unroll 16
                for (int f = 0; f < 32; f++) {
                    uint32_t w = wp[f * 256]; float2 x = act[f];
                    a0 = fmaf(x.x, bf_lo(w), a0); a1 = fmaf(x.x, bf_hi(w), a1); b0 = fmaf(x.y, bf_lo(w), b0); b1 = fmaf(x.y, bf_hi(w), b1);
                }
                asm volatile("st.relaxed.gpu.global.v4.b32 [%0], {%1,%2,%3,%2};" :: "l"(&g_yp[pass][c][tid]), "r"(FU(a0)), "r"(ytag), "r"(FU(a1)) : "memory");
                asm volatile("st.relaxed.gpu.global.v4.b32 [%0], {%1,%2,%3,%2};" :: "l"(&g_yp[pass][c][256 + tid]), "r"(FU(b0)), "r"(ytag), "r"(FU(b1)) : "memory");
            }
            if (c == 3 && tid == 0 && pass == 0) GT(1432);
        } else {
            const int r = c - NWK, j = tid & 63, part = tid >> 6, tk = r >> 2, dp = (r & 3) * 64 + j;
            const int tok = tk ? t1 : t0, old = tk ? p1 : p0;
            uint32_t hw = 0, nw = 0;
            if (part == 0) {
                hw = __ldcg((const uint32_t*)(g_h + (size_t)tok * DM) + dp); nw = __ldcg((const uint32_t*)(g_hn + (size_t)tok * DM) + dp);
                if (old >= 0 && old != t0 && old != t1) {
                    uint32_t ho = __ldcg((const uint32_t*)(g_h + (size_t)old * DM) + dp), no = __ldcg((const uint32_t*)(g_hn + (size_t)old * DM) + dp);
                    ((uint32_t*)(out + (size_t)old * DM))[dp] = pack2(bf_lo(ho) + bf_lo(no), bf_hi(ho) + bf_hi(no));
                }
            }
            float s0 = 0.f, s1 = 0.f;
            uint4 v[10]; uint32_t n = 0;
            bool ok;
#pragma unroll 1
            do {
                ok = true;
#pragma unroll
                for (int i = 0; i < 10; i++) {
                    const int src = part + 6 * i;
                    v[i] = src < NWK ? ldg_rlx4((const uint32_t*)&g_yp[pass][src][tk * 256 + dp]) : make_uint4(0, ytag, 0, ytag);
                }
#pragma unroll
                for (int i = 0; i < 10; i++) ok = ok && v[i].y == ytag && v[i].w == ytag;
                if (!ok) __nanosleep(100);
                if (++n > SPIN_LIMIT) { ABORT(7); break; }
            } while (!ok);
#pragma unroll
            for (int i = 0; i < 10; i++) { s0 += __uint_as_float(v[i].x); s1 += __uint_as_float(v[i].z); }
            float2* red = (float2*)(smem + F_RED);
            red[part * 64 + j] = make_float2(s0, s1);
            bar_sync(0, 384);
            if (part == 0) {
#pragma unroll
                for (int i = 1; i < 6; i++) { float2 q = red[i * 64 + j]; s0 += q.x; s1 += q.y; }
                const float rs = rbf(1.f / (1.f + __expf(-((float*)(smem + F_SEL))[2 + tk])));
                const float y0 = rbf(rbf(s0) * rs), y1 = rbf(rbf(s1) * rs);
                ((uint32_t*)(out + (size_t)tok * DM))[dp] = pack2(bf_lo(hw) + rbf(bf_lo(nw) + y0), bf_hi(hw) + rbf(bf_hi(nw) + y1));
            }
            if (tid == 0 && pass == 0 && r == 0) GT(1434);
        }
        p0 = t0; p1 = t1;
        if (c == 3 && tid == 0 && pass == 0) GT(1433);
        bar_sync(0, 384);
    }
}

constexpr int G_W = 0;
constexpr int G_RING = 131072;
constexpr int G_BUF = 163840;
constexpr int G_BAR = 229376;
constexpr int G_SMEM = G_BAR + 512;
enum { GB_W0 = 0, GB_W1, GB_WFREE, GB_FULL, GB_EMPTY = GB_FULL + 8, GB_KV = GB_EMPTY + 8, GB_STG = GB_KV + 2, GB_FREE = GB_STG + 2, GB_XN = GB_FREE + 2, GB_RL, GB_T1D, GB_VV, GB_KVF = GB_VV + 2, GB_VF, GB_N };
constexpr int SMEM_TOTAL = 232448;

__device__ __forceinline__ void wgmma_n128(float* d, uint64_t da, uint64_t db, int scale_d) {
    asm volatile("{\n.reg .pred p;\nsetp.ne.b32 p, %66, 0;\n"
        "wgmma.mma_async.sync.aligned.m64n128k16.f32.bf16.bf16 "
        "{%0,%1,%2,%3,%4,%5,%6,%7,%8,%9,%10,%11,%12,%13,%14,%15,%16,%17,%18,%19,%20,%21,%22,%23,%24,%25,%26,%27,%28,%29,%30,%31,"
        "%32,%33,%34,%35,%36,%37,%38,%39,%40,%41,%42,%43,%44,%45,%46,%47,%48,%49,%50,%51,%52,%53,%54,%55,%56,%57,%58,%59,%60,%61,%62,%63}, "
        "%64, %65, p, 1, 1, 0, 1;\n}"
        : "+f"(d[0]), "+f"(d[1]), "+f"(d[2]), "+f"(d[3]), "+f"(d[4]), "+f"(d[5]), "+f"(d[6]), "+f"(d[7]), "+f"(d[8]), "+f"(d[9]), "+f"(d[10]), "+f"(d[11]),
          "+f"(d[12]), "+f"(d[13]), "+f"(d[14]), "+f"(d[15]), "+f"(d[16]), "+f"(d[17]), "+f"(d[18]), "+f"(d[19]), "+f"(d[20]), "+f"(d[21]), "+f"(d[22]), "+f"(d[23]),
          "+f"(d[24]), "+f"(d[25]), "+f"(d[26]), "+f"(d[27]), "+f"(d[28]), "+f"(d[29]), "+f"(d[30]), "+f"(d[31]), "+f"(d[32]), "+f"(d[33]), "+f"(d[34]), "+f"(d[35]),
          "+f"(d[36]), "+f"(d[37]), "+f"(d[38]), "+f"(d[39]), "+f"(d[40]), "+f"(d[41]), "+f"(d[42]), "+f"(d[43]), "+f"(d[44]), "+f"(d[45]), "+f"(d[46]), "+f"(d[47]),
          "+f"(d[48]), "+f"(d[49]), "+f"(d[50]), "+f"(d[51]), "+f"(d[52]), "+f"(d[53]), "+f"(d[54]), "+f"(d[55]), "+f"(d[56]), "+f"(d[57]), "+f"(d[58]), "+f"(d[59]),
          "+f"(d[60]), "+f"(d[61]), "+f"(d[62]), "+f"(d[63])
        : "l"(da), "l"(db), "r"(scale_d));
}

__device__ __forceinline__ constexpr uint32_t slot_off(int slot) {
    return slot < 2 ? G_RING + slot * 16384 : G_BUF + (slot - 2) * 32768 + 16384;
}
template <int NSLOT>
__device__ __forceinline__ void gemm_tile(float* acc, uint32_t sb, int tile, int it, bool first, uint32_t wpar, int wg, bool pass, uint32_t l0) {
    const uint32_t bar = sb + G_BAR;
    bar_sync(3 + wg, 256);
    int prev = 0;
#pragma unroll
    for (int k = 0; k < 4; k++) {
        const int n = tile * 4 + k, slot = NSLOT == 4 ? k : n % 3;
        const uint32_t sz = sb + (((it + k) << 4) & sb & 0x3f0);
        const uint64_t da = desc_sw128(sz + slot_off(slot), 16, 1024), db0 = desc_sw128(sz + G_W, 65536, 1024);
        if ((k & 1) == 0 && first) mbar_wait_p(bar + 8 * (GB_W0 + (k >> 1)), wpar);
        bool rel = false;
        if (EREL && k > 0 && !__all_sync(0xffffffffu, mbar_test(bar + 8 * (GB_FULL + slot), tile & 1))) {
            asm volatile("wgmma.wait_group.sync.aligned 0;" ::: "memory");
            mbar_arrive2_if(bar + 8 * (GB_EMPTY + prev), l0);
            rel = true;
        }
        mbar_wait_p(bar + 8 * (GB_FULL + slot), NSLOT == 4 ? (tile & 1) : ((n / 3) & 1));
        if (k == 3 && pass) bar_arrive(3 + (wg ^ 1), 256);
        asm volatile("wgmma.fence.sync.aligned;" ::: "memory");
#pragma unroll
        for (int kk = 0; kk < 4; kk++) wgmma_n128(acc, da + kk * 2, db0 + k * 1024 + kk * 128, (k | kk) != 0);
        asm volatile("wgmma.commit_group.sync.aligned;" ::: "memory");
        if (k > 0) {
            asm volatile("wgmma.wait_group.sync.aligned 1;" ::: "memory");
            mbar_arrive2_if(bar + 8 * (GB_EMPTY + prev), rel ? 0 : l0);
        }
#pragma unroll
        for (int kk = 0; kk < 4; kk++) wgmma_n128(acc, da + 512 + kk * 2, db0 + k * 1024 + 512 + kk * 128, 1);
        asm volatile("wgmma.commit_group.sync.aligned;" ::: "memory");
        prev = slot;
    }
    asm volatile("wgmma.wait_group.sync.aligned 0;" ::: "memory");
    mbar_arrive2_if(bar + 8 * (GB_EMPTY + prev), l0);
}
__device__ __forceinline__ void stage_bf16(const float* acc, uint32_t buf, float s0, float s1) {
    const int lane = threadIdx.x & 31, wq = (threadIdx.x >> 5) & 3;
    const int row = wq * 16 + (lane & 7) + ((lane >> 3) & 1) * 8;
    const uint32_t base = buf + row * 128;
#pragma unroll
    for (int j = 0; j < 16; j += 2) {
        const int ch = (j & 7) + (lane >> 4);
        stsm4(base + (j >> 3) * 8192 + ((ch ^ (row & 7)) << 4),
              pack2(acc[4 * j] * s0, acc[4 * j + 1] * s0), pack2(acc[4 * j + 2] * s1, acc[4 * j + 3] * s1),
              pack2(acc[4 * j + 4] * s0, acc[4 * j + 5] * s0), pack2(acc[4 * j + 6] * s1, acc[4 * j + 7] * s1));
    }
}

__device__ __forceinline__ void store_perm(const float* acc, bf16* dst, int ld, float s0, float s1) {
#pragma unroll
    for (int i = 0; i < 4; i++) {
        const float* a = acc + 16 * i;
        *(uint4*)(dst + i * 32) = make_uint4(pack2(a[0] * s0, a[1] * s0), pack2(a[4] * s0, a[5] * s0), pack2(a[8] * s0, a[9] * s0), pack2(a[12] * s0, a[13] * s0));
        *(uint4*)(dst + 8 * ld + i * 32) = make_uint4(pack2(a[2] * s1, a[3] * s1), pack2(a[6] * s1, a[7] * s1), pack2(a[10] * s1, a[11] * s1), pack2(a[14] * s1, a[15] * s1));
    }
}
template <int ACC>
__device__ __forceinline__ void wgmma_rs64(float* d, const uint32_t* a, uint64_t db) {
    asm volatile("{\n.reg .pred p;\nsetp.ne.b32 p, %37, 0;\n"
        "wgmma.mma_async.sync.aligned.m64n64k16.f32.bf16.bf16 {%0,%1,%2,%3,%4,%5,%6,%7,%8,%9,%10,%11,%12,%13,%14,%15,%16,%17,%18,%19,%20,%21,%22,%23,%24,%25,%26,%27,%28,%29,%30,%31}, {%32,%33,%34,%35}, %36, p, 1, 1, 0;\n}"
        : "+f"(d[0]), "+f"(d[1]), "+f"(d[2]), "+f"(d[3]), "+f"(d[4]), "+f"(d[5]), "+f"(d[6]), "+f"(d[7]), "+f"(d[8]), "+f"(d[9]), "+f"(d[10]), "+f"(d[11]), "+f"(d[12]), "+f"(d[13]), "+f"(d[14]), "+f"(d[15]), "+f"(d[16]), "+f"(d[17]), "+f"(d[18]), "+f"(d[19]), "+f"(d[20]), "+f"(d[21]), "+f"(d[22]), "+f"(d[23]), "+f"(d[24]), "+f"(d[25]), "+f"(d[26]), "+f"(d[27]), "+f"(d[28]), "+f"(d[29]), "+f"(d[30]), "+f"(d[31])
        : "r"(a[0]), "r"(a[1]), "r"(a[2]), "r"(a[3]), "l"(db), "n"(ACC));
}
template <int ACC>
__device__ __forceinline__ void wgmma_rs128t(float* d, const uint32_t* a, uint64_t db) {
    asm volatile("{\n.reg .pred p;\nsetp.ne.b32 p, %69, 0;\n"
        "wgmma.mma_async.sync.aligned.m64n128k16.f32.bf16.bf16 {%0,%1,%2,%3,%4,%5,%6,%7,%8,%9,%10,%11,%12,%13,%14,%15,%16,%17,%18,%19,%20,%21,%22,%23,%24,%25,%26,%27,%28,%29,%30,%31,%32,%33,%34,%35,%36,%37,%38,%39,%40,%41,%42,%43,%44,%45,%46,%47,%48,%49,%50,%51,%52,%53,%54,%55,%56,%57,%58,%59,%60,%61,%62,%63}, {%64,%65,%66,%67}, %68, p, 1, 1, 1;\n}"
        : "+f"(d[0]), "+f"(d[1]), "+f"(d[2]), "+f"(d[3]), "+f"(d[4]), "+f"(d[5]), "+f"(d[6]), "+f"(d[7]), "+f"(d[8]), "+f"(d[9]), "+f"(d[10]), "+f"(d[11]), "+f"(d[12]), "+f"(d[13]), "+f"(d[14]), "+f"(d[15]), "+f"(d[16]), "+f"(d[17]), "+f"(d[18]), "+f"(d[19]), "+f"(d[20]), "+f"(d[21]), "+f"(d[22]), "+f"(d[23]), "+f"(d[24]), "+f"(d[25]), "+f"(d[26]), "+f"(d[27]), "+f"(d[28]), "+f"(d[29]), "+f"(d[30]), "+f"(d[31]), "+f"(d[32]), "+f"(d[33]), "+f"(d[34]), "+f"(d[35]), "+f"(d[36]), "+f"(d[37]), "+f"(d[38]), "+f"(d[39]), "+f"(d[40]), "+f"(d[41]), "+f"(d[42]), "+f"(d[43]), "+f"(d[44]), "+f"(d[45]), "+f"(d[46]), "+f"(d[47]), "+f"(d[48]), "+f"(d[49]), "+f"(d[50]), "+f"(d[51]), "+f"(d[52]), "+f"(d[53]), "+f"(d[54]), "+f"(d[55]), "+f"(d[56]), "+f"(d[57]), "+f"(d[58]), "+f"(d[59]), "+f"(d[60]), "+f"(d[61]), "+f"(d[62]), "+f"(d[63])
        : "r"(a[0]), "r"(a[1]), "r"(a[2]), "r"(a[3]), "l"(db), "n"(ACC));
}
__device__ __forceinline__ void attention_tile(float* acc, uint32_t sb, int tile, int h, int wg, int wq, uint32_t l0, uint32_t epoch, uint2 rec) {
    const uint32_t buf = sb + G_BUF + ((tile << 4) & sb & 0x3f0);
    const int lane = threadIdx.x & 31, g = lane >> 2, t = lane & 3;
    const int sg = wq >> 1, hf = wq & 1, seg = tile * 2 + sg;
    uint32_t qf[8][4];
#pragma unroll
    for (int kk = 0; kk < 8; kk++) {
        qf[kk][0] = pack2(acc[8 * kk], acc[8 * kk + 1]); qf[kk][1] = pack2(acc[8 * kk + 2], acc[8 * kk + 3]);
        qf[kk][2] = pack2(acc[8 * kk + 4], acc[8 * kk + 5]); qf[kk][3] = pack2(acc[8 * kk + 6], acc[8 * kk + 7]);
    }
    uint32_t* kvf = &g_KVf[seg][h][lane * 4];
    uint4 km[4], vm[4];
    const bool early = __all_sync(0xffffffffu, (rec.x >> 8) == epoch && (rec.y >> 8) == epoch && (rec.x & 255) > seg && (rec.y & 255) > seg);
#pragma unroll
    for (int i = 0; i < 4; i++) { km[i] = ldg_rlx4_if(kvf + i * 128, early); vm[i] = ldg_rlx4_if(kvf + 512 + i * 128, early); }
    mbar_wait_p(sb + G_BAR + 8 * (GB_KV + wg), (tile >> 1) & 1);
    if (h == 5 && (threadIdx.x & 127) == 0 && tile < 6) GT(1750 + tile * 8 + 2);
    float sc[5][4];
    {
        const uint64_t dk = desc_sw128(buf, 16, 1024);
        asm volatile("wgmma.fence.sync.aligned;" ::: "memory");
#pragma unroll
        for (int kk = 0; kk < 8; kk++) {
            if (kk == 0) wgmma_rs64<0>(acc, qf[kk], dk); else wgmma_rs64<1>(acc, qf[kk], dk + (kk >> 2) * 512 + (kk & 3) * 2);
        }
        asm volatile("wgmma.commit_group.sync.aligned;" ::: "memory");
        asm volatile("wgmma.wait_group.sync.aligned 0;" ::: "memory");
        mbar_arrive_if(sb + G_BAR + 8 * GB_KVF, l0);
#pragma unroll
        for (int i = 0; i < 32; i++) asm volatile("" : "+f"(acc[i]) :: "memory");
#pragma unroll
        for (int b = 0; b < 4; b++)
#pragma unroll
            for (int i = 0; i < 4; i++) sc[b][i] = sg ? acc[16 + 4 * b + i] : acc[4 * b + i];
        sc[4][0] = sc[4][1] = sc[4][2] = sc[4][3] = 0.f;
    }
    const float cexp = 0.08838834764831845f * 1.4426950408889634f;
    const int r0 = hf * 16 + g, r1 = r0 + 8;
#pragma unroll
    for (int b = 0; b < 4; b++) {
        const int j = b * 8 + 2 * t;
        if (j > r0) sc[b][0] = -INFINITY;
        if (j + 1 > r0) sc[b][1] = -INFINITY;
        if (j > r1) sc[b][2] = -INFINITY;
        if (j + 1 > r1) sc[b][3] = -INFINITY;
    }
    float m0 = -INFINITY, m1 = -INFINITY;
#pragma unroll
    for (int b = 0; b < 4; b++) { m0 = fmaxf(m0, fmaxf(sc[b][0], sc[b][1])); m1 = fmaxf(m1, fmaxf(sc[b][2], sc[b][3])); }
    m0 = fmaxf(m0, __shfl_xor_sync(0xffffffffu, m0, 1)); m0 = fmaxf(m0, __shfl_xor_sync(0xffffffffu, m0, 2));
    m1 = fmaxf(m1, __shfl_xor_sync(0xffffffffu, m1, 1)); m1 = fmaxf(m1, __shfl_xor_sync(0xffffffffu, m1, 2));
    float z0 = 0.f, z1 = 0.f;
    {
        const float c0 = -m0 * cexp, c1 = -m1 * cexp;
        uint32_t pf[4][2];
#pragma unroll
        for (int b = 0; b < 4; b++) {
            pf[b][0] = pack2(ex2(fmaf(sc[b][0], cexp, c0)), ex2(fmaf(sc[b][1], cexp, c0)));
            pf[b][1] = pack2(ex2(fmaf(sc[b][2], cexp, c1)), ex2(fmaf(sc[b][3], cexp, c1)));
            z0 += bf_lo(pf[b][0]) + bf_hi(pf[b][0]); z1 += bf_lo(pf[b][1]) + bf_hi(pf[b][1]);
        }
        uint32_t pa[4][4];
#pragma unroll
        for (int kk = 0; kk < 4; kk++)
#pragma unroll
            for (int i = 0; i < 4; i++) pa[kk][i] = (kk >> 1) == sg ? pf[(kk & 1) * 2 + (i >> 1)][i & 1] : 0u;
        const uint64_t dv = desc_sw128(buf + 32768, 8192, 1024);
        mbar_wait_p(sb + G_BAR + 8 * (GB_VV + wg), (tile >> 1) & 1);
        asm volatile("wgmma.fence.sync.aligned;" ::: "memory");
#pragma unroll
        for (int kk = 0; kk < 4; kk++) { if (kk == 0) wgmma_rs128t<0>(acc, pa[kk], dv); else wgmma_rs128t<1>(acc, pa[kk], dv + kk * 128); }
        asm volatile("wgmma.commit_group.sync.aligned;" ::: "memory");
        asm volatile("wgmma.wait_group.sync.aligned 0;" ::: "memory");
#pragma unroll
        for (int i = 0; i < 64; i++) asm volatile("" : "+f"(acc[i]) :: "memory");
    }
    mbar_arrive_if(sb + G_BAR + 8 * GB_VF, l0);
    if (h == 5 && (threadIdx.x & 127) == 0 && tile < 6) GT(1750 + tile * 8 + 3);
    if (!early) wait_rec(&g_f.rec[2 * h], epoch, seg + 1);
    if (seg == 63 && (threadIdx.x & 63) == 0) GT(1570 + h);
    if (h == 5 && (threadIdx.x & 127) == 0 && tile < 6) GT(1750 + tile * 8 + 4);
    __syncwarp();
    {
        uint32_t n = 0;
#pragma unroll 1
        while (true) {
            uint32_t mn = 0xffffffffu;
#pragma unroll
            for (int i = 0; i < 4; i++) mn = min(min(min(mn, min(km[i].x, km[i].y)), min(km[i].z, km[i].w)), min(min(vm[i].x, vm[i].y), min(vm[i].z, vm[i].w)));
            if (__all_sync(0xffffffffu, mn != 0)) break;
            if (++n > SPIN_LIMIT) { ABORT(4); break; }
#pragma unroll
            for (int i = 0; i < 4; i++) { km[i] = ldg_rlx4(kvf + i * 128); vm[i] = ldg_rlx4(kvf + 512 + i * 128); }
        }
#pragma unroll
        for (int i = 0; i < 4; i++) {
            km[i] = make_uint4(~km[i].x, ~km[i].y, ~km[i].z, ~km[i].w); vm[i] = make_uint4(~vm[i].x, ~vm[i].y, ~vm[i].z, ~vm[i].w);
        }
        if (hf) bar_arrive(5 + wg * 2 + sg, 64);
        float sb_[4] = {0.f, 0.f, 0.f, 0.f};
#pragma unroll
        for (int i = 0; i < 4; i++) { MMA(sc[4], qf[2 * i], km[i].x, km[i].y); MMA(sb_, qf[2 * i + 1], km[i].z, km[i].w); }
#pragma unroll
        for (int i = 0; i < 4; i++) sc[4][i] += sb_[i];
        float n0 = fmaxf(sc[4][0], sc[4][1]), n1 = fmaxf(sc[4][2], sc[4][3]);
        n0 = fmaxf(n0, __shfl_xor_sync(0xffffffffu, n0, 1)); n1 = fmaxf(n1, __shfl_xor_sync(0xffffffffu, n1, 1));
        n0 = fmaxf(n0, __shfl_xor_sync(0xffffffffu, n0, 2)); n1 = fmaxf(n1, __shfl_xor_sync(0xffffffffu, n1, 2));
        n0 = fmaxf(n0, m0); n1 = fmaxf(n1, m1);
        const float a0 = ex2((m0 - n0) * cexp), a1 = ex2((m1 - n1) * cexp);
        const float c0 = -n0 * cexp, c1 = -n1 * cexp;
        const uint32_t p0 = pack2(ex2(fmaf(sc[4][0], cexp, c0)), ex2(fmaf(sc[4][1], cexp, c0)));
        const uint32_t p1 = pack2(ex2(fmaf(sc[4][2], cexp, c1)), ex2(fmaf(sc[4][3], cexp, c1)));
        z0 = fmaf(z0, a0, bf_lo(p0) + bf_hi(p0)); z1 = fmaf(z1, a1, bf_lo(p1) + bf_hi(p1));
        const uint32_t* vmw = (const uint32_t*)vm;
#pragma unroll
        for (int j = 0; j < 16; j++) {
            float* o = acc + 4 * j;
            o[0] *= a0; o[1] *= a0; o[2] *= a1; o[3] *= a1;
            mma1688(o, p0, p1, vmw[j]);
        }
        z0 += __shfl_xor_sync(0xffffffffu, z0, 1); z1 += __shfl_xor_sync(0xffffffffu, z1, 1);
        z0 += __shfl_xor_sync(0xffffffffu, z0, 2); z1 += __shfl_xor_sync(0xffffffffu, z1, 2);
    }
    if (h == 5 && (threadIdx.x & 127) == 0 && tile < 6) GT(1750 + tile * 8 + 5);
    store_perm(acc, g_O + (size_t)(tile * 64 + wq * 16 + g) * HD + h * 128 + t * 8, HD, rcpf(z0), rcpf(z1));
    if (tile >= 2) mbar_wait_p(sb + G_BAR + 8 * (GB_FREE + wg), ((tile >> 1) - 1) & 1);
    mbar_arrive(sb + G_BAR + 8 * (GB_STG + wg));
    if (!hf) {
        bar_sync(5 + wg * 2 + sg, 64);
#pragma unroll
        for (int i = 0; i < 8; i++) stg4_h(kvf + i * 128, make_uint4(0, 0, 0, 0), pol_ef(3));
    }
}

__device__ __forceinline__ void g_consumer(uint32_t sb_, int g_, int wg_, uint32_t epoch) {
    const uint32_t sb = uni(sb_);
    const int g = uni(g_), wg = uni(wg_), wq = uni((threadIdx.x >> 5) & 3);
    const uint32_t l0 = opaque((threadIdx.x & 31) == 0);
    const uint32_t bar = sb + G_BAR, buf = sb + G_BUF + wg * 32768;
    const int lane = threadIdx.x & 31;
    float acc[64];
    if (wg == 1) bar_arrive(3, 256);
    const int n1 = g < 32 ? HSPLIT / 2 : NT - HSPLIT / 2;
#pragma unroll 1
    for (int i = 0; i < n1; i++) {
        gemm_tile<4>(acc, sb, wg, i, i == 0 || i == NT / 2, i >= NT / 2, wg, true, l0);
        if (i == n1 - 1 || i == NT / 2 - 1) mbar_arrive_if(bar + 8 * GB_WFREE, l0);
        if (threadIdx.x == 0 && i == 0) GT((64 + g) * 8 + 1);
        if (threadIdx.x == 128 && i == 3) GT((64 + g) * 8 + 2);
        if (i > 0) mbar_wait_p(bar + 8 * (GB_FREE + wg), (i - 1) & 1);
        stage_bf16(acc, buf, 1.f, 1.f);
        asm volatile("fence.proxy.async.shared::cta;" ::: "memory");
        mbar_arrive(bar + 8 * (GB_STG + wg));
    }
    if (threadIdx.x == 128) GT((64 + g) * 8 + 3);
    if (g < 32) {
#pragma unroll 1
        for (int i = 0; i < NT / 2; i++) {
            const int tile = 2 * i + wg;
            const uint2 rec = ldg_rlx2(&g_f.rec[2 * g]);
            gemm_tile<4>(acc, sb, tile, i, i == 0, 1, wg, tile != NT - 1, l0);
            if (threadIdx.x == 0 && i == 0) GT((64 + g) * 8 + 4);
            if (threadIdx.x == 128 && i == 3) GT((64 + g) * 8 + 5);
            if (g == 5 && (threadIdx.x & 127) == 0 && tile < 6) GT(1750 + tile * 8 + 1);
            attention_tile(acc, sb, tile, g, wg, wq, l0, epoch, rec);
            if (g == 5 && (threadIdx.x & 127) == 0 && tile < 6) GT(1750 + tile * 8 + 6);
        }
    } else {
#pragma unroll 1
        for (int i = 0; i < NT / 2; i++) {
            const int tile = 2 * i + wg;
            gemm_tile<4>(acc, sb, tile, i, i == 0, 0, wg, tile != NT - 1, l0);
            if (threadIdx.x == 0 && i == 0) GT((64 + g) * 8 + 4);
            if (threadIdx.x == 128 && i == 3) GT((64 + g) * 8 + 5);
            store_perm(acc, g_P + (size_t)(((g - 32) >> 2) * SQ + tile * 64 + wq * 16 + (lane >> 2)) * DM + ((g - 32) & 3) * 128 + (lane & 3) * 8, DM, 1.f, 1.f);
            mbar_wait_p(bar + 8 * (GB_FREE + wg), (i - 1) & 1);
            mbar_arrive(bar + 8 * (GB_STG + wg));
        }
    }
}

__device__ __forceinline__ void load_w(uint32_t sb, const CUtensorMap* tm, int col, int row, int k0 = 0, int k1 = 2) {
    const uint32_t bar = sb + G_BAR;
#pragma unroll
    for (int kh = k0; kh < k1; kh++) {
        mbar_expect_tx(bar + 8 * (GB_W0 + kh), 65536);
        tma2d_h(sb + G_W + kh * 32768, tm, col, row + kh * 256, bar + 8 * (GB_W0 + kh), pol_ef(5));
        tma2d_h(sb + G_W + 65536 + kh * 32768, tm, col + 64, row + kh * 256, bar + 8 * (GB_W0 + kh), pol_ef(5));
    }
}

__device__ __forceinline__ void rbf2(float& a, float& b) { uint32_t w = pack2(a, b); a = bf_lo(w); b = bf_hi(w); }
__device__ __forceinline__ void warp_sum2(float& a, float& b) {
#pragma unroll
    for (int o = 16; o; o >>= 1) { float c = __shfl_xor_sync(0xffffffffu, a, o), d = __shfl_xor_sync(0xffffffffu, b, o); a += c; b += d; }
}
__device__ __forceinline__ float sum16(const float* v) {
    return (((v[0] + v[1]) + (v[2] + v[3])) + ((v[4] + v[5]) + (v[6] + v[7]))) + (((v[8] + v[9]) + (v[10] + v[11])) + ((v[12] + v[13]) + (v[14] + v[15])));
}
__device__ __forceinline__ void ln_row2(float* v, float* u) {
    float sv = sum16(v), su = sum16(u);
    warp_sum2(sv, su);
    const float mv = sv * (1.f / DM), mu = su * (1.f / DM);
    float qv = 0.f, qu = 0.f, qv2 = 0.f, qu2 = 0.f;
#pragma unroll
    for (int i = 0; i < 16; i += 2) {
        float d0 = v[i] - mv, d1 = v[i + 1] - mv, e0 = u[i] - mu, e1 = u[i + 1] - mu;
        qv = fmaf(d0, d0, qv); qv2 = fmaf(d1, d1, qv2); qu = fmaf(e0, e0, qu); qu2 = fmaf(e1, e1, qu2);
    }
    qv += qv2; qu += qu2;
    warp_sum2(qv, qu);
    const float rv = rbf(mv), ru = rbf(mu);
    const float iv = __frcp_rn(rbf(sqrtf(rbf(rbf(qv * (1.f / DM)) + 1e-5f)))), iu = __frcp_rn(rbf(sqrtf(rbf(rbf(qu * (1.f / DM)) + 1e-5f))));
#pragma unroll
    for (int i = 0; i < 16; i += 2) {
        float a = v[i] - rv, b = v[i + 1] - rv, c = u[i] - ru, d = u[i + 1] - ru;
        rbf2(a, b); rbf2(c, d);
        a *= iv; b *= iv; c *= iu; d *= iu;
        rbf2(a, b); rbf2(c, d);
        v[i] = a; v[i + 1] = b; u[i] = c; u[i + 1] = d;
    }
}

__device__ __forceinline__ void ln_row1(float* v) {
    float sv = sum16(v);
#pragma unroll
    for (int o = 16; o; o >>= 1) sv += __shfl_xor_sync(0xffffffffu, sv, o);
    const float mv = sv * (1.f / DM);
    float qv = 0.f, qv2 = 0.f;
#pragma unroll
    for (int i = 0; i < 16; i += 2) { float d0 = v[i] - mv, d1 = v[i + 1] - mv; qv = fmaf(d0, d0, qv); qv2 = fmaf(d1, d1, qv2); }
    qv += qv2;
#pragma unroll
    for (int o = 16; o; o >>= 1) qv += __shfl_xor_sync(0xffffffffu, qv, o);
    const float rv = rbf(mv);
    float sq, iv;
    asm("sqrt.approx.f32 %0, %1;" : "=f"(sq) : "f"(rbf(rbf(qv * (1.f / DM)) + 1e-5f)));
    asm("rcp.approx.f32 %0, %1;" : "=f"(iv) : "f"(rbf(sq)));
#pragma unroll
    for (int i = 0; i < 16; i += 2) {
        float a = v[i] - rv, b = v[i + 1] - rv;
        rbf2(a, b);
        a *= iv; b *= iv;
        rbf2(a, b);
        v[i] = a; v[i + 1] = b;
    }
}
constexpr int FSPLIT = 28;
__device__ __forceinline__ int fin_row(int id, int i) {
    if (id < 64) { const int tile = i < FSPLIT / 2 ? 2 * i : i + FSPLIT / 2; return tile < NT ? tile * 64 + id : -1; }
    const int j = id - 64 + i * 48;
    return j < FSPLIT * 32 ? (j >> 6) * 128 + 64 + (j & 63) : -1;
}
__device__ __forceinline__ void finalizer(int id, const bf16* __restrict__ x, const bf16* __restrict__ wr, bf16* __restrict__ out, uint32_t epoch) {
    const int lane = threadIdx.x & 31;
    float b0 = -INFINITY, b1 = -INFINITY; int i0 = 0x7fffffff, i1 = 0x7fffffff;
    const uint32_t tag = (epoch & 0xfffffu) << 12;
    uint32_t fl = ~epoch;
    int row = fin_row(id, 0);
    const uint4 ra = *(const uint4*)(wr + lane * 8), rb = *(const uint4*)(wr + 256 + lane * 8);
    uint4 xa = *(const uint4*)(x + (size_t)row * DM + lane * 8), xb = *(const uint4*)(x + (size_t)row * DM + lane * 8 + 256);
#pragma unroll 1
    for (int it = 0; row >= 0; it++) {
        const int tile = row >> 6, nxt = fin_row(id, it + 1);
        const size_t o0 = (size_t)row * DM + lane * 8;
        uint32_t n = 0;
#pragma unroll 1
        while (!__all_sync(0xffffffffu, fl == epoch)) {
            if (n) __nanosleep(it ? 64 : 1000);
            fl = ldg_rlx(&g_f.p[tile][lane]);
            if (++n > SPIN_LIMIT) { ABORT(12); break; }
        }
        if (tile == NT - 1 && id == 63 && lane == 0) GT(1438);
        if ((id == 63 || id == 3 || id == 70) && lane == 0) GT(1800 + (id == 3) * 32 + tile);
        float v[16];
        {
            uint4 pa[8][2];
#pragma unroll
            for (int k = 0; k < 8; k++) {
                pa[k][0] = ldg4_h(g_P + (size_t)k * SQ * DM + o0, pol_ef(2));
                pa[k][1] = ldg4_h(g_P + (size_t)k * SQ * DM + o0 + 256, pol_ef(2));
            }
            fl = ldg_rlx(&g_f.p[max(nxt, 0) >> 6][lane]);
#pragma unroll
            for (int j = 0; j < 2; j++) {
#pragma unroll
                for (int i = 0; i < 4; i++) {
                    uint32_t w[8];
#pragma unroll
                    for (int k = 0; k < 8; k++) w[k] = i == 0 ? pa[k][j].x : (i == 1 ? pa[k][j].y : (i == 2 ? pa[k][j].z : pa[k][j].w));
                    v[j * 8 + 2 * i] = ((bf_lo(w[0]) + bf_lo(w[1])) + (bf_lo(w[2]) + bf_lo(w[3]))) + ((bf_lo(w[4]) + bf_lo(w[5])) + (bf_lo(w[6]) + bf_lo(w[7])));
                    v[j * 8 + 2 * i + 1] = ((bf_hi(w[0]) + bf_hi(w[1])) + (bf_hi(w[2]) + bf_hi(w[3]))) + ((bf_hi(w[4]) + bf_hi(w[5])) + (bf_hi(w[6]) + bf_hi(w[7])));
                }
            }
        }
        uint32_t hw[8];
        {
            const uint32_t xw[8] = {xa.x, xa.y, xa.z, xa.w, xb.x, xb.y, xb.z, xb.w};
            uint32_t aw[8];
#pragma unroll
            for (int i = 0; i < 8; i++) aw[i] = pack2(v[2 * i], v[2 * i + 1]);
#pragma unroll
            for (int d = 1; d <= 2; d++) {
                const bool up = lane & d;
#pragma unroll
                for (int i = 0; i < 8; i++) {
                    if (!(i & d)) {
                        const uint32_t r = __shfl_xor_sync(0xffffffffu, up ? aw[i] : aw[i | d], d);
                        if (up) aw[i] = r; else aw[i | d] = r;
                    }
                }
            }
#pragma unroll
            for (int i = 0; i < 8; i++) {
                hw[i] = pack2(bf_lo(aw[i]) + bf_lo(xw[i]), bf_hi(aw[i]) + bf_hi(xw[i]));
                v[2 * i] = bf_lo(hw[i]); v[2 * i + 1] = bf_hi(hw[i]);
            }
        }
        xa = *(const uint4*)(x + (size_t)max(nxt, 0) * DM + lane * 8); xb = *(const uint4*)(x + (size_t)max(nxt, 0) * DM + lane * 8 + 256);
        ln_row1(v);
        float r0 = 0.f, r1 = 0.f;
        {
            const uint32_t ww[8] = {ra.x, ra.y, ra.z, ra.w, rb.x, rb.y, rb.z, rb.w};
#pragma unroll
            for (int i = 0; i < 8; i++) { r0 = fmaf(v[2 * i], bf_lo(ww[i]), r0); r1 = fmaf(v[2 * i + 1], bf_hi(ww[i]), r1); }
        }
        r0 += r1;
#pragma unroll
        for (int o = 16; o; o >>= 1) r0 += __shfl_xor_sync(0xffffffffu, r0, o);
        r0 = rbf(r0);
        if (cand_better(r0, row, b0, i0)) { b1 = b0; i1 = i0; b0 = r0; i0 = row; }
        else if (cand_better(r0, row, b1, i1)) { b1 = r0; i1 = row; }
        if (tile == NT - 1 && id == 63 && lane == 0) GT(1439);
        const bool last = nxt < 0, spec = tile < SPEC_TILES && (last || (nxt >> 6) >= SPEC_TILES);
        const bool pub = (lane == 0 && spec) || (lane == 1 && last);
        if (pub)
            asm volatile("st.relaxed.gpu.global.v4.b32 [%0], {%1,%2,%3,%4};" :: "l"(&g_f.cand[lane][id]),
                         "r"(FU(b0)), "r"(tag | (uint32_t)min(i0, 4095)), "r"(FU(b1)), "r"(tag | (uint32_t)min(i1, 4095)) : "memory");
#pragma unroll
        for (int j = 0; j < 2; j++) {
            const uint32_t* hh = hw + j * 4; const float* nn = v + j * 8;
            stg4_h(out + o0 + j * 256, make_uint4(pack2(bf_lo(hh[0]) + nn[0], bf_hi(hh[0]) + nn[1]), pack2(bf_lo(hh[1]) + nn[2], bf_hi(hh[1]) + nn[3]),
                                                  pack2(bf_lo(hh[2]) + nn[4], bf_hi(hh[2]) + nn[5]), pack2(bf_lo(hh[3]) + nn[6], bf_hi(hh[3]) + nn[7])), pol_ef(4));
            if (i0 == row || i1 == row || i1 >= SQ || row == SQ - 1) {
                *(uint4*)(g_h + o0 + j * 256) = make_uint4(hh[0], hh[1], hh[2], hh[3]);
                *(uint4*)(g_hn + o0 + j * 256) = make_uint4(pack2(nn[0], nn[1]), pack2(nn[2], nn[3]), pack2(nn[4], nn[5]), pack2(nn[6], nn[7]));
            }
        }
        if (last || spec) {
            __threadfence();
            __syncwarp();
            if (pub) stg_rlx(&g_f.rows[lane][id], epoch);
        }
        row = nxt;
    }
    if (id == 0 && lane == 0) { g_epoch = epoch; if (epoch == 0xffffffu) { g_ticket[0] = 0; g_ticket[32] = 0; } }
}

__device__ __forceinline__ void g_producer(uint32_t sb, int g, const Maps& maps, uint32_t epoch, const bf16* __restrict__ x, const bf16* __restrict__ wr, bf16* __restrict__ out) {
    const uint32_t bar = sb + G_BAR;
    const int warp = (threadIdx.x >> 5) - 8;
    if (threadIdx.x == 256 && g == 5) GT(1410);
    if (threadIdx.x == 256 && g == 5) GT(1411);
    if (warp == 3) {
        wait_eq4(&g_f.xn[(threadIdx.x & 31) * 4], epoch, 13);
        __syncwarp();
        if ((threadIdx.x & 31) == 0) mbar_arrive(bar + 8 * GB_XN);
        wait_eq2(&g_f.rload[(threadIdx.x & 31) * 2], epoch, 13);
        __syncwarp();
        if ((threadIdx.x & 31) == 0) mbar_arrive(bar + 8 * GB_RL);
        finalizer(g, x, wr, out, epoch);
        if (g == 63 && (threadIdx.x & 31) == 0) GT(128 * 8 + 6);
    }
    if ((threadIdx.x & 31) != 0) return;
    if (threadIdx.x == 256 && g == 5) GT(1412);
    if (warp == 0) {
        wait_eq4(&g_f.xn[0], epoch, 13);
        const int rk = g & 1;
        const int m1 = g < 32 ? HSPLIT : 2 * NT - HSPLIT;
#pragma unroll 1
        for (int it = 0; it < m1; it++) {
            const int tile = it < NT ? it : it - NT + HSPLIT;
            if (it == HOLD) mbar_wait(bar + 8 * GB_RL, 0);
            if (it == 1) wait_eq4(&g_f.xn[4], epoch, 13);
            if (it == 2) mbar_wait(bar + 8 * GB_XN, 0);
            if (it == NT) {
                mbar_wait(bar + 8 * GB_WFREE, 0);
                load_w(sb, (g & 1) ? &maps.wv : &maps.wk, ((g - 32) >> 1) * 128, 0);
            }
#pragma unroll
            for (int k = 0; k < 4; k++) {
                if (k == 2 && it == 0) load_w(sb, (g & 1) ? &maps.wv : &maps.wk, (g >> 1) * 128, 0, 1, 2);
                mbar_wait(bar + 8 * (GB_EMPTY + k), (it & 1) ^ 1);
                mbar_expect_tx(bar + 8 * (GB_FULL + k), 16384);
                tma2d_mc(sb + slot_off(k) + rk * 8192, &maps.xn2, (k * 2 + rk) * 64, tile * 64, bar + 8 * (GB_FULL + k));
            }
        }
        mbar_wait(bar + 8 * GB_WFREE, g >= 32);
        const int u = g - 32, ks = u >> 2, ns = u & 3;
        if (g < 32) load_w(sb, &maps.wq, g * 128, 0);
        else {
#pragma unroll
            for (int kh = 0; kh < 2; kh++) {
                mbar_expect_tx(bar + 8 * (GB_W0 + kh), 65536);
#pragma unroll
                for (int nh = 0; nh < 2; nh++)
                    asm volatile("cp.async.bulk.tensor.5d.shared::cluster.global.mbarrier::complete_tx::bytes [%0], [%1, {%3, %4, %4, %4, %5}], [%2];"
                        :: "r"(sb + G_W + nh * 65536 + kh * 32768), "l"((uint64_t)&maps.wo2), "r"(bar + 8 * (GB_W0 + kh)), "r"(ns * 128 + nh * 64), "r"(0), "r"(ks * 16 + kh * 8) : "memory");
            }
        }
        if (g < 32) {
#pragma unroll 1
            for (int n = 0; n < NT * 4; n++) {
                const int slot = n & 3;
                mbar_wait(bar + 8 * (GB_EMPTY + slot), ((n >> 2) & 1) ^ 1);
                mbar_expect_tx(bar + 8 * (GB_FULL + slot), 16384);
                tma2d_mc(sb + slot_off(slot) + rk * 8192, &maps.xn2, (slot * 2 + rk) * 64, (n >> 2) * 64, bar + 8 * (GB_FULL + slot));
            }
        } else {
#pragma unroll 1
            for (int tile = 0; tile < NT; tile++) {
                wait_eq4(&g_f.o[tile][ks][0], epoch, 9);
                if (g == 40 && tile == NT - 1) GT(1437);
                if (tile == NT - 1) GT(1690 + g - 32);
#pragma unroll
                for (int k = 0; k < 4; k++) {
                    mbar_wait(bar + 8 * (GB_EMPTY + k), (tile & 1) ^ 1);
                    mbar_expect_tx(bar + 8 * (GB_FULL + k), 16384);
                    tma2d_mc_h(sb + slot_off(k) + rk * 8192, &maps.ox2, (ks * 8 + k * 2 + rk) * 64, tile * 64, bar + 8 * (GB_FULL + k), pol_ef(1));
                }
            }
        }
    } else if (warp < 3) {
        const int wg = warp - 1;
        const uint32_t buf = sb + G_BUF + wg * 32768;
        const CUtensorMap* tkv = (g & 1) ? &maps.vx3 : &maps.kx3;
        const int n1 = g < 32 ? HSPLIT / 2 : NT - HSPLIT / 2;
#pragma unroll 1
        for (int i = 0; i < n1; i++) {
            const int tile = (i < NT / 2 ? 2 * i : 2 * i - NT + HSPLIT) + wg, hd = (i < NT / 2 ? g : g - 32) >> 1;
            mbar_wait(bar + 8 * (GB_STG + wg), i & 1);
            tma_store3d(tkv, buf, tile * 64, hd * 2);
            asm volatile("cp.async.bulk.commit_group;" ::: "memory");
            asm volatile("cp.async.bulk.wait_group.read 0;" ::: "memory");
            mbar_arrive(bar + 8 * (GB_FREE + wg));
            asm volatile("cp.async.bulk.wait_group 0;" ::: "memory");
            PUBLISH(&g_f.kv[tile][hd][g & 1], epoch);
        }
        if (wg == 0) mbar_arrive(bar + 8 * GB_T1D);
        if (g < 32 && wg == 1) {
            mbar_wait(bar + 8 * GB_T1D, 0);
#pragma unroll 1
            for (int tile = 0; tile < NT; tile++) {
                wait_eq2(&g_f.kv[tile][g][0], epoch, 10);
                if (tile > 0) mbar_wait(bar + 8 * GB_KVF, (tile - 1) & 1);
                mbar_expect_tx(bar + 8 * (GB_KV + (tile & 1)), 16384);
                tma3d_h(sb + G_BUF, &maps.kx3, tile * 64, g * 2, bar + 8 * (GB_KV + (tile & 1)), pol_ef(0));
                if (tile > 0) mbar_wait(bar + 8 * GB_VF, (tile - 1) & 1);
                mbar_expect_tx(bar + 8 * (GB_VV + (tile & 1)), 16384);
                tma3d_h(sb + G_BUF + 32768, &maps.vx3, tile * 64, g * 2, bar + 8 * (GB_VV + (tile & 1)), pol_ef(0));
                if (PFK && tile + PFK < NT) {
                    const uint2 v = ldg_rlx2(&g_f.kv[tile + PFK][g][0]);
                    if (v.x == epoch && v.y == epoch) { tma_pf3d(&maps.kx3, (tile + PFK) * 64, g * 2); tma_pf3d(&maps.vx3, (tile + PFK) * 64, g * 2); }
                }
            }
        } else {
#pragma unroll 1
            for (int tile = g < 32 ? 0 : wg; tile < NT; tile += g < 32 ? 1 : 2) {
                mbar_wait(bar + 8 * (GB_STG + (tile & 1)), (tile >> 1) & 1);
                mbar_arrive(bar + 8 * (GB_FREE + (tile & 1)));
                PUBLISH(g < 32 ? &g_f.o[tile][g >> 2][g & 3] : &g_f.p[tile][g - 32], epoch);
                if (g == 3 && tile == NT - 1) GT(1436);
                if (g == 3) GT(1896 + tile);
                if (g < 32 && tile == NT - 1) GT(1610 + g);
                if (g == 40 && tile == NT - 1) GT(1435);
                if (g == 40) GT(1864 + tile);
                if (g >= 32 && tile == NT - 1) GT(1650 + g - 32);
            }
        }
    }
}

struct WPtr { const bf16 *q, *k, *v, *o; };
__device__ __forceinline__ int startup(uint8_t* smem, const bf16* __restrict__ x, const Maps& maps, uint32_t& epoch, const WPtr& pw) {
    const int tid = threadIdx.x, lane = tid & 31, w = tid >> 5, cta = blockIdx.x;
    volatile uint32_t* sh = (volatile uint32_t*)(smem + SH_OFF);
    if (cta == 4 && tid == 0) GT(1399);
    epoch = (ldg_rlx(&g_epoch) + 1) & 0x00ffffffu;
    if (w < 4) {
        if (!(cta & 1)) {
            uint32_t* pp = (uint32_t*)(xpage() + ((XR3 ^ 0x3000u) ^ ((w == 1 || w == 2) ? 0x1000u : 0u) ^ ((w & 2) << 13))) + (cta >> 1) * 8;
            if (lane < 8) stg_rlx(pp + lane, 0u);
            __syncwarp();
            if (lane == 0) {
                uint32_t best = 0xffffffffu, a = 0;
#pragma unroll 1
                for (int r = 0; r < NPROBE; r++) {
                    uint32_t t0 = clk32();
                    asm volatile("atom.relaxed.gpu.global.add.u32 %0, [%1], %2;" : "=r"(a) : "l"(pp), "r"(a + 1) : "memory");
                    if (a == 0x7fffffffu) ABORT(15);
                    uint32_t t1 = clk32();
                    if (r > 0) best = min(best, t1 - t0);
                    else if (w == 0) {
                        asm volatile("red.relaxed.gpu.global.max.u32 [%0], %1;" :: "l"(&g_ticket[0]), "r"(epoch << 8) : "memory");
                        asm volatile("red.relaxed.gpu.global.max.u32 [%0], %1;" :: "l"(&g_ticket[32]), "r"(epoch << 8) : "memory");
                    }
                }
                sh[w] = best;
            }
        }
        if (!(cta & 1)) bar_sync(1, 128);
        if (cta == 4 && tid == 0) GT(1400);
        if (w == 0) {
            if (lane == 0) {
                uint32_t rp;
                if (!(cta & 1)) {
                    uint32_t a = sh[0], b = sh[1], c = sh[2], d = sh[3];
                    uint32_t mid = (min(min(a, b), min(c, d)) + max(max(a, b), max(c, d))) >> 1;
                    const int dd = (int)min(a, d) - (int)min(b, c);
                    uint32_t cls = abs(dd) > 60 ? dd > 0 : a > mid;
                    uint32_t t = atomicAdd(&g_ticket[cls * 32], 1u) & 255;
                    if (t >= (cls ? 34u : 32u)) { cls ^= 1; t = atomicAdd(&g_ticket[cls * 32], 1u) & 255; }
                    rp = min(cls ? 32 + t : t, 65u);
                    stg_rlx(&g_table[(cta >> 1) * 8], (epoch << 8) | rp);
                } else {
                    uint32_t v, n = 0;
#pragma unroll 1
                    while (((v = ldg_rlx(&g_table[(cta >> 1) * 8])) >> 8) != epoch) { if (++n > SPIN_LIMIT) { ABORT(14); break; } }
                    rp = v & 255;
                }
                const int role = rp * 2 + (cta & 1);
                sh[8] = role; sh[9] = epoch;
                while (sh[10] != epoch + 1 && cta < NWAITLN) {}
                if (role < 64) rec_first_loads(smem_u32(smem), role, maps);
                else if (role < 128) load_w(smem_u32(smem), (role & 1) ? &maps.wv : &maps.wk, ((role - 64) >> 1) * 128, 0, 0, 1);
                if (cta == 4) GT(1401);
            }
        }
    } else if (cta < 128) {
        uint4 u[2][2];
        const int row0 = cta * 16 + (w - 4) * 2;
#pragma unroll
        for (int r = 0; r < 2; r++)
#pragma unroll
            for (int j = 0; j < 2; j++) u[r][j] = *(const uint4*)(x + (size_t)(row0 + r) * DM + j * 256 + lane * 8);
        if (cta < 48) {
            const uint32_t b = cta >> 3, off = (b >= 4 ? 0x8000u + (b & 1) * 0x4000u : ((b & 1) ? 0x3000u : 0u) + ((b & 2) << 13)) ^ aslot(cta & 7);
            *(uint4*)(xpage() + off + (tid - 128) * 16) = make_uint4(0, 0, 0, 0);
        }
        float v[2][16];
#pragma unroll
        for (int r = 0; r < 2; r++)
#pragma unroll
            for (int j = 0; j < 2; j++) {
                uint32_t ww[4] = {u[r][j].x, u[r][j].y, u[r][j].z, u[r][j].w};
#pragma unroll
                for (int i = 0; i < 4; i++) { v[r][j * 8 + 2 * i] = bf_lo(ww[i]); v[r][j * 8 + 2 * i + 1] = bf_hi(ww[i]); }
            }
        ln_row2(v[0], v[1]);
#pragma unroll
        for (int r = 0; r < 2; r++)
#pragma unroll
            for (int j = 0; j < 2; j++)
                *(uint4*)(g_xn + (size_t)(row0 + r) * DM + j * 256 + lane * 8) =
                    make_uint4(pack2(v[r][j * 8], v[r][j * 8 + 1]), pack2(v[r][j * 8 + 2], v[r][j * 8 + 3]), pack2(v[r][j * 8 + 4], v[r][j * 8 + 5]), pack2(v[r][j * 8 + 6], v[r][j * 8 + 7]));
        bar_sync(2, 256);
        if (tid == 160 && cta < NWAITLN) { st_rel(&g_f.xn[cta], epoch); sh[10] = epoch + 1; }
        if (cta == 4 && tid == 160) GT(1403);
        __syncwarp();
    }
    if (cta == 4 && tid == 128) GT(1402);
    __syncthreads();
    if (tid == 160 && cta >= NWAITLN && cta < 128) st_rel(&g_f.xn[cta], epoch);
    __syncwarp();
    const int role = sh[8];
    return role;
}

__global__ void __cluster_dims__(2, 1, 1) __launch_bounds__(384, 1)
main_kernel(const __grid_constant__ Maps maps, const bf16* __restrict__ x, const bf16* __restrict__ mem0, const bf16* __restrict__ wr,
            const bf16* __restrict__ wd, bf16* __restrict__ out, const WPtr pw) {
    extern __shared__ __align__(1024) uint8_t smem[];
    const uint32_t sb = smem_u32(smem);
    if (threadIdx.x == 0) {
        for (int i = 0; i < MB_N; i++) mbar_init(sb + R_BAR + 8 * i, i == MB_V ? 4 : 1);
        for (int i = 0; i < GB_N; i++)
            mbar_init(sb + G_BAR + 8 * i, i == GB_WFREE || (i >= GB_EMPTY && i < GB_KV) ? 8 : (i >= GB_KVF ? 4 : (i >= GB_STG && i < GB_FREE ? 128 : 1)));
        asm volatile("fence.mbarrier_init.release.cluster;" ::: "memory");
    }
    __syncwarp();
    asm volatile("barrier.cluster.arrive.relaxed.aligned;" ::: "memory");
    if (threadIdx.x >= 352 && threadIdx.x < 352 + (int)(sizeof(Maps) / sizeof(CUtensorMap)))
        asm volatile("prefetch.tensormap [%0];" :: "l"((const CUtensorMap*)&maps + (threadIdx.x - 352)) : "memory");
    uint32_t epoch;
    asm volatile("fence.proxy.async.shared::cta;" ::: "memory");
    const int role = uni(startup(smem, x, maps, epoch, pw));
    asm volatile("barrier.cluster.wait.aligned;" ::: "memory");
    const int wg = uni(threadIdx.x >> 7);
    if (role < 64) {
#define SETREG(n) do { if ((n) < 168) asm volatile("setmaxnreg.dec.sync.aligned.u32 %0;" :: "n"(n)); if ((n) > 168) asm volatile("setmaxnreg.inc.sync.aligned.u32 %0;" :: "n"(n)); } while (0)
#define RESREG(n) do { if ((n) < 168) asm volatile("setmaxnreg.inc.sync.aligned.u32 168;"); if ((n) > 168) asm volatile("setmaxnreg.dec.sync.aligned.u32 168;"); } while (0)
        if (wg == WGA) {
            SETREG(RGA);
            rec_a(sb, role, mem0, epoch);
            RESREG(RGA);
        } else if (wg == WGB) {
            SETREG(RGB);
            rec_b(sb, role, epoch);
            RESREG(RGB);
        } else {
            SETREG(RGC);
            rec_c(sb, role, mem0, maps, epoch);
            RESREG(RGC);
        }
        ffn_phase(maps, wd, out);
        if (threadIdx.x == 0) GT(((volatile int*)(smem + SH_OFF))[8] * 8 + 6);
    } else if (role < 128) {
        if (wg < 2) {
            asm volatile("setmaxnreg.inc.sync.aligned.u32 192;");
            g_consumer(sb, role - 64, wg, epoch);
            if (threadIdx.x == 128) GT(role * 8 + 6);
        } else {
            asm volatile("setmaxnreg.dec.sync.aligned.u32 120;");
            g_producer(sb, role - 64, maps, epoch, x, wr, out);
        }
    } else {
        finalizer(64 + (threadIdx.x >> 5) * 4 + role - 128, x, wr, out, epoch);
    }
}

typedef CUresult (*EncodeFn)(CUtensorMap*, CUtensorMapDataType, cuuint32_t, void*, const cuuint64_t*, const cuuint64_t*, const cuuint32_t*, const cuuint32_t*,
                             CUtensorMapInterleave, CUtensorMapSwizzle, CUtensorMapL2promotion, CUtensorMapFloatOOBfill);
static void make_map3(EncodeFn fn, CUtensorMap* m, const void* ptr, uint64_t cols, uint64_t rows) {
    cuuint64_t dims[3] = {64, rows, cols / 64};
    cuuint64_t strides[2] = {cols * 2, 128};
    cuuint32_t box[3] = {64, 64, 2};
    cuuint32_t es[3] = {1, 1, 1};
    fn(m, CU_TENSOR_MAP_DATA_TYPE_BFLOAT16, 3, (void*)ptr, dims, strides, box, es, CU_TENSOR_MAP_INTERLEAVE_NONE, CU_TENSOR_MAP_SWIZZLE_128B,
       CU_TENSOR_MAP_L2_PROMOTION_L2_256B, CU_TENSOR_MAP_FLOAT_OOB_FILL_NONE);
}
static void make_map(EncodeFn fn, CUtensorMap* m, const void* ptr, uint64_t cols, uint64_t rows, uint32_t bcols, uint32_t brows,
                     bool f32 = false, CUtensorMapSwizzle sw = CU_TENSOR_MAP_SWIZZLE_128B) {
    cuuint64_t dims[2] = {cols, rows};
    cuuint64_t strides[1] = {cols * (f32 ? 4 : 2)};
    cuuint32_t box[2] = {bcols, brows};
    cuuint32_t es[2] = {1, 1};
    fn(m, f32 ? CU_TENSOR_MAP_DATA_TYPE_FLOAT32 : CU_TENSOR_MAP_DATA_TYPE_BFLOAT16, 2, (void*)ptr, dims, strides, box, es, CU_TENSOR_MAP_INTERLEAVE_NONE, sw,
       CU_TENSOR_MAP_L2_PROMOTION_L2_256B, CU_TENSOR_MAP_FLOAT_OOB_FILL_NONE);
}

extern "C" void kernel_launch(void* const* d_in, const int* in_sizes, int n_in, void* d_out, int out_size) {
    const bf16* x = (const bf16*)d_in[0];
    const bf16* mem0 = (const bf16*)d_in[1];
    const bf16* Wq = (const bf16*)d_in[2];
    const bf16* Wk = (const bf16*)d_in[3];
    const bf16* Wv = (const bf16*)d_in[4];
    const bf16* Wo = (const bf16*)d_in[5];
    const bf16* wr = (const bf16*)d_in[8];
    const bf16* wg = (const bf16*)d_in[9];
    const bf16* wu = (const bf16*)d_in[10];
    const bf16* wd = (const bf16*)d_in[11];
    bf16* out = (bf16*)d_out;

    static EncodeFn enc = nullptr;
    static void *pxn, *pK, *pV, *pO, *pacc;
    if (!enc) {
        cudaDriverEntryPointQueryResult qr;
        void* fn = nullptr;
        cudaGetDriverEntryPoint("cuTensorMapEncodeTiled", &fn, cudaEnableDefault, &qr);
        enc = (EncodeFn)fn;
        cudaGetSymbolAddress(&pxn, g_xn); cudaGetSymbolAddress(&pK, g_K); cudaGetSymbolAddress(&pV, g_V);
        cudaGetSymbolAddress(&pO, g_O); cudaGetSymbolAddress(&pacc, g_P);
        cudaFuncSetAttribute(main_kernel, cudaFuncAttributeMaxDynamicSharedMemorySize, SMEM_TOTAL);
    }
    Maps m;
    make_map(enc, &m.wq, Wq, HD, DM, 64, 256);
    make_map(enc, &m.wk, Wk, HD, DM, 64, 256);
    make_map(enc, &m.wv, Wv, HD, DM, 64, 256);
    make_map(enc, &m.wo, Wo, DM, HD, 64, 128);
    {
        cuuint64_t dims[5] = {DM, 2, 4, 4, HD / 32};
        cuuint64_t strides[4] = {DM * 2, 8 * DM * 2, 2 * DM * 2, 32 * DM * 2};
        cuuint32_t box[5] = {64, 2, 4, 4, 8};
        cuuint32_t es[5] = {1, 1, 1, 1, 1};
        enc(&m.wo2, CU_TENSOR_MAP_DATA_TYPE_BFLOAT16, 5, (void*)Wo, dims, strides, box, es, CU_TENSOR_MAP_INTERLEAVE_NONE, CU_TENSOR_MAP_SWIZZLE_128B,
            CU_TENSOR_MAP_L2_PROMOTION_L2_256B, CU_TENSOR_MAP_FLOAT_OOB_FILL_NONE);
    }
    make_map(enc, &m.kx, pK, HD, SQ, 64, 64);
    make_map(enc, &m.ox2, pO, HD, SQ, 64, 64);
    make_map(enc, &m.xn2, pxn, DM, SQ, 64, 64);
    make_map3(enc, &m.kx3, pK, HD, SQ); make_map3(enc, &m.vx3, pV, HD, SQ);
    make_map(enc, &m.wg, wg, FF, DM, 32, 256, false, CU_TENSOR_MAP_SWIZZLE_NONE);
    make_map(enc, &m.wu, wu, FF, DM, 32, 256, false, CU_TENSOR_MAP_SWIZZLE_NONE);

    cudaStream_t st = cudaStreamPerThread;
    main_kernel<<<NCTA, 384, SMEM_TOTAL, st>>>(m, x, mem0, wr, wd, out, WPtr{Wq, Wk, Wv, Wo});
}
```

```cpp
#include <cuda_runtime.h>
#include <cuda_bf16.h>
#include <cuda.h>
#include <stdint.h>
#include <stddef.h>

typedef __nv_bfloat16 bf16;

constexpr int SQ = 2048, DM = 512, NH = 32, DH = 128, NSEG = 64, HD = 4096, FF = 1792;

constexpr int NT = 32;
#define SPEC_TILES 30
__device__ __align__(1024) bf16 g_xn[SQ * DM];
__device__ __align__(1024) bf16 g_K[SQ * HD];
__device__ __align__(1024) bf16 g_V[SQ * HD];
__device__ __align__(1024) bf16 g_O[SQ * HD];
__device__ __align__(1024) uint32_t g_KVf[NSEG][NH][1024];
__device__ __align__(1024) bf16 g_P[8 * SQ * DM];
__device__ __align__(1024) bf16 g_h[SQ * DM];
__device__ __align__(1024) bf16 g_hn[SQ * DM];
__device__ uint8_t g_xraw[12 << 20];
#define XPG 0
__device__ __forceinline__ uint64_t xpage() { return (((uint64_t)g_xraw + (2 << 20) - 1) & ~(uint64_t)((2 << 20) - 1)) + ((uint64_t)XPG << 21); }
constexpr uint32_t XR3 = (1u << 20) | (1u << 19) | (1u << 12);
__device__ __forceinline__ uint32_t aslot(uint32_t s) { return ((s & 1) << 18) | ((s & 2) << 19) | ((s & 4) * 0xc000u); }
__device__ __forceinline__ uint32_t acc_base(uint32_t W) { return ((W & 2) ? 0x3000u : 0u) + ((W & 4) << 12) + (W & 1) * 2048; }
__device__ __forceinline__ uint32_t ext_base(uint32_t W) { return 0x8000u + ((W & 4) << 12) + (W & 3) * 1024; }
#define XHS 256
#define XSS 32
__device__ __forceinline__ uint32_t zero_off(uint32_t c, uint32_t ln) {
    return ln < 8 ? acc_base(c >> 3) + (c & 7) * 256 + ln * 16 : ext_base(c >> 3) + ((c >> 2) & 1) * XHS + ((c >> 1) & 1) * XSS + (c & 1) * 16;
}
struct Flags {
    uint32_t kv[NT][NH][2];
    uint32_t o[NT][8][32];
    uint32_t rec[64];
    uint32_t xn[128];
    uint32_t rload[64];
    uint32_t p[NT][32];
    uint32_t rows[2][128];
    uint4 cand[2][128];
    uint4 norm[64];
};
__device__ __align__(1024) Flags g_f;
__device__ __align__(1024) uint4 g_yp[2][FF / 32][DM];
__device__ __align__(1024) uint32_t g_table[66 * 8];
__device__ __align__(256) uint32_t g_ticket[64];
__device__ uint32_t g_epoch;
#define HOLD 6
#define HSPLIT 24
#define EREL 0
#define PFK 2
#define PFO 0
#define PFS 0
#define NWAITLN 8
#define WGA 0
#define WGB 1
#define WGC (3 - WGA - WGB)
#define NPROBE 3
constexpr int NCTA = 132;
constexpr int NFW = 112;
__device__ uint32_t g_abort;
__device__ long long g_dbg[4096];
#define TR(slot, v)

__device__ __forceinline__ uint32_t smem_u32(const void* p) { return (uint32_t)__cvta_generic_to_shared(p); }
__device__ __forceinline__ void mbar_init(uint32_t a, uint32_t c) { asm volatile("mbarrier.init.shared::cta.b64 [%0], %1;" :: "r"(a), "r"(c) : "memory"); }
__device__ __forceinline__ void mbar_expect_tx(uint32_t a, uint32_t tx) { asm volatile("mbarrier.arrive.expect_tx.shared::cta.b64 _, [%0], %1;" :: "r"(a), "r"(tx) : "memory"); }
__device__ __forceinline__ void mbar_arrive(uint32_t a) { asm volatile("mbarrier.arrive.shared::cta.b64 _, [%0];" :: "r"(a) : "memory"); }
__device__ __forceinline__ void mbar_arrive_if(uint32_t a, uint32_t pred) {
    asm volatile("{\n.reg .pred p;\nsetp.ne.u32 p, %1, 0;\n@p mbarrier.arrive.shared::cta.b64 _, [%0];\n}" :: "r"(a), "r"(pred) : "memory");
}
__device__ __forceinline__ bool mbar_try(uint32_t a, uint32_t ph) {
    uint32_t ok;
    asm volatile("{\n.reg .pred p;\nmbarrier.try_wait.parity.shared::cta.b64 p, [%1], %2;\nselp.u32 %0, 1, 0, p;\n}" : "=r"(ok) : "r"(a), "r"(ph) : "memory");
    return ok != 0;
}
#define SPINLOG 20
constexpr uint32_t SPIN_LIMIT = 1u << SPINLOG;
#define ABORT(code_) atomicCAS(&g_abort, 0u, (code_))
__device__ __forceinline__ void mbar_wait(uint32_t a, uint32_t ph) {
    uint32_t n = 0;
#pragma unroll 1
    while (!mbar_try(a, ph)) { if (++n > SPIN_LIMIT) { ABORT(1); break; } }
}
__device__ __forceinline__ void bar_sync(int id, int n) { asm volatile("bar.sync %0, %1;" :: "r"(id), "r"(n) : "memory"); }
__device__ __forceinline__ void bar_arrive(int id, int n) { asm volatile("bar.arrive %0, %1;" :: "r"(id), "r"(n) : "memory"); }

__device__ __forceinline__ void ldsm4(uint32_t* r, uint32_t a) {
    asm volatile("ldmatrix.sync.aligned.m8n8.x4.shared.b16 {%0,%1,%2,%3}, [%4];" : "=r"(r[0]), "=r"(r[1]), "=r"(r[2]), "=r"(r[3]) : "r"(a) : "memory");
}
__device__ __forceinline__ void ldsm4t(uint32_t* r, uint32_t a) {
    asm volatile("ldmatrix.sync.aligned.m8n8.x4.trans.shared.b16 {%0,%1,%2,%3}, [%4];" : "=r"(r[0]), "=r"(r[1]), "=r"(r[2]), "=r"(r[3]) : "r"(a) : "memory");
}
__device__ __forceinline__ void stsm4t(uint32_t a, uint32_t r0, uint32_t r1, uint32_t r2, uint32_t r3) {
    asm volatile("stmatrix.sync.aligned.m8n8.x4.trans.shared.b16 [%0], {%1,%2,%3,%4};" :: "r"(a), "r"(r0), "r"(r1), "r"(r2), "r"(r3) : "memory");
}
__device__ __forceinline__ void stsm4(uint32_t a, uint32_t r0, uint32_t r1, uint32_t r2, uint32_t r3) {
    asm volatile("stmatrix.sync.aligned.m8n8.x4.shared.b16 [%0], {%1,%2,%3,%4};" :: "r"(a), "r"(r0), "r"(r1), "r"(r2), "r"(r3) : "memory");
}
__device__ __forceinline__ uint32_t movm(uint32_t a) { uint32_t d; asm volatile("movmatrix.sync.aligned.m8n8.trans.b16 %0, %1;" : "=r"(d) : "r"(a)); return d; }
__device__ __forceinline__ void mma16816(float* d, uint32_t a0, uint32_t a1, uint32_t a2, uint32_t a3, uint32_t b0, uint32_t b1) {
    asm volatile("mma.sync.aligned.m16n8k16.row.col.f32.bf16.bf16.f32 {%0,%1,%2,%3}, {%4,%5,%6,%7}, {%8,%9}, {%0,%1,%2,%3};"
        : "+f"(d[0]), "+f"(d[1]), "+f"(d[2]), "+f"(d[3]) : "r"(a0), "r"(a1), "r"(a2), "r"(a3), "r"(b0), "r"(b1));
}
__device__ __forceinline__ void mma1688(float* d, uint32_t a0, uint32_t a1, uint32_t b0) {
    asm volatile("mma.sync.aligned.m16n8k8.row.col.f32.bf16.bf16.f32 {%0,%1,%2,%3}, {%4,%5}, {%6}, {%0,%1,%2,%3};"
        : "+f"(d[0]), "+f"(d[1]), "+f"(d[2]), "+f"(d[3]) : "r"(a0), "r"(a1), "r"(b0));
}
__device__ __forceinline__ uint32_t pack2(float a, float b) { uint32_t d; asm("cvt.rn.bf16x2.f32 %0, %1, %2;" : "=r"(d) : "f"(b), "f"(a)); return d; }
__device__ __forceinline__ float bf_lo(uint32_t w) { return __uint_as_float(w << 16); }
__device__ __forceinline__ float bf_hi(uint32_t w) { return __uint_as_float(w & 0xffff0000u); }
__device__ __forceinline__ float rbf(float x) { return __bfloat162float(__float2bfloat16_rn(x)); }

__device__ __forceinline__ void sts128(uint32_t a, float x, float y, float z, float w) { asm volatile("st.shared.v4.f32 [%0], {%1,%2,%3,%4};" :: "r"(a), "f"(x), "f"(y), "f"(z), "f"(w) : "memory"); }
__device__ __forceinline__ void sts128u(uint32_t a, uint32_t x, uint32_t y, uint32_t z, uint32_t w) { asm volatile("st.shared.v4.b32 [%0], {%1,%2,%3,%4};" :: "r"(a), "r"(x), "r"(y), "r"(z), "r"(w) : "memory"); }
__device__ __forceinline__ void sts64(uint32_t a, float x, float y) { asm volatile("st.shared.v2.f32 [%0], {%1,%2};" :: "r"(a), "f"(x), "f"(y) : "memory"); }
__device__ __forceinline__ float4 lds128(uint32_t a) { float4 v; asm volatile("ld.shared.v4.f32 {%0,%1,%2,%3}, [%4];" : "=f"(v.x), "=f"(v.y), "=f"(v.z), "=f"(v.w) : "r"(a) : "memory"); return v; }
__device__ __forceinline__ float2 lds64(uint32_t a) { float2 v; asm volatile("ld.shared.v2.f32 {%0,%1}, [%2];" : "=f"(v.x), "=f"(v.y) : "r"(a) : "memory"); return v; }
__device__ __forceinline__ uint2 lds64u(uint32_t a) { uint2 v; asm volatile("ld.shared.v2.b32 {%0,%1}, [%2];" : "=r"(v.x), "=r"(v.y) : "r"(a) : "memory"); return v; }
__device__ __forceinline__ float4 lds128v(uint32_t a) { float4 v; asm volatile("ld.volatile.shared.v4.f32 {%0,%1,%2,%3}, [%4];" : "=f"(v.x), "=f"(v.y), "=f"(v.z), "=f"(v.w) : "r"(a) : "memory"); return v; }
__device__ __forceinline__ float2 lds64v(uint32_t a) { float2 v; asm volatile("ld.volatile.shared.v2.f32 {%0,%1}, [%2];" : "=f"(v.x), "=f"(v.y) : "r"(a) : "memory"); return v; }
__device__ __forceinline__ uint4 lds128uv(uint32_t a) { uint4 v; asm volatile("ld.volatile.shared.v4.b32 {%0,%1,%2,%3}, [%4];" : "=r"(v.x), "=r"(v.y), "=r"(v.z), "=r"(v.w) : "r"(a) : "memory"); return v; }
__device__ __forceinline__ void st_async4(uint32_t a, float x, float y, float z, float w, uint32_t mb) {
    asm volatile("st.async.weak.shared::cluster.mbarrier::complete_tx::bytes.v4.f32 [%0], {%1,%2,%3,%4}, [%5];" :: "r"(a), "f"(x), "f"(y), "f"(z), "f"(w), "r"(mb) : "memory");
}
__device__ __forceinline__ void st_async2(uint32_t a, uint32_t x, uint32_t y, uint32_t mb) {
    asm volatile("st.async.weak.shared::cluster.mbarrier::complete_tx::bytes.v2.b32 [%0], {%1,%2}, [%3];" :: "r"(a), "r"(x), "r"(y), "r"(mb) : "memory");
}
__device__ __forceinline__ uint32_t ldg_rlx(const uint32_t* p) { uint32_t v; asm volatile("ld.relaxed.gpu.global.b32 %0, [%1];" : "=r"(v) : "l"(p) : "memory"); return v; }
__device__ __forceinline__ uint4 ldg_rlx4(const uint32_t* p) { uint4 v; asm volatile("ld.relaxed.gpu.global.v4.b32 {%0,%1,%2,%3}, [%4];" : "=r"(v.x), "=r"(v.y), "=r"(v.z), "=r"(v.w) : "l"(p) : "memory"); return v; }
__device__ __forceinline__ uint4 ldg_rlx4_if(const uint32_t* p, bool c) {
    uint4 v;
    asm volatile("{\n.reg .pred p;\nsetp.ne.u32 p, %5, 0;\nmov.b32 %0, 0;\nmov.b32 %1, 0;\nmov.b32 %2, 0;\nmov.b32 %3, 0;\n@p ld.relaxed.gpu.global.v4.b32 {%0,%1,%2,%3}, [%4];\n}"
                 : "=r"(v.x), "=r"(v.y), "=r"(v.z), "=r"(v.w) : "l"(p), "r"((uint32_t)c) : "memory");
    return v;
}
__device__ __forceinline__ void stg_rlx(uint32_t* p, uint32_t v) { asm volatile("st.relaxed.gpu.global.b32 [%0], %1;" :: "l"(p), "r"(v) : "memory"); }
__device__ __forceinline__ void tma2d(uint32_t dst, const CUtensorMap* tm, int c0, int c1, uint32_t mb) {
    asm volatile("cp.async.bulk.tensor.2d.shared::cluster.global.mbarrier::complete_tx::bytes [%0], [%1, {%3, %4}], [%2];"
        :: "r"(dst), "l"((uint64_t)tm), "r"(mb), "r"(c0), "r"(c1) : "memory");
}

__device__ __forceinline__ void tma3d(uint32_t dst, const CUtensorMap* tm, int row, int chunk, uint32_t mb) {
    asm volatile("cp.async.bulk.tensor.3d.shared::cluster.global.mbarrier::complete_tx::bytes [%0], [%1, {%3, %4, %5}], [%2];"
        :: "r"(dst), "l"((uint64_t)tm), "r"(mb), "r"(0), "r"(row), "r"(chunk) : "memory");
}
#define EF 0xff
__device__ __forceinline__ uint64_t pol_ef(int bit) {
    uint64_t p;
    if ((EF >> bit) & 1) asm("createpolicy.fractional.L2::evict_first.b64 %0, 1.0;" : "=l"(p));
    else asm("createpolicy.fractional.L2::evict_normal.b64 %0, 1.0;" : "=l"(p));
    return p;
}
__device__ __forceinline__ void tma3d_h(uint32_t dst, const CUtensorMap* tm, int row, int chunk, uint32_t mb, uint64_t pol) {
    asm volatile("cp.async.bulk.tensor.3d.shared::cluster.global.mbarrier::complete_tx::bytes.L2::cache_hint [%0], [%1, {%3, %4, %5}], [%2], %6;"
        :: "r"(dst), "l"((uint64_t)tm), "r"(mb), "r"(0), "r"(row), "r"(chunk), "l"(pol) : "memory");
}
__device__ __forceinline__ void tma2d_h(uint32_t dst, const CUtensorMap* tm, int c0, int c1, uint32_t mb, uint64_t pol) {
    asm volatile("cp.async.bulk.tensor.2d.shared::cluster.global.mbarrier::complete_tx::bytes.L2::cache_hint [%0], [%1, {%3, %4}], [%2], %5;"
        :: "r"(dst), "l"((uint64_t)tm), "r"(mb), "r"(c0), "r"(c1), "l"(pol) : "memory");
}
__device__ __forceinline__ void tma2d_mc_h(uint32_t dst, const CUtensorMap* tm, int c0, int c1, uint32_t mb, uint64_t pol) {
    asm volatile("cp.async.bulk.tensor.2d.shared::cluster.global.mbarrier::complete_tx::bytes.multicast::cluster.L2::cache_hint [%0], [%1, {%3, %4}], [%2], %5, %6;"
        :: "r"(dst), "l"((uint64_t)tm), "r"(mb), "r"(c0), "r"(c1), "h"((uint16_t)3), "l"(pol) : "memory");
}
__device__ __forceinline__ uint4 ldg4_h(const void* p, uint64_t pol) {
    uint4 v;
    asm volatile("ld.relaxed.gpu.global.L2::cache_hint.v4.b32 {%0,%1,%2,%3}, [%4], %5;" : "=r"(v.x), "=r"(v.y), "=r"(v.z), "=r"(v.w) : "l"(p), "l"(pol) : "memory");
    return v;
}
__device__ __forceinline__ void stg4_h(void* p, uint4 v, uint64_t pol) {
    asm volatile("st.relaxed.gpu.global.L2::cache_hint.v4.b32 [%0], {%1,%2,%3,%4}, %5;" :: "l"(p), "r"(v.x), "r"(v.y), "r"(v.z), "r"(v.w), "l"(pol) : "memory");
}
__device__ __forceinline__ void tma2d_mc(uint32_t dst, const CUtensorMap* tm, int c0, int c1, uint32_t mb) {
    asm volatile("cp.async.bulk.tensor.2d.shared::cluster.global.mbarrier::complete_tx::bytes.multicast::cluster [%0], [%1, {%3, %4}], [%2], %5;"
        :: "r"(dst), "l"((uint64_t)tm), "r"(mb), "r"(c0), "r"(c1), "h"((uint16_t)3) : "memory");
}
__device__ __forceinline__ void mbar_arrive2_if(uint32_t a, uint32_t pred) {
    asm volatile("{\n.reg .pred p;\nsetp.ne.u32 p, %1, 0;\n@p mbarrier.arrive.shared::cta.b64 _, [%0];\n@p mbarrier.arrive.shared::cluster.b64 _, [%2];\n}"
                 :: "r"(a), "r"(pred), "r"(a ^ 0x01000000u) : "memory");
}
__device__ __forceinline__ void tma_pf3d(const CUtensorMap* tm, int row, int chunk) {
    asm volatile("cp.async.bulk.prefetch.tensor.3d.L2.global.tile [%0, {%1, %2, %3}];" :: "l"((uint64_t)tm), "r"(0), "r"(row), "r"(chunk) : "memory");
}
__device__ __forceinline__ void tma_pf2d(const CUtensorMap* tm, int c0, int c1) {
    asm volatile("cp.async.bulk.prefetch.tensor.2d.L2.global.tile [%0, {%1, %2}];" :: "l"((uint64_t)tm), "r"(c0), "r"(c1) : "memory");
}
__device__ __forceinline__ void tma_store3d(const CUtensorMap* tm, uint32_t src, int row, int chunk) {
    asm volatile("cp.async.bulk.tensor.3d.global.shared::cta.bulk_group [%0, {%2, %3, %4}], [%1];" :: "l"((uint64_t)tm), "r"(src), "r"(0), "r"(row), "r"(chunk) : "memory");
}
__device__ __forceinline__ void bulk_store(void* dst, uint32_t src, uint32_t bytes) {
    asm volatile("cp.async.bulk.global.shared::cta.bulk_group [%0], [%1], %2;" :: "l"(dst), "r"(src), "r"(bytes) : "memory");
}
#define GT(slot)
#define CNT(k)
#define CNT2(k, c)
#define TS(i, dep)
#define TSACC()
#define TSDECL
struct Maps { CUtensorMap wq, wk, wv, wo, wo2, kx, ox2, kx3, vx3, xn2, wg, wu; };
typedef Maps RecMaps;
__device__ __forceinline__ void st_rel(uint32_t* p, uint32_t v) { asm volatile("st.release.gpu.global.u32 [%0], %1;" :: "l"(p), "r"(v) : "memory"); }
#define PUBLISH(p, v) st_rel(p, v)
__device__ __forceinline__ uint2 ldg_rlx2(const uint32_t* p) { uint2 v; asm volatile("ld.relaxed.gpu.global.v2.b32 {%0,%1}, [%2];" : "=r"(v.x), "=r"(v.y) : "l"(p) : "memory"); return v; }
__device__ __forceinline__ void wait_eq2(const uint32_t* p, uint32_t e, int code) {
    uint32_t n = 0;
#pragma unroll 1
    while (true) { uint2 v = ldg_rlx2(p); if (v.x == e && v.y == e) break; __nanosleep(64); if (++n > SPIN_LIMIT) { ABORT(code); break; } }
}
__device__ __forceinline__ void wait_eq4(const uint32_t* p, uint32_t e, int code) {
    uint32_t n = 0;
#pragma unroll 1
    while (true) { uint4 v = ldg_rlx4(p); if (v.x == e && v.y == e && v.z == e && v.w == e) break; __nanosleep(64); if (++n > SPIN_LIMIT) { ABORT(code); break; } }
}
__device__ __forceinline__ void wait_rec(const uint32_t* p, uint32_t e, uint32_t steps) {
    uint32_t n = 0;
#pragma unroll 1
    while (true) {
        uint2 v = ldg_rlx2(p);
        if (__all_sync(0xffffffffu, (v.x >> 8) == e && (v.y >> 8) == e && (v.x & 255) >= steps && (v.y & 255) >= steps)) break;
        __nanosleep(64); if (++n > SPIN_LIMIT) { ABORT(8); break; }
    }
}

constexpr int R_QK1 = 0;
constexpr int R_WO = 65536;
constexpr int R_T = 131072;
constexpr int R_SLOT1 = R_T;
constexpr int R_MEMB = R_T + 24576;
constexpr int R_QP = R_MEMB + 8192;
constexpr int R_VRED = R_QP + 4096;
constexpr int R_STG = R_VRED + 2048;
constexpr int R_AX = R_STG + 2048;
constexpr int R_SLOT0 = 196608;
constexpr int R_SLOC = R_SLOT0 + 24576;
constexpr int R_SREM = R_SLOC + 1536;
constexpr int R_VB = R_SREM + 1536;
constexpr int R_MISC = R_VB + 2048;
constexpr int R_LT = R_MISC + 128;
constexpr int R_BAR = 229888;
constexpr int R_TS = 229888 + 128;
static_assert(R_AX + 24576 <= R_SLOT0 && R_LT + 2560 <= 229376, "smem map");
enum { MB_W0 = 0, MB_W1, MB_WV, MB_WO, MB_S, MB_FULL0, MB_FULL1, MB_V, MB_N };

__device__ __forceinline__ float ex2(float x) { float y; asm("ex2.approx.ftz.f32 %0, %1;" : "=f"(y) : "f"(x)); return y; }
__device__ __forceinline__ float rcpf(float x) { float y; asm("rcp.approx.ftz.f32 %0, %1;" : "=f"(y) : "f"(x)); return y; }
__device__ __forceinline__ void mma16816z(float* d, uint32_t a0, uint32_t a1, uint32_t a2, uint32_t a3, uint32_t b0, uint32_t b1) {
    asm volatile("mma.sync.aligned.m16n8k16.row.col.f32.bf16.bf16.f32 {%0,%1,%2,%3}, {%4,%5,%6,%7}, {%8,%9}, {%10,%10,%10,%10};"
        : "=f"(d[0]), "=f"(d[1]), "=f"(d[2]), "=f"(d[3]) : "r"(a0), "r"(a1), "r"(a2), "r"(a3), "r"(b0), "r"(b1), "f"(0.f));
}
__device__ __forceinline__ void mma1688hz(float* d, uint32_t a0, uint32_t a1, uint32_t b0) {
    asm volatile("mma.sync.aligned.m16n8k8.row.col.f32.f16.f16.f32 {%0,%1,%2,%3}, {%4,%5}, {%6}, {%7,%7,%7,%7};"
        : "=f"(d[0]), "=f"(d[1]), "=f"(d[2]), "=f"(d[3]) : "r"(a0), "r"(a1), "r"(b0), "f"(0.f));
}
#define MMA(d, a, b0, b1) mma16816(d, a[0], a[1], a[2], a[3], b0, b1)
#define MMAZ(d, a, b0, b1) mma16816z(d, a[0], a[1], a[2], a[3], b0, b1)
#define MMAF(first, d, a, b0, b1) do { if (first) MMAZ(d, a, b0, b1); else MMA(d, a, b0, b1); } while (0)

__device__ __forceinline__ uint32_t uni(uint32_t x) { return __reduce_max_sync(0xffffffffu, x); }
__device__ __forceinline__ void mbar_wait_u(uint32_t a, uint32_t ph) {
    uint32_t n = 0;
#pragma unroll 1
    while (!__all_sync(0xffffffffu, mbar_try(a, ph))) { if (++n > SPIN_LIMIT) { ABORT(1); break; } }
}
__device__ __forceinline__ void mbar_wait_p(uint32_t a, uint32_t ph) {
    asm volatile("{\n.reg .pred p, q;\n.reg .u32 n;\nmov.u32 n, 0;\nWL: mbarrier.try_wait.parity.shared::cta.b64 p, [%0], %1;\nadd.u32 n, n, 1;\n"
                 "setp.lt.and.u32 q, n, %2, !p;\n@q bra.uni WL;\n}" :: "r"(a), "r"(ph), "n"(SPIN_LIMIT) : "memory");
}
__device__ __forceinline__ uint32_t mbar_test(uint32_t a, uint32_t ph) {
    uint32_t ok;
    asm volatile("{\n.reg .pred p;\nmbarrier.test_wait.parity.shared::cta.b64 p, [%1], %2;\nselp.u32 %0, 1, 0, p;\n}" : "=r"(ok) : "r"(a), "r"(ph) : "memory");
    return ok;
}
__device__ __forceinline__ uint32_t opaque(uint32_t x) { return __shfl_sync(0xffffffffu, x, threadIdx.x & 31); }
__device__ __forceinline__ const uint32_t* mkptr(uint32_t lo, uint32_t hi) { uint64_t r; asm("mov.b64 %0, {%1, %2};" : "=l"(r) : "r"(lo), "r"(hi)); return (const uint32_t*)r; }
__device__ __forceinline__ uint32_t prmt(uint32_t a, uint32_t b, uint32_t s) { uint32_t d; asm("prmt.b32 %0, %1, %2, %3;" : "=r"(d) : "r"(a), "r"(b), "r"(s)); return d; }
__device__ __forceinline__ uint32_t packh2(float a, float b) { uint32_t d; asm("cvt.rn.f16x2.f32 %0, %1, %2;" : "=r"(d) : "f"(b), "f"(a)); return d; }
__device__ __forceinline__ uint32_t hadd2b(uint32_t a, uint32_t b) { uint32_t d; asm("add.rn.bf16x2 %0, %1, %2;" : "=r"(d) : "r"(a), "r"(b)); return d; }
__device__ __forceinline__ uint32_t hmul2b(uint32_t a, uint32_t b) { uint32_t d; asm("mul.rn.bf16x2 %0, %1, %2;" : "=r"(d) : "r"(a), "r"(b)); return d; }
__device__ __forceinline__ uint32_t amax2b(uint32_t a, uint32_t b) { uint32_t d; asm("max.xorsign.abs.bf16x2 %0, %1, %2;" : "=r"(d) : "r"(a), "r"(b)); return d; }
__device__ __forceinline__ uint32_t amax2h(uint32_t a, uint32_t b) { uint32_t d; asm("max.xorsign.abs.f16x2 %0, %1, %2;" : "=r"(d) : "r"(a), "r"(b)); return d; }
__device__ __forceinline__ void sts32(uint32_t a, uint32_t x) { asm volatile("st.shared.b32 [%0], %1;" :: "r"(a), "r"(x) : "memory"); }
__device__ __forceinline__ uint32_t lds32v_(uint32_t a) { uint32_t v; asm volatile("ld.volatile.shared.b32 %0, [%1];" : "=r"(v) : "r"(a) : "memory"); return v; }
__device__ __forceinline__ void stg4(void* p, uint4 v) { asm volatile("st.relaxed.gpu.global.v4.b32 [%0], {%1,%2,%3,%4};" :: "l"(p), "r"(v.x), "r"(v.y), "r"(v.z), "r"(v.w) : "memory"); }
__device__ __forceinline__ void lds_frag(uint32_t* r, uint32_t a) {
    asm volatile("ld.shared.v4.b32 {%0,%1,%2,%3}, [%4];" : "=r"(r[0]), "=r"(r[1]), "=r"(r[2]), "=r"(r[3]) : "r"(a) : "memory");
}
__device__ __forceinline__ void lds_fragv(uint32_t* r, uint32_t a) {
    asm volatile("ld.volatile.shared.v4.b32 {%0,%1,%2,%3}, [%4];" : "=r"(r[0]), "=r"(r[1]), "=r"(r[2]), "=r"(r[3]) : "r"(a) : "memory");
}
__device__ __forceinline__ uint32_t xorv(uint32_t a, uint32_t b) { uint32_t d; asm volatile("xor.b32 %0, %1, %2;" : "=r"(d) : "r"(a), "r"(b)); return d; }
#define SCHED(k) asm volatile("{\n.reg .pred p;\nsetp.ne.u32 p, %0, %1;\n@p bra.uni SD;\nSL: nanosleep.u32 64;\nbra.uni SL;\nSD:\n}" :: "r"(sbu - s), "n"(k) : "memory")
#define PINM() asm volatile("{\n.reg .pred p;\nsetp.eq.u32 p, %0, 1;\n@p st.shared.u32 [%0], 0;\n}" :: "r"(sbu) : "memory")
__device__ __forceinline__ uint32_t or_and(uint32_t a, uint32_t b, uint32_t c) { uint32_t d; asm("lop3.b32 %0, %1, %2, %3, 0xF8;" : "=r"(d) : "r"(a), "r"(b), "r"(c)); return d; }
__device__ __forceinline__ uint32_t pack2v(float a, float b) { uint32_t d; asm volatile("cvt.rn.bf16x2.f32 %0, %1, %2;" : "=r"(d) : "f"(b), "f"(a)); return d; }
#define FU(x) __float_as_uint(x)
__device__ __forceinline__ uint32_t clk32() { uint32_t t; asm volatile("mov.u32 %0, %%clock;" : "=r"(t) :: "memory"); return t; }
__device__ __forceinline__ void spin_until(uint32_t t0, uint32_t d) {
    if (d) {
#pragma unroll 1
        while (__any_sync(0xffffffffu, clk32() - t0 < d)) {}
    }
}
constexpr int SH_OFF = 229376 + 384;
constexpr uint32_t HONE2 = 0x3c003c00u, HCNT2 = 0x50005000u;

__device__ __forceinline__ uint64_t desc_sw128(uint32_t addr, uint32_t lbo, uint32_t sbo) {
    return (uint64_t)((addr & 0x3FFFF) >> 4) | ((uint64_t)(lbo >> 4) << 16) | ((uint64_t)(sbo >> 4) << 32) | (1ull << 62);
}
#define DP 390
#define NAX 3
#define NXL 0
#define NCX 2
#define NCL 1
#define DC 0
#define FLIP 1
#define VTA 1
#define KXB 4
#define KXI 5
#define ANB 3
#define BNB 3
#define CNB 3
#define SMA 0
#define SMB 0
#define SMC 0x01
#define IVA 0
#define RGA 160
#define RGC 160
#define RGB (504 - RGA - RGC)
#define NRW 8
#define NBR 16
#define E0 0
#define E1 6
#define E2 4
#define E3 8
#define IV 2
#define DEX 0
#define G2V 0
#define G2K 2
#define VDEP 0
#define AEARLY 0
#define VTP 2
#define LORD 1
#define TRK 1
#define TW 0
#define T2N 14
#define TEARLY 1
#define DT 0
#define NB0 0
#define NB1 9
#define DB2 80
#define DITHER 0
#define DA 40
#define DB 40
#define DS 200

__device__ __forceinline__ uint32_t wrow_off(int kk, int ch) {
    const int lane = threadIdx.x & 31, r = lane & 7;
    const int row = 64 * (kk >> 2) + 32 * (r & 1) + 16 * (kk & 1) + 8 * (lane >> 4) + 4 * ((kk >> 1) & 1) + (r >> 1);
    return row * 128 + ((ch ^ (row & 7)) << 4);
}
template <int K> __device__ __forceinline__ void sched(uint32_t key) {
    asm volatile("{\n.reg .pred p;\nsetp.ne.u32 p, %0, %1;\n@p bra.uni SD;\nSL: nanosleep.u32 64;\nbra.uni SL;\nSD:\n}" :: "r"(key), "n"(K) : "memory");
}
__device__ __forceinline__ void sched_i(int i, uint32_t key) {
    if (i == -1) sched<20>(key); if (i == 0) sched<21>(key); if (i == 1) sched<22>(key); if (i == 2) sched<23>(key);
    if (i == 3) sched<24>(key); if (i == 4) sched<25>(key); if (i == 5) sched<26>(key); if (i == 6) sched<27>(key);
}
template <int NB, int SM, class F>
__device__ __forceinline__ void g1(float* q0, float* k0, uint32_t (*wq)[4], uint32_t (*wk)[4], uint32_t ga, uint32_t key, F&& hook) {
    float q1[4], k1[4];
    uint32_t b[NB][4];
#pragma unroll
    for (int i = 0; i < NB; i++) ldsm4(b[i], ga + i * 512);
    hook(-1, b[0]);
    if (SM & 1) sched_i(-1, key);
#pragma unroll
    for (int i = 0; i < 8; i++) {
        uint32_t* c = b[i % NB];
        MMAF(i == 0, q0, wq[2 * i], c[0], c[1]); MMAF(i == 0, k0, wk[2 * i], c[0], c[1]);
        MMAF(i == 0, q1, wq[2 * i + 1], c[2], c[3]); MMAF(i == 0, k1, wk[2 * i + 1], c[2], c[3]);
        const uint32_t cc_[4] = {c[0], c[1], c[2], c[3]};
        if (i + NB < 8) ldsm4(b[i % NB], ga + (i + NB) * 512);
        hook(i, cc_);
        if ((SM >> (i + 1)) & 1) sched_i(i, key);
    }
#pragma unroll
    for (int i = 0; i < 4; i++) { q0[i] += q1[i]; k0[i] += k1[i]; }
}
__device__ __forceinline__ float frag_norm2(uint32_t (*w)[4]) {
    float d0[4], d1[4];
#pragma unroll
    for (int i = 0; i < 32; i++) { MMAF(i == 0, d0, w[i], w[i][0], w[i][2]); MMAF(i == 0, d1, w[i], w[i][1], w[i][3]); }
    const int lane = threadIdx.x & 31, g = lane >> 2, t = lane & 3;
    float v = g == 2 * t ? d0[0] + d1[2] : (g == 2 * t + 1 ? d0[1] + d1[3] : 0.f);
#pragma unroll
    for (int o = 16; o; o >>= 1) v += __shfl_xor_sync(0xffffffffu, v, o);
    return v;
}
__device__ __forceinline__ void load_slot(uint32_t sb, int c, int tile, const Maps& maps) {
    const uint32_t dst = sb + ((tile & 1) ? R_SLOT1 : R_SLOT0), mb = sb + R_BAR + 8 * (MB_FULL0 + (tile & 1));
    mbar_expect_tx(mb, 24576);
    if ((EF >> 8) & 1) {
        tma2d_h(dst + 16384, &maps.kx, c * 64, tile * 64, mb, pol_ef(8));
        tma3d_h(dst, &maps.vx3, tile * 64, (c >> 1) * 2, mb, pol_ef(8));
    } else {
        tma2d(dst + 16384, &maps.kx, c * 64, tile * 64, mb);
        tma3d(dst, &maps.vx3, tile * 64, (c >> 1) * 2, mb);
    }
}
__device__ __forceinline__ uint32_t put_mem0(uint32_t sb, int W, const bf16* __restrict__ mem0) {
    const int lane = threadIdx.x & 31;
    const uint4 a = *(const uint4*)(mem0 + (lane & 7) * DM + W * 64 + (lane >> 3) * 8), b = *(const uint4*)(mem0 + (lane & 7) * DM + W * 64 + 32 + (lane >> 3) * 8);
    const uint4 m0 = make_uint4(prmt(a.x, b.x, 0x5410u), prmt(a.x, b.x, 0x7632u), prmt(a.y, b.y, 0x5410u), prmt(a.y, b.y, 0x7632u));
    const uint4 m1 = make_uint4(prmt(a.z, b.z, 0x5410u), prmt(a.z, b.z, 0x7632u), prmt(a.w, b.w, 0x5410u), prmt(a.w, b.w, 0x7632u));
    bar_sync(3, 256);
    sts128u(sb + R_MEMB + W * 1024 + lane * 16, m0.x, m0.y, m0.z, m0.w);
    sts128u(sb + R_MEMB + W * 1024 + 512 + lane * 16, m1.x, m1.y, m1.z, m1.w);
    return amax2b(amax2b(amax2b(m0.x, m0.y), amax2b(m0.z, m0.w)), amax2b(amax2b(m1.x, m1.y), amax2b(m1.z, m1.w)));
}
#define PUT_MAX(rL, W) sts32(rL + R_STG + 1024 + ((W) >> 2) * 512 + ((W) & 3) * 4, amax2b(amax2b(mx, my), mz));
__device__ __forceinline__ uint32_t h2b(uint32_t w) {
    uint32_t d;
    asm("{\n.reg .f16 l, h;\n.reg .f32 a, b;\nmov.b32 {l, h}, %1;\ncvt.f32.f16 a, l;\ncvt.f32.f16 b, h;\ncvt.rn.bf16x2.f32 %0, b, a;\n}" : "=r"(d) : "r"(w));
    return d;
}
#define GATHER1(HALF)                                                                                           \
        {                                                                                                       \
            const uint4 x0 = ldg_rlx4(pm), x1 = ldg_rlx4(pm + 256); const uint2 y = ldg_rlx2(px);                 \
            cw = (sel & 0x4000u) ? prmt(x0.w, x1.w, 0x7632u) : prmt(y.x, y.y, 0x5410u);                         \
            const uint32_t p0 = h2b(x0.x), p1 = h2b(x0.y), p2 = h2b(x0.z), p3 = h2b(prmt(x0.w, y.x, sel));      \
            stsm4t(rG + R_MEMB + HALF * 4096, p0, p1, p2, p3);                                                  \
            const uint32_t p4 = h2b(x1.x), p5 = h2b(x1.y), p6 = h2b(x1.z), p7 = h2b(prmt(x1.w, y.y, sel));      \
            stsm4t(rG + R_MEMB + HALF * 4096 + 512, p4, p5, p6, p7);                                            \
            mx = amax2b(amax2b(p0, p1), amax2b(p2, p3)); my = amax2b(p4, p5); mz = amax2b(p6, p7);              \
        }
#define GATHER(HALF, PRE, SYNC, AFTER)                                                                                      \
        {                                                                                                       \
            const uint32_t so = aslot(s);                                                                       \
            const uint32_t ua = (glo + acc_base(HALF * 4 + fo)) ^ so, ux = (glo + ext_base(HALF * 4 + fo)) ^ so; \
            uint2 lt;                                                                                           \
            lt.x = lds32v_(rL + R_LT); lt.y = lds32v_(rL + R_LT + 4);                                           \
            const uint32_t sel = 0x7610u - ((lt.x ^ (lt.x >> 2)) & 16) * 0x440u;                                \
            const uint32_t* pm = mkptr(ua + lt.x, ghi);                                                         \
            const uint32_t* px = mkptr(ux + lt.y, ghi);                                                         \
            PRE                                                                                                 \
            bar_sync(5, 384);                                                                                   \
            const uint32_t t0 = clk32();                                                                        \
            TSACC();                                                                        \
            SYNC                                                                                                \
            spin_until(t0, DP + DITHER);                                                                                 \
            \
            TS(10, 0);                                                                                          \
            uint32_t cw, nr = 0;                                                                                \
            _Pragma("unroll 1") do {                                                                            \
                GATHER1(HALF)                                                                                   \
                nr++;                                                                                           \
            } while (__any_sync(0xffffffffu, cw != HCNT2 && nr < SPIN_LIMIT));                                  \
            TS(11, cw);                                                                                         \
            AFTER                                                                                               \
            CNT2(HALF * 4 + (s & 1) * 2 + (nr > 2), nr > 1);                                                    \
            \
        }
#define GOBAR (fo == 3 ? 14 : 10 + fo)

__device__ __forceinline__ void rec_a(uint32_t sb, int c, const bf16* __restrict__ mem0, uint32_t epoch) {
    const int tid = threadIdx.x - WGA * 128, lane = tid & 31, f = tid >> 5;
    uint32_t wq[16][4], wk[16][4], mx, my = 0, mz = 0;
    const int lrow = ((lane >> 4) << 3) + (lane & 7), lsel = (lane >> 3) & 1;
    {
        mbar_wait(sb + R_BAR + 8 * MB_W0, 0);
        if (c == 7 && tid == 0) GT(1421);
#pragma unroll
        for (int kk = 0; kk < 16; kk++) { const uint32_t a = sb + R_T + wrow_off(kk, 2 * f + lsel); ldsm4t(wq[kk], a); ldsm4t(wk[kk], a + 32768); }
        __syncwarp();
        mx = put_mem0(sb, f, mem0);
    }
    const uint32_t rL = opaque(sb + lane * 16), rG = opaque(sb + lane * 16 + f * 1024);
    const uint32_t sbu = uni(sb), fo = uni(f), cc = uni(c);
    const uint64_t gx = xpage();
    const uint32_t ghi = uni((uint32_t)(gx >> 32)), glo = uni((uint32_t)gx);
#pragma unroll
    for (int i = 0; i < NAX; i++) {
        sts128u(rG + R_AX + 4096 * i, wq[i][0], wq[i][1], wq[i][2], wq[i][3]);
        sts128u(rG + R_AX + 4096 * i + 512, wk[i][0], wk[i][1], wk[i][2], wk[i][3]);
    }
    sts128u(rL + R_LT + 512 + f * 512, (sb + R_SREM + (f >= 2 ? lane * 8 + f * 256 : lane * 16 + f * 1024)) ^ 0x01000000u, (sb + R_BAR + 8 * MB_S) ^ 0x01000000u,
            sb + R_QP + (lane >> 4) * 128 + lsel * 512 + (lane & 7) * 16 + (f == 3 ? 2048 : 0), sb + R_SLOT0 + lrow * 128 + ((lsel ^ (lane & 7)) << 4));
    __syncwarp();
    if (tid == 0) GT(c * 8 + 1);
    TSDECL;
    const float cexp = 0.08838834764831845f * 1.4426950408889634f;
    float cs = cexp;
    auto step = [&](int s, bool first) -> bool {
        bar_sync(1, 128);
        float q0[4], k0[4];
        uint4 ta;
        uint32_t zr, rl2;
        g1<ANB, SMA>(q0, k0, wq, wk, rL + R_MEMB, sbu - s, [&](int i, const uint32_t* c_) {
            if (i == 0) TS(0, c_[0]);
            if (i == -1) {
#pragma unroll
                for (int n = NAX - NXL; n < NAX; n++) { lds_fragv(wq[n], rG + R_AX + 4096 * n); lds_fragv(wk[n], rG + R_AX + 4096 * n + 512); }
                ta = lds128uv(rL + R_LT + 512 + fo * 512);
                zr = ta.w & 1; rl2 = rL | zr;
            }
            if (i == IVA) { PUT_MAX(rl2, fo) bar_arrive(15, 256); bar_arrive(GOBAR, 96); }
        });
        stsm4t(rG + R_QP, pack2(q0[0], q0[1]), pack2(q0[2], q0[3]), pack2(k0[0], k0[1]), pack2(k0[2], k0[3]));
        TS(1, FU(k0[3]));
        if (first) mbar_wait_p(sbu + R_BAR + 8 * MB_FULL0, 0);
        if (fo >= 2) {
            bar_sync(3, 256);
            uint32_t kb[4], kc[4], qa[4], qc[4];
            ldsm4(kb, ta.z + 256); ldsm4(qa, ta.z);
            ldsm4(kc, ta.z + 1280); ldsm4(qc, ta.z + 1024);
            const uint32_t k0_ = hadd2b(kb[0], kb[1]), k1_ = hadd2b(kb[2], kb[3]), k2_ = hadd2b(kc[0], kc[1]), k3_ = hadd2b(kc[2], kc[3]);
            float s0[4], s2[4];
            MMAZ(s0, qa, k0_, k1_); MMAZ(s2, qc, k2_, k3_);
            const float x = ((s0[0] + s0[2]) + (s2[0] + s2[2])) * cs, y = ((s0[1] + s0[3]) + (s2[1] + s2[3])) * cs;
            st_async2(ta.x, FU(x), FU(y), ta.y);
            TS(3, FU(y));
            sts64((ta.x ^ 0x01000000u) + (R_SLOC - R_SREM), x, y);
            sts128u(rl2 + R_STG + (fo & 1) * 512, k0_, k1_, k2_, k3_);
            bar_arrive(9, 192);
        } else {
            uint32_t qa[4][4], kx[4][4];
#pragma unroll
            for (int kk = 0; kk < KXB; kk++) ldsm4(kx[kk], (ta.w ^ (kk * 32)) + (16384 + fo * 2048));
            bar_sync(3, 256);
#pragma unroll
            for (int kk = 0; kk < 4; kk++) {
                if (kk >= KXB) ldsm4(kx[kk], (ta.w ^ (kk * 32)) + (16384 + fo * 2048));
                ldsm4(qa[kk], ta.z + kk * 1024);
            }
            float s0[4], s1[4], s2[4], s3[4];
            MMAZ(s0, qa[0], kx[0][0], kx[0][1]); MMAZ(s1, qa[0], kx[0][2], kx[0][3]);
            MMAZ(s2, qa[1], kx[1][0], kx[1][1]); MMAZ(s3, qa[1], kx[1][2], kx[1][3]);
            MMA(s0, qa[2], kx[2][0], kx[2][1]); MMA(s1, qa[2], kx[2][2], kx[2][3]);
            MMA(s2, qa[3], kx[3][0], kx[3][1]); MMA(s3, qa[3], kx[3][2], kx[3][3]);
            const float x = ((s0[0] + s0[2]) + (s2[0] + s2[2])) * cs, y = ((s0[1] + s0[3]) + (s2[1] + s2[3])) * cs;
            const float z = ((s1[0] + s1[2]) + (s3[0] + s3[2])) * cs, w = ((s1[1] + s1[3]) + (s3[1] + s3[3])) * cs;
            st_async4(ta.x, x, y, z, w, ta.y);
            TS(3, FU(w));
            sts128(rG + R_SLOC, x, y, z, w);
        }
        const uint32_t r8 = (rl2 + sbu) >> 1;
        uint32_t vt00[4], vt01[4], vt10[4], vt11[4];
        const uint32_t rV = ta.w ^ ((fo & 1) * 64), vo = (fo >> 1) * 8192;
        if (!VTA && VTP < 2) { ldsm4t(vt00, rV + vo); ldsm4t(vt10, (rV ^ 32) + vo); }
        if (!VTA && VTP < 1) { ldsm4t(vt01, rV + vo + 2048); ldsm4t(vt11, (rV ^ 32) + vo + 2048); }
        bar_sync(4, 128);
        const float2 l2 = lds64v(r8 + R_SLOC + 512), l3 = lds64v(r8 + R_SLOC + 768);
        const float4 l0 = lds128v(rL + R_SLOC), l1 = lds128v(rL + R_SLOC + 1024);
        if (VTA && VTP < 2) { ldsm4t(vt00, rV + vo); ldsm4t(vt10, (rV ^ 32) + vo); }
        if (VTA && VTP < 1) { ldsm4t(vt01, rV + vo + 2048); ldsm4t(vt11, (rV ^ 32) + vo + 2048); }

        if (s == NSEG - 1) { mbar_wait_u(sbu + R_BAR + 8 * MB_S, 1); mbar_wait_u(sbu + R_BAR + 8 * MB_V, 1); return true; }
        TS(2, FU(l3.y));
        mbar_wait_p(sbu + R_BAR + 8 * MB_S, s & 1);
        TS(4, 0);
        {
            const float2 r2 = lds64v(r8 + R_SREM + 512), r3 = lds64v(r8 + R_SREM + 768);
            const float4 r0 = lds128v(rL + R_SREM), r1 = lds128v(rL + R_SREM + 1024);
            if (VTP >= 1) PINM();
            if (VTP >= 2) { ldsm4t(vt00, rV + vo); ldsm4t(vt10, (rV ^ 32) + vo); }
            if (VTP >= 1) { ldsm4t(vt01, rV + vo + 2048); ldsm4t(vt11, (rV ^ 32) + vo + 2048); }
            float sv[10];
            sv[0] = l0.x + r0.x; sv[1] = l0.y + r0.y; sv[2] = l0.z + r0.z; sv[3] = l0.w + r0.w;
            sv[4] = l1.x + r1.x; sv[5] = l1.y + r1.y; sv[6] = l1.z + r1.z; sv[7] = l1.w + r1.w;
            sv[8] = ((l2.x + l3.x) + r2.x) + r3.x; sv[9] = ((l2.y + l3.y) + r2.y) + r3.y;
            float m = fmaxf(fmaxf(fmaxf(fmaxf(sv[8], sv[9]), sv[0]), fmaxf(fmaxf(sv[2], sv[3]), sv[1])), fmaxf(fmaxf(sv[4], sv[5]), fmaxf(sv[6], sv[7])));
            {
                const float m1 = __shfl_xor_sync(0xffffffffu, m, 1), m2 = __shfl_xor_sync(0xffffffffu, m, 2), m3 = __shfl_xor_sync(0xffffffffu, m, 3);
                m = fmaxf(fmaxf(m, m1), fmaxf(m2, m3));
            }
            TS(5, FU(m));
            const uint32_t ONE2 = 0x3f803f80u;
            float o0[4], o1[4], sm[4];
            const uint32_t pb0 = pack2(ex2(sv[0] - m), ex2(sv[1] - m)), pb1 = pack2(ex2(sv[2] - m), ex2(sv[3] - m));
            mma16816z(sm, ONE2, ONE2, ONE2, ONE2, pb0, pb1);
            MMAZ(o0, vt00, pb0, pb1); MMAZ(o1, vt10, pb0, pb1);
            const uint32_t z = (VDEP == 0 ? FU(m) : pb0) & zr;
            const uint32_t vok = mbar_test(sbu + R_BAR + 8 * MB_V + z, s & 1);
            const uint32_t rv = r8 + vok * 8;
            float2 va = lds64v(rv + R_VB - 8 + fo * 512);
            float2 vb = lds64v(rv + R_VB - 8 + fo * 512 + 256);
            float sig = __uint_as_float(lds32v_(sbu + R_MISC + 40));
            const uint32_t pb2 = pack2(ex2(sv[4] - m), ex2(sv[5] - m)), pb3 = pack2(ex2(sv[6] - m), ex2(sv[7] - m));
            mma16816(sm, ONE2, ONE2, ONE2, ONE2, pb2, pb3);
            const uint32_t pb4 = pack2(ex2(sv[8] - m), ex2(sv[9] - m));
            MMA(o0, vt01, pb2, pb3); MMA(o1, vt11, pb2, pb3);
            mma1688(sm, ONE2, ONE2, pb4);
            const float z0 = rcpf(sm[0]), z1 = rcpf(sm[1]);
#define PUT_O()                                                                                                   \
            {                                                                                                     \
                float a0[4] = {o0[0], o0[1], o0[2], o0[3]}, a1[4] = {o1[0], o1[1], o1[2], o1[3]};                 \
                mma1688(a0, FU(va.x), FU(va.y), pb4); mma1688(a1, FU(vb.x), FU(vb.y), pb4);                       \
                const float i0 = z0 * sig, i1 = z1 * sig;                                                         \
                stsm4t(rG + R_QP, pack2(a0[0] * i0, a0[1] * i1), pack2(a0[2] * i0, a0[3] * i1), pack2(a1[0] * i0, a1[1] * i1), pack2(a1[2] * i0, a1[3] * i1)); \
            }
            PUT_O()
            asm volatile("{\n.reg .pred p;\nsetp.ne.u32 p, %0, 0;\n@p bar.arrive 8, 256;\n}" :: "r"(vok) : "memory");
            if (__builtin_expect(__any_sync(0xffffffffu, vok == 0), 0)) {
                mbar_wait_p(sbu + R_BAR + 8 * MB_V, s & 1);
                va = lds64v(r8 + R_VB + fo * 512); vb = lds64v(r8 + R_VB + fo * 512 + 256);
                sig = __uint_as_float(lds32v_(sbu + R_MISC + 40));
                PUT_O()
                bar_arrive(8, 256);
                CNT(8);
            }
            TS(6, 0);
            const float r = __uint_as_float(0x7f000000u - FU(sig));
            cs = cexp * r * (fo >= 2 ? r : 1.f);
        }
        return false;
    };
    step(0, true);
#pragma unroll 1
    for (int s = 0;; s++) {
        if (s & 1) mbar_wait_p(sbu + R_BAR + 8 * (MB_FULL0 + (((s + 1) >> 1) & 1)), ((s + 1) >> 2) & 1);
        {
            const uint32_t a = rL + R_LT + 512 + 12 + fo * 512;
            sts32(a, lds32v_(a) + ((s & 1) ? ((s & 2) ? R_SLOT0 - R_SLOT1 - 4096 : R_SLOT1 - R_SLOT0 - 4096) : 4096));
        }
        auto early = [&]() {
            SCHED(13);
#pragma unroll
            for (int i = 0; i < NAX - NXL; i++) { lds_fragv(wq[i], rG + R_AX + 4096 * i); lds_fragv(wk[i], rG + R_AX + 4096 * i + 512); }
        };
        GATHER(0, , early();, )
        if (step(s + 1, false)) break;
    }
    CNT(9);
    if (rG == sbu) GT(cc * 8 + 4);
}

__device__ __forceinline__ void rec_b(uint32_t sb, int c, uint32_t epoch) {
    const int tid = threadIdx.x - WGB * 128, lane = tid & 31, f = tid >> 5;
    uint32_t wq[16][4], wk[16][4], wo[32][4];
    const int lrow = ((lane >> 4) << 3) + (lane & 7), lsel = (lane >> 3) & 1;
    const uint32_t rL = opaque(sb + lane * 16), rW = opaque(sb + lane * 16 + f * 16384);
    const uint32_t sbu = uni(sb), fo = uni(f), cc = uni(c), po = cc & 1, ep = uni(epoch);
    {
        mbar_wait(sb + R_BAR + 8 * MB_WO, 0);
        if (c == 7 && tid == 0) GT(1426);
        const uint32_t aO = sb + R_WO + f * 16384 + lrow * 128 + ((lsel ^ (lane & 7)) << 4);
#pragma unroll
        for (int i = 0; i < 32; i++) {
            const int tile = (i >> 4) * 2 + (i & 1), kk = (i >> 1) & 7;
            ldsm4t(wo[i], (aO ^ (32 * tile)) + kk * 2048);
        }
        const float no = frag_norm2(wo);
        if (lane == 0) sts32(sb + R_MISC + 80 + f * 4, FU(no));
        __syncwarp();
        bar_sync(0, 256);
        if (tid == 0) {
            const float4 a = lds128(sb + R_MISC + 64), b = lds128(sb + R_MISC + 80);
            stg4(&g_f.norm[c], make_uint4(FU((a.x + a.y) + (a.z + a.w)), epoch, FU((b.x + b.y) + (b.z + b.w)), epoch));
        }
        __syncwarp();
#pragma unroll
        for (int i = NRW; i < 32; i++) sts128u(rW + R_WO + i * 512, wo[i][0], wo[i][1], wo[i][2], wo[i][3]);
        mbar_wait(sb + R_BAR + 8 * MB_W1, 0);
        if (c == 7 && tid == 0) GT(1422);
        if (tid == 0) stg_rlx(&g_f.rload[c], epoch);
        __syncwarp();
#pragma unroll
        for (int kk = 0; kk < 16; kk++) { const uint32_t a = sb + R_QK1 + wrow_off(kk, 2 * f + lsel); ldsm4t(wq[kk], a); ldsm4t(wk[kk], a + 32768); }
        bar_sync(13, 128);
#pragma unroll
        for (int i = 0; i < 16; i++) {
            sts128u(rW + R_QK1 + i * 1024, wq[i][0], wq[i][1], wq[i][2], wq[i][3]);
            sts128u(rW + R_QK1 + i * 1024 + 512, wk[i][0], wk[i][1], wk[i][2], wk[i][3]);
        }
        __syncwarp();
    }
    const uint64_t gx = xpage();
    const uint32_t ghi = uni((uint32_t)(gx >> 32)), glo = uni((uint32_t)gx);
    TSDECL;
#pragma unroll 1
    for (int s = 0;; s++) {
        bar_sync(2, 256);
        float q0[4], k0[4];
        g1<BNB, SMB>(q0, k0, wq, wk, rL + R_MEMB + 4096, sbu - s, [&](int i, const uint32_t* c_) {
            if (i == 0) TS(0, c_[0]);
            if (i >= 2 && i < 6) {
#pragma unroll
                for (int n = NRW + (i - 2) * E0 / 4; n < NRW + (i - 1) * E0 / 4; n++) lds_fragv(wo[n], rW + R_WO + n * 512);
            }
            if (i == IV) bar_arrive(GOBAR, 96);
        });
        stsm4t(rL + fo * 1024 + R_QP + 512, pack2(q0[0], q0[1]), pack2(q0[2], q0[3]), pack2(k0[0], k0[1]), pack2(k0[2], k0[3]));
        bar_arrive(3, 256);
        TS(1, FU(k0[3]));
        const uint32_t so = aslot(s);
        uint2 lt;
        { const float2 t = lds64v(rL + R_LT + 8); lt.x = FU(t.x); lt.y = FU(t.y); }
        const uint32_t sel = 0x3210u + (lt.x & 16) * 0x440u;
        uint32_t* pm = (uint32_t*)mkptr(((glo + acc_base(po * 4 + fo)) ^ so) + lt.x, ghi);
        uint32_t* px = (uint32_t*)mkptr(((glo + ext_base(po * 4 + fo)) ^ so) + lt.y, ghi);
        if (s == NSEG - 1) break;
        {
            const uint32_t z = lt.x & 1;
#pragma unroll
            for (int n = NRW; n < NRW + E0 + E1 + E2 + E3; n++) {
                const int d = n - (n < NRW + T2N ? TRK + 1 : TRK);
                lds_fragv(wo[n], (d >= NRW ? or_and(rW, wo[d][0], z) : rW) + R_WO + n * 512);
            }
        }
        TS(2, wo[NRW + E0 + E1 + E2 + E3 - 1][0]);
        SCHED(4);
        bar_sync(8, 256);
        {
            float o[4][4];
            uint32_t b[4][4];
#pragma unroll
            for (int i = 0; i < 4; i++) ldsm4(b[i], rL + R_QP + i * 1024);
            PINM();
#pragma unroll
            for (int n = NRW + E0 + E1 + E2 + E3; n < 32; n++) lds_fragv(wo[n], rW + R_WO + n * 512);
            float p[4][4];
#define G2_STEP(o, hf, kk) _Pragma("unroll") for (int i = 0; i < 2; i++) MMAF((kk) < 2, o[((kk) & 1) * 2 + i], wo[(hf) * 16 + (kk) * 2 + i], b[(kk) >> 1][((kk) & 1) * 2], b[(kk) >> 1][((kk) & 1) * 2 + 1])
#define G2_RED(o, wl, h) const uint32_t wl = packh2(o[1][2] + o[3][2], o[1][3] + o[3][3]);                            \
                asm volatile("red.relaxed.gpu.global.add.noftz.v4.f16x2 [%0], {%1,%2,%3,%4};" :: "l"(pm + (h) * 16),  \
                    "r"(packh2(o[0][0] + o[2][0], o[0][1] + o[2][1])), "r"(packh2(o[0][2] + o[2][2], o[0][3] + o[2][3])), \
                    "r"(packh2(o[1][0] + o[3][0], o[1][1] + o[3][1])), "r"(prmt(wl, HONE2, (h) ? sel : sel ^ 0x4400u)) : "memory")
            if (G2V == 1) SCHED(11);
#pragma unroll
            for (int kk = 0; kk < 8; kk++) { G2_STEP(o, 0, kk); }
            TS(7, b[0][0]);
            if (G2V == 0) SCHED(11);
            else {
#pragma unroll
                for (int i = 0; i < 4; i++) wo[16 + i][0] = or_and(wo[16 + i][0], FU(o[i][0]), lt.x & 1);
            }
#pragma unroll
            for (int kk = 0; kk < G2K; kk++) { G2_STEP(p, 1, kk); }
#pragma unroll
            for (int i = 0; i < NB0; i++) { lds_fragv(wq[i], rW + R_QK1 + i * 1024); lds_fragv(wk[i], rW + R_QK1 + i * 1024 + 512); }
            G2_RED(o, w3, 0);
            TS(8, w3);
            if (G2V == 0) SCHED(12);
#pragma unroll
            for (int kk = G2K; kk < 8; kk++) { G2_STEP(p, 1, kk); }
            G2_RED(p, w7, 1);
            asm volatile("red.relaxed.gpu.global.add.noftz.f16x2 [%0], %1;" :: "l"(px), "r"(prmt((w3 & 0xffff0000u) | 0x3c00u, w7, sel)) : "memory");
            TS(9, w7);
        }
        bar_arrive(5, 384);
        asm volatile("{\n.reg .pred p;\nsetp.eq.u32 p, %0, %1;\n@p mbarrier.arrive.expect_tx.shared::cta.b64 _, [%2], 1536;\n}"
                     :: "r"(rW), "r"(sbu), "r"(sbu + R_BAR + 8 * MB_S) : "memory");
        const uint32_t tb = clk32();
        TSACC();
        spin_until(tb, DB);
#pragma unroll
        for (int i = NB0; i < NBR; i++) {
            if (i == NB1) spin_until(tb, DP + DB2);
            lds_fragv(wq[i], rW + R_QK1 + i * 1024); lds_fragv(wk[i], rW + R_QK1 + i * 1024 + 512);
        }
    }
}

#undef lds_fragv
__device__ __forceinline__ void rec_first_loads(uint32_t sb, int c, const Maps& maps) {
    const uint32_t bar = sb + R_BAR;
    const int F0 = c * 64;
    mbar_expect_tx(bar + 8 * MB_W0, 65536); mbar_expect_tx(bar + 8 * MB_WO, 65536); mbar_expect_tx(bar + 8 * MB_WV, 65536);
    tma2d(sb + R_QK1, &maps.wv, F0, 0, bar + 8 * MB_WV); tma2d(sb + R_QK1 + 32768, &maps.wv, F0, 256, bar + 8 * MB_WV);
    tma2d(sb + R_T + 32768, &maps.wk, F0, 0, bar + 8 * MB_W0);
    if (!LORD) {
        for (int i = 0; i < 4; i++) tma2d(sb + R_WO + i * 16384, &maps.wo, (c & 1) * 256 + i * 64, (c >> 1) * 128, bar + 8 * MB_WO);
        tma2d(sb + R_T, &maps.wq, F0, 0, bar + 8 * MB_W0);
    }
    mbar_expect_tx(bar + 8 * MB_S, 1536);
}
__device__ __forceinline__ void rec_c(uint32_t sb, int c, const bf16* __restrict__ mem0, const Maps& maps, uint32_t epoch) {
    const int tid = threadIdx.x - WGC * 128, lane = tid & 31, u = tid >> 5;
    const uint32_t bar = sb + R_BAR;
    const int lrow = ((lane >> 4) << 3) + (lane & 7), lsel = (lane >> 3) & 1;
    const int kh = u >> 1, j = u & 1;
    uint32_t wv[32][4], mx, my = 0, mz = 0;
    {
        if (u == 0) {
            sts128u(sb + lane * 16 + R_LT, (lane >> 3) * 256 + (lane & 7) * 16, ((lane >> 2) & 1) * XHS + (lane >> 4) * XSS + (lane & 8) * 2 + (lane & 2) * 4,
                    (lane >> 2) * 256 + (lane & 3) * 16, (lane & 1) * XHS + ((lane >> 3) & 1) * XSS + (lane & 6) * 4 + (lane >> 4) * 4);
        }
        mbar_wait(bar + 8 * MB_WV, 0);
        if (c == 7 && tid == 0) GT(1425);
        if (LORD && tid == 32) {
            for (int i = 0; i < 4; i++) tma2d(sb + R_WO + i * 16384, &maps.wo, (c & 1) * 256 + i * 64, (c >> 1) * 128, bar + 8 * MB_WO);
            tma2d(sb + R_T, &maps.wq, c * 64, 0, bar + 8 * MB_W0);
        }
        __syncwarp();
#pragma unroll
        for (int kk = 0; kk < 16; kk++) {
            const uint32_t aa = sb + R_QK1 + kh * 32768 + wrow_off(kk, 4 * j + 2 * kh + lsel);
            ldsm4t(wv[kk], aa); ldsm4t(wv[16 + kk], aa ^ 32);
        }
        {
            uint32_t x = 0;
#pragma unroll
            for (int i = 0; i < 32; i++) x ^= wv[i][0];
            sts32(sb + R_MISC + 96 + u * 4, __reduce_xor_sync(0xffffffffu, x));
        }
        bar_sync(9, 128);
        if (c == 7 && tid == 0) GT(1423);
        if (tid == 0) {
            mbar_expect_tx(bar + 8 * MB_W1, 65536);
            tma2d(sb + R_QK1 + 32768, &maps.wk, c * 64, 256, bar + 8 * MB_W1); tma2d(sb + R_QK1, &maps.wq, c * 64, 256, bar + 8 * MB_W1);
        }
        __syncwarp();
        const float nv = frag_norm2(wv);
        if (lane == 0) sts32(sb + R_MISC + 64 + u * 4, FU(nv));
        __syncwarp();
        bar_arrive(0, 256);
        mx = put_mem0(sb, 4 + u, mem0);
    }
    const uint32_t rL = opaque(sb + lane * 16), rG = opaque(sb + lane * 16 + u * 1024);
    const uint32_t sbu = uni(sb), fo = uni(u), cc = uni(c), ep = uni(epoch);
    const uint64_t gx = xpage();
    const uint32_t ghi = uni((uint32_t)(gx >> 32)), glo = uni((uint32_t)gx);
    constexpr int CX = R_AX + NAX * 4096;
    static_assert(NAX + NCX <= 6, "AX");
#pragma unroll
    for (int i = 0; i < NCX; i++) {
        sts128u(rG + CX + 4096 * i, wv[i][0], wv[i][1], wv[i][2], wv[i][3]);
        sts128u(rG + CX + 4096 * i + 512, wv[16 + i][0], wv[16 + i][1], wv[16 + i][2], wv[16 + i][3]);
    }
    __syncwarp();
    TSDECL;
    uint32_t rpb = 0x3f800000u;
    bar_arrive(2, 256);
    if (fo == 3) {
        uint32_t n = 0;
#pragma unroll 1
        while (true) {
            const uint2 v = ldg_rlx2(&g_f.kv[0][cc >> 1][0]);
            if (__all_sync(0xffffffffu, v.x == ep && v.y == ep)) break;
            __nanosleep(32);
            if (++n > SPIN_LIMIT) { ABORT(6); break; }
        }
        if (rL == sbu) load_slot(sbu, cc, 0, maps);
        __syncwarp();
        if (cc == 7 && rL == sbu) GT(1427);
    }
#pragma unroll 1
    for (int s = 0;; s++) {
        if (TEARLY && fo == 3 && !(s & 1) && s > 0 && s + 2 < NSEG) {
            if (rL == sbu) load_slot(sbu, cc, (s + 2) >> 1, maps);
            __syncwarp();
        } else spin_until(clk32(), DC);
#pragma unroll
        for (int i = NCX - NCL; i < NCX; i++) { lds_fragv(wv[i], rG + CX + 4096 * i); lds_fragv(wv[16 + i], rG + CX + 4096 * i + 512); }
        PUT_MAX(rL, 4 + fo)
        if (fo == 0) {
                bar_sync(15, 256);
                if (s == 0) {
                    const uint32_t* np = (const uint32_t*)&g_f.norm[0] + ((rL ^ sbu) >> 2);
                    uint4 r, q; uint32_t n = 0;
#pragma unroll 1
                    while (true) {
                        r = ldg_rlx4(np); q = ldg_rlx4(np + 128);
                        const uint2 z = ldg_rlx2(&g_f.xn[(rL ^ sbu) >> 3]);
                        if (__all_sync(0xffffffffu, r.y == ep && r.w == ep && q.y == ep && q.w == ep && z.x == ep && z.y == ep)) break;
                        if (++n > SPIN_LIMIT) { ABORT(5); break; }
                    }
                    float nv = __uint_as_float(r.x) + __uint_as_float(q.x), no = __uint_as_float(r.z) + __uint_as_float(q.z);
#pragma unroll
                    for (int o = 16; o; o >>= 1) { nv += __shfl_xor_sync(0xffffffffu, nv, o); no += __shfl_xor_sync(0xffffffffu, no, o); }
                    const int lc = ((int)(FU(nv) >> 23) + (int)(FU(no) >> 23) - 252 + 9 + 1) >> 1;
                    sts32(sbu + R_MISC + 32, 140 - lc);
                    __syncwarp();
                }
                const uint4 ma = lds128uv(rL + R_STG + 1024), mb = lds128uv(rL + R_STG + 1536);
                const uint32_t m_ = amax2b(amax2b(amax2b(ma.x, ma.y), amax2b(ma.z, ma.w)), amax2b(amax2b(mb.x, mb.y), amax2b(mb.z, mb.w)));
                const int em = (int)(__reduce_max_sync(0xffffffffu, amax2b(m_, m_ << 16) & 0x7f800000u) >> 23) + (int)(rpb >> 23) - 127;
                const int es = min(max((int)lds32v_(sbu + R_MISC + 32) - max(em, 127), -60), 60);
                sts32(sbu + R_MISC + 40, (127 + es) << 23);
                TS(4, es);
        } else bar_arrive(15, 256);
        bar_sync(GOBAR, 96);
        float v0[4], v1[4];
        g1<CNB, SMC>(v0, v1, wv, wv + 16, rL + R_MEMB + (fo >> 1) * 4096, sbu - s, [&](int i, const uint32_t* c_) { if (i == 0) TS(0, c_[0]); });
        TS(1, FU(v1[3]));
        const uint32_t l16 = (rL ^ sbu) | (lds32v_(rL + R_LT + 4) & 1);
        const uint32_t r8 = sbu + (l16 >> 1);
        {
            sts128(rL + R_VRED + fo * 512, v1[0], v1[1], v1[2], v1[3]);
            const uint32_t d = r8 + R_VB + ((cc & 1) * 4 + (fo & 1) * 2 + (fo >> 1)) * 256;
            const uint32_t dr = xorv(d, 0x01000000u), br = xorv(sbu + R_BAR + 8 * MB_V, 0x01000000u);
            bar_sync(6 + (fo & 1), 64);
            const float4 a0 = lds128(rL + R_VRED + (fo ^ 2) * 512);
            const float rp = __uint_as_float(rpb);
            const uint32_t w0 = pack2((v0[0] + a0.x) * rp, (v0[1] + a0.y) * rp), w1 = pack2((v0[2] + a0.z) * rp, (v0[3] + a0.w) * rp);
            st_async2(dr, w0, w1, br);
            TS(3, w1);
            sts64(d, __uint_as_float(w0), __uint_as_float(w1));
            __syncwarp();
            asm volatile("{\n.reg .pred p;\nsetp.eq.u32 p, %0, %1;\n@p mbarrier.arrive.expect_tx.shared::cta.b64 _, [%2], 256;\n}"
                         :: "r"(rL), "r"(sbu), "r"(sbu + R_BAR + 8 * MB_V) : "memory");
        }
        if (fo == 1) {
            bar_sync(9, 192);
            uint8_t* dst = (uint8_t*)&g_KVf[s][cc >> 1][(cc & 1) * 256] + l16;
            const uint32_t r2 = prmt(rpb, 0, 0x3232u);
#pragma unroll
            for (int i = 0; i < 2; i++) {
                const uint4 a = lds128uv(rL + R_STG + i * 512);
                stg4(dst + i * 512, make_uint4(~hmul2b(a.x, r2), ~hmul2b(a.y, r2), ~hmul2b(a.z, r2), ~hmul2b(a.w, r2)));
                const float2 b0 = lds64v(r8 + R_VB + (cc & 1) * 1024 + i * 512), b1 = lds64v(r8 + R_VB + (cc & 1) * 1024 + i * 512 + 256);
                stg4(dst + 2048 + i * 512, make_uint4(~FU(b0.x), ~FU(b0.y), ~FU(b1.x), ~FU(b1.y)));
            }
            __syncwarp();
            if (l16 == 0) { stg_rlx(&g_f.rec[cc], (ep << 8) | (s + 1)); if (s == NSEG - 1) GT(1500 + cc); }
            __syncwarp();
        } else {
            bar_arrive(9, 192);
            if (fo == 2) {
                if (l16 < 144) stg4((void*)mkptr((glo + zero_off(cc, l16 >> 4)) ^ aslot(s + 4), ghi), make_uint4(0, 0, 0, 0));
                __syncwarp();
            } else if (fo == 3) {
                if (((s & 1) || s == 0) && s + 3 < NSEG) {
                    const uint32_t* fp = &g_f.kv[(s + 3) >> 1][cc >> 1][0];
                    uint32_t n = 0;
#pragma unroll 1
                    while (true) {
                        const uint2 v = ldg_rlx2(fp);
                        if (__all_sync(0xffffffffu, v.x == ep && v.y == ep)) break;
                        __nanosleep(64);
                        if (++n > SPIN_LIMIT) { ABORT(6); break; }
                    }
                }
                if (!(s & 1) && s + 2 < NSEG && (!TEARLY || s == 0)) {
                    spin_until(clk32(), DT);
                    if (l16 == 0) load_slot(sbu, cc, (s + 2) >> 1, maps);
                    __syncwarp();
                }
            }
        }
        if (s == NSEG - 1) break;
        auto early = [&]() {
#pragma unroll
            for (int i = 0; i < NCX - NCL; i++) { lds_fragv(wv[i], rG + CX + 4096 * i); lds_fragv(wv[16 + i], rG + CX + 4096 * i + 512); }
        };
        GATHER(1, , early(); rpb = 0x7f000000u - lds32v_(sbu + R_MISC + 40);, bar_arrive(2, 256);)
    }
}

__device__ __forceinline__ bool cand_better(float v, int i, float bv, int bi) { return v > bv || (v == bv && i < bi); }
constexpr int F_WG = 0, F_WU = 32768, F_WD = 65536, F_X = 98304, F_RED = F_X + 4096, F_ACT = F_RED + 8192, F_SEL = F_ACT + 256;

__device__ __noinline__ void ffn_phase(const Maps& maps, const bf16* __restrict__ wd, bf16* __restrict__ out) {
    extern __shared__ __align__(1024) uint8_t smem[];
    const uint32_t sb = smem_u32(smem);
    const int c = ((volatile int*)(smem + SH_OFF))[8];
    const uint32_t epoch = ((volatile uint32_t*)(smem + SH_OFF))[9];
    const int tid = threadIdx.x;
    constexpr int NWK = FF / 32;
    const bool worker = c < NWK;
    bar_sync(0, 384);
    const uint32_t mb = sb + R_BAR + 8 * MB_W0;
    if (tid == 32 && worker) {
        asm volatile("fence.proxy.async.shared::cta;" ::: "memory");
        mbar_expect_tx(mb, 98304);
        tma2d(sb + F_WG, &maps.wg, c * 32, 0, mb); tma2d(sb + F_WG + 16384, &maps.wg, c * 32, 256, mb);
        tma2d(sb + F_WU, &maps.wu, c * 32, 0, mb); tma2d(sb + F_WU + 16384, &maps.wu, c * 32, 256, mb);
        asm volatile("cp.async.bulk.shared::cluster.global.mbarrier::complete_tx::bytes [%0], [%1], %2, [%3];"
            :: "r"(sb + F_WD), "l"(wd + (size_t)c * 32 * DM), "r"(32768), "r"(mb) : "memory");
    }
    int p0 = -1, p1 = -1;
#pragma unroll 1
    for (int pass = 0; pass < 2; pass++) {
        if (tid < 32) {
            const uint32_t tag = epoch & 0xfffffu;
            uint4 r[4]; uint32_t n = 0;
            const int t3 = tid + 96 < NFW ? tid + 96 : tid;
#pragma unroll 1
            while (true) {
                bool ok = true;
#pragma unroll
                for (int i = 0; i < 4; i++) r[i] = ldg_rlx4((const uint32_t*)&g_f.cand[pass][i < 3 ? tid + 32 * i : t3]);
#pragma unroll
                for (int i = 0; i < 4; i++) ok = ok && (r[i].y >> 12) == tag && (r[i].w >> 12) == tag;
                if (__all_sync(0xffffffffu, ok)) break;
                __nanosleep(32);
                if (++n > SPIN_LIMIT) { ABORT(7); break; }
            }
            float b0 = __uint_as_float(r[0].x), b1 = __uint_as_float(r[0].z); int i0 = r[0].y & 4095, i1 = r[0].w & 4095;
#pragma unroll
            for (int i = 1; i < 4; i++) {
                if (i < 3 || t3 != tid) {
                    float c0 = __uint_as_float(r[i].x), c1 = __uint_as_float(r[i].z); int j0 = r[i].y & 4095, j1 = r[i].w & 4095;
                    if (cand_better(c0, j0, b0, i0)) {
                        if (cand_better(c1, j1, b0, i0)) { b1 = c1; i1 = j1; } else { b1 = b0; i1 = i0; }
                        b0 = c0; i0 = j0;
                    } else if (cand_better(c0, j0, b1, i1)) { b1 = c0; i1 = j0; }
                }
            }
#pragma unroll
            for (int o = 16; o; o >>= 1) {
                float c0 = __shfl_xor_sync(0xffffffffu, b0, o), c1 = __shfl_xor_sync(0xffffffffu, b1, o);
                int j0 = __shfl_xor_sync(0xffffffffu, i0, o), j1 = __shfl_xor_sync(0xffffffffu, i1, o);
                if (cand_better(c0, j0, b0, i0)) {
                    if (cand_better(c1, j1, b0, i0)) { b1 = c1; i1 = j1; } else { b1 = b0; i1 = i0; }
                    b0 = c0; i0 = j0;
                } else if (cand_better(c0, j0, b1, i1)) { b1 = c0; i1 = j0; }
            }
            i0 = min(i0, SQ - 1); i1 = min(i1, SQ - 1);
            if (i0 != p0 || i1 != p1) {
                n = 0;
#pragma unroll 1
                while (!__all_sync(0xffffffffu, (ldg_rlx(&g_f.rows[pass][tid]) == epoch) & (ldg_rlx(&g_f.rows[pass][tid + 32]) == epoch) &
                                                   (ldg_rlx(&g_f.rows[pass][tid + 64]) == epoch) & (ldg_rlx(&g_f.rows[pass][t3]) == epoch))) { __nanosleep(32); if (++n > SPIN_LIMIT) { ABORT(7); break; } }
            }
            int* sel = (int*)(smem + F_SEL);
            if (pass && tid == 0) GT(c * 8 + 5);
            if (tid == 0) { sel[0] = i0; sel[1] = i1; ((float*)sel)[2] = b0; ((float*)sel)[3] = b1; }
        }
        bar_sync(0, 384);
        const int t0 = ((int*)(smem + F_SEL))[0], t1 = ((int*)(smem + F_SEL))[1];
        if (c == 3 && tid == 0 && pass == 0) GT(1430);
        if (t0 == p0 && t1 == p1) break;
        const uint32_t ytag = epoch * 2 + pass + 1;
        if (worker) {
            float2* xs = (float2*)(smem + F_X);
            if (tid < 256) {
                uint32_t a = __ldcg((const uint32_t*)(g_hn + (size_t)t0 * DM) + tid), b = __ldcg((const uint32_t*)(g_hn + (size_t)t1 * DM) + tid);
                *(float4*)(xs + tid * 2) = make_float4(bf_lo(a), bf_lo(b), bf_hi(a), bf_hi(b));
            }
            mbar_wait(mb, 1);
            if (c == 3 && tid == 0 && pass == 0) GT(1431);
            bar_sync(0, 384);
            float4* red = (float4*)(smem + F_RED);
            if (tid < 256) {
                const int cp = tid & 31, kg = tid >> 5;
                const uint32_t* wp = (const uint32_t*)(smem + (cp < 16 ? F_WG : F_WU)) + (cp & 15);
                float a0 = 0.f, a1 = 0.f, b0 = 0.f, b1 = 0.f;
#pragma unroll 16
                for (int k = kg * 64; k < kg * 64 + 64; k++) {
                    uint32_t w = wp[k * 16]; float2 x = xs[k];
                    a0 = fmaf(x.x, bf_lo(w), a0); a1 = fmaf(x.x, bf_hi(w), a1); b0 = fmaf(x.y, bf_lo(w), b0); b1 = fmaf(x.y, bf_hi(w), b1);
                }
                red[kg * 32 + cp] = make_float4(a0, a1, b0, b1);
            }
            bar_sync(0, 384);
            float2* act = (float2*)(smem + F_ACT);
            if (tid < 64) {
                const int f = tid & 31, tk = tid >> 5;
                const float* r = (const float*)red + (f >> 1) * 4 + tk * 2 + (f & 1);
                float gsum = 0.f, usum = 0.f;
#pragma unroll
                for (int kg = 0; kg < 8; kg++) { gsum += r[kg * 128]; usum += r[kg * 128 + 64]; }
                gsum = rbf(gsum); usum = rbf(usum);
                float sg = rbf(gsum / (1.f + __expf(-gsum)));
                ((float*)act)[f * 2 + tk] = rbf(sg * usum);
            }
            bar_sync(0, 384);
            if (tid < 256) {
                const uint32_t* wp = (const uint32_t*)(smem + F_WD) + tid;
                float a0 = 0.f, a1 = 0.f, b0 = 0.f, b1 = 0.f;
#pragma unroll 16
                for (int f = 0; f < 32; f++) {
                    uint32_t w = wp[f * 256]; float2 x = act[f];
                    a0 = fmaf(x.x, bf_lo(w), a0); a1 = fmaf(x.x, bf_hi(w), a1); b0 = fmaf(x.y, bf_lo(w), b0); b1 = fmaf(x.y, bf_hi(w), b1);
                }
                asm volatile("st.relaxed.gpu.global.v4.b32 [%0], {%1,%2,%3,%2};" :: "l"(&g_yp[pass][c][tid]), "r"(FU(a0)), "r"(ytag), "r"(FU(a1)) : "memory");
                asm volatile("st.relaxed.gpu.global.v4.b32 [%0], {%1,%2,%3,%2};" :: "l"(&g_yp[pass][c][256 + tid]), "r"(FU(b0)), "r"(ytag), "r"(FU(b1)) : "memory");
            }
            if (c == 3 && tid == 0 && pass == 0) GT(1432);
        } else {
            const int r = c - NWK, j = tid & 63, part = tid >> 6, tk = r >> 2, dp = (r & 3) * 64 + j;
            const int tok = tk ? t1 : t0, old = tk ? p1 : p0;
            uint32_t hw = 0, nw = 0;
            if (part == 0) {
                hw = __ldcg((const uint32_t*)(g_h + (size_t)tok * DM) + dp); nw = __ldcg((const uint32_t*)(g_hn + (size_t)tok * DM) + dp);
                if (old >= 0 && old != t0 && old != t1) {
                    uint32_t ho = __ldcg((const uint32_t*)(g_h + (size_t)old * DM) + dp), no = __ldcg((const uint32_t*)(g_hn + (size_t)old * DM) + dp);
                    ((uint32_t*)(out + (size_t)old * DM))[dp] = pack2(bf_lo(ho) + bf_lo(no), bf_hi(ho) + bf_hi(no));
                }
            }
            float s0 = 0.f, s1 = 0.f;
            uint4 v[10]; uint32_t n = 0;
            bool ok;
#pragma unroll 1
            do {
                ok = true;
#pragma unroll
                for (int i = 0; i < 10; i++) {
                    const int src = part + 6 * i;
                    v[i] = src < NWK ? ldg_rlx4((const uint32_t*)&g_yp[pass][src][tk * 256 + dp]) : make_uint4(0, ytag, 0, ytag);
                }
#pragma unroll
                for (int i = 0; i < 10; i++) ok = ok && v[i].y == ytag && v[i].w == ytag;
                if (!ok) __nanosleep(100);
                if (++n > SPIN_LIMIT) { ABORT(7); break; }
            } while (!ok);
#pragma unroll
            for (int i = 0; i < 10; i++) { s0 += __uint_as_float(v[i].x); s1 += __uint_as_float(v[i].z); }
            float2* red = (float2*)(smem + F_RED);
            red[part * 64 + j] = make_float2(s0, s1);
            bar_sync(0, 384);
            if (part == 0) {
#pragma unroll
                for (int i = 1; i < 6; i++) { float2 q = red[i * 64 + j]; s0 += q.x; s1 += q.y; }
                const float rs = rbf(1.f / (1.f + __expf(-((float*)(smem + F_SEL))[2 + tk])));
                const float y0 = rbf(rbf(s0) * rs), y1 = rbf(rbf(s1) * rs);
                ((uint32_t*)(out + (size_t)tok * DM))[dp] = pack2(bf_lo(hw) + rbf(bf_lo(nw) + y0), bf_hi(hw) + rbf(bf_hi(nw) + y1));
            }
            if (tid == 0 && pass == 0 && r == 0) GT(1434);
        }
        p0 = t0; p1 = t1;
        if (c == 3 && tid == 0 && pass == 0) GT(1433);
        bar_sync(0, 384);
    }
}

constexpr int G_W = 0;
constexpr int G_RING = 131072;
constexpr int G_BUF = 163840;
constexpr int G_BAR = 229376;
constexpr int G_SMEM = G_BAR + 512;
enum { GB_W0 = 0, GB_W1, GB_WFREE, GB_FULL, GB_EMPTY = GB_FULL + 8, GB_KV = GB_EMPTY + 8, GB_STG = GB_KV + 2, GB_FREE = GB_STG + 2, GB_XN = GB_FREE + 2, GB_RL, GB_T1D, GB_VV, GB_KVF = GB_VV + 2, GB_VF, GB_N };
constexpr int SMEM_TOTAL = 232448;

__device__ __forceinline__ void wgmma_n128(float* d, uint64_t da, uint64_t db, int scale_d) {
    asm volatile("{\n.reg .pred p;\nsetp.ne.b32 p, %66, 0;\n"
        "wgmma.mma_async.sync.aligned.m64n128k16.f32.bf16.bf16 "
        "{%0,%1,%2,%3,%4,%5,%6,%7,%8,%9,%10,%11,%12,%13,%14,%15,%16,%17,%18,%19,%20,%21,%22,%23,%24,%25,%26,%27,%28,%29,%30,%31,"
        "%32,%33,%34,%35,%36,%37,%38,%39,%40,%41,%42,%43,%44,%45,%46,%47,%48,%49,%50,%51,%52,%53,%54,%55,%56,%57,%58,%59,%60,%61,%62,%63}, "
        "%64, %65, p, 1, 1, 0, 1;\n}"
        : "+f"(d[0]), "+f"(d[1]), "+f"(d[2]), "+f"(d[3]), "+f"(d[4]), "+f"(d[5]), "+f"(d[6]), "+f"(d[7]), "+f"(d[8]), "+f"(d[9]), "+f"(d[10]), "+f"(d[11]),
          "+f"(d[12]), "+f"(d[13]), "+f"(d[14]), "+f"(d[15]), "+f"(d[16]), "+f"(d[17]), "+f"(d[18]), "+f"(d[19]), "+f"(d[20]), "+f"(d[21]), "+f"(d[22]), "+f"(d[23]),
          "+f"(d[24]), "+f"(d[25]), "+f"(d[26]), "+f"(d[27]), "+f"(d[28]), "+f"(d[29]), "+f"(d[30]), "+f"(d[31]), "+f"(d[32]), "+f"(d[33]), "+f"(d[34]), "+f"(d[35]),
          "+f"(d[36]), "+f"(d[37]), "+f"(d[38]), "+f"(d[39]), "+f"(d[40]), "+f"(d[41]), "+f"(d[42]), "+f"(d[43]), "+f"(d[44]), "+f"(d[45]), "+f"(d[46]), "+f"(d[47]),
          "+f"(d[48]), "+f"(d[49]), "+f"(d[50]), "+f"(d[51]), "+f"(d[52]), "+f"(d[53]), "+f"(d[54]), "+f"(d[55]), "+f"(d[56]), "+f"(d[57]), "+f"(d[58]), "+f"(d[59]),
          "+f"(d[60]), "+f"(d[61]), "+f"(d[62]), "+f"(d[63])
        : "l"(da), "l"(db), "r"(scale_d));
}

__device__ __forceinline__ constexpr uint32_t slot_off(int slot) {
    return slot < 2 ? G_RING + slot * 16384 : G_BUF + (slot - 2) * 32768 + 16384;
}
template <int NSLOT, class F>
__device__ __forceinline__ void gemm_tile(float* acc, uint32_t sb, int tile, int it, bool first, uint32_t wpar, int wg, bool pass, uint32_t l0, F&& hook) {
    const uint32_t bar = sb + G_BAR;
    bar_sync(3 + wg, 256);
    int prev = 0;
#pragma unroll
    for (int k = 0; k < 4; k++) {
        const int n = tile * 4 + k, slot = NSLOT == 4 ? k : n % 3;
        const uint32_t sz = sb + (((it + k) << 4) & sb & 0x3f0);
        const uint64_t da = desc_sw128(sz + slot_off(slot), 16, 1024), db0 = desc_sw128(sz + G_W, 65536, 1024);
        if ((k & 1) == 0 && first) mbar_wait_p(bar + 8 * (GB_W0 + (k >> 1)), wpar);
        bool rel = false;
        if (EREL && k > 0 && !__all_sync(0xffffffffu, mbar_test(bar + 8 * (GB_FULL + slot), tile & 1))) {
            asm volatile("wgmma.wait_group.sync.aligned 0;" ::: "memory");
            mbar_arrive2_if(bar + 8 * (GB_EMPTY + prev), l0);
            rel = true;
        }
        mbar_wait_p(bar + 8 * (GB_FULL + slot), NSLOT == 4 ? (tile & 1) : ((n / 3) & 1));
        if (k == 3 && pass) bar_arrive(3 + (wg ^ 1), 256);
        asm volatile("wgmma.fence.sync.aligned;" ::: "memory");
#pragma unroll
        for (int kk = 0; kk < 4; kk++) wgmma_n128(acc, da + kk * 2, db0 + k * 1024 + kk * 128, (k | kk) != 0);
        asm volatile("wgmma.commit_group.sync.aligned;" ::: "memory");
        if (k > 0) {
            asm volatile("wgmma.wait_group.sync.aligned 1;" ::: "memory");
            mbar_arrive2_if(bar + 8 * (GB_EMPTY + prev), rel ? 0 : l0);
        }
#pragma unroll
        for (int kk = 0; kk < 4; kk++) wgmma_n128(acc, da + 512 + kk * 2, db0 + k * 1024 + 512 + kk * 128, 1);
        asm volatile("wgmma.commit_group.sync.aligned;" ::: "memory");
        if (k == 1) hook();
        prev = slot;
    }
    asm volatile("wgmma.wait_group.sync.aligned 0;" ::: "memory");
    mbar_arrive2_if(bar + 8 * (GB_EMPTY + prev), l0);
}
__device__ __forceinline__ void stage_bf16(const float* acc, uint32_t buf, float s0, float s1) {
    const int lane = threadIdx.x & 31, wq = (threadIdx.x >> 5) & 3;
    const int row = wq * 16 + (lane & 7) + ((lane >> 3) & 1) * 8;
    const uint32_t base = buf + row * 128;
#pragma unroll
    for (int j = 0; j < 16; j += 2) {
        const int ch = (j & 7) + (lane >> 4);
        stsm4(base + (j >> 3) * 8192 + ((ch ^ (row & 7)) << 4),
              pack2(acc[4 * j] * s0, acc[4 * j + 1] * s0), pack2(acc[4 * j + 2] * s1, acc[4 * j + 3] * s1),
              pack2(acc[4 * j + 4] * s0, acc[4 * j + 5] * s0), pack2(acc[4 * j + 6] * s1, acc[4 * j + 7] * s1));
    }
}

__device__ __forceinline__ void store_perm(const float* acc, bf16* dst, int ld, float s0, float s1) {
#pragma unroll
    for (int i = 0; i < 4; i++) {
        const float* a = acc + 16 * i;
        *(uint4*)(dst + i * 32) = make_uint4(pack2(a[0] * s0, a[1] * s0), pack2(a[4] * s0, a[5] * s0), pack2(a[8] * s0, a[9] * s0), pack2(a[12] * s0, a[13] * s0));
        *(uint4*)(dst + 8 * ld + i * 32) = make_uint4(pack2(a[2] * s1, a[3] * s1), pack2(a[6] * s1, a[7] * s1), pack2(a[10] * s1, a[11] * s1), pack2(a[14] * s1, a[15] * s1));
    }
}
template <int ACC>
__device__ __forceinline__ void wgmma_rs64(float* d, const uint32_t* a, uint64_t db) {
    asm volatile("{\n.reg .pred p;\nsetp.ne.b32 p, %37, 0;\n"
        "wgmma.mma_async.sync.aligned.m64n64k16.f32.bf16.bf16 {%0,%1,%2,%3,%4,%5,%6,%7,%8,%9,%10,%11,%12,%13,%14,%15,%16,%17,%18,%19,%20,%21,%22,%23,%24,%25,%26,%27,%28,%29,%30,%31}, {%32,%33,%34,%35}, %36, p, 1, 1, 0;\n}"
        : "+f"(d[0]), "+f"(d[1]), "+f"(d[2]), "+f"(d[3]), "+f"(d[4]), "+f"(d[5]), "+f"(d[6]), "+f"(d[7]), "+f"(d[8]), "+f"(d[9]), "+f"(d[10]), "+f"(d[11]), "+f"(d[12]), "+f"(d[13]), "+f"(d[14]), "+f"(d[15]), "+f"(d[16]), "+f"(d[17]), "+f"(d[18]), "+f"(d[19]), "+f"(d[20]), "+f"(d[21]), "+f"(d[22]), "+f"(d[23]), "+f"(d[24]), "+f"(d[25]), "+f"(d[26]), "+f"(d[27]), "+f"(d[28]), "+f"(d[29]), "+f"(d[30]), "+f"(d[31])
        : "r"(a[0]), "r"(a[1]), "r"(a[2]), "r"(a[3]), "l"(db), "n"(ACC));
}
template <int ACC>
__device__ __forceinline__ void wgmma_rs128t(float* d, const uint32_t* a, uint64_t db) {
    asm volatile("{\n.reg .pred p;\nsetp.ne.b32 p, %69, 0;\n"
        "wgmma.mma_async.sync.aligned.m64n128k16.f32.bf16.bf16 {%0,%1,%2,%3,%4,%5,%6,%7,%8,%9,%10,%11,%12,%13,%14,%15,%16,%17,%18,%19,%20,%21,%22,%23,%24,%25,%26,%27,%28,%29,%30,%31,%32,%33,%34,%35,%36,%37,%38,%39,%40,%41,%42,%43,%44,%45,%46,%47,%48,%49,%50,%51,%52,%53,%54,%55,%56,%57,%58,%59,%60,%61,%62,%63}, {%64,%65,%66,%67}, %68, p, 1, 1, 1;\n}"
        : "+f"(d[0]), "+f"(d[1]), "+f"(d[2]), "+f"(d[3]), "+f"(d[4]), "+f"(d[5]), "+f"(d[6]), "+f"(d[7]), "+f"(d[8]), "+f"(d[9]), "+f"(d[10]), "+f"(d[11]), "+f"(d[12]), "+f"(d[13]), "+f"(d[14]), "+f"(d[15]), "+f"(d[16]), "+f"(d[17]), "+f"(d[18]), "+f"(d[19]), "+f"(d[20]), "+f"(d[21]), "+f"(d[22]), "+f"(d[23]), "+f"(d[24]), "+f"(d[25]), "+f"(d[26]), "+f"(d[27]), "+f"(d[28]), "+f"(d[29]), "+f"(d[30]), "+f"(d[31]), "+f"(d[32]), "+f"(d[33]), "+f"(d[34]), "+f"(d[35]), "+f"(d[36]), "+f"(d[37]), "+f"(d[38]), "+f"(d[39]), "+f"(d[40]), "+f"(d[41]), "+f"(d[42]), "+f"(d[43]), "+f"(d[44]), "+f"(d[45]), "+f"(d[46]), "+f"(d[47]), "+f"(d[48]), "+f"(d[49]), "+f"(d[50]), "+f"(d[51]), "+f"(d[52]), "+f"(d[53]), "+f"(d[54]), "+f"(d[55]), "+f"(d[56]), "+f"(d[57]), "+f"(d[58]), "+f"(d[59]), "+f"(d[60]), "+f"(d[61]), "+f"(d[62]), "+f"(d[63])
        : "r"(a[0]), "r"(a[1]), "r"(a[2]), "r"(a[3]), "l"(db), "n"(ACC));
}
__device__ __forceinline__ void attention_tile(float* acc, uint32_t sb, int tile, int h, int wg, int wq, uint32_t l0, uint32_t epoch, uint4* km, uint4* vm) {
    const uint32_t buf = sb + G_BUF + ((tile << 4) & sb & 0x3f0);
    const int lane = threadIdx.x & 31, g = lane >> 2, t = lane & 3;
    const int sg = wq >> 1, hf = wq & 1, seg = tile * 2 + sg;
    uint32_t qf[8][4];
#pragma unroll
    for (int kk = 0; kk < 8; kk++) {
        qf[kk][0] = pack2(acc[8 * kk], acc[8 * kk + 1]); qf[kk][1] = pack2(acc[8 * kk + 2], acc[8 * kk + 3]);
        qf[kk][2] = pack2(acc[8 * kk + 4], acc[8 * kk + 5]); qf[kk][3] = pack2(acc[8 * kk + 6], acc[8 * kk + 7]);
    }
    uint32_t* kvf = &g_KVf[seg][h][lane * 4];
    auto kv_valid = [&]() {
        uint32_t mn = 0xffffffffu;
#pragma unroll
        for (int i = 0; i < 4; i++) mn = min(min(min(mn, min(km[i].x, km[i].y)), min(km[i].z, km[i].w)), min(min(vm[i].x, vm[i].y), min(vm[i].z, vm[i].w)));
        return __all_sync(0xffffffffu, mn != 0);
    };
    float sc[5][4];
    auto mem_scores = [&]() {
        float sb_[4];
#pragma unroll
        for (int i = 0; i < 4; i++) { MMAF(i == 0, sc[4], qf[2 * i], ~km[i].x, ~km[i].y); MMAF(i == 0, sb_, qf[2 * i + 1], ~km[i].z, ~km[i].w); }
#pragma unroll
        for (int i = 0; i < 4; i++) sc[4][i] += sb_[i];
    };
    mbar_wait_p(sb + G_BAR + 8 * (GB_KV + wg), (tile >> 1) & 1);
    if (h == 5 && (threadIdx.x & 127) == 0 && tile < 6) GT(1750 + tile * 8 + 2);
    bool fast;
    {
        const uint64_t dk = desc_sw128(buf, 16, 1024);
        asm volatile("wgmma.fence.sync.aligned;" ::: "memory");
#pragma unroll
        for (int kk = 0; kk < 8; kk++) {
            if (kk == 0) wgmma_rs64<0>(acc, qf[kk], dk); else wgmma_rs64<1>(acc, qf[kk], dk + (kk >> 2) * 512 + (kk & 3) * 2);
        }
        asm volatile("wgmma.commit_group.sync.aligned;" ::: "memory");
        mem_scores();
        fast = kv_valid();
        asm volatile("wgmma.wait_group.sync.aligned 0;" ::: "memory");
        mbar_arrive_if(sb + G_BAR + 8 * GB_KVF, l0);
#pragma unroll
        for (int i = 0; i < 32; i++) asm volatile("" : "+f"(acc[i]) :: "memory");
#pragma unroll
        for (int b = 0; b < 4; b++)
#pragma unroll
            for (int i = 0; i < 4; i++) sc[b][i] = sg ? acc[16 + 4 * b + i] : acc[4 * b + i];
#pragma unroll
        for (int i = 0; i < 4; i++) sc[4][i] = fast ? sc[4][i] : -INFINITY;
    }
    const float cexp = 0.08838834764831845f * 1.4426950408889634f;
    const int r0 = hf * 16 + g, r1 = r0 + 8;
#pragma unroll
    for (int b = 0; b < 4; b++) {
        const int j = b * 8 + 2 * t;
        if (j > r0) sc[b][0] = -INFINITY;
        if (j + 1 > r0) sc[b][1] = -INFINITY;
        if (j > r1) sc[b][2] = -INFINITY;
        if (j + 1 > r1) sc[b][3] = -INFINITY;
    }
    float m0 = -INFINITY, m1 = -INFINITY;
#pragma unroll
    for (int b = 0; b < 5; b++) { m0 = fmaxf(m0, fmaxf(sc[b][0], sc[b][1])); m1 = fmaxf(m1, fmaxf(sc[b][2], sc[b][3])); }
    m0 = fmaxf(m0, __shfl_xor_sync(0xffffffffu, m0, 1)); m1 = fmaxf(m1, __shfl_xor_sync(0xffffffffu, m1, 1));
    m0 = fmaxf(m0, __shfl_xor_sync(0xffffffffu, m0, 2)); m1 = fmaxf(m1, __shfl_xor_sync(0xffffffffu, m1, 2));
    float z0 = 0.f, z1 = 0.f;
    uint32_t p0, p1;
    {
        const float c0 = -m0 * cexp, c1 = -m1 * cexp;
        uint32_t pf[5][2];
#pragma unroll
        for (int b = 0; b < 5; b++) {
            pf[b][0] = pack2(ex2(fmaf(sc[b][0], cexp, c0)), ex2(fmaf(sc[b][1], cexp, c0)));
            pf[b][1] = pack2(ex2(fmaf(sc[b][2], cexp, c1)), ex2(fmaf(sc[b][3], cexp, c1)));
        }
        p0 = pf[4][0]; p1 = pf[4][1];
        uint32_t pa[4][4];
#pragma unroll
        for (int kk = 0; kk < 4; kk++)
#pragma unroll
            for (int i = 0; i < 4; i++) pa[kk][i] = (kk >> 1) == sg ? pf[(kk & 1) * 2 + (i >> 1)][i & 1] : 0u;
        const uint64_t dv = desc_sw128(buf + 32768, 8192, 1024);
        mbar_wait_p(sb + G_BAR + 8 * (GB_VV + wg), (tile >> 1) & 1);
        asm volatile("wgmma.fence.sync.aligned;" ::: "memory");
#pragma unroll
        for (int kk = 0; kk < 4; kk++) { if (kk == 0) wgmma_rs128t<0>(acc, pa[kk], dv); else wgmma_rs128t<1>(acc, pa[kk], dv + kk * 128); }
        asm volatile("wgmma.commit_group.sync.aligned;" ::: "memory");
#pragma unroll
        for (int b = 0; b < 5; b++) { z0 += bf_lo(pf[b][0]) + bf_hi(pf[b][0]); z1 += bf_lo(pf[b][1]) + bf_hi(pf[b][1]); }
        asm volatile("wgmma.wait_group.sync.aligned 0;" ::: "memory");
#pragma unroll
        for (int i = 0; i < 64; i++) asm volatile("" : "+f"(acc[i]) :: "memory");
    }
    mbar_arrive_if(sb + G_BAR + 8 * GB_VF, l0);
    if (h == 5 && (threadIdx.x & 127) == 0 && tile < 6) GT(1750 + tile * 8 + 3);
    if (!fast) {
        wait_rec(&g_f.rec[2 * h], epoch, seg + 1);
        if (seg == 63 && (threadIdx.x & 63) == 0) GT(1570 + h);
        uint32_t n = 0;
#pragma unroll 1
        do {
#pragma unroll
            for (int i = 0; i < 4; i++) { km[i] = ldg_rlx4(kvf + i * 128); vm[i] = ldg_rlx4(kvf + 512 + i * 128); }
            if (++n > SPIN_LIMIT) { ABORT(4); break; }
        } while (!kv_valid());
        mem_scores();
        float n0 = fmaxf(sc[4][0], sc[4][1]), n1 = fmaxf(sc[4][2], sc[4][3]);
        n0 = fmaxf(n0, __shfl_xor_sync(0xffffffffu, n0, 1)); n1 = fmaxf(n1, __shfl_xor_sync(0xffffffffu, n1, 1));
        n0 = fmaxf(n0, __shfl_xor_sync(0xffffffffu, n0, 2)); n1 = fmaxf(n1, __shfl_xor_sync(0xffffffffu, n1, 2));
        n0 = fmaxf(n0, m0); n1 = fmaxf(n1, m1);
        const float a0 = ex2((m0 - n0) * cexp), a1 = ex2((m1 - n1) * cexp);
        const float c0 = -n0 * cexp, c1 = -n1 * cexp;
        p0 = pack2(ex2(fmaf(sc[4][0], cexp, c0)), ex2(fmaf(sc[4][1], cexp, c0)));
        p1 = pack2(ex2(fmaf(sc[4][2], cexp, c1)), ex2(fmaf(sc[4][3], cexp, c1)));
        z0 = fmaf(z0, a0, bf_lo(p0) + bf_hi(p0)); z1 = fmaf(z1, a1, bf_lo(p1) + bf_hi(p1));
#pragma unroll
        for (int j = 0; j < 16; j++) { float* o = acc + 4 * j; o[0] *= a0; o[1] *= a0; o[2] *= a1; o[3] *= a1; }
    }
    if (h == 5 && (threadIdx.x & 127) == 0 && tile < 6) GT(1750 + tile * 8 + 4);
    if (hf) bar_arrive(5 + wg * 2 + sg, 64);
#pragma unroll
    for (int i = 0; i < 4; i++) {
        mma1688(acc + 16 * i, p0, p1, ~vm[i].x); mma1688(acc + 16 * i + 4, p0, p1, ~vm[i].y);
        mma1688(acc + 16 * i + 8, p0, p1, ~vm[i].z); mma1688(acc + 16 * i + 12, p0, p1, ~vm[i].w);
    }
    z0 += __shfl_xor_sync(0xffffffffu, z0, 1); z1 += __shfl_xor_sync(0xffffffffu, z1, 1);
    z0 += __shfl_xor_sync(0xffffffffu, z0, 2); z1 += __shfl_xor_sync(0xffffffffu, z1, 2);
    if (h == 5 && (threadIdx.x & 127) == 0 && tile < 6) GT(1750 + tile * 8 + 5);
    if (tile >= 2) mbar_wait_p(sb + G_BAR + 8 * (GB_FREE + wg), ((tile >> 1) - 1) & 1);
    store_perm(acc, g_O + (size_t)(tile * 64 + wq * 16 + g) * HD + h * 128 + t * 8, HD, rcpf(z0), rcpf(z1));
    mbar_arrive(sb + G_BAR + 8 * (GB_STG + wg));
    if (!hf) {
        bar_sync(5 + wg * 2 + sg, 64);
#pragma unroll
        for (int i = 0; i < 8; i++) stg4_h(kvf + i * 128, make_uint4(0, 0, 0, 0), pol_ef(3));
    }
}

__device__ __forceinline__ void g_consumer(uint32_t sb_, int g_, int wg_, uint32_t epoch) {
    const uint32_t sb = uni(sb_);
    const int g = uni(g_), wg = uni(wg_), wq = uni((threadIdx.x >> 5) & 3);
    const uint32_t l0 = opaque((threadIdx.x & 31) == 0);
    const uint32_t bar = sb + G_BAR, buf = sb + G_BUF + wg * 32768;
    const int lane = threadIdx.x & 31;
    float acc[64];
    if (wg == 1) bar_arrive(3, 256);
    const int n1 = g < 32 ? HSPLIT / 2 : NT - HSPLIT / 2;
#pragma unroll 1
    for (int i = 0; i < n1; i++) {
        gemm_tile<4>(acc, sb, wg, i, i == 0 || i == NT / 2, i >= NT / 2, wg, true, l0, []() {});
        if (i == n1 - 1 || i == NT / 2 - 1) mbar_arrive_if(bar + 8 * GB_WFREE, l0);
        if (threadIdx.x == 0 && i == 0) GT((64 + g) * 8 + 1);
        if (threadIdx.x == 128 && i == 3) GT((64 + g) * 8 + 2);
        if (i > 0) mbar_wait_p(bar + 8 * (GB_FREE + wg), (i - 1) & 1);
        stage_bf16(acc, buf, 1.f, 1.f);
        asm volatile("fence.proxy.async.shared::cta;" ::: "memory");
        mbar_arrive(bar + 8 * (GB_STG + wg));
    }
    if (threadIdx.x == 128) GT((64 + g) * 8 + 3);
    if (g < 32) {
#pragma unroll 1
        for (int i = 0; i < NT / 2; i++) {
            const int tile = 2 * i + wg;
            const uint2 rec = ldg_rlx2(&g_f.rec[2 * g]);
            uint4 km[4], vm[4];
            gemm_tile<4>(acc, sb, tile, i, i == 0, 1, wg, tile != NT - 1, l0, [&]() {
                const uint32_t seg = tile * 2 + (wq >> 1);
                const uint32_t* kvf = &g_KVf[seg][g][lane * 4];
                const bool early = (rec.x >> 8) == epoch && (rec.y >> 8) == epoch && (rec.x & 255) > seg && (rec.y & 255) > seg;
#pragma unroll
                for (int j = 0; j < 4; j++) { km[j] = ldg_rlx4_if(kvf + j * 128, early); vm[j] = ldg_rlx4_if(kvf + 512 + j * 128, early); }
            });
            if (threadIdx.x == 0 && i == 0) GT((64 + g) * 8 + 4);
            if (threadIdx.x == 128 && i == 3) GT((64 + g) * 8 + 5);
            if (g == 5 && (threadIdx.x & 127) == 0 && tile < 6) GT(1750 + tile * 8 + 1);
            attention_tile(acc, sb, tile, g, wg, wq, l0, epoch, km, vm);
            if (g == 5 && (threadIdx.x & 127) == 0 && tile < 6) GT(1750 + tile * 8 + 6);
        }
    } else {
#pragma unroll 1
        for (int i = 0; i < NT / 2; i++) {
            const int tile = 2 * i + wg;
            gemm_tile<4>(acc, sb, tile, i, i == 0, 0, wg, tile != NT - 1, l0, []() {});
            if (threadIdx.x == 0 && i == 0) GT((64 + g) * 8 + 4);
            if (threadIdx.x == 128 && i == 3) GT((64 + g) * 8 + 5);
            mbar_wait_p(bar + 8 * (GB_FREE + wg), (i - 1) & 1);
            store_perm(acc, g_P + (size_t)(((g - 32) >> 2) * SQ + tile * 64 + wq * 16 + (lane >> 2)) * DM + ((g - 32) & 3) * 128 + (lane & 3) * 8, DM, 1.f, 1.f);
            mbar_arrive(bar + 8 * (GB_STG + wg));
        }
    }
}

__device__ __forceinline__ void load_w(uint32_t sb, const CUtensorMap* tm, int col, int row, int k0 = 0, int k1 = 2) {
    const uint32_t bar = sb + G_BAR;
#pragma unroll
    for (int kh = k0; kh < k1; kh++) {
        mbar_expect_tx(bar + 8 * (GB_W0 + kh), 65536);
        tma2d_h(sb + G_W + kh * 32768, tm, col, row + kh * 256, bar + 8 * (GB_W0 + kh), pol_ef(5));
        tma2d_h(sb + G_W + 65536 + kh * 32768, tm, col + 64, row + kh * 256, bar + 8 * (GB_W0 + kh), pol_ef(5));
    }
}

__device__ __forceinline__ void rbf2(float& a, float& b) { uint32_t w = pack2(a, b); a = bf_lo(w); b = bf_hi(w); }
__device__ __forceinline__ void warp_sum2(float& a, float& b) {
#pragma unroll
    for (int o = 16; o; o >>= 1) { float c = __shfl_xor_sync(0xffffffffu, a, o), d = __shfl_xor_sync(0xffffffffu, b, o); a += c; b += d; }
}
__device__ __forceinline__ float sum16(const float* v) {
    return (((v[0] + v[1]) + (v[2] + v[3])) + ((v[4] + v[5]) + (v[6] + v[7]))) + (((v[8] + v[9]) + (v[10] + v[11])) + ((v[12] + v[13]) + (v[14] + v[15])));
}
__device__ __forceinline__ void ln_row2(float* v, float* u) {
    float sv = sum16(v), su = sum16(u);
    warp_sum2(sv, su);
    const float mv = sv * (1.f / DM), mu = su * (1.f / DM);
    float qv = 0.f, qu = 0.f, qv2 = 0.f, qu2 = 0.f;
#pragma unroll
    for (int i = 0; i < 16; i += 2) {
        float d0 = v[i] - mv, d1 = v[i + 1] - mv, e0 = u[i] - mu, e1 = u[i + 1] - mu;
        qv = fmaf(d0, d0, qv); qv2 = fmaf(d1, d1, qv2); qu = fmaf(e0, e0, qu); qu2 = fmaf(e1, e1, qu2);
    }
    qv += qv2; qu += qu2;
    warp_sum2(qv, qu);
    const float rv = rbf(mv), ru = rbf(mu);
    const float iv = __frcp_rn(rbf(sqrtf(rbf(rbf(qv * (1.f / DM)) + 1e-5f)))), iu = __frcp_rn(rbf(sqrtf(rbf(rbf(qu * (1.f / DM)) + 1e-5f))));
#pragma unroll
    for (int i = 0; i < 16; i += 2) {
        float a = v[i] - rv, b = v[i + 1] - rv, c = u[i] - ru, d = u[i + 1] - ru;
        rbf2(a, b); rbf2(c, d);
        a *= iv; b *= iv; c *= iu; d *= iu;
        rbf2(a, b); rbf2(c, d);
        v[i] = a; v[i + 1] = b; u[i] = c; u[i + 1] = d;
    }
}

__device__ __forceinline__ void ln_row1(float* v) {
    float sv = sum16(v);
#pragma unroll
    for (int o = 16; o; o >>= 1) sv += __shfl_xor_sync(0xffffffffu, sv, o);
    const float mv = sv * (1.f / DM);
    float qv = 0.f, qv2 = 0.f;
#pragma unroll
    for (int i = 0; i < 16; i += 2) { float d0 = v[i] - mv, d1 = v[i + 1] - mv; qv = fmaf(d0, d0, qv); qv2 = fmaf(d1, d1, qv2); }
    qv += qv2;
#pragma unroll
    for (int o = 16; o; o >>= 1) qv += __shfl_xor_sync(0xffffffffu, qv, o);
    const float rv = rbf(mv);
    float sq, iv;
    asm("sqrt.approx.f32 %0, %1;" : "=f"(sq) : "f"(rbf(rbf(qv * (1.f / DM)) + 1e-5f)));
    asm("rcp.approx.f32 %0, %1;" : "=f"(iv) : "f"(rbf(sq)));
#pragma unroll
    for (int i = 0; i < 16; i += 2) {
        float a = v[i] - rv, b = v[i + 1] - rv;
        rbf2(a, b);
        a *= iv; b *= iv;
        rbf2(a, b);
        v[i] = a; v[i + 1] = b;
    }
}
constexpr int FSPLIT = 28;
__device__ __forceinline__ int fin_row(int id, int i) {
    if (id < 64) { const int tile = i < FSPLIT / 2 ? 2 * i : i + FSPLIT / 2; return tile < NT ? tile * 64 + id : -1; }
    const int j = id - 64 + i * 48;
    return j < FSPLIT * 32 ? (j >> 6) * 128 + 64 + (j & 63) : -1;
}
__device__ __forceinline__ void finalizer(int id, const bf16* __restrict__ x, const bf16* __restrict__ wr, bf16* __restrict__ out, uint32_t epoch) {
    const int lane = threadIdx.x & 31;
    float b0 = -INFINITY, b1 = -INFINITY; int i0 = 0x7fffffff, i1 = 0x7fffffff;
    const uint32_t tag = (epoch & 0xfffffu) << 12;
    uint32_t fl = ~epoch;
    int row = fin_row(id, 0);
    const uint4 ra = *(const uint4*)(wr + lane * 8), rb = *(const uint4*)(wr + 256 + lane * 8);
    uint4 xa = *(const uint4*)(x + (size_t)row * DM + lane * 8), xb = *(const uint4*)(x + (size_t)row * DM + lane * 8 + 256);
#pragma unroll 1
    for (int it = 0; row >= 0; it++) {
        const int tile = row >> 6, nxt = fin_row(id, it + 1);
        const size_t o0 = (size_t)row * DM + lane * 8;
        uint32_t n = 0;
#pragma unroll 1
        while (!__all_sync(0xffffffffu, fl == epoch)) {
            if (n) __nanosleep(it ? 64 : 1000);
            fl = ldg_rlx(&g_f.p[tile][lane]);
            if (++n > SPIN_LIMIT) { ABORT(12); break; }
        }
        if (tile == NT - 1 && id == 63 && lane == 0) GT(1438);
        if ((id == 63 || id == 3 || id == 70) && lane == 0) GT(1800 + (id == 3) * 32 + tile);
        float v[16];
        {
            uint4 pa[8][2];
#pragma unroll
            for (int k = 0; k < 8; k++) {
                pa[k][0] = ldg4_h(g_P + (size_t)k * SQ * DM + o0, pol_ef(2));
                pa[k][1] = ldg4_h(g_P + (size_t)k * SQ * DM + o0 + 256, pol_ef(2));
            }
            fl = ldg_rlx(&g_f.p[max(nxt, 0) >> 6][lane]);
#pragma unroll
            for (int j = 0; j < 2; j++) {
#pragma unroll
                for (int i = 0; i < 4; i++) {
                    uint32_t w[8];
#pragma unroll
                    for (int k = 0; k < 8; k++) w[k] = i == 0 ? pa[k][j].x : (i == 1 ? pa[k][j].y : (i == 2 ? pa[k][j].z : pa[k][j].w));
                    v[j * 8 + 2 * i] = ((bf_lo(w[0]) + bf_lo(w[1])) + (bf_lo(w[2]) + bf_lo(w[3]))) + ((bf_lo(w[4]) + bf_lo(w[5])) + (bf_lo(w[6]) + bf_lo(w[7])));
                    v[j * 8 + 2 * i + 1] = ((bf_hi(w[0]) + bf_hi(w[1])) + (bf_hi(w[2]) + bf_hi(w[3]))) + ((bf_hi(w[4]) + bf_hi(w[5])) + (bf_hi(w[6]) + bf_hi(w[7])));
                }
            }
        }
        uint32_t hw[8];
        {
            const uint32_t xw[8] = {xa.x, xa.y, xa.z, xa.w, xb.x, xb.y, xb.z, xb.w};
            uint32_t aw[8];
#pragma unroll
            for (int i = 0; i < 8; i++) aw[i] = pack2(v[2 * i], v[2 * i + 1]);
#pragma unroll
            for (int d = 1; d <= 2; d++) {
                const bool up = lane & d;
#pragma unroll
                for (int i = 0; i < 8; i++) {
                    if (!(i & d)) {
                        const uint32_t r = __shfl_xor_sync(0xffffffffu, up ? aw[i] : aw[i | d], d);
                        if (up) aw[i] = r; else aw[i | d] = r;
                    }
                }
            }
#pragma unroll
            for (int i = 0; i < 8; i++) {
                hw[i] = pack2(bf_lo(aw[i]) + bf_lo(xw[i]), bf_hi(aw[i]) + bf_hi(xw[i]));
                v[2 * i] = bf_lo(hw[i]); v[2 * i + 1] = bf_hi(hw[i]);
            }
        }
        xa = *(const uint4*)(x + (size_t)max(nxt, 0) * DM + lane * 8); xb = *(const uint4*)(x + (size_t)max(nxt, 0) * DM + lane * 8 + 256);
        ln_row1(v);
        float r0 = 0.f, r1 = 0.f;
        {
            const uint32_t ww[8] = {ra.x, ra.y, ra.z, ra.w, rb.x, rb.y, rb.z, rb.w};
#pragma unroll
            for (int i = 0; i < 8; i++) { r0 = fmaf(v[2 * i], bf_lo(ww[i]), r0); r1 = fmaf(v[2 * i + 1], bf_hi(ww[i]), r1); }
        }
        r0 += r1;
#pragma unroll
        for (int o = 16; o; o >>= 1) r0 += __shfl_xor_sync(0xffffffffu, r0, o);
        r0 = rbf(r0);
        if (cand_better(r0, row, b0, i0)) { b1 = b0; i1 = i0; b0 = r0; i0 = row; }
        else if (cand_better(r0, row, b1, i1)) { b1 = r0; i1 = row; }
        if (tile == NT - 1 && id == 63 && lane == 0) GT(1439);
        const bool last = nxt < 0, spec = tile < SPEC_TILES && (last || (nxt >> 6) >= SPEC_TILES);
        const bool pub = (lane == 0 && spec) || (lane == 1 && last);
        if (pub)
            asm volatile("st.relaxed.gpu.global.v4.b32 [%0], {%1,%2,%3,%4};" :: "l"(&g_f.cand[lane][id]),
                         "r"(FU(b0)), "r"(tag | (uint32_t)min(i0, 4095)), "r"(FU(b1)), "r"(tag | (uint32_t)min(i1, 4095)) : "memory");
#pragma unroll
        for (int j = 0; j < 2; j++) {
            const uint32_t* hh = hw + j * 4; const float* nn = v + j * 8;
            stg4_h(out + o0 + j * 256, make_uint4(pack2(bf_lo(hh[0]) + nn[0], bf_hi(hh[0]) + nn[1]), pack2(bf_lo(hh[1]) + nn[2], bf_hi(hh[1]) + nn[3]),
                                                  pack2(bf_lo(hh[2]) + nn[4], bf_hi(hh[2]) + nn[5]), pack2(bf_lo(hh[3]) + nn[6], bf_hi(hh[3]) + nn[7])), pol_ef(4));
            if (i0 == row || i1 == row || i1 >= SQ || row == SQ - 1) {
                *(uint4*)(g_h + o0 + j * 256) = make_uint4(hh[0], hh[1], hh[2], hh[3]);
                *(uint4*)(g_hn + o0 + j * 256) = make_uint4(pack2(nn[0], nn[1]), pack2(nn[2], nn[3]), pack2(nn[4], nn[5]), pack2(nn[6], nn[7]));
            }
        }
        if (last || spec) {
            __threadfence();
            __syncwarp();
            if (pub) stg_rlx(&g_f.rows[lane][id], epoch);
        }
        row = nxt;
    }
    if (id == 0 && lane == 0) { g_epoch = epoch; if (epoch == 0xffffffu) { g_ticket[0] = 0; g_ticket[32] = 0; } }
}

__device__ __forceinline__ void g_producer(uint32_t sb, int g, const Maps& maps, uint32_t epoch, const bf16* __restrict__ x, const bf16* __restrict__ wr, bf16* __restrict__ out) {
    const uint32_t bar = sb + G_BAR;
    const int warp = (threadIdx.x >> 5) - 8;
    if (threadIdx.x == 256 && g == 5) GT(1410);
    if (threadIdx.x == 256 && g == 5) GT(1411);
    if (warp == 3) {
        wait_eq4(&g_f.xn[(threadIdx.x & 31) * 4], epoch, 13);
        __syncwarp();
        if ((threadIdx.x & 31) == 0) mbar_arrive(bar + 8 * GB_XN);
        wait_eq2(&g_f.rload[(threadIdx.x & 31) * 2], epoch, 13);
        __syncwarp();
        if ((threadIdx.x & 31) == 0) mbar_arrive(bar + 8 * GB_RL);
        finalizer(g, x, wr, out, epoch);
        if (g == 63 && (threadIdx.x & 31) == 0) GT(128 * 8 + 6);
    }
    if ((threadIdx.x & 31) != 0) return;
    if (threadIdx.x == 256 && g == 5) GT(1412);
    if (warp == 0) {
        wait_eq4(&g_f.xn[0], epoch, 13);
        const int rk = g & 1;
        const int m1 = g < 32 ? HSPLIT : 2 * NT - HSPLIT;
#pragma unroll 1
        for (int it = 0; it < m1; it++) {
            const int tile = it < NT ? it : it - NT + HSPLIT;
            if (it == HOLD) mbar_wait(bar + 8 * GB_RL, 0);
            if (it == 1) wait_eq4(&g_f.xn[4], epoch, 13);
            if (it == 2) mbar_wait(bar + 8 * GB_XN, 0);
            if (it == NT) {
                mbar_wait(bar + 8 * GB_WFREE, 0);
                load_w(sb, (g & 1) ? &maps.wv : &maps.wk, ((g - 32) >> 1) * 128, 0);
            }
#pragma unroll
            for (int k = 0; k < 4; k++) {
                if (k == 2 && it == 0) load_w(sb, (g & 1) ? &maps.wv : &maps.wk, (g >> 1) * 128, 0, 1, 2);
                mbar_wait(bar + 8 * (GB_EMPTY + k), (it & 1) ^ 1);
                mbar_expect_tx(bar + 8 * (GB_FULL + k), 16384);
                tma2d_mc(sb + slot_off(k) + rk * 8192, &maps.xn2, (k * 2 + rk) * 64, tile * 64, bar + 8 * (GB_FULL + k));
            }
        }
        mbar_wait(bar + 8 * GB_WFREE, g >= 32);
        const int u = g - 32, ks = u >> 2, ns = u & 3;
        if (g < 32) load_w(sb, &maps.wq, g * 128, 0);
        else {
#pragma unroll
            for (int kh = 0; kh < 2; kh++) {
                mbar_expect_tx(bar + 8 * (GB_W0 + kh), 65536);
#pragma unroll
                for (int nh = 0; nh < 2; nh++)
                    asm volatile("cp.async.bulk.tensor.5d.shared::cluster.global.mbarrier::complete_tx::bytes [%0], [%1, {%3, %4, %4, %4, %5}], [%2];"
                        :: "r"(sb + G_W + nh * 65536 + kh * 32768), "l"((uint64_t)&maps.wo2), "r"(bar + 8 * (GB_W0 + kh)), "r"(ns * 128 + nh * 64), "r"(0), "r"(ks * 16 + kh * 8) : "memory");
            }
        }
        if (g < 32) {
#pragma unroll 1
            for (int n = 0; n < NT * 4; n++) {
                const int slot = n & 3;
                mbar_wait(bar + 8 * (GB_EMPTY + slot), ((n >> 2) & 1) ^ 1);
                mbar_expect_tx(bar + 8 * (GB_FULL + slot), 16384);
                tma2d_mc(sb + slot_off(slot) + rk * 8192, &maps.xn2, (slot * 2 + rk) * 64, (n >> 2) * 64, bar + 8 * (GB_FULL + slot));
            }
        } else {
#pragma unroll 1
            for (int tile = 0; tile < NT; tile++) {
                wait_eq4(&g_f.o[tile][ks][0], epoch, 9);
                if (g == 40 && tile == NT - 1) GT(1437);
                if (tile == NT - 1) GT(1690 + g - 32);
#pragma unroll
                for (int k = 0; k < 4; k++) {
                    mbar_wait(bar + 8 * (GB_EMPTY + k), (tile & 1) ^ 1);
                    mbar_expect_tx(bar + 8 * (GB_FULL + k), 16384);
                    tma2d_mc_h(sb + slot_off(k) + rk * 8192, &maps.ox2, (ks * 8 + k * 2 + rk) * 64, tile * 64, bar + 8 * (GB_FULL + k), pol_ef(1));
                }
            }
        }
    } else if (warp < 3) {
        const int wg = warp - 1;
        const uint32_t buf = sb + G_BUF + wg * 32768;
        const CUtensorMap* tkv = (g & 1) ? &maps.vx3 : &maps.kx3;
        const int n1 = g < 32 ? HSPLIT / 2 : NT - HSPLIT / 2;
#pragma unroll 1
        for (int i = 0; i < n1; i++) {
            const int tile = (i < NT / 2 ? 2 * i : 2 * i - NT + HSPLIT) + wg, hd = (i < NT / 2 ? g : g - 32) >> 1;
            mbar_wait(bar + 8 * (GB_STG + wg), i & 1);
            tma_store3d(tkv, buf, tile * 64, hd * 2);
            asm volatile("cp.async.bulk.commit_group;" ::: "memory");
            asm volatile("cp.async.bulk.wait_group.read 0;" ::: "memory");
            mbar_arrive(bar + 8 * (GB_FREE + wg));
            asm volatile("cp.async.bulk.wait_group 0;" ::: "memory");
            PUBLISH(&g_f.kv[tile][hd][g & 1], epoch);
        }
        if (wg == 0) mbar_arrive(bar + 8 * GB_T1D);
        if (g < 32 && wg == 1) {
            mbar_wait(bar + 8 * GB_T1D, 0);
#pragma unroll 1
            for (int tile = 0; tile < NT; tile++) {
                wait_eq2(&g_f.kv[tile][g][0], epoch, 10);
                if (tile > 0) mbar_wait(bar + 8 * GB_KVF, (tile - 1) & 1);
                mbar_expect_tx(bar + 8 * (GB_KV + (tile & 1)), 16384);
                tma3d_h(sb + G_BUF, &maps.kx3, tile * 64, g * 2, bar + 8 * (GB_KV + (tile & 1)), pol_ef(0));
                if (tile > 0) mbar_wait(bar + 8 * GB_VF, (tile - 1) & 1);
                mbar_expect_tx(bar + 8 * (GB_VV + (tile & 1)), 16384);
                tma3d_h(sb + G_BUF + 32768, &maps.vx3, tile * 64, g * 2, bar + 8 * (GB_VV + (tile & 1)), pol_ef(0));
                if (PFK && tile + PFK < NT) {
                    const uint2 v = ldg_rlx2(&g_f.kv[tile + PFK][g][0]);
                    if (v.x == epoch && v.y == epoch) { tma_pf3d(&maps.kx3, (tile + PFK) * 64, g * 2); tma_pf3d(&maps.vx3, (tile + PFK) * 64, g * 2); }
                }
            }
        } else {
#pragma unroll 1
            for (int tile = g < 32 ? 0 : wg; tile < NT; tile += g < 32 ? 1 : 2) {
                mbar_wait(bar + 8 * (GB_STG + (tile & 1)), (tile >> 1) & 1);
                mbar_arrive(bar + 8 * (GB_FREE + (tile & 1)));
                PUBLISH(g < 32 ? &g_f.o[tile][g >> 2][g & 3] : &g_f.p[tile][g - 32], epoch);
                if (g == 3 && tile == NT - 1) GT(1436);
                if (g == 3) GT(1896 + tile);
                if (g < 32 && tile == NT - 1) GT(1610 + g);
                if (g == 40 && tile == NT - 1) GT(1435);
                if (g == 40) GT(1864 + tile);
                if (g >= 32 && tile == NT - 1) GT(1650 + g - 32);
            }
        }
    }
}

struct WPtr { const bf16 *q, *k, *v, *o; };
__device__ __forceinline__ int startup(uint8_t* smem, const bf16* __restrict__ x, const Maps& maps, uint32_t& epoch, const WPtr& pw) {
    const int tid = threadIdx.x, lane = tid & 31, w = tid >> 5, cta = blockIdx.x;
    volatile uint32_t* sh = (volatile uint32_t*)(smem + SH_OFF);
    if (cta == 4 && tid == 0) GT(1399);
    epoch = (ldg_rlx(&g_epoch) + 1) & 0x00ffffffu;
    if (w < 4) {
        if (!(cta & 1)) {
            uint32_t* pp = (uint32_t*)(xpage() + ((XR3 ^ 0x3000u) ^ ((w == 1 || w == 2) ? 0x1000u : 0u) ^ ((w & 2) << 13))) + (cta >> 1) * 8;
            if (lane < 8) stg_rlx(pp + lane, 0u);
            __syncwarp();
            if (lane == 0) {
                uint32_t best = 0xffffffffu, a = 0;
#pragma unroll 1
                for (int r = 0; r < NPROBE; r++) {
                    uint32_t t0 = clk32();
                    asm volatile("atom.relaxed.gpu.global.add.u32 %0, [%1], %2;" : "=r"(a) : "l"(pp), "r"(a + 1) : "memory");
                    if (a == 0x7fffffffu) ABORT(15);
                    uint32_t t1 = clk32();
                    if (r > 0) best = min(best, t1 - t0);
                    else if (w == 0) {
                        asm volatile("red.relaxed.gpu.global.max.u32 [%0], %1;" :: "l"(&g_ticket[0]), "r"(epoch << 8) : "memory");
                        asm volatile("red.relaxed.gpu.global.max.u32 [%0], %1;" :: "l"(&g_ticket[32]), "r"(epoch << 8) : "memory");
                    }
                }
                sh[w] = best;
            }
        }
        if (!(cta & 1)) bar_sync(1, 128);
        if (cta == 4 && tid == 0) GT(1400);
        if (w == 0) {
            if (lane == 0) {
                uint32_t rp;
                if (!(cta & 1)) {
                    uint32_t a = sh[0], b = sh[1], c = sh[2], d = sh[3];
                    uint32_t mid = (min(min(a, b), min(c, d)) + max(max(a, b), max(c, d))) >> 1;
                    const int dd = (int)min(a, d) - (int)min(b, c);
                    uint32_t cls = abs(dd) > 60 ? dd > 0 : a > mid;
                    uint32_t t = atomicAdd(&g_ticket[cls * 32], 1u) & 255;
                    if (t >= (cls ? 34u : 32u)) { cls ^= 1; t = atomicAdd(&g_ticket[cls * 32], 1u) & 255; }
                    rp = min(cls ? 32 + t : t, 65u);
                    stg_rlx(&g_table[(cta >> 1) * 8], (epoch << 8) | rp);
                } else {
                    uint32_t v, n = 0;
#pragma unroll 1
                    while (((v = ldg_rlx(&g_table[(cta >> 1) * 8])) >> 8) != epoch) { if (++n > SPIN_LIMIT) { ABORT(14); break; } }
                    rp = v & 255;
                }
                const int role = rp * 2 + (cta & 1);
                sh[8] = role; sh[9] = epoch;
                while (sh[10] != epoch + 1 && cta < NWAITLN) {}
                if (role < 64) rec_first_loads(smem_u32(smem), role, maps);
                else if (role < 128) load_w(smem_u32(smem), (role & 1) ? &maps.wv : &maps.wk, ((role - 64) >> 1) * 128, 0, 0, 1);
                if (cta == 4) GT(1401);
            }
        }
    } else if (cta < 128) {
        uint4 u[2][2];
        const int row0 = cta * 16 + (w - 4) * 2;
#pragma unroll
        for (int r = 0; r < 2; r++)
#pragma unroll
            for (int j = 0; j < 2; j++) u[r][j] = *(const uint4*)(x + (size_t)(row0 + r) * DM + j * 256 + lane * 8);
        if (cta < 48) {
            const uint32_t b = cta >> 3, off = (b >= 4 ? 0x8000u + (b & 1) * 0x4000u : ((b & 1) ? 0x3000u : 0u) + ((b & 2) << 13)) ^ aslot(cta & 7);
            *(uint4*)(xpage() + off + (tid - 128) * 16) = make_uint4(0, 0, 0, 0);
        }
        float v[2][16];
#pragma unroll
        for (int r = 0; r < 2; r++)
#pragma unroll
            for (int j = 0; j < 2; j++) {
                uint32_t ww[4] = {u[r][j].x, u[r][j].y, u[r][j].z, u[r][j].w};
#pragma unroll
                for (int i = 0; i < 4; i++) { v[r][j * 8 + 2 * i] = bf_lo(ww[i]); v[r][j * 8 + 2 * i + 1] = bf_hi(ww[i]); }
            }
        ln_row2(v[0], v[1]);
#pragma unroll
        for (int r = 0; r < 2; r++)
#pragma unroll
            for (int j = 0; j < 2; j++)
                *(uint4*)(g_xn + (size_t)(row0 + r) * DM + j * 256 + lane * 8) =
                    make_uint4(pack2(v[r][j * 8], v[r][j * 8 + 1]), pack2(v[r][j * 8 + 2], v[r][j * 8 + 3]), pack2(v[r][j * 8 + 4], v[r][j * 8 + 5]), pack2(v[r][j * 8 + 6], v[r][j * 8 + 7]));
        bar_sync(2, 256);
        if (tid == 160 && cta < NWAITLN) { st_rel(&g_f.xn[cta], epoch); sh[10] = epoch + 1; }
        if (cta == 4 && tid == 160) GT(1403);
        __syncwarp();
    }
    if (cta == 4 && tid == 128) GT(1402);
    __syncthreads();
    if (tid == 160 && cta >= NWAITLN && cta < 128) st_rel(&g_f.xn[cta], epoch);
    __syncwarp();
    const int role = sh[8];
    return role;
}

__global__ void __cluster_dims__(2, 1, 1) __launch_bounds__(384, 1)
main_kernel(const __grid_constant__ Maps maps, const bf16* __restrict__ x, const bf16* __restrict__ mem0, const bf16* __restrict__ wr,
            const bf16* __restrict__ wd, bf16* __restrict__ out, const WPtr pw) {
    extern __shared__ __align__(1024) uint8_t smem[];
    const uint32_t sb = smem_u32(smem);
    if (threadIdx.x == 0) {
        for (int i = 0; i < MB_N; i++) mbar_init(sb + R_BAR + 8 * i, i == MB_V ? 4 : 1);
        for (int i = 0; i < GB_N; i++)
            mbar_init(sb + G_BAR + 8 * i, i == GB_WFREE || (i >= GB_EMPTY && i < GB_KV) ? 8 : (i >= GB_KVF ? 4 : (i >= GB_STG && i < GB_FREE ? 128 : 1)));
        asm volatile("fence.mbarrier_init.release.cluster;" ::: "memory");
    }
    __syncwarp();
    asm volatile("barrier.cluster.arrive.relaxed.aligned;" ::: "memory");
    if (threadIdx.x >= 352 && threadIdx.x < 352 + (int)(sizeof(Maps) / sizeof(CUtensorMap)))
        asm volatile("prefetch.tensormap [%0];" :: "l"((const CUtensorMap*)&maps + (threadIdx.x - 352)) : "memory");
    uint32_t epoch;
    asm volatile("fence.proxy.async.shared::cta;" ::: "memory");
    const int role = uni(startup(smem, x, maps, epoch, pw));
    asm volatile("barrier.cluster.wait.aligned;" ::: "memory");
    const int wg = uni(threadIdx.x >> 7);
    if (role < 64) {
#define SETREG(n) do { if ((n) < 168) asm volatile("setmaxnreg.dec.sync.aligned.u32 %0;" :: "n"(n)); if ((n) > 168) asm volatile("setmaxnreg.inc.sync.aligned.u32 %0;" :: "n"(n)); } while (0)
#define RESREG(n) do { if ((n) < 168) asm volatile("setmaxnreg.inc.sync.aligned.u32 168;"); if ((n) > 168) asm volatile("setmaxnreg.dec.sync.aligned.u32 168;"); } while (0)
        if (wg == WGA) {
            SETREG(RGA);
            rec_a(sb, role, mem0, epoch);
            RESREG(RGA);
        } else if (wg == WGB) {
            SETREG(RGB);
            rec_b(sb, role, epoch);
            RESREG(RGB);
        } else {
            SETREG(RGC);
            rec_c(sb, role, mem0, maps, epoch);
            RESREG(RGC);
        }
        ffn_phase(maps, wd, out);
        if (threadIdx.x == 0) GT(((volatile int*)(smem + SH_OFF))[8] * 8 + 6);
    } else if (role < 128) {
        if (wg < 2) {
            asm volatile("setmaxnreg.inc.sync.aligned.u32 192;");
            g_consumer(sb, role - 64, wg, epoch);
            if (threadIdx.x == 128) GT(role * 8 + 6);
        } else {
            asm volatile("setmaxnreg.dec.sync.aligned.u32 120;");
            g_producer(sb, role - 64, maps, epoch, x, wr, out);
        }
    } else {
        finalizer(64 + (threadIdx.x >> 5) * 4 + role - 128, x, wr, out, epoch);
    }
}

typedef CUresult (*EncodeFn)(CUtensorMap*, CUtensorMapDataType, cuuint32_t, void*, const cuuint64_t*, const cuuint64_t*, const cuuint32_t*, const cuuint32_t*,
                             CUtensorMapInterleave, CUtensorMapSwizzle, CUtensorMapL2promotion, CUtensorMapFloatOOBfill);
static void make_map3(EncodeFn fn, CUtensorMap* m, const void* ptr, uint64_t cols, uint64_t rows) {
    cuuint64_t dims[3] = {64, rows, cols / 64};
    cuuint64_t strides[2] = {cols * 2, 128};
    cuuint32_t box[3] = {64, 64, 2};
    cuuint32_t es[3] = {1, 1, 1};
    fn(m, CU_TENSOR_MAP_DATA_TYPE_BFLOAT16, 3, (void*)ptr, dims, strides, box, es, CU_TENSOR_MAP_INTERLEAVE_NONE, CU_TENSOR_MAP_SWIZZLE_128B,
       CU_TENSOR_MAP_L2_PROMOTION_L2_256B, CU_TENSOR_MAP_FLOAT_OOB_FILL_NONE);
}
static void make_map(EncodeFn fn, CUtensorMap* m, const void* ptr, uint64_t cols, uint64_t rows, uint32_t bcols, uint32_t brows,
                     bool f32 = false, CUtensorMapSwizzle sw = CU_TENSOR_MAP_SWIZZLE_128B) {
    cuuint64_t dims[2] = {cols, rows};
    cuuint64_t strides[1] = {cols * (f32 ? 4 : 2)};
    cuuint32_t box[2] = {bcols, brows};
    cuuint32_t es[2] = {1, 1};
    fn(m, f32 ? CU_TENSOR_MAP_DATA_TYPE_FLOAT32 : CU_TENSOR_MAP_DATA_TYPE_BFLOAT16, 2, (void*)ptr, dims, strides, box, es, CU_TENSOR_MAP_INTERLEAVE_NONE, sw,
       CU_TENSOR_MAP_L2_PROMOTION_L2_256B, CU_TENSOR_MAP_FLOAT_OOB_FILL_NONE);
}

extern "C" void kernel_launch(void* const* d_in, const int* in_sizes, int n_in, void* d_out, int out_size) {
    const bf16* x = (const bf16*)d_in[0];
    const bf16* mem0 = (const bf16*)d_in[1];
    const bf16* Wq = (const bf16*)d_in[2];
    const bf16* Wk = (const bf16*)d_in[3];
    const bf16* Wv = (const bf16*)d_in[4];
    const bf16* Wo = (const bf16*)d_in[5];
    const bf16* wr = (const bf16*)d_in[8];
    const bf16* wg = (const bf16*)d_in[9];
    const bf16* wu = (const bf16*)d_in[10];
    const bf16* wd = (const bf16*)d_in[11];
    bf16* out = (bf16*)d_out;

    static EncodeFn enc = nullptr;
    static void *pxn, *pK, *pV, *pO, *pacc;
    if (!enc) {
        cudaDriverEntryPointQueryResult qr;
        void* fn = nullptr;
        cudaGetDriverEntryPoint("cuTensorMapEncodeTiled", &fn, cudaEnableDefault, &qr);
        enc = (EncodeFn)fn;
        cudaGetSymbolAddress(&pxn, g_xn); cudaGetSymbolAddress(&pK, g_K); cudaGetSymbolAddress(&pV, g_V);
        cudaGetSymbolAddress(&pO, g_O); cudaGetSymbolAddress(&pacc, g_P);
        cudaFuncSetAttribute(main_kernel, cudaFuncAttributeMaxDynamicSharedMemorySize, SMEM_TOTAL);
    }
    Maps m;
    make_map(enc, &m.wq, Wq, HD, DM, 64, 256);
    make_map(enc, &m.wk, Wk, HD, DM, 64, 256);
    make_map(enc, &m.wv, Wv, HD, DM, 64, 256);
    make_map(enc, &m.wo, Wo, DM, HD, 64, 128);
    {
        cuuint64_t dims[5] = {DM, 2, 4, 4, HD / 32};
        cuuint64_t strides[4] = {DM * 2, 8 * DM * 2, 2 * DM * 2, 32 * DM * 2};
        cuuint32_t box[5] = {64, 2, 4, 4, 8};
        cuuint32_t es[5] = {1, 1, 1, 1, 1};
        enc(&m.wo2, CU_TENSOR_MAP_DATA_TYPE_BFLOAT16, 5, (void*)Wo, dims, strides, box, es, CU_TENSOR_MAP_INTERLEAVE_NONE, CU_TENSOR_MAP_SWIZZLE_128B,
            CU_TENSOR_MAP_L2_PROMOTION_L2_256B, CU_TENSOR_MAP_FLOAT_OOB_FILL_NONE);
    }
    make_map(enc, &m.kx, pK, HD, SQ, 64, 64);
    make_map(enc, &m.ox2, pO, HD, SQ, 64, 64);
    make_map(enc, &m.xn2, pxn, DM, SQ, 64, 64);
    make_map3(enc, &m.kx3, pK, HD, SQ); make_map3(enc, &m.vx3, pV, HD, SQ);
    make_map(enc, &m.wg, wg, FF, DM, 32, 256, false, CU_TENSOR_MAP_SWIZZLE_NONE);
    make_map(enc, &m.wu, wu, FF, DM, 32, 256, false, CU_TENSOR_MAP_SWIZZLE_NONE);

    cudaStream_t st = cudaStreamPerThread;
    main_kernel<<<NCTA, 384, SMEM_TOTAL, st>>>(m, x, mem0, wr, wd, out, WPtr{Wq, Wk, Wv, Wo});
}
```

```cpp
#include <cuda_runtime.h>
#include <cuda_bf16.h>
#include <cuda.h>
#include <stdint.h>
#include <stddef.h>

typedef __nv_bfloat16 bf16;

constexpr int SQ = 2048, DM = 512, NH = 32, DH = 128, NSEG = 64, HD = 4096, FF = 1792;

constexpr int NT = 32;
#define SPEC_TILES 30
__device__ __align__(1024) bf16 g_xn[SQ * DM];
__device__ __align__(1024) bf16 g_K[SQ * HD];
__device__ __align__(1024) bf16 g_V[SQ * HD];
__device__ __align__(1024) bf16 g_O[SQ * HD];
__device__ __align__(1024) uint32_t g_KVf[NSEG][NH][1024];
__device__ __align__(1024) bf16 g_P[8 * SQ * DM];
__device__ __align__(1024) bf16 g_h[SQ * DM];
__device__ __align__(1024) bf16 g_hn[SQ * DM];
__device__ uint8_t g_xraw[12 << 20];
#define XPG 0
__device__ __forceinline__ uint64_t xpage() { return (((uint64_t)g_xraw + (2 << 20) - 1) & ~(uint64_t)((2 << 20) - 1)) + ((uint64_t)XPG << 21); }
constexpr uint32_t XR3 = (1u << 20) | (1u << 19) | (1u << 12);
__device__ __forceinline__ uint32_t aslot(uint32_t s) { return ((s & 1) << 18) | ((s & 2) << 19) | ((s & 4) * 0xc000u); }
__device__ __forceinline__ uint32_t acc_base(uint32_t W) { return ((W & 2) ? 0x3000u : 0u) + ((W & 4) << 12) + (W & 1) * 2048; }
__device__ __forceinline__ uint32_t ext_base(uint32_t W) { return 0x8000u + ((W & 4) << 12) + (W & 3) * 1024; }
#define XHS 256
#define XSS 32
__device__ __forceinline__ uint32_t zero_off(uint32_t c, uint32_t ln) {
    return ln < 8 ? acc_base(c >> 3) + (c & 7) * 256 + ln * 16 : ext_base(c >> 3) + ((c >> 2) & 1) * XHS + ((c >> 1) & 1) * XSS + (c & 1) * 16;
}
struct Flags {
    uint32_t kv[NT][NH][2];
    uint32_t o[NT][8][32];
    uint32_t rec[64];
    uint32_t xn[128];
    uint32_t p[NT][32];
    uint32_t rows[2][128];
    uint4 cand[2][128];
    uint4 norm[64];
};
__device__ __align__(1024) Flags g_f;
__device__ __align__(1024) uint4 g_yp[2][FF / 32][DM];
__device__ __align__(1024) uint32_t g_table[66 * 8];
__device__ __align__(256) uint32_t g_ticket[64];
__device__ uint32_t g_epoch;
#define NS3 6
#define HSPLIT 24
#define PFK 2
#define NWAITLN 8
#define WGA 0
#define WGB 1
#define WGC (3 - WGA - WGB)
#define NPROBE 3
constexpr int NCTA = 132;
constexpr int NFW = 112;
__device__ uint32_t g_abort;
__device__ long long g_dbg[4096];
#define TR(slot, v)

__device__ __forceinline__ uint32_t smem_u32(const void* p) { return (uint32_t)__cvta_generic_to_shared(p); }
__device__ __forceinline__ void mbar_init(uint32_t a, uint32_t c) { asm volatile("mbarrier.init.shared::cta.b64 [%0], %1;" :: "r"(a), "r"(c) : "memory"); }
__device__ __forceinline__ void mbar_expect_tx(uint32_t a, uint32_t tx) { asm volatile("mbarrier.arrive.expect_tx.shared::cta.b64 _, [%0], %1;" :: "r"(a), "r"(tx) : "memory"); }
__device__ __forceinline__ void mbar_arrive(uint32_t a) { asm volatile("mbarrier.arrive.shared::cta.b64 _, [%0];" :: "r"(a) : "memory"); }
__device__ __forceinline__ void mbar_arrive_if(uint32_t a, uint32_t pred) {
    asm volatile("{\n.reg .pred p;\nsetp.ne.u32 p, %1, 0;\n@p mbarrier.arrive.shared::cta.b64 _, [%0];\n}" :: "r"(a), "r"(pred) : "memory");
}
__device__ __forceinline__ bool mbar_try(uint32_t a, uint32_t ph) {
    uint32_t ok;
    asm volatile("{\n.reg .pred p;\nmbarrier.try_wait.parity.shared::cta.b64 p, [%1], %2;\nselp.u32 %0, 1, 0, p;\n}" : "=r"(ok) : "r"(a), "r"(ph) : "memory");
    return ok != 0;
}
#define SPINLOG 20
constexpr uint32_t SPIN_LIMIT = 1u << SPINLOG;
#define ABORT(code_) atomicCAS(&g_abort, 0u, (code_))
__device__ __forceinline__ void mbar_wait(uint32_t a, uint32_t ph) {
    uint32_t n = 0;
#pragma unroll 1
    while (!mbar_try(a, ph)) { if (++n > SPIN_LIMIT) { ABORT(1); break; } }
}
__device__ __forceinline__ void bar_sync(int id, int n) { asm volatile("bar.sync %0, %1;" :: "r"(id), "r"(n) : "memory"); }
__device__ __forceinline__ void bar_arrive(int id, int n) { asm volatile("bar.arrive %0, %1;" :: "r"(id), "r"(n) : "memory"); }

__device__ __forceinline__ void ldsm4(uint32_t* r, uint32_t a) {
    asm volatile("ldmatrix.sync.aligned.m8n8.x4.shared.b16 {%0,%1,%2,%3}, [%4];" : "=r"(r[0]), "=r"(r[1]), "=r"(r[2]), "=r"(r[3]) : "r"(a) : "memory");
}
__device__ __forceinline__ void ldsm4t(uint32_t* r, uint32_t a) {
    asm volatile("ldmatrix.sync.aligned.m8n8.x4.trans.shared.b16 {%0,%1,%2,%3}, [%4];" : "=r"(r[0]), "=r"(r[1]), "=r"(r[2]), "=r"(r[3]) : "r"(a) : "memory");
}
__device__ __forceinline__ void stsm4t(uint32_t a, uint32_t r0, uint32_t r1, uint32_t r2, uint32_t r3) {
    asm volatile("stmatrix.sync.aligned.m8n8.x4.trans.shared.b16 [%0], {%1,%2,%3,%4};" :: "r"(a), "r"(r0), "r"(r1), "r"(r2), "r"(r3) : "memory");
}
__device__ __forceinline__ void stsm4(uint32_t a, uint32_t r0, uint32_t r1, uint32_t r2, uint32_t r3) {
    asm volatile("stmatrix.sync.aligned.m8n8.x4.shared.b16 [%0], {%1,%2,%3,%4};" :: "r"(a), "r"(r0), "r"(r1), "r"(r2), "r"(r3) : "memory");
}
__device__ __forceinline__ uint32_t movm(uint32_t a) { uint32_t d; asm volatile("movmatrix.sync.aligned.m8n8.trans.b16 %0, %1;" : "=r"(d) : "r"(a)); return d; }
__device__ __forceinline__ void mma16816(float* d, uint32_t a0, uint32_t a1, uint32_t a2, uint32_t a3, uint32_t b0, uint32_t b1) {
    asm volatile("mma.sync.aligned.m16n8k16.row.col.f32.bf16.bf16.f32 {%0,%1,%2,%3}, {%4,%5,%6,%7}, {%8,%9}, {%0,%1,%2,%3};"
        : "+f"(d[0]), "+f"(d[1]), "+f"(d[2]), "+f"(d[3]) : "r"(a0), "r"(a1), "r"(a2), "r"(a3), "r"(b0), "r"(b1));
}
__device__ __forceinline__ void mma1688(float* d, uint32_t a0, uint32_t a1, uint32_t b0) {
    asm volatile("mma.sync.aligned.m16n8k8.row.col.f32.bf16.bf16.f32 {%0,%1,%2,%3}, {%4,%5}, {%6}, {%0,%1,%2,%3};"
        : "+f"(d[0]), "+f"(d[1]), "+f"(d[2]), "+f"(d[3]) : "r"(a0), "r"(a1), "r"(b0));
}
__device__ __forceinline__ uint32_t pack2(float a, float b) { uint32_t d; asm("cvt.rn.bf16x2.f32 %0, %1, %2;" : "=r"(d) : "f"(b), "f"(a)); return d; }
__device__ __forceinline__ float bf_lo(uint32_t w) { return __uint_as_float(w << 16); }
__device__ __forceinline__ float bf_hi(uint32_t w) { return __uint_as_float(w & 0xffff0000u); }
__device__ __forceinline__ float rbf(float x) { return __bfloat162float(__float2bfloat16_rn(x)); }

__device__ __forceinline__ void sts128(uint32_t a, float x, float y, float z, float w) { asm volatile("st.shared.v4.f32 [%0], {%1,%2,%3,%4};" :: "r"(a), "f"(x), "f"(y), "f"(z), "f"(w) : "memory"); }
__device__ __forceinline__ void sts128u(uint32_t a, uint32_t x, uint32_t y, uint32_t z, uint32_t w) { asm volatile("st.shared.v4.b32 [%0], {%1,%2,%3,%4};" :: "r"(a), "r"(x), "r"(y), "r"(z), "r"(w) : "memory"); }
__device__ __forceinline__ void sts64(uint32_t a, float x, float y) { asm volatile("st.shared.v2.f32 [%0], {%1,%2};" :: "r"(a), "f"(x), "f"(y) : "memory"); }
__device__ __forceinline__ float4 lds128(uint32_t a) { float4 v; asm volatile("ld.shared.v4.f32 {%0,%1,%2,%3}, [%4];" : "=f"(v.x), "=f"(v.y), "=f"(v.z), "=f"(v.w) : "r"(a) : "memory"); return v; }
__device__ __forceinline__ float2 lds64(uint32_t a) { float2 v; asm volatile("ld.shared.v2.f32 {%0,%1}, [%2];" : "=f"(v.x), "=f"(v.y) : "r"(a) : "memory"); return v; }
__device__ __forceinline__ uint2 lds64u(uint32_t a) { uint2 v; asm volatile("ld.shared.v2.b32 {%0,%1}, [%2];" : "=r"(v.x), "=r"(v.y) : "r"(a) : "memory"); return v; }
__device__ __forceinline__ float4 lds128v(uint32_t a) { float4 v; asm volatile("ld.volatile.shared.v4.f32 {%0,%1,%2,%3}, [%4];" : "=f"(v.x), "=f"(v.y), "=f"(v.z), "=f"(v.w) : "r"(a) : "memory"); return v; }
__device__ __forceinline__ float2 lds64v(uint32_t a) { float2 v; asm volatile("ld.volatile.shared.v2.f32 {%0,%1}, [%2];" : "=f"(v.x), "=f"(v.y) : "r"(a) : "memory"); return v; }
__device__ __forceinline__ uint4 lds128uv(uint32_t a) { uint4 v; asm volatile("ld.volatile.shared.v4.b32 {%0,%1,%2,%3}, [%4];" : "=r"(v.x), "=r"(v.y), "=r"(v.z), "=r"(v.w) : "r"(a) : "memory"); return v; }
__device__ __forceinline__ void st_async4(uint32_t a, float x, float y, float z, float w, uint32_t mb) {
    asm volatile("st.async.weak.shared::cluster.mbarrier::complete_tx::bytes.v4.f32 [%0], {%1,%2,%3,%4}, [%5];" :: "r"(a), "f"(x), "f"(y), "f"(z), "f"(w), "r"(mb) : "memory");
}
__device__ __forceinline__ void st_async2(uint32_t a, uint32_t x, uint32_t y, uint32_t mb) {
    asm volatile("st.async.weak.shared::cluster.mbarrier::complete_tx::bytes.v2.b32 [%0], {%1,%2}, [%3];" :: "r"(a), "r"(x), "r"(y), "r"(mb) : "memory");
}
__device__ __forceinline__ uint32_t ldg_rlx(const uint32_t* p) { uint32_t v; asm volatile("ld.relaxed.gpu.global.b32 %0, [%1];" : "=r"(v) : "l"(p) : "memory"); return v; }
__device__ __forceinline__ uint4 ldg_rlx4(const uint32_t* p) { uint4 v; asm volatile("ld.relaxed.gpu.global.v4.b32 {%0,%1,%2,%3}, [%4];" : "=r"(v.x), "=r"(v.y), "=r"(v.z), "=r"(v.w) : "l"(p) : "memory"); return v; }
__device__ __forceinline__ uint4 ldg_rlx4_if(const uint32_t* p, bool c) {
    uint4 v;
    asm volatile("{\n.reg .pred p;\nsetp.ne.u32 p, %5, 0;\nmov.b32 %0, 0;\nmov.b32 %1, 0;\nmov.b32 %2, 0;\nmov.b32 %3, 0;\n@p ld.relaxed.gpu.global.v4.b32 {%0,%1,%2,%3}, [%4];\n}"
                 : "=r"(v.x), "=r"(v.y), "=r"(v.z), "=r"(v.w) : "l"(p), "r"((uint32_t)c) : "memory");
    return v;
}
__device__ __forceinline__ void stg_rlx(uint32_t* p, uint32_t v) { asm volatile("st.relaxed.gpu.global.b32 [%0], %1;" :: "l"(p), "r"(v) : "memory"); }
__device__ __forceinline__ void tma2d(uint32_t dst, const CUtensorMap* tm, int c0, int c1, uint32_t mb) {
    asm volatile("cp.async.bulk.tensor.2d.shared::cluster.global.mbarrier::complete_tx::bytes [%0], [%1, {%3, %4}], [%2];"
        :: "r"(dst), "l"((uint64_t)tm), "r"(mb), "r"(c0), "r"(c1) : "memory");
}

__device__ __forceinline__ void tma3d(uint32_t dst, const CUtensorMap* tm, int row, int chunk, uint32_t mb) {
    asm volatile("cp.async.bulk.tensor.3d.shared::cluster.global.mbarrier::complete_tx::bytes [%0], [%1, {%3, %4, %5}], [%2];"
        :: "r"(dst), "l"((uint64_t)tm), "r"(mb), "r"(0), "r"(row), "r"(chunk) : "memory");
}
#define EF 0xff
__device__ __forceinline__ uint64_t pol_ef(int bit) {
    uint64_t p;
    if ((EF >> bit) & 1) asm("createpolicy.fractional.L2::evict_first.b64 %0, 1.0;" : "=l"(p));
    else asm("createpolicy.fractional.L2::evict_normal.b64 %0, 1.0;" : "=l"(p));
    return p;
}
__device__ __forceinline__ void tma3d_h(uint32_t dst, const CUtensorMap* tm, int row, int chunk, uint32_t mb, uint64_t pol) {
    asm volatile("cp.async.bulk.tensor.3d.shared::cluster.global.mbarrier::complete_tx::bytes.L2::cache_hint [%0], [%1, {%3, %4, %5}], [%2], %6;"
        :: "r"(dst), "l"((uint64_t)tm), "r"(mb), "r"(0), "r"(row), "r"(chunk), "l"(pol) : "memory");
}
__device__ __forceinline__ void tma2d_h(uint32_t dst, const CUtensorMap* tm, int c0, int c1, uint32_t mb, uint64_t pol) {
    asm volatile("cp.async.bulk.tensor.2d.shared::cluster.global.mbarrier::complete_tx::bytes.L2::cache_hint [%0], [%1, {%3, %4}], [%2], %5;"
        :: "r"(dst), "l"((uint64_t)tm), "r"(mb), "r"(c0), "r"(c1), "l"(pol) : "memory");
}
__device__ __forceinline__ void tma2d_mc_h(uint32_t dst, const CUtensorMap* tm, int c0, int c1, uint32_t mb, uint64_t pol) {
    asm volatile("cp.async.bulk.tensor.2d.shared::cluster.global.mbarrier::complete_tx::bytes.multicast::cluster.L2::cache_hint [%0], [%1, {%3, %4}], [%2], %5, %6;"
        :: "r"(dst), "l"((uint64_t)tm), "r"(mb), "r"(c0), "r"(c1), "h"((uint16_t)3), "l"(pol) : "memory");
}
__device__ __forceinline__ uint4 ldg4_h(const void* p, uint64_t pol) {
    uint4 v;
    asm volatile("ld.relaxed.gpu.global.L2::cache_hint.v4.b32 {%0,%1,%2,%3}, [%4], %5;" : "=r"(v.x), "=r"(v.y), "=r"(v.z), "=r"(v.w) : "l"(p), "l"(pol) : "memory");
    return v;
}
__device__ __forceinline__ void stg4_h(void* p, uint4 v, uint64_t pol) {
    asm volatile("st.relaxed.gpu.global.L2::cache_hint.v4.b32 [%0], {%1,%2,%3,%4}, %5;" :: "l"(p), "r"(v.x), "r"(v.y), "r"(v.z), "r"(v.w), "l"(pol) : "memory");
}
__device__ __forceinline__ void tma2d_mc(uint32_t dst, const CUtensorMap* tm, int c0, int c1, uint32_t mb) {
    asm volatile("cp.async.bulk.tensor.2d.shared::cluster.global.mbarrier::complete_tx::bytes.multicast::cluster [%0], [%1, {%3, %4}], [%2], %5;"
        :: "r"(dst), "l"((uint64_t)tm), "r"(mb), "r"(c0), "r"(c1), "h"((uint16_t)3) : "memory");
}
__device__ __forceinline__ void mbar_arrive2_if(uint32_t a, uint32_t pred) {
    asm volatile("{\n.reg .pred p;\nsetp.ne.u32 p, %1, 0;\n@p mbarrier.arrive.shared::cta.b64 _, [%0];\n@p mbarrier.arrive.shared::cluster.b64 _, [%2];\n}"
                 :: "r"(a), "r"(pred), "r"(a ^ 0x01000000u) : "memory");
}
__device__ __forceinline__ void tma_pf3d(const CUtensorMap* tm, int row, int chunk) {
    asm volatile("cp.async.bulk.prefetch.tensor.3d.L2.global.tile [%0, {%1, %2, %3}];" :: "l"((uint64_t)tm), "r"(0), "r"(row), "r"(chunk) : "memory");
}
__device__ __forceinline__ void tma_pf2d(const CUtensorMap* tm, int c0, int c1) {
    asm volatile("cp.async.bulk.prefetch.tensor.2d.L2.global.tile [%0, {%1, %2}];" :: "l"((uint64_t)tm), "r"(c0), "r"(c1) : "memory");
}
__device__ __forceinline__ void tma_store3d(const CUtensorMap* tm, uint32_t src, int row, int chunk) {
    asm volatile("cp.async.bulk.tensor.3d.global.shared::cta.bulk_group [%0, {%2, %3, %4}], [%1];" :: "l"((uint64_t)tm), "r"(src), "r"(0), "r"(row), "r"(chunk) : "memory");
}
__device__ __forceinline__ void bulk_store(void* dst, uint32_t src, uint32_t bytes) {
    asm volatile("cp.async.bulk.global.shared::cta.bulk_group [%0], [%1], %2;" :: "l"(dst), "r"(src), "r"(bytes) : "memory");
}
#define GT(slot)
#define CNT(k)
#define CNT2(k, c)
#define TS(i, dep)
#define TSACC()
#define TSDECL
struct Maps { CUtensorMap wq, wk, wv, wo, wo2, kx, ox2, kx3, vx3, xn2, wg, wu, wq4, wk4, wv4; };
typedef Maps RecMaps;
__device__ __forceinline__ void st_rel(uint32_t* p, uint32_t v) { asm volatile("st.release.gpu.global.u32 [%0], %1;" :: "l"(p), "r"(v) : "memory"); }
#define PUBLISH(p, v) st_rel(p, v)
__device__ __forceinline__ uint2 ldg_rlx2(const uint32_t* p) { uint2 v; asm volatile("ld.relaxed.gpu.global.v2.b32 {%0,%1}, [%2];" : "=r"(v.x), "=r"(v.y) : "l"(p) : "memory"); return v; }
__device__ __forceinline__ void wait_eq2(const uint32_t* p, uint32_t e, int code) {
    uint32_t n = 0;
#pragma unroll 1
    while (true) { uint2 v = ldg_rlx2(p); if (v.x == e && v.y == e) break; __nanosleep(64); if (++n > SPIN_LIMIT) { ABORT(code); break; } }
}
__device__ __forceinline__ void wait_eq4(const uint32_t* p, uint32_t e, int code) {
    uint32_t n = 0;
#pragma unroll 1
    while (true) { uint4 v = ldg_rlx4(p); if (v.x == e && v.y == e && v.z == e && v.w == e) break; __nanosleep(64); if (++n > SPIN_LIMIT) { ABORT(code); break; } }
}
__device__ __forceinline__ void wait_rec(const uint32_t* p, uint32_t e, uint32_t steps) {
    uint32_t n = 0;
#pragma unroll 1
    while (true) {
        uint2 v = ldg_rlx2(p);
        if (__all_sync(0xffffffffu, (v.x >> 8) == e && (v.y >> 8) == e && (v.x & 255) >= steps && (v.y & 255) >= steps)) break;
        __nanosleep(64); if (++n > SPIN_LIMIT) { ABORT(8); break; }
    }
}

constexpr int R_QK1 = 0;
constexpr int R_WO = 65536;
constexpr int R_T = 131072;
constexpr int R_SLOT1 = R_T;
constexpr int R_MEMB = R_T + 24576;
constexpr int R_QP = R_MEMB + 8192;
constexpr int R_VRED = R_QP + 4096;
constexpr int R_STG = R_VRED + 2048;
constexpr int R_AX = R_STG + 2048;
constexpr int R_SLOT0 = 196608;
constexpr int R_SLOC = R_SLOT0 + 24576;
constexpr int R_SREM = R_SLOC + 1536;
constexpr int R_VB = R_SREM + 1536;
constexpr int R_MISC = R_VB + 2048;
constexpr int R_LT = R_MISC + 128;
constexpr int R_BAR = 229888;
constexpr int R_TS = 229888 + 128;
static_assert(R_AX + 24576 <= R_SLOT0 && R_LT + 2560 <= 229376, "smem map");
enum { MB_W0 = 0, MB_W1, MB_WV, MB_WO, MB_S, MB_FULL0, MB_FULL1, MB_V, MB_N };

__device__ __forceinline__ float ex2(float x) { float y; asm("ex2.approx.ftz.f32 %0, %1;" : "=f"(y) : "f"(x)); return y; }
__device__ __forceinline__ float rcpf(float x) { float y; asm("rcp.approx.ftz.f32 %0, %1;" : "=f"(y) : "f"(x)); return y; }
__device__ __forceinline__ void mma16816z(float* d, uint32_t a0, uint32_t a1, uint32_t a2, uint32_t a3, uint32_t b0, uint32_t b1) {
    asm volatile("mma.sync.aligned.m16n8k16.row.col.f32.bf16.bf16.f32 {%0,%1,%2,%3}, {%4,%5,%6,%7}, {%8,%9}, {%10,%10,%10,%10};"
        : "=f"(d[0]), "=f"(d[1]), "=f"(d[2]), "=f"(d[3]) : "r"(a0), "r"(a1), "r"(a2), "r"(a3), "r"(b0), "r"(b1), "f"(0.f));
}
__device__ __forceinline__ void mma1688hz(float* d, uint32_t a0, uint32_t a1, uint32_t b0) {
    asm volatile("mma.sync.aligned.m16n8k8.row.col.f32.f16.f16.f32 {%0,%1,%2,%3}, {%4,%5}, {%6}, {%7,%7,%7,%7};"
        : "=f"(d[0]), "=f"(d[1]), "=f"(d[2]), "=f"(d[3]) : "r"(a0), "r"(a1), "r"(b0), "f"(0.f));
}
#define MMA(d, a, b0, b1) mma16816(d, a[0], a[1], a[2], a[3], b0, b1)
#define MMAZ(d, a, b0, b1) mma16816z(d, a[0], a[1], a[2], a[3], b0, b1)
#define MMAF(first, d, a, b0, b1) do { if (first) MMAZ(d, a, b0, b1); else MMA(d, a, b0, b1); } while (0)

__device__ __forceinline__ uint32_t uni(uint32_t x) { return __reduce_max_sync(0xffffffffu, x); }
__device__ __forceinline__ void mbar_wait_u(uint32_t a, uint32_t ph) {
    uint32_t n = 0;
#pragma unroll 1
    while (!__all_sync(0xffffffffu, mbar_try(a, ph))) { if (++n > SPIN_LIMIT) { ABORT(1); break; } }
}
__device__ __forceinline__ void mbar_wait_p(uint32_t a, uint32_t ph) {
    asm volatile("{\n.reg .pred p, q;\n.reg .u32 n;\nmov.u32 n, 0;\nWL: mbarrier.try_wait.parity.shared::cta.b64 p, [%0], %1;\nadd.u32 n, n, 1;\n"
                 "setp.lt.and.u32 q, n, %2, !p;\n@q bra.uni WL;\n}" :: "r"(a), "r"(ph), "n"(SPIN_LIMIT) : "memory");
}
__device__ __forceinline__ uint32_t mbar_test(uint32_t a, uint32_t ph) {
    uint32_t ok;
    asm volatile("{\n.reg .pred p;\nmbarrier.test_wait.parity.shared::cta.b64 p, [%1], %2;\nselp.u32 %0, 1, 0, p;\n}" : "=r"(ok) : "r"(a), "r"(ph) : "memory");
    return ok;
}
__device__ __forceinline__ uint32_t opaque(uint32_t x) { return __shfl_sync(0xffffffffu, x, threadIdx.x & 31); }
__device__ __forceinline__ const uint32_t* mkptr(uint32_t lo, uint32_t hi) { uint64_t r; asm("mov.b64 %0, {%1, %2};" : "=l"(r) : "r"(lo), "r"(hi)); return (const uint32_t*)r; }
__device__ __forceinline__ uint32_t prmt(uint32_t a, uint32_t b, uint32_t s) { uint32_t d; asm("prmt.b32 %0, %1, %2, %3;" : "=r"(d) : "r"(a), "r"(b), "r"(s)); return d; }
__device__ __forceinline__ uint32_t packh2(float a, float b) { uint32_t d; asm("cvt.rn.f16x2.f32 %0, %1, %2;" : "=r"(d) : "f"(b), "f"(a)); return d; }
__device__ __forceinline__ uint32_t hadd2b(uint32_t a, uint32_t b) { uint32_t d; asm("add.rn.bf16x2 %0, %1, %2;" : "=r"(d) : "r"(a), "r"(b)); return d; }
__device__ __forceinline__ uint32_t hmul2b(uint32_t a, uint32_t b) { uint32_t d; asm("mul.rn.bf16x2 %0, %1, %2;" : "=r"(d) : "r"(a), "r"(b)); return d; }
__device__ __forceinline__ uint32_t amax2b(uint32_t a, uint32_t b) { uint32_t d; asm("max.xorsign.abs.bf16x2 %0, %1, %2;" : "=r"(d) : "r"(a), "r"(b)); return d; }
__device__ __forceinline__ uint32_t amax2h(uint32_t a, uint32_t b) { uint32_t d; asm("max.xorsign.abs.f16x2 %0, %1, %2;" : "=r"(d) : "r"(a), "r"(b)); return d; }
__device__ __forceinline__ void sts32(uint32_t a, uint32_t x) { asm volatile("st.shared.b32 [%0], %1;" :: "r"(a), "r"(x) : "memory"); }
__device__ __forceinline__ uint32_t lds32v_(uint32_t a) { uint32_t v; asm volatile("ld.volatile.shared.b32 %0, [%1];" : "=r"(v) : "r"(a) : "memory"); return v; }
__device__ __forceinline__ void stg4(void* p, uint4 v) { asm volatile("st.relaxed.gpu.global.v4.b32 [%0], {%1,%2,%3,%4};" :: "l"(p), "r"(v.x), "r"(v.y), "r"(v.z), "r"(v.w) : "memory"); }
__device__ __forceinline__ void lds_frag(uint32_t* r, uint32_t a) {
    asm volatile("ld.shared.v4.b32 {%0,%1,%2,%3}, [%4];" : "=r"(r[0]), "=r"(r[1]), "=r"(r[2]), "=r"(r[3]) : "r"(a) : "memory");
}
__device__ __forceinline__ void lds_fragv(uint32_t* r, uint32_t a) {
    asm volatile("ld.volatile.shared.v4.b32 {%0,%1,%2,%3}, [%4];" : "=r"(r[0]), "=r"(r[1]), "=r"(r[2]), "=r"(r[3]) : "r"(a) : "memory");
}
__device__ __forceinline__ uint32_t xorv(uint32_t a, uint32_t b) { uint32_t d; asm volatile("xor.b32 %0, %1, %2;" : "=r"(d) : "r"(a), "r"(b)); return d; }
#define SCHED(k) asm volatile("{\n.reg .pred p;\nsetp.ne.u32 p, %0, %1;\n@p bra.uni SD;\nSL: nanosleep.u32 64;\nbra.uni SL;\nSD:\n}" :: "r"(sbu - s), "n"(k) : "memory")
#define PINM() asm volatile("{\n.reg .pred p;\nsetp.eq.u32 p, %0, 1;\n@p st.shared.u32 [%0], 0;\n}" :: "r"(sbu) : "memory")
__device__ __forceinline__ uint32_t or_and(uint32_t a, uint32_t b, uint32_t c) { uint32_t d; asm("lop3.b32 %0, %1, %2, %3, 0xF8;" : "=r"(d) : "r"(a), "r"(b), "r"(c)); return d; }
__device__ __forceinline__ uint32_t pack2v(float a, float b) { uint32_t d; asm volatile("cvt.rn.bf16x2.f32 %0, %1, %2;" : "=r"(d) : "f"(b), "f"(a)); return d; }
#define FU(x) __float_as_uint(x)
__device__ __forceinline__ uint32_t clk32() { uint32_t t; asm volatile("mov.u32 %0, %%clock;" : "=r"(t) :: "memory"); return t; }
__device__ __forceinline__ void spin_until(uint32_t t0, uint32_t d) {
    if (d) {
#pragma unroll 1
        while (__any_sync(0xffffffffu, clk32() - t0 < d)) {}
    }
}
constexpr int SH_OFF = 229376 + 384;
constexpr uint32_t HONE2 = 0x3c003c00u, HCNT2 = 0x50005000u;

__device__ __forceinline__ uint64_t desc_sw128(uint32_t addr, uint32_t lbo, uint32_t sbo) {
    return (uint64_t)((addr & 0x3FFFF) >> 4) | ((uint64_t)(lbo >> 4) << 16) | ((uint64_t)(sbo >> 4) << 32) | (1ull << 62);
}
#define DP 390
#define NAX 3
#define NXL 0
#define NCX 2
#define NCL 1
#define DC 0
#define FLIP 1
#define VTA 1
#define KXB 4
#define KXI 5
#define ANB 3
#define BNB 3
#define CNB 3
#define SMA 0
#define SMB 0
#define SMC 0x01
#define IVA 0
#define RGA 160
#define RGC 160
#define RGB (504 - RGA - RGC)
#define NRW 8
#define NBR 16
#define E0 0
#define E1 6
#define E2 4
#define E3 8
#define IV 2
#define DEX 0
#define G2V 0
#define G2K 2
#define VDEP 0
#define AEARLY 0
#define VTP 2
#define LORD 1
#define TRK 1
#define TW 0
#define T2N 14
#define TEARLY 1
#define DT 0
#define NB0 0
#define NB1 9
#define DB2 80
#define DITHER 0
#define DA 40
#define DB 40
#define DS 200

__device__ __forceinline__ uint32_t wrow_off(int kk, int ch) {
    const int lane = threadIdx.x & 31, r = lane & 7;
    const int row = 64 * (kk >> 2) + 32 * (r & 1) + 16 * (kk & 1) + 8 * (lane >> 4) + 4 * ((kk >> 1) & 1) + (r >> 1);
    return row * 128 + ((ch ^ (row & 7)) << 4);
}
template <int K> __device__ __forceinline__ void sched(uint32_t key) {
    asm volatile("{\n.reg .pred p;\nsetp.ne.u32 p, %0, %1;\n@p bra.uni SD;\nSL: nanosleep.u32 64;\nbra.uni SL;\nSD:\n}" :: "r"(key), "n"(K) : "memory");
}
__device__ __forceinline__ void sched_i(int i, uint32_t key) {
    if (i == -1) sched<20>(key); if (i == 0) sched<21>(key); if (i == 1) sched<22>(key); if (i == 2) sched<23>(key);
    if (i == 3) sched<24>(key); if (i == 4) sched<25>(key); if (i == 5) sched<26>(key); if (i == 6) sched<27>(key);
}
template <int NB, int SM, class F>
__device__ __forceinline__ void g1(float* q0, float* k0, uint32_t (*wq)[4], uint32_t (*wk)[4], uint32_t ga, uint32_t key, F&& hook) {
    float q1[4], k1[4];
    uint32_t b[NB][4];
#pragma unroll
    for (int i = 0; i < NB; i++) ldsm4(b[i], ga + i * 512);
    hook(-1, b[0]);
    if (SM & 1) sched_i(-1, key);
#pragma unroll
    for (int i = 0; i < 8; i++) {
        uint32_t* c = b[i % NB];
        MMAF(i == 0, q0, wq[2 * i], c[0], c[1]); MMAF(i == 0, k0, wk[2 * i], c[0], c[1]);
        MMAF(i == 0, q1, wq[2 * i + 1], c[2], c[3]); MMAF(i == 0, k1, wk[2 * i + 1], c[2], c[3]);
        const uint32_t cc_[4] = {c[0], c[1], c[2], c[3]};
        if (i + NB < 8) ldsm4(b[i % NB], ga + (i + NB) * 512);
        hook(i, cc_);
        if ((SM >> (i + 1)) & 1) sched_i(i, key);
    }
#pragma unroll
    for (int i = 0; i < 4; i++) { q0[i] += q1[i]; k0[i] += k1[i]; }
}
__device__ __forceinline__ float frag_norm2(uint32_t (*w)[4]) {
    float d0[4], d1[4];
#pragma unroll
    for (int i = 0; i < 32; i++) { MMAF(i == 0, d0, w[i], w[i][0], w[i][2]); MMAF(i == 0, d1, w[i], w[i][1], w[i][3]); }
    const int lane = threadIdx.x & 31, g = lane >> 2, t = lane & 3;
    float v = g == 2 * t ? d0[0] + d1[2] : (g == 2 * t + 1 ? d0[1] + d1[3] : 0.f);
#pragma unroll
    for (int o = 16; o; o >>= 1) v += __shfl_xor_sync(0xffffffffu, v, o);
    return v;
}
__device__ __forceinline__ void load_slot(uint32_t sb, int c, int tile, const Maps& maps) {
    const uint32_t dst = sb + ((tile & 1) ? R_SLOT1 : R_SLOT0), mb = sb + R_BAR + 8 * (MB_FULL0 + (tile & 1));
    mbar_expect_tx(mb, 24576);
    if ((EF >> 8) & 1) {
        tma2d_h(dst + 16384, &maps.kx, c * 64, tile * 64, mb, pol_ef(8));
        tma3d_h(dst, &maps.vx3, tile * 64, (c >> 1) * 2, mb, pol_ef(8));
    } else {
        tma2d(dst + 16384, &maps.kx, c * 64, tile * 64, mb);
        tma3d(dst, &maps.vx3, tile * 64, (c >> 1) * 2, mb);
    }
}
__device__ __forceinline__ uint32_t put_mem0(uint32_t sb, int W, const bf16* __restrict__ mem0) {
    const int lane = threadIdx.x & 31;
    const uint4 a = *(const uint4*)(mem0 + (lane & 7) * DM + W * 64 + (lane >> 3) * 8), b = *(const uint4*)(mem0 + (lane & 7) * DM + W * 64 + 32 + (lane >> 3) * 8);
    const uint4 m0 = make_uint4(prmt(a.x, b.x, 0x5410u), prmt(a.x, b.x, 0x7632u), prmt(a.y, b.y, 0x5410u), prmt(a.y, b.y, 0x7632u));
    const uint4 m1 = make_uint4(prmt(a.z, b.z, 0x5410u), prmt(a.z, b.z, 0x7632u), prmt(a.w, b.w, 0x5410u), prmt(a.w, b.w, 0x7632u));
    bar_sync(3, 256);
    sts128u(sb + R_MEMB + W * 1024 + lane * 16, m0.x, m0.y, m0.z, m0.w);
    sts128u(sb + R_MEMB + W * 1024 + 512 + lane * 16, m1.x, m1.y, m1.z, m1.w);
    return amax2b(amax2b(amax2b(m0.x, m0.y), amax2b(m0.z, m0.w)), amax2b(amax2b(m1.x, m1.y), amax2b(m1.z, m1.w)));
}
#define PUT_MAX(rL, W) sts32(rL + R_STG + 1024 + ((W) >> 2) * 512 + ((W) & 3) * 4, amax2b(amax2b(mx, my), mz));
__device__ __forceinline__ uint32_t h2b(uint32_t w) {
    uint32_t d;
    asm("{\n.reg .f16 l, h;\n.reg .f32 a, b;\nmov.b32 {l, h}, %1;\ncvt.f32.f16 a, l;\ncvt.f32.f16 b, h;\ncvt.rn.bf16x2.f32 %0, b, a;\n}" : "=r"(d) : "r"(w));
    return d;
}
#define GATHER1(HALF)                                                                                           \
        {                                                                                                       \
            const uint4 x0 = ldg_rlx4(pm), x1 = ldg_rlx4(pm + 256); const uint2 y = ldg_rlx2(px);                 \
            cw = (sel & 0x4000u) ? prmt(x0.w, x1.w, 0x7632u) : prmt(y.x, y.y, 0x5410u);                         \
            const uint32_t p0 = h2b(x0.x), p1 = h2b(x0.y), p2 = h2b(x0.z), p3 = h2b(prmt(x0.w, y.x, sel));      \
            stsm4t(rG + R_MEMB + HALF * 4096, p0, p1, p2, p3);                                                  \
            const uint32_t p4 = h2b(x1.x), p5 = h2b(x1.y), p6 = h2b(x1.z), p7 = h2b(prmt(x1.w, y.y, sel));      \
            stsm4t(rG + R_MEMB + HALF * 4096 + 512, p4, p5, p6, p7);                                            \
            mx = amax2b(amax2b(p0, p1), amax2b(p2, p3)); my = amax2b(p4, p5); mz = amax2b(p6, p7);              \
        }
#define GATHER(HALF, PRE, SYNC, AFTER)                                                                                      \
        {                                                                                                       \
            const uint32_t so = aslot(s);                                                                       \
            const uint32_t ua = (glo + acc_base(HALF * 4 + fo)) ^ so, ux = (glo + ext_base(HALF * 4 + fo)) ^ so; \
            uint2 lt;                                                                                           \
            lt.x = lds32v_(rL + R_LT); lt.y = lds32v_(rL + R_LT + 4);                                           \
            const uint32_t sel = 0x7610u - ((lt.x ^ (lt.x >> 2)) & 16) * 0x440u;                                \
            const uint32_t* pm = mkptr(ua + lt.x, ghi);                                                         \
            const uint32_t* px = mkptr(ux + lt.y, ghi);                                                         \
            PRE                                                                                                 \
            bar_sync(5, 384);                                                                                   \
            const uint32_t t0 = clk32();                                                                        \
            TSACC();                                                                        \
            SYNC                                                                                                \
            spin_until(t0, DP + DITHER);                                                                                 \
            \
            TS(10, 0);                                                                                          \
            uint32_t cw, nr = 0;                                                                                \
            _Pragma("unroll 1") do {                                                                            \
                GATHER1(HALF)                                                                                   \
                nr++;                                                                                           \
            } while (__any_sync(0xffffffffu, cw != HCNT2 && nr < SPIN_LIMIT));                                  \
            TS(11, cw);                                                                                         \
            AFTER                                                                                               \
            CNT2(HALF * 4 + (s & 1) * 2 + (nr > 2), nr > 1);                                                    \
            \
        }
#define GOBAR (fo == 3 ? 14 : 10 + fo)

__device__ __forceinline__ void rec_a(uint32_t sb, int c, const bf16* __restrict__ mem0, uint32_t epoch) {
    const int tid = threadIdx.x - WGA * 128, lane = tid & 31, f = tid >> 5;
    uint32_t wq[16][4], wk[16][4], mx, my = 0, mz = 0;
    const int lrow = ((lane >> 4) << 3) + (lane & 7), lsel = (lane >> 3) & 1;
    {
        mbar_wait(sb + R_BAR + 8 * MB_W0, 0);
        if (c == 7 && tid == 0) GT(1421);
#pragma unroll
        for (int kk = 0; kk < 16; kk++) { const uint32_t a = sb + R_T + wrow_off(kk, 2 * f + lsel); ldsm4t(wq[kk], a); ldsm4t(wk[kk], a + 32768); }
        __syncwarp();
        mx = put_mem0(sb, f, mem0);
    }
    const uint32_t rL = opaque(sb + lane * 16), rG = opaque(sb + lane * 16 + f * 1024);
    const uint32_t sbu = uni(sb), fo = uni(f), cc = uni(c);
    const uint64_t gx = xpage();
    const uint32_t ghi = uni((uint32_t)(gx >> 32)), glo = uni((uint32_t)gx);
#pragma unroll
    for (int i = 0; i < NAX; i++) {
        sts128u(rG + R_AX + 4096 * i, wq[i][0], wq[i][1], wq[i][2], wq[i][3]);
        sts128u(rG + R_AX + 4096 * i + 512, wk[i][0], wk[i][1], wk[i][2], wk[i][3]);
    }
    sts128u(rL + R_LT + 512 + f * 512, (sb + R_SREM + (f >= 2 ? lane * 8 + f * 256 : lane * 16 + f * 1024)) ^ 0x01000000u, (sb + R_BAR + 8 * MB_S) ^ 0x01000000u,
            sb + R_QP + (lane >> 4) * 128 + lsel * 512 + (lane & 7) * 16 + (f == 3 ? 2048 : 0), sb + R_SLOT0 + lrow * 128 + ((lsel ^ (lane & 7)) << 4));
    __syncwarp();
    if (tid == 0) GT(c * 8 + 1);
    TSDECL;
    const float cexp = 0.08838834764831845f * 1.4426950408889634f;
    float cs = cexp;
    auto step = [&](int s, bool first) -> bool {
        bar_sync(1, 128);
        float q0[4], k0[4];
        uint4 ta;
        uint32_t zr, rl2;
        g1<ANB, SMA>(q0, k0, wq, wk, rL + R_MEMB, sbu - s, [&](int i, const uint32_t* c_) {
            if (i == 0) TS(0, c_[0]);
            if (i == -1) {
#pragma unroll
                for (int n = NAX - NXL; n < NAX; n++) { lds_fragv(wq[n], rG + R_AX + 4096 * n); lds_fragv(wk[n], rG + R_AX + 4096 * n + 512); }
                ta = lds128uv(rL + R_LT + 512 + fo * 512);
                zr = ta.w & 1; rl2 = rL | zr;
            }
            if (i == IVA) { PUT_MAX(rl2, fo) bar_arrive(15, 256); bar_arrive(GOBAR, 96); }
        });
        stsm4t(rG + R_QP, pack2(q0[0], q0[1]), pack2(q0[2], q0[3]), pack2(k0[0], k0[1]), pack2(k0[2], k0[3]));
        TS(1, FU(k0[3]));
        if (first) mbar_wait_p(sbu + R_BAR + 8 * MB_FULL0, 0);
        if (fo >= 2) {
            bar_sync(3, 256);
            uint32_t kb[4], kc[4], qa[4], qc[4];
            ldsm4(kb, ta.z + 256); ldsm4(qa, ta.z);
            ldsm4(kc, ta.z + 1280); ldsm4(qc, ta.z + 1024);
            const uint32_t k0_ = hadd2b(kb[0], kb[1]), k1_ = hadd2b(kb[2], kb[3]), k2_ = hadd2b(kc[0], kc[1]), k3_ = hadd2b(kc[2], kc[3]);
            float s0[4], s2[4];
            MMAZ(s0, qa, k0_, k1_); MMAZ(s2, qc, k2_, k3_);
            const float x = ((s0[0] + s0[2]) + (s2[0] + s2[2])) * cs, y = ((s0[1] + s0[3]) + (s2[1] + s2[3])) * cs;
            st_async2(ta.x, FU(x), FU(y), ta.y);
            TS(3, FU(y));
            sts64((ta.x ^ 0x01000000u) + (R_SLOC - R_SREM), x, y);
            sts128u(rl2 + R_STG + (fo & 1) * 512, k0_, k1_, k2_, k3_);
            bar_arrive(9, 192);
        } else {
            uint32_t qa[4][4], kx[4][4];
#pragma unroll
            for (int kk = 0; kk < KXB; kk++) ldsm4(kx[kk], (ta.w ^ (kk * 32)) + (16384 + fo * 2048));
            bar_sync(3, 256);
#pragma unroll
            for (int kk = 0; kk < 4; kk++) {
                if (kk >= KXB) ldsm4(kx[kk], (ta.w ^ (kk * 32)) + (16384 + fo * 2048));
                ldsm4(qa[kk], ta.z + kk * 1024);
            }
            float s0[4], s1[4], s2[4], s3[4];
            MMAZ(s0, qa[0], kx[0][0], kx[0][1]); MMAZ(s1, qa[0], kx[0][2], kx[0][3]);
            MMAZ(s2, qa[1], kx[1][0], kx[1][1]); MMAZ(s3, qa[1], kx[1][2], kx[1][3]);
            MMA(s0, qa[2], kx[2][0], kx[2][1]); MMA(s1, qa[2], kx[2][2], kx[2][3]);
            MMA(s2, qa[3], kx[3][0], kx[3][1]); MMA(s3, qa[3], kx[3][2], kx[3][3]);
            const float x = ((s0[0] + s0[2]) + (s2[0] + s2[2])) * cs, y = ((s0[1] + s0[3]) + (s2[1] + s2[3])) * cs;
            const float z = ((s1[0] + s1[2]) + (s3[0] + s3[2])) * cs, w = ((s1[1] + s1[3]) + (s3[1] + s3[3])) * cs;
            st_async4(ta.x, x, y, z, w, ta.y);
            TS(3, FU(w));
            sts128(rG + R_SLOC, x, y, z, w);
        }
        const uint32_t r8 = (rl2 + sbu) >> 1;
        uint32_t vt00[4], vt01[4], vt10[4], vt11[4];
        const uint32_t rV = ta.w ^ ((fo & 1) * 64), vo = (fo >> 1) * 8192;
        if (!VTA && VTP < 2) { ldsm4t(vt00, rV + vo); ldsm4t(vt10, (rV ^ 32) + vo); }
        if (!VTA && VTP < 1) { ldsm4t(vt01, rV + vo + 2048); ldsm4t(vt11, (rV ^ 32) + vo + 2048); }
        bar_sync(4, 128);
        const float2 l2 = lds64v(r8 + R_SLOC + 512), l3 = lds64v(r8 + R_SLOC + 768);
        const float4 l0 = lds128v(rL + R_SLOC), l1 = lds128v(rL + R_SLOC + 1024);
        if (VTA && VTP < 2) { ldsm4t(vt00, rV + vo); ldsm4t(vt10, (rV ^ 32) + vo); }
        if (VTA && VTP < 1) { ldsm4t(vt01, rV + vo + 2048); ldsm4t(vt11, (rV ^ 32) + vo + 2048); }

        if (s == NSEG - 1) { mbar_wait_u(sbu + R_BAR + 8 * MB_S, 1); mbar_wait_u(sbu + R_BAR + 8 * MB_V, 1); return true; }
        TS(2, FU(l3.y));
        mbar_wait_p(sbu + R_BAR + 8 * MB_S, s & 1);
        TS(4, 0);
        {
            const float2 r2 = lds64v(r8 + R_SREM + 512), r3 = lds64v(r8 + R_SREM + 768);
            const float4 r0 = lds128v(rL + R_SREM), r1 = lds128v(rL + R_SREM + 1024);
            if (VTP >= 1) PINM();
            if (VTP >= 2) { ldsm4t(vt00, rV + vo); ldsm4t(vt10, (rV ^ 32) + vo); }
            if (VTP >= 1) { ldsm4t(vt01, rV + vo + 2048); ldsm4t(vt11, (rV ^ 32) + vo + 2048); }
            float sv[10];
            sv[0] = l0.x + r0.x; sv[1] = l0.y + r0.y; sv[2] = l0.z + r0.z; sv[3] = l0.w + r0.w;
            sv[4] = l1.x + r1.x; sv[5] = l1.y + r1.y; sv[6] = l1.z + r1.z; sv[7] = l1.w + r1.w;
            sv[8] = ((l2.x + l3.x) + r2.x) + r3.x; sv[9] = ((l2.y + l3.y) + r2.y) + r3.y;
            float m = fmaxf(fmaxf(fmaxf(fmaxf(sv[8], sv[9]), sv[0]), fmaxf(fmaxf(sv[2], sv[3]), sv[1])), fmaxf(fmaxf(sv[4], sv[5]), fmaxf(sv[6], sv[7])));
            {
                const float m1 = __shfl_xor_sync(0xffffffffu, m, 1), m2 = __shfl_xor_sync(0xffffffffu, m, 2), m3 = __shfl_xor_sync(0xffffffffu, m, 3);
                m = fmaxf(fmaxf(m, m1), fmaxf(m2, m3));
            }
            TS(5, FU(m));
            const uint32_t ONE2 = 0x3f803f80u;
            float o0[4], o1[4], sm[4];
            const uint32_t pb0 = pack2(ex2(sv[0] - m), ex2(sv[1] - m)), pb1 = pack2(ex2(sv[2] - m), ex2(sv[3] - m));
            mma16816z(sm, ONE2, ONE2, ONE2, ONE2, pb0, pb1);
            MMAZ(o0, vt00, pb0, pb1); MMAZ(o1, vt10, pb0, pb1);
            const uint32_t z = (VDEP == 0 ? FU(m) : pb0) & zr;
            const uint32_t vok = mbar_test(sbu + R_BAR + 8 * MB_V + z, s & 1);
            const uint32_t rv = r8 + vok * 8;
            float2 va = lds64v(rv + R_VB - 8 + fo * 512);
            float2 vb = lds64v(rv + R_VB - 8 + fo * 512 + 256);
            float sig = __uint_as_float(lds32v_(sbu + R_MISC + 40));
            const uint32_t pb2 = pack2(ex2(sv[4] - m), ex2(sv[5] - m)), pb3 = pack2(ex2(sv[6] - m), ex2(sv[7] - m));
            mma16816(sm, ONE2, ONE2, ONE2, ONE2, pb2, pb3);
            const uint32_t pb4 = pack2(ex2(sv[8] - m), ex2(sv[9] - m));
            MMA(o0, vt01, pb2, pb3); MMA(o1, vt11, pb2, pb3);
            mma1688(sm, ONE2, ONE2, pb4);
            const float z0 = rcpf(sm[0]), z1 = rcpf(sm[1]);
#define PUT_O()                                                                                                   \
            {                                                                                                     \
                float a0[4] = {o0[0], o0[1], o0[2], o0[3]}, a1[4] = {o1[0], o1[1], o1[2], o1[3]};                 \
                mma1688(a0, FU(va.x), FU(va.y), pb4); mma1688(a1, FU(vb.x), FU(vb.y), pb4);                       \
                const float i0 = z0 * sig, i1 = z1 * sig;                                                         \
                stsm4t(rG + R_QP, pack2(a0[0] * i0, a0[1] * i1), pack2(a0[2] * i0, a0[3] * i1), pack2(a1[0] * i0, a1[1] * i1), pack2(a1[2] * i0, a1[3] * i1)); \
            }
            PUT_O()
            asm volatile("{\n.reg .pred p;\nsetp.ne.u32 p, %0, 0;\n@p bar.arrive 8, 256;\n}" :: "r"(vok) : "memory");
            if (__builtin_expect(__any_sync(0xffffffffu, vok == 0), 0)) {
                mbar_wait_p(sbu + R_BAR + 8 * MB_V, s & 1);
                va = lds64v(r8 + R_VB + fo * 512); vb = lds64v(r8 + R_VB + fo * 512 + 256);
                sig = __uint_as_float(lds32v_(sbu + R_MISC + 40));
                PUT_O()
                bar_arrive(8, 256);
                CNT(8);
            }
            TS(6, 0);
            const float r = __uint_as_float(0x7f000000u - FU(sig));
            cs = cexp * r * (fo >= 2 ? r : 1.f);
        }
        return false;
    };
    step(0, true);
#pragma unroll 1
    for (int s = 0;; s++) {
        if (s & 1) mbar_wait_p(sbu + R_BAR + 8 * (MB_FULL0 + (((s + 1) >> 1) & 1)), ((s + 1) >> 2) & 1);
        {
            const uint32_t a = rL + R_LT + 512 + 12 + fo * 512;
            sts32(a, lds32v_(a) + ((s & 1) ? ((s & 2) ? R_SLOT0 - R_SLOT1 - 4096 : R_SLOT1 - R_SLOT0 - 4096) : 4096));
        }
        auto early = [&]() {
            SCHED(13);
#pragma unroll
            for (int i = 0; i < NAX - NXL; i++) { lds_fragv(wq[i], rG + R_AX + 4096 * i); lds_fragv(wk[i], rG + R_AX + 4096 * i + 512); }
        };
        GATHER(0, , early();, )
        if (step(s + 1, false)) break;
    }
    CNT(9);
    if (rG == sbu) GT(cc * 8 + 4);
}

__device__ __forceinline__ void rec_b(uint32_t sb, int c, uint32_t epoch) {
    const int tid = threadIdx.x - WGB * 128, lane = tid & 31, f = tid >> 5;
    uint32_t wq[16][4], wk[16][4], wo[32][4];
    const int lrow = ((lane >> 4) << 3) + (lane & 7), lsel = (lane >> 3) & 1;
    const uint32_t rL = opaque(sb + lane * 16), rW = opaque(sb + lane * 16 + f * 16384);
    const uint32_t sbu = uni(sb), fo = uni(f), cc = uni(c), po = cc & 1, ep = uni(epoch);
    {
        mbar_wait(sb + R_BAR + 8 * MB_WO, 0);
        if (c == 7 && tid == 0) GT(1426);
        const uint32_t aO = sb + R_WO + f * 16384 + lrow * 128 + ((lsel ^ (lane & 7)) << 4);
#pragma unroll
        for (int i = 0; i < 32; i++) {
            const int tile = (i >> 4) * 2 + (i & 1), kk = (i >> 1) & 7;
            ldsm4t(wo[i], (aO ^ (32 * tile)) + kk * 2048);
        }
        const float no = frag_norm2(wo);
        if (lane == 0) sts32(sb + R_MISC + 80 + f * 4, FU(no));
        __syncwarp();
        bar_sync(0, 256);
        if (tid == 0) {
            const float4 a = lds128(sb + R_MISC + 64), b = lds128(sb + R_MISC + 80);
            stg4(&g_f.norm[c], make_uint4(FU((a.x + a.y) + (a.z + a.w)), epoch, FU((b.x + b.y) + (b.z + b.w)), epoch));
        }
        __syncwarp();
#pragma unroll
        for (int i = NRW; i < 32; i++) sts128u(rW + R_WO + i * 512, wo[i][0], wo[i][1], wo[i][2], wo[i][3]);
        mbar_wait(sb + R_BAR + 8 * MB_W1, 0);
        if (c == 7 && tid == 0) GT(1422);
        __syncwarp();
#pragma unroll
        for (int kk = 0; kk < 16; kk++) { const uint32_t a = sb + R_QK1 + wrow_off(kk, 2 * f + lsel); ldsm4t(wq[kk], a); ldsm4t(wk[kk], a + 32768); }
        bar_sync(13, 128);
#pragma unroll
        for (int i = 0; i < 16; i++) {
            sts128u(rW + R_QK1 + i * 1024, wq[i][0], wq[i][1], wq[i][2], wq[i][3]);
            sts128u(rW + R_QK1 + i * 1024 + 512, wk[i][0], wk[i][1], wk[i][2], wk[i][3]);
        }
        __syncwarp();
    }
    const uint64_t gx = xpage();
    const uint32_t ghi = uni((uint32_t)(gx >> 32)), glo = uni((uint32_t)gx);
    TSDECL;
#pragma unroll 1
    for (int s = 0;; s++) {
        bar_sync(2, 256);
        float q0[4], k0[4];
        g1<BNB, SMB>(q0, k0, wq, wk, rL + R_MEMB + 4096, sbu - s, [&](int i, const uint32_t* c_) {
            if (i == 0) TS(0, c_[0]);
            if (i >= 2 && i < 6) {
#pragma unroll
                for (int n = NRW + (i - 2) * E0 / 4; n < NRW + (i - 1) * E0 / 4; n++) lds_fragv(wo[n], rW + R_WO + n * 512);
            }
            if (i == IV) bar_arrive(GOBAR, 96);
        });
        stsm4t(rL + fo * 1024 + R_QP + 512, pack2(q0[0], q0[1]), pack2(q0[2], q0[3]), pack2(k0[0], k0[1]), pack2(k0[2], k0[3]));
        bar_arrive(3, 256);
        TS(1, FU(k0[3]));
        const uint32_t so = aslot(s);
        uint2 lt;
        { const float2 t = lds64v(rL + R_LT + 8); lt.x = FU(t.x); lt.y = FU(t.y); }
        const uint32_t sel = 0x3210u + (lt.x & 16) * 0x440u;
        uint32_t* pm = (uint32_t*)mkptr(((glo + acc_base(po * 4 + fo)) ^ so) + lt.x, ghi);
        uint32_t* px = (uint32_t*)mkptr(((glo + ext_base(po * 4 + fo)) ^ so) + lt.y, ghi);
        if (s == NSEG - 1) break;
        {
            const uint32_t z = lt.x & 1;
#pragma unroll
            for (int n = NRW; n < NRW + E0 + E1 + E2 + E3; n++) {
                const int d = n - (n < NRW + T2N ? TRK + 1 : TRK);
                lds_fragv(wo[n], (d >= NRW ? or_and(rW, wo[d][0], z) : rW) + R_WO + n * 512);
            }
        }
        TS(2, wo[NRW + E0 + E1 + E2 + E3 - 1][0]);
        SCHED(4);
        bar_sync(8, 256);
        {
            float o[4][4];
            uint32_t b[4][4];
#pragma unroll
            for (int i = 0; i < 4; i++) ldsm4(b[i], rL + R_QP + i * 1024);
            PINM();
#pragma unroll
            for (int n = NRW + E0 + E1 + E2 + E3; n < 32; n++) lds_fragv(wo[n], rW + R_WO + n * 512);
            float p[4][4];
#define G2_STEP(o, hf, kk) _Pragma("unroll") for (int i = 0; i < 2; i++) MMAF((kk) < 2, o[((kk) & 1) * 2 + i], wo[(hf) * 16 + (kk) * 2 + i], b[(kk) >> 1][((kk) & 1) * 2], b[(kk) >> 1][((kk) & 1) * 2 + 1])
#define G2_RED(o, wl, h) const uint32_t wl = packh2(o[1][2] + o[3][2], o[1][3] + o[3][3]);                            \
                asm volatile("red.relaxed.gpu.global.add.noftz.v4.f16x2 [%0], {%1,%2,%3,%4};" :: "l"(pm + (h) * 16),  \
                    "r"(packh2(o[0][0] + o[2][0], o[0][1] + o[2][1])), "r"(packh2(o[0][2] + o[2][2], o[0][3] + o[2][3])), \
                    "r"(packh2(o[1][0] + o[3][0], o[1][1] + o[3][1])), "r"(prmt(wl, HONE2, (h) ? sel : sel ^ 0x4400u)) : "memory")
            if (G2V == 1) SCHED(11);
#pragma unroll
            for (int kk = 0; kk < 8; kk++) { G2_STEP(o, 0, kk); }
            TS(7, b[0][0]);
            if (G2V == 0) SCHED(11);
            else {
#pragma unroll
                for (int i = 0; i < 4; i++) wo[16 + i][0] = or_and(wo[16 + i][0], FU(o[i][0]), lt.x & 1);
            }
#pragma unroll
            for (int kk = 0; kk < G2K; kk++) { G2_STEP(p, 1, kk); }
#pragma unroll
            for (int i = 0; i < NB0; i++) { lds_fragv(wq[i], rW + R_QK1 + i * 1024); lds_fragv(wk[i], rW + R_QK1 + i * 1024 + 512); }
            G2_RED(o, w3, 0);
            TS(8, w3);
            if (G2V == 0) SCHED(12);
#pragma unroll
            for (int kk = G2K; kk < 8; kk++) { G2_STEP(p, 1, kk); }
            G2_RED(p, w7, 1);
            asm volatile("red.relaxed.gpu.global.add.noftz.f16x2 [%0], %1;" :: "l"(px), "r"(prmt((w3 & 0xffff0000u) | 0x3c00u, w7, sel)) : "memory");
            TS(9, w7);
        }
        bar_arrive(5, 384);
        asm volatile("{\n.reg .pred p;\nsetp.eq.u32 p, %0, %1;\n@p mbarrier.arrive.expect_tx.shared::cta.b64 _, [%2], 1536;\n}"
                     :: "r"(rW), "r"(sbu), "r"(sbu + R_BAR + 8 * MB_S) : "memory");
        const uint32_t tb = clk32();
        TSACC();
        spin_until(tb, DB);
#pragma unroll
        for (int i = NB0; i < NBR; i++) {
            if (i == NB1) spin_until(tb, DP + DB2);
            lds_fragv(wq[i], rW + R_QK1 + i * 1024); lds_fragv(wk[i], rW + R_QK1 + i * 1024 + 512);
        }
    }
}

#undef lds_fragv
__device__ __forceinline__ void rec_first_loads(uint32_t sb, int c, const Maps& maps) {
    const uint32_t bar = sb + R_BAR;
    const int F0 = c * 64;
    mbar_expect_tx(bar + 8 * MB_W0, 65536); mbar_expect_tx(bar + 8 * MB_WO, 65536); mbar_expect_tx(bar + 8 * MB_WV, 65536);
    tma2d(sb + R_QK1, &maps.wv, F0, 0, bar + 8 * MB_WV); tma2d(sb + R_QK1 + 32768, &maps.wv, F0, 256, bar + 8 * MB_WV);
    tma2d(sb + R_T + 32768, &maps.wk, F0, 0, bar + 8 * MB_W0);
    if (!LORD) {
        for (int i = 0; i < 4; i++) tma2d(sb + R_WO + i * 16384, &maps.wo, (c & 1) * 256 + i * 64, (c >> 1) * 128, bar + 8 * MB_WO);
        tma2d(sb + R_T, &maps.wq, F0, 0, bar + 8 * MB_W0);
    }
    mbar_expect_tx(bar + 8 * MB_S, 1536);
}
__device__ __forceinline__ void rec_c(uint32_t sb, int c, const bf16* __restrict__ mem0, const Maps& maps, uint32_t epoch) {
    const int tid = threadIdx.x - WGC * 128, lane = tid & 31, u = tid >> 5;
    const uint32_t bar = sb + R_BAR;
    const int lrow = ((lane >> 4) << 3) + (lane & 7), lsel = (lane >> 3) & 1;
    const int kh = u >> 1, j = u & 1;
    uint32_t wv[32][4], mx, my = 0, mz = 0;
    {
        if (u == 0) {
            sts128u(sb + lane * 16 + R_LT, (lane >> 3) * 256 + (lane & 7) * 16, ((lane >> 2) & 1) * XHS + (lane >> 4) * XSS + (lane & 8) * 2 + (lane & 2) * 4,
                    (lane >> 2) * 256 + (lane & 3) * 16, (lane & 1) * XHS + ((lane >> 3) & 1) * XSS + (lane & 6) * 4 + (lane >> 4) * 4);
        }
        mbar_wait(bar + 8 * MB_WV, 0);
        if (c == 7 && tid == 0) GT(1425);
        if (LORD && tid == 32) {
            for (int i = 0; i < 4; i++) tma2d(sb + R_WO + i * 16384, &maps.wo, (c & 1) * 256 + i * 64, (c >> 1) * 128, bar + 8 * MB_WO);
            tma2d(sb + R_T, &maps.wq, c * 64, 0, bar + 8 * MB_W0);
        }
        __syncwarp();
#pragma unroll
        for (int kk = 0; kk < 16; kk++) {
            const uint32_t aa = sb + R_QK1 + kh * 32768 + wrow_off(kk, 4 * j + 2 * kh + lsel);
            ldsm4t(wv[kk], aa); ldsm4t(wv[16 + kk], aa ^ 32);
        }
        {
            uint32_t x = 0;
#pragma unroll
            for (int i = 0; i < 32; i++) x ^= wv[i][0];
            sts32(sb + R_MISC + 96 + u * 4, __reduce_xor_sync(0xffffffffu, x));
        }
        bar_sync(9, 128);
        if (c == 7 && tid == 0) GT(1423);
        if (tid == 0) {
            mbar_expect_tx(bar + 8 * MB_W1, 65536);
            tma2d(sb + R_QK1 + 32768, &maps.wk, c * 64, 256, bar + 8 * MB_W1); tma2d(sb + R_QK1, &maps.wq, c * 64, 256, bar + 8 * MB_W1);
        }
        __syncwarp();
        const float nv = frag_norm2(wv);
        if (lane == 0) sts32(sb + R_MISC + 64 + u * 4, FU(nv));
        __syncwarp();
        bar_arrive(0, 256);
        mx = put_mem0(sb, 4 + u, mem0);
    }
    const uint32_t rL = opaque(sb + lane * 16), rG = opaque(sb + lane * 16 + u * 1024);
    const uint32_t sbu = uni(sb), fo = uni(u), cc = uni(c), ep = uni(epoch);
    const uint64_t gx = xpage();
    const uint32_t ghi = uni((uint32_t)(gx >> 32)), glo = uni((uint32_t)gx);
    constexpr int CX = R_AX + NAX * 4096;
    static_assert(NAX + NCX <= 6, "AX");
#pragma unroll
    for (int i = 0; i < NCX; i++) {
        sts128u(rG + CX + 4096 * i, wv[i][0], wv[i][1], wv[i][2], wv[i][3]);
        sts128u(rG + CX + 4096 * i + 512, wv[16 + i][0], wv[16 + i][1], wv[16 + i][2], wv[16 + i][3]);
    }
    __syncwarp();
    TSDECL;
    uint32_t rpb = 0x3f800000u;
    bar_arrive(2, 256);
    if (fo == 3) {
        uint32_t n = 0;
#pragma unroll 1
        while (true) {
            const uint2 v = ldg_rlx2(&g_f.kv[0][cc >> 1][0]);
            if (__all_sync(0xffffffffu, v.x == ep && v.y == ep)) break;
            __nanosleep(32);
            if (++n > SPIN_LIMIT) { ABORT(6); break; }
        }
        if (rL == sbu) load_slot(sbu, cc, 0, maps);
        __syncwarp();
        if (cc == 7 && rL == sbu) GT(1427);
    }
#pragma unroll 1
    for (int s = 0;; s++) {
        if (TEARLY && fo == 3 && !(s & 1) && s > 0 && s + 2 < NSEG) {
            if (rL == sbu) load_slot(sbu, cc, (s + 2) >> 1, maps);
            __syncwarp();
        } else spin_until(clk32(), DC);
#pragma unroll
        for (int i = NCX - NCL; i < NCX; i++) { lds_fragv(wv[i], rG + CX + 4096 * i); lds_fragv(wv[16 + i], rG + CX + 4096 * i + 512); }
        PUT_MAX(rL, 4 + fo)
        if (fo == 0) {
                bar_sync(15, 256);
                if (s == 0) {
                    const uint32_t* np = (const uint32_t*)&g_f.norm[0] + ((rL ^ sbu) >> 2);
                    uint4 r, q; uint32_t n = 0;
#pragma unroll 1
                    while (true) {
                        r = ldg_rlx4(np); q = ldg_rlx4(np + 128);
                        const uint2 z = ldg_rlx2(&g_f.xn[(rL ^ sbu) >> 3]);
                        if (__all_sync(0xffffffffu, r.y == ep && r.w == ep && q.y == ep && q.w == ep && z.x == ep && z.y == ep)) break;
                        if (++n > SPIN_LIMIT) { ABORT(5); break; }
                    }
                    float nv = __uint_as_float(r.x) + __uint_as_float(q.x), no = __uint_as_float(r.z) + __uint_as_float(q.z);
#pragma unroll
                    for (int o = 16; o; o >>= 1) { nv += __shfl_xor_sync(0xffffffffu, nv, o); no += __shfl_xor_sync(0xffffffffu, no, o); }
                    const int lc = ((int)(FU(nv) >> 23) + (int)(FU(no) >> 23) - 252 + 9 + 1) >> 1;
                    sts32(sbu + R_MISC + 32, 140 - lc);
                    __syncwarp();
                }
                const uint4 ma = lds128uv(rL + R_STG + 1024), mb = lds128uv(rL + R_STG + 1536);
                const uint32_t m_ = amax2b(amax2b(amax2b(ma.x, ma.y), amax2b(ma.z, ma.w)), amax2b(amax2b(mb.x, mb.y), amax2b(mb.z, mb.w)));
                const int em = (int)(__reduce_max_sync(0xffffffffu, amax2b(m_, m_ << 16) & 0x7f800000u) >> 23) + (int)(rpb >> 23) - 127;
                const int es = min(max((int)lds32v_(sbu + R_MISC + 32) - max(em, 127), -60), 60);
                sts32(sbu + R_MISC + 40, (127 + es) << 23);
                TS(4, es);
        } else bar_arrive(15, 256);
        bar_sync(GOBAR, 96);
        float v0[4], v1[4];
        g1<CNB, SMC>(v0, v1, wv, wv + 16, rL + R_MEMB + (fo >> 1) * 4096, sbu - s, [&](int i, const uint32_t* c_) { if (i == 0) TS(0, c_[0]); });
        TS(1, FU(v1[3]));
        const uint32_t l16 = (rL ^ sbu) | (lds32v_(rL + R_LT + 4) & 1);
        const uint32_t r8 = sbu + (l16 >> 1);
        {
            sts128(rL + R_VRED + fo * 512, v1[0], v1[1], v1[2], v1[3]);
            const uint32_t d = r8 + R_VB + ((cc & 1) * 4 + (fo & 1) * 2 + (fo >> 1)) * 256;
            const uint32_t dr = xorv(d, 0x01000000u), br = xorv(sbu + R_BAR + 8 * MB_V, 0x01000000u);
            bar_sync(6 + (fo & 1), 64);
            const float4 a0 = lds128(rL + R_VRED + (fo ^ 2) * 512);
            const float rp = __uint_as_float(rpb);
            const uint32_t w0 = pack2((v0[0] + a0.x) * rp, (v0[1] + a0.y) * rp), w1 = pack2((v0[2] + a0.z) * rp, (v0[3] + a0.w) * rp);
            st_async2(dr, w0, w1, br);
            TS(3, w1);
            sts64(d, __uint_as_float(w0), __uint_as_float(w1));
            __syncwarp();
            asm volatile("{\n.reg .pred p;\nsetp.eq.u32 p, %0, %1;\n@p mbarrier.arrive.expect_tx.shared::cta.b64 _, [%2], 256;\n}"
                         :: "r"(rL), "r"(sbu), "r"(sbu + R_BAR + 8 * MB_V) : "memory");
        }
        if (fo == 1) {
            bar_sync(9, 192);
            uint8_t* dst = (uint8_t*)&g_KVf[s][cc >> 1][(cc & 1) * 256] + l16;
            const uint32_t r2 = prmt(rpb, 0, 0x3232u);
#pragma unroll
            for (int i = 0; i < 2; i++) {
                const uint4 a = lds128uv(rL + R_STG + i * 512);
                stg4(dst + i * 512, make_uint4(~hmul2b(a.x, r2), ~hmul2b(a.y, r2), ~hmul2b(a.z, r2), ~hmul2b(a.w, r2)));
                const float2 b0 = lds64v(r8 + R_VB + (cc & 1) * 1024 + i * 512), b1 = lds64v(r8 + R_VB + (cc & 1) * 1024 + i * 512 + 256);
                stg4(dst + 2048 + i * 512, make_uint4(~FU(b0.x), ~FU(b0.y), ~FU(b1.x), ~FU(b1.y)));
            }
            __syncwarp();
            if (l16 == 0) { stg_rlx(&g_f.rec[cc], (ep << 8) | (s + 1)); if (s == NSEG - 1) GT(1500 + cc); }
            __syncwarp();
        } else {
            bar_arrive(9, 192);
            if (fo == 2) {
                if (l16 < 144) stg4((void*)mkptr((glo + zero_off(cc, l16 >> 4)) ^ aslot(s + 4), ghi), make_uint4(0, 0, 0, 0));
                __syncwarp();
            } else if (fo == 3) {
                if (((s & 1) || s == 0) && s + 3 < NSEG) {
                    const uint32_t* fp = &g_f.kv[(s + 3) >> 1][cc >> 1][0];
                    uint32_t n = 0;
#pragma unroll 1
                    while (true) {
                        const uint2 v = ldg_rlx2(fp);
                        if (__all_sync(0xffffffffu, v.x == ep && v.y == ep)) break;
                        __nanosleep(64);
                        if (++n > SPIN_LIMIT) { ABORT(6); break; }
                    }
                }
                if (!(s & 1) && s + 2 < NSEG && (!TEARLY || s == 0)) {
                    spin_until(clk32(), DT);
                    if (l16 == 0) load_slot(sbu, cc, (s + 2) >> 1, maps);
                    __syncwarp();
                }
            }
        }
        if (s == NSEG - 1) break;
        auto early = [&]() {
#pragma unroll
            for (int i = 0; i < NCX - NCL; i++) { lds_fragv(wv[i], rG + CX + 4096 * i); lds_fragv(wv[16 + i], rG + CX + 4096 * i + 512); }
        };
        GATHER(1, , early(); rpb = 0x7f000000u - lds32v_(sbu + R_MISC + 40);, bar_arrive(2, 256);)
    }
}

__device__ __forceinline__ bool cand_better(float v, int i, float bv, int bi) { return v > bv || (v == bv && i < bi); }
constexpr int F_WG = 0, F_WU = 32768, F_WD = 65536, F_X = 98304, F_RED = F_X + 4096, F_ACT = F_RED + 8192, F_SEL = F_ACT + 256;

__device__ __noinline__ void ffn_phase(const Maps& maps, const bf16* __restrict__ wd, bf16* __restrict__ out) {
    extern __shared__ __align__(1024) uint8_t smem[];
    const uint32_t sb = smem_u32(smem);
    const int c = ((volatile int*)(smem + SH_OFF))[8];
    const uint32_t epoch = ((volatile uint32_t*)(smem + SH_OFF))[9];
    const int tid = threadIdx.x;
    constexpr int NWK = FF / 32;
    const bool worker = c < NWK;
    bar_sync(0, 384);
    const uint32_t mb = sb + R_BAR + 8 * MB_W0;
    if (tid == 32 && worker) {
        asm volatile("fence.proxy.async.shared::cta;" ::: "memory");
        mbar_expect_tx(mb, 98304);
        tma2d(sb + F_WG, &maps.wg, c * 32, 0, mb); tma2d(sb + F_WG + 16384, &maps.wg, c * 32, 256, mb);
        tma2d(sb + F_WU, &maps.wu, c * 32, 0, mb); tma2d(sb + F_WU + 16384, &maps.wu, c * 32, 256, mb);
        asm volatile("cp.async.bulk.shared::cluster.global.mbarrier::complete_tx::bytes [%0], [%1], %2, [%3];"
            :: "r"(sb + F_WD), "l"(wd + (size_t)c * 32 * DM), "r"(32768), "r"(mb) : "memory");
    }
    int p0 = -1, p1 = -1;
#pragma unroll 1
    for (int pass = 0; pass < 2; pass++) {
        if (tid < 32) {
            const uint32_t tag = epoch & 0xfffffu;
            uint4 r[4]; uint32_t n = 0;
            const int t3 = tid + 96 < NFW ? tid + 96 : tid;
#pragma unroll 1
            while (true) {
                bool ok = true;
#pragma unroll
                for (int i = 0; i < 4; i++) r[i] = ldg_rlx4((const uint32_t*)&g_f.cand[pass][i < 3 ? tid + 32 * i : t3]);
#pragma unroll
                for (int i = 0; i < 4; i++) ok = ok && (r[i].y >> 12) == tag && (r[i].w >> 12) == tag;
                if (__all_sync(0xffffffffu, ok)) break;
                __nanosleep(32);
                if (++n > SPIN_LIMIT) { ABORT(7); break; }
            }
            float b0 = __uint_as_float(r[0].x), b1 = __uint_as_float(r[0].z); int i0 = r[0].y & 4095, i1 = r[0].w & 4095;
#pragma unroll
            for (int i = 1; i < 4; i++) {
                if (i < 3 || t3 != tid) {
                    float c0 = __uint_as_float(r[i].x), c1 = __uint_as_float(r[i].z); int j0 = r[i].y & 4095, j1 = r[i].w & 4095;
                    if (cand_better(c0, j0, b0, i0)) {
                        if (cand_better(c1, j1, b0, i0)) { b1 = c1; i1 = j1; } else { b1 = b0; i1 = i0; }
                        b0 = c0; i0 = j0;
                    } else if (cand_better(c0, j0, b1, i1)) { b1 = c0; i1 = j0; }
                }
            }
#pragma unroll
            for (int o = 16; o; o >>= 1) {
                float c0 = __shfl_xor_sync(0xffffffffu, b0, o), c1 = __shfl_xor_sync(0xffffffffu, b1, o);
                int j0 = __shfl_xor_sync(0xffffffffu, i0, o), j1 = __shfl_xor_sync(0xffffffffu, i1, o);
                if (cand_better(c0, j0, b0, i0)) {
                    if (cand_better(c1, j1, b0, i0)) { b1 = c1; i1 = j1; } else { b1 = b0; i1 = i0; }
                    b0 = c0; i0 = j0;
                } else if (cand_better(c0, j0, b1, i1)) { b1 = c0; i1 = j0; }
            }
            i0 = min(i0, SQ - 1); i1 = min(i1, SQ - 1);
            if (i0 != p0 || i1 != p1) {
                n = 0;
#pragma unroll 1
                while (!__all_sync(0xffffffffu, (ldg_rlx(&g_f.rows[pass][tid]) == epoch) & (ldg_rlx(&g_f.rows[pass][tid + 32]) == epoch) &
                                                   (ldg_rlx(&g_f.rows[pass][tid + 64]) == epoch) & (ldg_rlx(&g_f.rows[pass][t3]) == epoch))) { __nanosleep(32); if (++n > SPIN_LIMIT) { ABORT(7); break; } }
            }
            int* sel = (int*)(smem + F_SEL);
            if (pass && tid == 0) GT(c * 8 + 5);
            if (tid == 0) { sel[0] = i0; sel[1] = i1; ((float*)sel)[2] = b0; ((float*)sel)[3] = b1; }
        }
        bar_sync(0, 384);
        const int t0 = ((int*)(smem + F_SEL))[0], t1 = ((int*)(smem + F_SEL))[1];
        if (c == 3 && tid == 0 && pass == 0) GT(1430);
        if (t0 == p0 && t1 == p1) break;
        const uint32_t ytag = epoch * 2 + pass + 1;
        if (worker) {
            float2* xs = (float2*)(smem + F_X);
            if (tid < 256) {
                uint32_t a = __ldcg((const uint32_t*)(g_hn + (size_t)t0 * DM) + tid), b = __ldcg((const uint32_t*)(g_hn + (size_t)t1 * DM) + tid);
                *(float4*)(xs + tid * 2) = make_float4(bf_lo(a), bf_lo(b), bf_hi(a), bf_hi(b));
            }
            mbar_wait(mb, 1);
            if (c == 3 && tid == 0 && pass == 0) GT(1431);
            bar_sync(0, 384);
            float4* red = (float4*)(smem + F_RED);
            if (tid < 256) {
                const int cp = tid & 31, kg = tid >> 5;
                const uint32_t* wp = (const uint32_t*)(smem + (cp < 16 ? F_WG : F_WU)) + (cp & 15);
                float a0 = 0.f, a1 = 0.f, b0 = 0.f, b1 = 0.f;
#pragma unroll 16
                for (int k = kg * 64; k < kg * 64 + 64; k++) {
                    uint32_t w = wp[k * 16]; float2 x = xs[k];
                    a0 = fmaf(x.x, bf_lo(w), a0); a1 = fmaf(x.x, bf_hi(w), a1); b0 = fmaf(x.y, bf_lo(w), b0); b1 = fmaf(x.y, bf_hi(w), b1);
                }
                red[kg * 32 + cp] = make_float4(a0, a1, b0, b1);
            }
            bar_sync(0, 384);
            float2* act = (float2*)(smem + F_ACT);
            if (tid < 64) {
                const int f = tid & 31, tk = tid >> 5;
                const float* r = (const float*)red + (f >> 1) * 4 + tk * 2 + (f & 1);
                float gsum = 0.f, usum = 0.f;
#pragma unroll
                for (int kg = 0; kg < 8; kg++) { gsum += r[kg * 128]; usum += r[kg * 128 + 64]; }
                gsum = rbf(gsum); usum = rbf(usum);
                float sg = rbf(gsum / (1.f + __expf(-gsum)));
                ((float*)act)[f * 2 + tk] = rbf(sg * usum);
            }
            bar_sync(0, 384);
            if (tid < 256) {
                const uint32_t* wp = (const uint32_t*)(smem + F_WD) + tid;
                float a0 = 0.f, a1 = 0.f, b0 = 0.f, b1 = 0.f;
#pragma unroll 16
                for (int f = 0; f < 32; f++) {
                    uint32_t w = wp[f * 256]; float2 x = act[f];
                    a0 = fmaf(x.x, bf_lo(w), a0); a1 = fmaf(x.x, bf_hi(w), a1); b0 = fmaf(x.y, bf_lo(w), b0); b1 = fmaf(x.y, bf_hi(w), b1);
                }
                asm volatile("st.relaxed.gpu.global.v4.b32 [%0], {%1,%2,%3,%2};" :: "l"(&g_yp[pass][c][tid]), "r"(FU(a0)), "r"(ytag), "r"(FU(a1)) : "memory");
                asm volatile("st.relaxed.gpu.global.v4.b32 [%0], {%1,%2,%3,%2};" :: "l"(&g_yp[pass][c][256 + tid]), "r"(FU(b0)), "r"(ytag), "r"(FU(b1)) : "memory");
            }
            if (c == 3 && tid == 0 && pass == 0) GT(1432);
        } else {
            const int r = c - NWK, j = tid & 63, part = tid >> 6, tk = r >> 2, dp = (r & 3) * 64 + j;
            const int tok = tk ? t1 : t0, old = tk ? p1 : p0;
            uint32_t hw = 0, nw = 0;
            if (part == 0) {
                hw = __ldcg((const uint32_t*)(g_h + (size_t)tok * DM) + dp); nw = __ldcg((const uint32_t*)(g_hn + (size_t)tok * DM) + dp);
                if (old >= 0 && old != t0 && old != t1) {
                    uint32_t ho = __ldcg((const uint32_t*)(g_h + (size_t)old * DM) + dp), no = __ldcg((const uint32_t*)(g_hn + (size_t)old * DM) + dp);
                    ((uint32_t*)(out + (size_t)old * DM))[dp] = pack2(bf_lo(ho) + bf_lo(no), bf_hi(ho) + bf_hi(no));
                }
            }
            float s0 = 0.f, s1 = 0.f;
            uint4 v[10]; uint32_t n = 0;
            bool ok;
#pragma unroll 1
            do {
                ok = true;
#pragma unroll
                for (int i = 0; i < 10; i++) {
                    const int src = part + 6 * i;
                    v[i] = src < NWK ? ldg_rlx4((const uint32_t*)&g_yp[pass][src][tk * 256 + dp]) : make_uint4(0, ytag, 0, ytag);
                }
#pragma unroll
                for (int i = 0; i < 10; i++) ok = ok && v[i].y == ytag && v[i].w == ytag;
                if (!ok) __nanosleep(100);
                if (++n > SPIN_LIMIT) { ABORT(7); break; }
            } while (!ok);
#pragma unroll
            for (int i = 0; i < 10; i++) { s0 += __uint_as_float(v[i].x); s1 += __uint_as_float(v[i].z); }
            float2* red = (float2*)(smem + F_RED);
            red[part * 64 + j] = make_float2(s0, s1);
            bar_sync(0, 384);
            if (part == 0) {
#pragma unroll
                for (int i = 1; i < 6; i++) { float2 q = red[i * 64 + j]; s0 += q.x; s1 += q.y; }
                const float rs = rbf(1.f / (1.f + __expf(-((float*)(smem + F_SEL))[2 + tk])));
                const float y0 = rbf(rbf(s0) * rs), y1 = rbf(rbf(s1) * rs);
                ((uint32_t*)(out + (size_t)tok * DM))[dp] = pack2(bf_lo(hw) + rbf(bf_lo(nw) + y0), bf_hi(hw) + rbf(bf_hi(nw) + y1));
            }
            if (tid == 0 && pass == 0 && r == 0) GT(1434);
        }
        p0 = t0; p1 = t1;
        if (c == 3 && tid == 0 && pass == 0) GT(1433);
        bar_sync(0, 384);
    }
}

constexpr int G_W = 0;
constexpr int G_RING = 131072;
constexpr int G_BUF = 163840;
constexpr int G_BAR = 229376;
constexpr int G_SMEM = G_BAR + 512;
enum { GB_FULL = 0, GB_EMPTY = GB_FULL + 8, GB_KV = GB_EMPTY + 8, GB_STG = GB_KV + 2, GB_FREE = GB_STG + 2, GB_XN = GB_FREE + 2, GB_T1D, GB_VV, GB_KVF = GB_VV + 2, GB_VF, GB_N };
constexpr int SMEM_TOTAL = 232448;

__device__ __forceinline__ void wgmma_n128(float* d, uint64_t da, uint64_t db, int scale_d) {
    asm volatile("{\n.reg .pred p;\nsetp.ne.b32 p, %66, 0;\n"
        "wgmma.mma_async.sync.aligned.m64n128k16.f32.bf16.bf16 "
        "{%0,%1,%2,%3,%4,%5,%6,%7,%8,%9,%10,%11,%12,%13,%14,%15,%16,%17,%18,%19,%20,%21,%22,%23,%24,%25,%26,%27,%28,%29,%30,%31,"
        "%32,%33,%34,%35,%36,%37,%38,%39,%40,%41,%42,%43,%44,%45,%46,%47,%48,%49,%50,%51,%52,%53,%54,%55,%56,%57,%58,%59,%60,%61,%62,%63}, "
        "%64, %65, p, 1, 1, 0, 1;\n}"
        : "+f"(d[0]), "+f"(d[1]), "+f"(d[2]), "+f"(d[3]), "+f"(d[4]), "+f"(d[5]), "+f"(d[6]), "+f"(d[7]), "+f"(d[8]), "+f"(d[9]), "+f"(d[10]), "+f"(d[11]),
          "+f"(d[12]), "+f"(d[13]), "+f"(d[14]), "+f"(d[15]), "+f"(d[16]), "+f"(d[17]), "+f"(d[18]), "+f"(d[19]), "+f"(d[20]), "+f"(d[21]), "+f"(d[22]), "+f"(d[23]),
          "+f"(d[24]), "+f"(d[25]), "+f"(d[26]), "+f"(d[27]), "+f"(d[28]), "+f"(d[29]), "+f"(d[30]), "+f"(d[31]), "+f"(d[32]), "+f"(d[33]), "+f"(d[34]), "+f"(d[35]),
          "+f"(d[36]), "+f"(d[37]), "+f"(d[38]), "+f"(d[39]), "+f"(d[40]), "+f"(d[41]), "+f"(d[42]), "+f"(d[43]), "+f"(d[44]), "+f"(d[45]), "+f"(d[46]), "+f"(d[47]),
          "+f"(d[48]), "+f"(d[49]), "+f"(d[50]), "+f"(d[51]), "+f"(d[52]), "+f"(d[53]), "+f"(d[54]), "+f"(d[55]), "+f"(d[56]), "+f"(d[57]), "+f"(d[58]), "+f"(d[59]),
          "+f"(d[60]), "+f"(d[61]), "+f"(d[62]), "+f"(d[63])
        : "l"(da), "l"(db), "r"(scale_d));
}

__device__ __forceinline__ constexpr uint32_t slot_off(int slot) {
    return slot < 2 ? G_RING + slot * 16384 : G_BUF + (slot & 1) * 32768 + (slot < 4 ? 16384 : 0);
}
constexpr int PO = (HSPLIT / 2) & 1;
template <int NSLOT, class F>
__device__ __forceinline__ void gemm_tile(float* acc, uint32_t sb, int tile, int it, int wg, bool pass, uint32_t l0, F&& hook) {
    const uint32_t bar = sb + G_BAR;
    bar_sync(3 + wg, 256);
    int prev = 0;
#pragma unroll
    for (int k = 0; k < 4; k++) {
        const int n = tile * 4 + k, slot = NSLOT == 4 ? k : n % NSLOT;
        const uint32_t sz = sb + (((it + k) << 4) & sb & 0x3f0);
        const uint64_t da = desc_sw128(sz + slot_off(slot), 16, 1024), db0 = desc_sw128(sz + G_W, 65536, 1024);
        mbar_wait_p(bar + 8 * (GB_FULL + slot), NSLOT == 4 ? (tile & 1) : ((n / NSLOT) & 1));
        if (k == 3 && pass) bar_arrive(3 + (wg ^ 1), 256);
        asm volatile("wgmma.fence.sync.aligned;" ::: "memory");
#pragma unroll
        for (int kk = 0; kk < 4; kk++) wgmma_n128(acc, da + kk * 2, db0 + k * 1024 + kk * 128, (k | kk) != 0);
        asm volatile("wgmma.commit_group.sync.aligned;" ::: "memory");
        if (k > 0) {
            asm volatile("wgmma.wait_group.sync.aligned 1;" ::: "memory");
            mbar_arrive2_if(bar + 8 * (GB_EMPTY + prev), l0);
        }
#pragma unroll
        for (int kk = 0; kk < 4; kk++) wgmma_n128(acc, da + 512 + kk * 2, db0 + k * 1024 + 512 + kk * 128, 1);
        asm volatile("wgmma.commit_group.sync.aligned;" ::: "memory");
        if (k == 1) hook();
        prev = slot;
    }
    asm volatile("wgmma.wait_group.sync.aligned 0;" ::: "memory");
    mbar_arrive2_if(bar + 8 * (GB_EMPTY + prev), l0);
}
__device__ __forceinline__ void stage_bf16(const float* acc, uint32_t buf, float s0, float s1) {
    const int lane = threadIdx.x & 31, wq = (threadIdx.x >> 5) & 3;
    const int row = wq * 16 + (lane & 7) + ((lane >> 3) & 1) * 8;
    const uint32_t base = buf + row * 128;
#pragma unroll
    for (int j = 0; j < 16; j += 2) {
        const int ch = (j & 7) + (lane >> 4);
        stsm4(base + (j >> 3) * 8192 + ((ch ^ (row & 7)) << 4),
              pack2(acc[4 * j] * s0, acc[4 * j + 1] * s0), pack2(acc[4 * j + 2] * s1, acc[4 * j + 3] * s1),
              pack2(acc[4 * j + 4] * s0, acc[4 * j + 5] * s0), pack2(acc[4 * j + 6] * s1, acc[4 * j + 7] * s1));
    }
}

__device__ __forceinline__ void store_perm(const float* acc, bf16* dst, int ld, float s0, float s1) {
#pragma unroll
    for (int i = 0; i < 4; i++) {
        const float* a = acc + 16 * i;
        *(uint4*)(dst + i * 32) = make_uint4(pack2(a[0] * s0, a[1] * s0), pack2(a[4] * s0, a[5] * s0), pack2(a[8] * s0, a[9] * s0), pack2(a[12] * s0, a[13] * s0));
        *(uint4*)(dst + 8 * ld + i * 32) = make_uint4(pack2(a[2] * s1, a[3] * s1), pack2(a[6] * s1, a[7] * s1), pack2(a[10] * s1, a[11] * s1), pack2(a[14] * s1, a[15] * s1));
    }
}
template <int ACC>
__device__ __forceinline__ void wgmma_rs64(float* d, const uint32_t* a, uint64_t db) {
    asm volatile("{\n.reg .pred p;\nsetp.ne.b32 p, %37, 0;\n"
        "wgmma.mma_async.sync.aligned.m64n64k16.f32.bf16.bf16 {%0,%1,%2,%3,%4,%5,%6,%7,%8,%9,%10,%11,%12,%13,%14,%15,%16,%17,%18,%19,%20,%21,%22,%23,%24,%25,%26,%27,%28,%29,%30,%31}, {%32,%33,%34,%35}, %36, p, 1, 1, 0;\n}"
        : "+f"(d[0]), "+f"(d[1]), "+f"(d[2]), "+f"(d[3]), "+f"(d[4]), "+f"(d[5]), "+f"(d[6]), "+f"(d[7]), "+f"(d[8]), "+f"(d[9]), "+f"(d[10]), "+f"(d[11]), "+f"(d[12]), "+f"(d[13]), "+f"(d[14]), "+f"(d[15]), "+f"(d[16]), "+f"(d[17]), "+f"(d[18]), "+f"(d[19]), "+f"(d[20]), "+f"(d[21]), "+f"(d[22]), "+f"(d[23]), "+f"(d[24]), "+f"(d[25]), "+f"(d[26]), "+f"(d[27]), "+f"(d[28]), "+f"(d[29]), "+f"(d[30]), "+f"(d[31])
        : "r"(a[0]), "r"(a[1]), "r"(a[2]), "r"(a[3]), "l"(db), "n"(ACC));
}
template <int ACC>
__device__ __forceinline__ void wgmma_rs128t(float* d, const uint32_t* a, uint64_t db) {
    asm volatile("{\n.reg .pred p;\nsetp.ne.b32 p, %69, 0;\n"
        "wgmma.mma_async.sync.aligned.m64n128k16.f32.bf16.bf16 {%0,%1,%2,%3,%4,%5,%6,%7,%8,%9,%10,%11,%12,%13,%14,%15,%16,%17,%18,%19,%20,%21,%22,%23,%24,%25,%26,%27,%28,%29,%30,%31,%32,%33,%34,%35,%36,%37,%38,%39,%40,%41,%42,%43,%44,%45,%46,%47,%48,%49,%50,%51,%52,%53,%54,%55,%56,%57,%58,%59,%60,%61,%62,%63}, {%64,%65,%66,%67}, %68, p, 1, 1, 1;\n}"
        : "+f"(d[0]), "+f"(d[1]), "+f"(d[2]), "+f"(d[3]), "+f"(d[4]), "+f"(d[5]), "+f"(d[6]), "+f"(d[7]), "+f"(d[8]), "+f"(d[9]), "+f"(d[10]), "+f"(d[11]), "+f"(d[12]), "+f"(d[13]), "+f"(d[14]), "+f"(d[15]), "+f"(d[16]), "+f"(d[17]), "+f"(d[18]), "+f"(d[19]), "+f"(d[20]), "+f"(d[21]), "+f"(d[22]), "+f"(d[23]), "+f"(d[24]), "+f"(d[25]), "+f"(d[26]), "+f"(d[27]), "+f"(d[28]), "+f"(d[29]), "+f"(d[30]), "+f"(d[31]), "+f"(d[32]), "+f"(d[33]), "+f"(d[34]), "+f"(d[35]), "+f"(d[36]), "+f"(d[37]), "+f"(d[38]), "+f"(d[39]), "+f"(d[40]), "+f"(d[41]), "+f"(d[42]), "+f"(d[43]), "+f"(d[44]), "+f"(d[45]), "+f"(d[46]), "+f"(d[47]), "+f"(d[48]), "+f"(d[49]), "+f"(d[50]), "+f"(d[51]), "+f"(d[52]), "+f"(d[53]), "+f"(d[54]), "+f"(d[55]), "+f"(d[56]), "+f"(d[57]), "+f"(d[58]), "+f"(d[59]), "+f"(d[60]), "+f"(d[61]), "+f"(d[62]), "+f"(d[63])
        : "r"(a[0]), "r"(a[1]), "r"(a[2]), "r"(a[3]), "l"(db), "n"(ACC));
}
__device__ __forceinline__ void attention_tile(float* acc, uint32_t sb, int tile, int h, int wg, int wq, uint32_t l0, uint32_t epoch, uint4* km, uint4* vm) {
    const uint32_t buf = sb + G_BUF + ((tile << 4) & sb & 0x3f0);
    const int lane = threadIdx.x & 31, g = lane >> 2, t = lane & 3;
    const int sg = wq >> 1, hf = wq & 1, seg = tile * 2 + sg;
    uint32_t qf[8][4];
#pragma unroll
    for (int kk = 0; kk < 8; kk++) {
        qf[kk][0] = pack2(acc[8 * kk], acc[8 * kk + 1]); qf[kk][1] = pack2(acc[8 * kk + 2], acc[8 * kk + 3]);
        qf[kk][2] = pack2(acc[8 * kk + 4], acc[8 * kk + 5]); qf[kk][3] = pack2(acc[8 * kk + 6], acc[8 * kk + 7]);
    }
    uint32_t* kvf = &g_KVf[seg][h][lane * 4];
    auto kv_valid = [&]() {
        uint32_t mn = 0xffffffffu;
#pragma unroll
        for (int i = 0; i < 4; i++) mn = min(min(min(mn, min(km[i].x, km[i].y)), min(km[i].z, km[i].w)), min(min(vm[i].x, vm[i].y), min(vm[i].z, vm[i].w)));
        return __all_sync(0xffffffffu, mn != 0);
    };
    float sc[5][4];
    auto mem_scores = [&]() {
        float sb_[4];
#pragma unroll
        for (int i = 0; i < 4; i++) { MMAF(i == 0, sc[4], qf[2 * i], ~km[i].x, ~km[i].y); MMAF(i == 0, sb_, qf[2 * i + 1], ~km[i].z, ~km[i].w); }
#pragma unroll
        for (int i = 0; i < 4; i++) sc[4][i] += sb_[i];
    };
    mbar_wait_p(sb + G_BAR + 8 * (GB_KV + wg), (tile >> 1) & 1);
    if (h == 5 && (threadIdx.x & 127) == 0 && tile < 6) GT(1750 + tile * 8 + 2);
    bool fast;
    {
        const uint64_t dk = desc_sw128(buf, 16, 1024);
        asm volatile("wgmma.fence.sync.aligned;" ::: "memory");
#pragma unroll
        for (int kk = 0; kk < 8; kk++) {
            if (kk == 0) wgmma_rs64<0>(acc, qf[kk], dk); else wgmma_rs64<1>(acc, qf[kk], dk + (kk >> 2) * 512 + (kk & 3) * 2);
        }
        asm volatile("wgmma.commit_group.sync.aligned;" ::: "memory");
        mem_scores();
        fast = kv_valid();
        asm volatile("wgmma.wait_group.sync.aligned 0;" ::: "memory");
        mbar_arrive_if(sb + G_BAR + 8 * GB_KVF, l0);
#pragma unroll
        for (int i = 0; i < 32; i++) asm volatile("" : "+f"(acc[i]) :: "memory");
#pragma unroll
        for (int b = 0; b < 4; b++)
#pragma unroll
            for (int i = 0; i < 4; i++) sc[b][i] = sg ? acc[16 + 4 * b + i] : acc[4 * b + i];
#pragma unroll
        for (int i = 0; i < 4; i++) sc[4][i] = fast ? sc[4][i] : -INFINITY;
    }
    const float cexp = 0.08838834764831845f * 1.4426950408889634f;
    const int r0 = hf * 16 + g, r1 = r0 + 8;
#pragma unroll
    for (int b = 0; b < 4; b++) {
        const int j = b * 8 + 2 * t;
        if (j > r0) sc[b][0] = -INFINITY;
        if (j + 1 > r0) sc[b][1] = -INFINITY;
        if (j > r1) sc[b][2] = -INFINITY;
        if (j + 1 > r1) sc[b][3] = -INFINITY;
    }
    float m0 = -INFINITY, m1 = -INFINITY;
#pragma unroll
    for (int b = 0; b < 5; b++) { m0 = fmaxf(m0, fmaxf(sc[b][0], sc[b][1])); m1 = fmaxf(m1, fmaxf(sc[b][2], sc[b][3])); }
    m0 = fmaxf(m0, __shfl_xor_sync(0xffffffffu, m0, 1)); m1 = fmaxf(m1, __shfl_xor_sync(0xffffffffu, m1, 1));
    m0 = fmaxf(m0, __shfl_xor_sync(0xffffffffu, m0, 2)); m1 = fmaxf(m1, __shfl_xor_sync(0xffffffffu, m1, 2));
    float z0 = 0.f, z1 = 0.f;
    uint32_t p0, p1;
    {
        const float c0 = -m0 * cexp, c1 = -m1 * cexp;
        uint32_t pf[5][2];
#pragma unroll
        for (int b = 0; b < 5; b++) {
            pf[b][0] = pack2(ex2(fmaf(sc[b][0], cexp, c0)), ex2(fmaf(sc[b][1], cexp, c0)));
            pf[b][1] = pack2(ex2(fmaf(sc[b][2], cexp, c1)), ex2(fmaf(sc[b][3], cexp, c1)));
        }
        p0 = pf[4][0]; p1 = pf[4][1];
        uint32_t pa[4][4];
#pragma unroll
        for (int kk = 0; kk < 4; kk++)
#pragma unroll
            for (int i = 0; i < 4; i++) pa[kk][i] = (kk >> 1) == sg ? pf[(kk & 1) * 2 + (i >> 1)][i & 1] : 0u;
        const uint64_t dv = desc_sw128(buf + 32768, 8192, 1024);
        mbar_wait_p(sb + G_BAR + 8 * (GB_VV + wg), (tile >> 1) & 1);
        asm volatile("wgmma.fence.sync.aligned;" ::: "memory");
#pragma unroll
        for (int kk = 0; kk < 4; kk++) { if (kk == 0) wgmma_rs128t<0>(acc, pa[kk], dv); else wgmma_rs128t<1>(acc, pa[kk], dv + kk * 128); }
        asm volatile("wgmma.commit_group.sync.aligned;" ::: "memory");
#pragma unroll
        for (int b = 0; b < 5; b++) { z0 += bf_lo(pf[b][0]) + bf_hi(pf[b][0]); z1 += bf_lo(pf[b][1]) + bf_hi(pf[b][1]); }
        asm volatile("wgmma.wait_group.sync.aligned 0;" ::: "memory");
#pragma unroll
        for (int i = 0; i < 64; i++) asm volatile("" : "+f"(acc[i]) :: "memory");
    }
    mbar_arrive_if(sb + G_BAR + 8 * GB_VF, l0);
    if (h == 5 && (threadIdx.x & 127) == 0 && tile < 6) GT(1750 + tile * 8 + 3);
    if (!fast) {
        wait_rec(&g_f.rec[2 * h], epoch, seg + 1);
        if (seg == 63 && (threadIdx.x & 63) == 0) GT(1570 + h);
        uint32_t n = 0;
#pragma unroll 1
        do {
#pragma unroll
            for (int i = 0; i < 4; i++) { km[i] = ldg_rlx4(kvf + i * 128); vm[i] = ldg_rlx4(kvf + 512 + i * 128); }
            if (++n > SPIN_LIMIT) { ABORT(4); break; }
        } while (!kv_valid());
        mem_scores();
        float n0 = fmaxf(sc[4][0], sc[4][1]), n1 = fmaxf(sc[4][2], sc[4][3]);
        n0 = fmaxf(n0, __shfl_xor_sync(0xffffffffu, n0, 1)); n1 = fmaxf(n1, __shfl_xor_sync(0xffffffffu, n1, 1));
        n0 = fmaxf(n0, __shfl_xor_sync(0xffffffffu, n0, 2)); n1 = fmaxf(n1, __shfl_xor_sync(0xffffffffu, n1, 2));
        n0 = fmaxf(n0, m0); n1 = fmaxf(n1, m1);
        const float a0 = ex2((m0 - n0) * cexp), a1 = ex2((m1 - n1) * cexp);
        const float c0 = -n0 * cexp, c1 = -n1 * cexp;
        p0 = pack2(ex2(fmaf(sc[4][0], cexp, c0)), ex2(fmaf(sc[4][1], cexp, c0)));
        p1 = pack2(ex2(fmaf(sc[4][2], cexp, c1)), ex2(fmaf(sc[4][3], cexp, c1)));
        z0 = fmaf(z0, a0, bf_lo(p0) + bf_hi(p0)); z1 = fmaf(z1, a1, bf_lo(p1) + bf_hi(p1));
#pragma unroll
        for (int j = 0; j < 16; j++) { float* o = acc + 4 * j; o[0] *= a0; o[1] *= a0; o[2] *= a1; o[3] *= a1; }
    }
    if (h == 5 && (threadIdx.x & 127) == 0 && tile < 6) GT(1750 + tile * 8 + 4);
    if (hf) bar_arrive(5 + wg * 2 + sg, 64);
#pragma unroll
    for (int i = 0; i < 4; i++) {
        mma1688(acc + 16 * i, p0, p1, ~vm[i].x); mma1688(acc + 16 * i + 4, p0, p1, ~vm[i].y);
        mma1688(acc + 16 * i + 8, p0, p1, ~vm[i].z); mma1688(acc + 16 * i + 12, p0, p1, ~vm[i].w);
    }
    z0 += __shfl_xor_sync(0xffffffffu, z0, 1); z1 += __shfl_xor_sync(0xffffffffu, z1, 1);
    z0 += __shfl_xor_sync(0xffffffffu, z0, 2); z1 += __shfl_xor_sync(0xffffffffu, z1, 2);
    if (h == 5 && (threadIdx.x & 127) == 0 && tile < 6) GT(1750 + tile * 8 + 5);
    if (tile >= 2) mbar_wait_p(sb + G_BAR + 8 * (GB_FREE + wg), ((tile >> 1) - 1 + PO) & 1);
    store_perm(acc, g_O + (size_t)(tile * 64 + wq * 16 + g) * HD + h * 128 + t * 8, HD, rcpf(z0), rcpf(z1));
    mbar_arrive(sb + G_BAR + 8 * (GB_STG + wg));
    if (!hf) {
        bar_sync(5 + wg * 2 + sg, 64);
#pragma unroll
        for (int i = 0; i < 8; i++) stg4_h(kvf + i * 128, make_uint4(0, 0, 0, 0), pol_ef(3));
    }
}

__device__ __forceinline__ void g_consumer(uint32_t sb_, int g_, int wg_, uint32_t epoch) {
    const uint32_t sb = uni(sb_);
    const int g = uni(g_), wg = uni(wg_), wq = uni((threadIdx.x >> 5) & 3);
    const uint32_t l0 = opaque((threadIdx.x & 31) == 0);
    const uint32_t bar = sb + G_BAR, buf = sb + G_BUF + wg * 32768;
    const int lane = threadIdx.x & 31;
    float acc[64];
    if (wg == 1) bar_arrive(3, 256);
    const int n1 = g < 32 ? HSPLIT / 2 : NT - HSPLIT / 2;
#pragma unroll 1
    for (int i = 0; i < n1; i++) {
        gemm_tile<4>(acc, sb, wg, i, wg, true, l0, []() {});
        if (threadIdx.x == 0 && i == 0) GT((64 + g) * 8 + 1);
        if (threadIdx.x == 128 && i == 3) GT((64 + g) * 8 + 2);
        if (i > 0) mbar_wait_p(bar + 8 * (GB_FREE + wg), (i - 1) & 1);
        stage_bf16(acc, buf, 1.f, 1.f);
        asm volatile("fence.proxy.async.shared::cta;" ::: "memory");
        mbar_arrive(bar + 8 * (GB_STG + wg));
    }
    if (threadIdx.x == 128) GT((64 + g) * 8 + 3);
    if (g < 32) {
#pragma unroll 1
        for (int i = 0; i < NT / 2; i++) {
            const int tile = 2 * i + wg;
            const uint2 rec = ldg_rlx2(&g_f.rec[2 * g]);
            uint4 km[4], vm[4];
            gemm_tile<4>(acc, sb, tile, i, wg, tile != NT - 1, l0, [&]() {
                const uint32_t seg = tile * 2 + (wq >> 1);
                const uint32_t* kvf = &g_KVf[seg][g][lane * 4];
                const bool early = (rec.x >> 8) == epoch && (rec.y >> 8) == epoch && (rec.x & 255) > seg && (rec.y & 255) > seg;
#pragma unroll
                for (int j = 0; j < 4; j++) { km[j] = ldg_rlx4_if(kvf + j * 128, early); vm[j] = ldg_rlx4_if(kvf + 512 + j * 128, early); }
            });
            if (threadIdx.x == 0 && i == 0) GT((64 + g) * 8 + 4);
            if (threadIdx.x == 128 && i == 3) GT((64 + g) * 8 + 5);
            if (g == 5 && (threadIdx.x & 127) == 0 && tile < 6) GT(1750 + tile * 8 + 1);
            attention_tile(acc, sb, tile, g, wg, wq, l0, epoch, km, vm);
            if (g == 5 && (threadIdx.x & 127) == 0 && tile < 6) GT(1750 + tile * 8 + 6);
        }
    } else {
#pragma unroll 1
        for (int i = 0; i < NT / 2; i++) {
            const int tile = 2 * i + wg;
            gemm_tile<NS3>(acc, sb, tile, i, wg, tile != NT - 1, l0, []() {});
            if (threadIdx.x == 0 && i == 0) GT((64 + g) * 8 + 4);
            if (threadIdx.x == 128 && i == 3) GT((64 + g) * 8 + 5);
            mbar_wait_p(bar + 8 * (GB_FREE + wg), (i - 1 + PO) & 1);
            store_perm(acc, g_P + (size_t)(((g - 32) >> 2) * SQ + tile * 64 + wq * 16 + (lane >> 2)) * DM + ((g - 32) & 3) * 128 + (lane & 3) * 8, DM, 1.f, 1.f);
            mbar_arrive(bar + 8 * (GB_STG + wg));
        }
    }
}

__device__ __forceinline__ void load_w(uint32_t sb, const CUtensorMap* tm, int col, int k) {
    tma2d_h(sb + G_W + k * 16384, tm, col, k * 128, sb + G_BAR + 8 * (GB_FULL + k), pol_ef(5));
    tma2d_h(sb + G_W + 65536 + k * 16384, tm, col + 64, k * 128, sb + G_BAR + 8 * (GB_FULL + k), pol_ef(5));
}

__device__ __forceinline__ void rbf2(float& a, float& b) { uint32_t w = pack2(a, b); a = bf_lo(w); b = bf_hi(w); }
__device__ __forceinline__ void warp_sum2(float& a, float& b) {
#pragma unroll
    for (int o = 16; o; o >>= 1) { float c = __shfl_xor_sync(0xffffffffu, a, o), d = __shfl_xor_sync(0xffffffffu, b, o); a += c; b += d; }
}
__device__ __forceinline__ float sum16(const float* v) {
    return (((v[0] + v[1]) + (v[2] + v[3])) + ((v[4] + v[5]) + (v[6] + v[7]))) + (((v[8] + v[9]) + (v[10] + v[11])) + ((v[12] + v[13]) + (v[14] + v[15])));
}
__device__ __forceinline__ void ln_row2(float* v, float* u) {
    float sv = sum16(v), su = sum16(u);
    warp_sum2(sv, su);
    const float mv = sv * (1.f / DM), mu = su * (1.f / DM);
    float qv = 0.f, qu = 0.f, qv2 = 0.f, qu2 = 0.f;
#pragma unroll
    for (int i = 0; i < 16; i += 2) {
        float d0 = v[i] - mv, d1 = v[i + 1] - mv, e0 = u[i] - mu, e1 = u[i + 1] - mu;
        qv = fmaf(d0, d0, qv); qv2 = fmaf(d1, d1, qv2); qu = fmaf(e0, e0, qu); qu2 = fmaf(e1, e1, qu2);
    }
    qv += qv2; qu += qu2;
    warp_sum2(qv, qu);
    const float rv = rbf(mv), ru = rbf(mu);
    const float iv = __frcp_rn(rbf(sqrtf(rbf(rbf(qv * (1.f / DM)) + 1e-5f)))), iu = __frcp_rn(rbf(sqrtf(rbf(rbf(qu * (1.f / DM)) + 1e-5f))));
#pragma unroll
    for (int i = 0; i < 16; i += 2) {
        float a = v[i] - rv, b = v[i + 1] - rv, c = u[i] - ru, d = u[i + 1] - ru;
        rbf2(a, b); rbf2(c, d);
        a *= iv; b *= iv; c *= iu; d *= iu;
        rbf2(a, b); rbf2(c, d);
        v[i] = a; v[i + 1] = b; u[i] = c; u[i + 1] = d;
    }
}

__device__ __forceinline__ void ln_row1(float* v) {
    float sv = sum16(v);
#pragma unroll
    for (int o = 16; o; o >>= 1) sv += __shfl_xor_sync(0xffffffffu, sv, o);
    const float mv = sv * (1.f / DM);
    float qv = 0.f, qv2 = 0.f;
#pragma unroll
    for (int i = 0; i < 16; i += 2) { float d0 = v[i] - mv, d1 = v[i + 1] - mv; qv = fmaf(d0, d0, qv); qv2 = fmaf(d1, d1, qv2); }
    qv += qv2;
#pragma unroll
    for (int o = 16; o; o >>= 1) qv += __shfl_xor_sync(0xffffffffu, qv, o);
    const float rv = rbf(mv);
    float sq, iv;
    asm("sqrt.approx.f32 %0, %1;" : "=f"(sq) : "f"(rbf(rbf(qv * (1.f / DM)) + 1e-5f)));
    asm("rcp.approx.f32 %0, %1;" : "=f"(iv) : "f"(rbf(sq)));
#pragma unroll
    for (int i = 0; i < 16; i += 2) {
        float a = v[i] - rv, b = v[i + 1] - rv;
        rbf2(a, b);
        a *= iv; b *= iv;
        rbf2(a, b);
        v[i] = a; v[i + 1] = b;
    }
}
constexpr int FSPLIT = 28;
__device__ __forceinline__ int fin_row(int id, int i) {
    if (id < 64) { const int tile = i < FSPLIT / 2 ? 2 * i : i + FSPLIT / 2; return tile < NT ? tile * 64 + id : -1; }
    const int j = id - 64 + i * 48;
    return j < FSPLIT * 32 ? (j >> 6) * 128 + 64 + (j & 63) : -1;
}
__device__ __forceinline__ void finalizer(int id, const bf16* __restrict__ x, const bf16* __restrict__ wr, bf16* __restrict__ out, uint32_t epoch) {
    const int lane = threadIdx.x & 31;
    float b0 = -INFINITY, b1 = -INFINITY; int i0 = 0x7fffffff, i1 = 0x7fffffff;
    const uint32_t tag = (epoch & 0xfffffu) << 12;
    uint32_t fl = ~epoch;
    int row = fin_row(id, 0);
    const uint4 ra = *(const uint4*)(wr + lane * 8), rb = *(const uint4*)(wr + 256 + lane * 8);
    uint4 xa = *(const uint4*)(x + (size_t)row * DM + lane * 8), xb = *(const uint4*)(x + (size_t)row * DM + lane * 8 + 256);
#pragma unroll 1
    for (int it = 0; row >= 0; it++) {
        const int tile = row >> 6, nxt = fin_row(id, it + 1);
        const size_t o0 = (size_t)row * DM + lane * 8;
        uint32_t n = 0;
#pragma unroll 1
        while (!__all_sync(0xffffffffu, fl == epoch)) {
            if (n) __nanosleep(it ? 64 : 1000);
            fl = ldg_rlx(&g_f.p[tile][lane]);
            if (++n > SPIN_LIMIT) { ABORT(12); break; }
        }
        if (tile == NT - 1 && id == 63 && lane == 0) GT(1438);
        if ((id == 63 || id == 3 || id == 70) && lane == 0) GT(1800 + (id == 3) * 32 + tile);
        float v[16];
        {
            uint4 pa[8][2];
#pragma unroll
            for (int k = 0; k < 8; k++) {
                pa[k][0] = ldg4_h(g_P + (size_t)k * SQ * DM + o0, pol_ef(2));
                pa[k][1] = ldg4_h(g_P + (size_t)k * SQ * DM + o0 + 256, pol_ef(2));
            }
            fl = ldg_rlx(&g_f.p[max(nxt, 0) >> 6][lane]);
#pragma unroll
            for (int j = 0; j < 2; j++) {
#pragma unroll
                for (int i = 0; i < 4; i++) {
                    uint32_t w[8];
#pragma unroll
                    for (int k = 0; k < 8; k++) w[k] = i == 0 ? pa[k][j].x : (i == 1 ? pa[k][j].y : (i == 2 ? pa[k][j].z : pa[k][j].w));
                    v[j * 8 + 2 * i] = ((bf_lo(w[0]) + bf_lo(w[1])) + (bf_lo(w[2]) + bf_lo(w[3]))) + ((bf_lo(w[4]) + bf_lo(w[5])) + (bf_lo(w[6]) + bf_lo(w[7])));
                    v[j * 8 + 2 * i + 1] = ((bf_hi(w[0]) + bf_hi(w[1])) + (bf_hi(w[2]) + bf_hi(w[3]))) + ((bf_hi(w[4]) + bf_hi(w[5])) + (bf_hi(w[6]) + bf_hi(w[7])));
                }
            }
        }
        uint32_t hw[8];
        {
            const uint32_t xw[8] = {xa.x, xa.y, xa.z, xa.w, xb.x, xb.y, xb.z, xb.w};
            uint32_t aw[8];
#pragma unroll
            for (int i = 0; i < 8; i++) aw[i] = pack2(v[2 * i], v[2 * i + 1]);
#pragma unroll
            for (int d = 1; d <= 2; d++) {
                const bool up = lane & d;
#pragma unroll
                for (int i = 0; i < 8; i++) {
                    if (!(i & d)) {
                        const uint32_t r = __shfl_xor_sync(0xffffffffu, up ? aw[i] : aw[i | d], d);
                        if (up) aw[i] = r; else aw[i | d] = r;
                    }
                }
            }
#pragma unroll
            for (int i = 0; i < 8; i++) {
                hw[i] = pack2(bf_lo(aw[i]) + bf_lo(xw[i]), bf_hi(aw[i]) + bf_hi(xw[i]));
                v[2 * i] = bf_lo(hw[i]); v[2 * i + 1] = bf_hi(hw[i]);
            }
        }
        xa = *(const uint4*)(x + (size_t)max(nxt, 0) * DM + lane * 8); xb = *(const uint4*)(x + (size_t)max(nxt, 0) * DM + lane * 8 + 256);
        ln_row1(v);
        float r0 = 0.f, r1 = 0.f;
        {
            const uint32_t ww[8] = {ra.x, ra.y, ra.z, ra.w, rb.x, rb.y, rb.z, rb.w};
#pragma unroll
            for (int i = 0; i < 8; i++) { r0 = fmaf(v[2 * i], bf_lo(ww[i]), r0); r1 = fmaf(v[2 * i + 1], bf_hi(ww[i]), r1); }
        }
        r0 += r1;
#pragma unroll
        for (int o = 16; o; o >>= 1) r0 += __shfl_xor_sync(0xffffffffu, r0, o);
        r0 = rbf(r0);
        if (cand_better(r0, row, b0, i0)) { b1 = b0; i1 = i0; b0 = r0; i0 = row; }
        else if (cand_better(r0, row, b1, i1)) { b1 = r0; i1 = row; }
        if (tile == NT - 1 && id == 63 && lane == 0) GT(1439);
        const bool last = nxt < 0, spec = tile < SPEC_TILES && (last || (nxt >> 6) >= SPEC_TILES);
        const bool pub = (lane == 0 && spec) || (lane == 1 && last);
        if (pub)
            asm volatile("st.relaxed.gpu.global.v4.b32 [%0], {%1,%2,%3,%4};" :: "l"(&g_f.cand[lane][id]),
                         "r"(FU(b0)), "r"(tag | (uint32_t)min(i0, 4095)), "r"(FU(b1)), "r"(tag | (uint32_t)min(i1, 4095)) : "memory");
#pragma unroll
        for (int j = 0; j < 2; j++) {
            const uint32_t* hh = hw + j * 4; const float* nn = v + j * 8;
            stg4_h(out + o0 + j * 256, make_uint4(pack2(bf_lo(hh[0]) + nn[0], bf_hi(hh[0]) + nn[1]), pack2(bf_lo(hh[1]) + nn[2], bf_hi(hh[1]) + nn[3]),
                                                  pack2(bf_lo(hh[2]) + nn[4], bf_hi(hh[2]) + nn[5]), pack2(bf_lo(hh[3]) + nn[6], bf_hi(hh[3]) + nn[7])), pol_ef(4));
            if (i0 == row || i1 == row || i1 >= SQ || row == SQ - 1) {
                *(uint4*)(g_h + o0 + j * 256) = make_uint4(hh[0], hh[1], hh[2], hh[3]);
                *(uint4*)(g_hn + o0 + j * 256) = make_uint4(pack2(nn[0], nn[1]), pack2(nn[2], nn[3]), pack2(nn[4], nn[5]), pack2(nn[6], nn[7]));
            }
        }
        if (last || spec) {
            __threadfence();
            __syncwarp();
            if (pub) stg_rlx(&g_f.rows[lane][id], epoch);
        }
        row = nxt;
    }
    if (id == 0 && lane == 0) { g_epoch = epoch; if (epoch == 0xffffffu) { g_ticket[0] = 0; g_ticket[32] = 0; } }
}

__device__ __forceinline__ void g_producer(uint32_t sb, int g, const Maps& maps, uint32_t epoch, const bf16* __restrict__ x, const bf16* __restrict__ wr, bf16* __restrict__ out) {
    const uint32_t bar = sb + G_BAR;
    const int warp = (threadIdx.x >> 5) - 8;
    if (threadIdx.x == 256 && g == 5) GT(1410);
    if (threadIdx.x == 256 && g == 5) GT(1411);
    if (warp == 3) {
        wait_eq4(&g_f.xn[(threadIdx.x & 31) * 4], epoch, 13);
        __syncwarp();
        if ((threadIdx.x & 31) == 0) mbar_arrive(bar + 8 * GB_XN);
        finalizer(g, x, wr, out, epoch);
        if (g == 63 && (threadIdx.x & 31) == 0) GT(128 * 8 + 6);
    }
    if ((threadIdx.x & 31) != 0) return;
    if (threadIdx.x == 256 && g == 5) GT(1412);
    if (warp == 0) {
        wait_eq4(&g_f.xn[0], epoch, 13);
        const int rk = g & 1;
        const int m1 = g < 32 ? HSPLIT : 2 * NT - HSPLIT;
        const int mx = g < 32 ? m1 + NT : m1;
#pragma unroll 1
        for (int it = 0; it < mx; it++) {
            const int tile = g < 32 ? (it < m1 ? it : it - m1) : (it < NT ? it : it - NT + HSPLIT);
            if (it == 1) wait_eq4(&g_f.xn[4], epoch, 13);
            if (it == 2) mbar_wait(bar + 8 * GB_XN, 0);
            const bool nw = it == 0 || it == (g < 32 ? m1 : NT);
#pragma unroll
            for (int k = 0; k < 4; k++) {
                mbar_wait(bar + 8 * (GB_EMPTY + k), (it & 1) ^ 1);
                mbar_expect_tx(bar + 8 * (GB_FULL + k), nw ? 49152 : 16384);
                tma2d_mc(sb + slot_off(k) + rk * 8192, &maps.xn2, (k * 2 + rk) * 64, tile * 64, bar + 8 * (GB_FULL + k));
                if (nw && (it > 0 || k >= 2))
                    load_w(sb, it > 0 && g < 32 ? &maps.wq4 : ((g & 1) ? &maps.wv4 : &maps.wk4), it == 0 ? (g >> 1) * 128 : (g < 32 ? g * 128 : ((g - 32) >> 1) * 128), k);
            }
        }
        if (g >= 32) {
            const int u = g - 32, ks = u >> 2, ns = u & 3;
            int slot = 0, ph = 1;
#pragma unroll 1
            for (int tile = 0; tile < NT; tile++) {
                if (tile > 0) wait_eq4(&g_f.o[tile][ks][0], epoch, 9);
                if (g == 40 && tile == NT - 1) GT(1437);
                if (tile == NT - 1) GT(1690 + g - 32);
#pragma unroll 1
                for (int k = 0; k < 4; k++) {
                    mbar_wait(bar + 8 * (GB_EMPTY + slot), slot < 4 ? ph : ph ^ 1);
                    mbar_expect_tx(bar + 8 * (GB_FULL + slot), tile == 0 ? 49152 : 16384);
                    if (tile == 0) {
#pragma unroll
                        for (int nh = 0; nh < 2; nh++)
                            asm volatile("cp.async.bulk.tensor.5d.shared::cluster.global.mbarrier::complete_tx::bytes [%0], [%1, {%3, %4, %4, %4, %5}], [%2];"
                                :: "r"(sb + G_W + nh * 65536 + k * 16384), "l"((uint64_t)&maps.wo2), "r"(bar + 8 * (GB_FULL + k)), "r"(ns * 128 + nh * 64), "r"(0), "r"(ks * 16 + k * 4) : "memory");
                        if (k == 0) wait_eq4(&g_f.o[0][ks][0], epoch, 9);
                    }
                    tma2d_mc_h(sb + slot_off(slot) + rk * 8192, &maps.ox2, (ks * 8 + k * 2 + rk) * 64, tile * 64, bar + 8 * (GB_FULL + slot), pol_ef(1));
                    if (++slot == NS3) { slot = 0; ph ^= 1; }
                }
            }
        }
    } else if (warp < 3) {
        const int wg = warp - 1;
        const uint32_t buf = sb + G_BUF + wg * 32768;
        const CUtensorMap* tkv = (g & 1) ? &maps.vx3 : &maps.kx3;
        const int n1 = g < 32 ? HSPLIT / 2 : NT - HSPLIT / 2;
#pragma unroll 1
        for (int i = 0; i < n1; i++) {
            const int tile = (i < NT / 2 ? 2 * i : 2 * i - NT + HSPLIT) + wg, hd = (i < NT / 2 ? g : g - 32) >> 1;
            mbar_wait(bar + 8 * (GB_STG + wg), i & 1);
            tma_store3d(tkv, buf, tile * 64, hd * 2);
            asm volatile("cp.async.bulk.commit_group;" ::: "memory");
            asm volatile("cp.async.bulk.wait_group.read 0;" ::: "memory");
            mbar_arrive(bar + 8 * (GB_FREE + wg));
            asm volatile("cp.async.bulk.wait_group 0;" ::: "memory");
            PUBLISH(&g_f.kv[tile][hd][g & 1], epoch);
        }
        if (wg == 0) mbar_arrive(bar + 8 * GB_T1D);
        if (g >= 32) for (int i = 0; i < 4; i++) mbar_arrive2_if(bar + 8 * (GB_EMPTY + 4 + wg), 1);
        if (g < 32 && wg == 1) {
            mbar_wait(bar + 8 * GB_T1D, 0);
#pragma unroll 1
            for (int tile = 0; tile < NT; tile++) {
                wait_eq2(&g_f.kv[tile][g][0], epoch, 10);
                if (tile > 0) mbar_wait(bar + 8 * GB_KVF, (tile - 1) & 1);
                mbar_expect_tx(bar + 8 * (GB_KV + (tile & 1)), 16384);
                tma3d_h(sb + G_BUF, &maps.kx3, tile * 64, g * 2, bar + 8 * (GB_KV + (tile & 1)), pol_ef(0));
                if (tile > 0) mbar_wait(bar + 8 * GB_VF, (tile - 1) & 1);
                mbar_expect_tx(bar + 8 * (GB_VV + (tile & 1)), 16384);
                tma3d_h(sb + G_BUF + 32768, &maps.vx3, tile * 64, g * 2, bar + 8 * (GB_VV + (tile & 1)), pol_ef(0));
                if (PFK && tile + PFK < NT) {
                    const uint2 v = ldg_rlx2(&g_f.kv[tile + PFK][g][0]);
                    if (v.x == epoch && v.y == epoch) { tma_pf3d(&maps.kx3, (tile + PFK) * 64, g * 2); tma_pf3d(&maps.vx3, (tile + PFK) * 64, g * 2); }
                }
            }
        } else {
#pragma unroll 1
            for (int tile = g < 32 ? 0 : wg; tile < NT; tile += g < 32 ? 1 : 2) {
                mbar_wait(bar + 8 * (GB_STG + (tile & 1)), ((tile >> 1) + PO) & 1);
                mbar_arrive(bar + 8 * (GB_FREE + (tile & 1)));
                PUBLISH(g < 32 ? &g_f.o[tile][g >> 2][g & 3] : &g_f.p[tile][g - 32], epoch);
                if (g == 3 && tile == NT - 1) GT(1436);
                if (g == 3) GT(1896 + tile);
                if (g < 32 && tile == NT - 1) GT(1610 + g);
                if (g == 40 && tile == NT - 1) GT(1435);
                if (g == 40) GT(1864 + tile);
                if (g >= 32 && tile == NT - 1) GT(1650 + g - 32);
            }
        }
    }
}

struct WPtr { const bf16 *q, *k, *v, *o; };
__device__ __forceinline__ int startup(uint8_t* smem, const bf16* __restrict__ x, const Maps& maps, uint32_t& epoch, const WPtr& pw) {
    const int tid = threadIdx.x, lane = tid & 31, w = tid >> 5, cta = blockIdx.x;
    volatile uint32_t* sh = (volatile uint32_t*)(smem + SH_OFF);
    if (cta == 4 && tid == 0) GT(1399);
    epoch = (ldg_rlx(&g_epoch) + 1) & 0x00ffffffu;
    if (w < 4) {
        if (!(cta & 1)) {
            uint32_t* pp = (uint32_t*)(xpage() + ((XR3 ^ 0x3000u) ^ ((w == 1 || w == 2) ? 0x1000u : 0u) ^ ((w & 2) << 13))) + (cta >> 1) * 8;
            if (lane < 8) stg_rlx(pp + lane, 0u);
            __syncwarp();
            if (lane == 0) {
                uint32_t best = 0xffffffffu, a = 0;
#pragma unroll 1
                for (int r = 0; r < NPROBE; r++) {
                    uint32_t t0 = clk32();
                    asm volatile("atom.relaxed.gpu.global.add.u32 %0, [%1], %2;" : "=r"(a) : "l"(pp), "r"(a + 1) : "memory");
                    if (a == 0x7fffffffu) ABORT(15);
                    uint32_t t1 = clk32();
                    if (r > 0) best = min(best, t1 - t0);
                    else if (w == 0) {
                        asm volatile("red.relaxed.gpu.global.max.u32 [%0], %1;" :: "l"(&g_ticket[0]), "r"(epoch << 8) : "memory");
                        asm volatile("red.relaxed.gpu.global.max.u32 [%0], %1;" :: "l"(&g_ticket[32]), "r"(epoch << 8) : "memory");
                    }
                }
                sh[w] = best;
            }
        }
        if (!(cta & 1)) bar_sync(1, 128);
        if (cta == 4 && tid == 0) GT(1400);
        if (w == 0) {
            if (lane == 0) {
                uint32_t rp;
                if (!(cta & 1)) {
                    uint32_t a = sh[0], b = sh[1], c = sh[2], d = sh[3];
                    uint32_t mid = (min(min(a, b), min(c, d)) + max(max(a, b), max(c, d))) >> 1;
                    const int dd = (int)min(a, d) - (int)min(b, c);
                    uint32_t cls = abs(dd) > 60 ? dd > 0 : a > mid;
                    uint32_t t = atomicAdd(&g_ticket[cls * 32], 1u) & 255;
                    if (t >= (cls ? 34u : 32u)) { cls ^= 1; t = atomicAdd(&g_ticket[cls * 32], 1u) & 255; }
                    rp = min(cls ? 32 + t : t, 65u);
                    stg_rlx(&g_table[(cta >> 1) * 8], (epoch << 8) | rp);
                } else {
                    uint32_t v, n = 0;
#pragma unroll 1
                    while (((v = ldg_rlx(&g_table[(cta >> 1) * 8])) >> 8) != epoch) { if (++n > SPIN_LIMIT) { ABORT(14); break; } }
                    rp = v & 255;
                }
                const int role = rp * 2 + (cta & 1);
                sh[8] = role; sh[9] = epoch;
                while (sh[10] != epoch + 1 && cta < NWAITLN) {}
                if (role < 64) rec_first_loads(smem_u32(smem), role, maps);
                else if (role < 128) for (int k = 0; k < 2; k++) load_w(smem_u32(smem), (role & 1) ? &maps.wv4 : &maps.wk4, ((role - 64) >> 1) * 128, k);
                if (cta == 4) GT(1401);
            }
        }
    } else if (cta < 128) {
        uint4 u[2][2];
        const int row0 = cta * 16 + (w - 4) * 2;
#pragma unroll
        for (int r = 0; r < 2; r++)
#pragma unroll
            for (int j = 0; j < 2; j++) u[r][j] = *(const uint4*)(x + (size_t)(row0 + r) * DM + j * 256 + lane * 8);
        if (cta < 48) {
            const uint32_t b = cta >> 3, off = (b >= 4 ? 0x8000u + (b & 1) * 0x4000u : ((b & 1) ? 0x3000u : 0u) + ((b & 2) << 13)) ^ aslot(cta & 7);
            *(uint4*)(xpage() + off + (tid - 128) * 16) = make_uint4(0, 0, 0, 0);
        }
        float v[2][16];
#pragma unroll
        for (int r = 0; r < 2; r++)
#pragma unroll
            for (int j = 0; j < 2; j++) {
                uint32_t ww[4] = {u[r][j].x, u[r][j].y, u[r][j].z, u[r][j].w};
#pragma unroll
                for (int i = 0; i < 4; i++) { v[r][j * 8 + 2 * i] = bf_lo(ww[i]); v[r][j * 8 + 2 * i + 1] = bf_hi(ww[i]); }
            }
        ln_row2(v[0], v[1]);
#pragma unroll
        for (int r = 0; r < 2; r++)
#pragma unroll
            for (int j = 0; j < 2; j++)
                *(uint4*)(g_xn + (size_t)(row0 + r) * DM + j * 256 + lane * 8) =
                    make_uint4(pack2(v[r][j * 8], v[r][j * 8 + 1]), pack2(v[r][j * 8 + 2], v[r][j * 8 + 3]), pack2(v[r][j * 8 + 4], v[r][j * 8 + 5]), pack2(v[r][j * 8 + 6], v[r][j * 8 + 7]));
        bar_sync(2, 256);
        if (tid == 160 && cta < NWAITLN) { st_rel(&g_f.xn[cta], epoch); sh[10] = epoch + 1; }
        if (cta == 4 && tid == 160) GT(1403);
        __syncwarp();
    }
    if (cta == 4 && tid == 128) GT(1402);
    __syncthreads();
    if (tid == 160 && cta >= NWAITLN && cta < 128) st_rel(&g_f.xn[cta], epoch);
    __syncwarp();
    const int role = sh[8];
    return role;
}

__global__ void __cluster_dims__(2, 1, 1) __launch_bounds__(384, 1)
main_kernel(const __grid_constant__ Maps maps, const bf16* __restrict__ x, const bf16* __restrict__ mem0, const bf16* __restrict__ wr,
            const bf16* __restrict__ wd, bf16* __restrict__ out, const WPtr pw) {
    extern __shared__ __align__(1024) uint8_t smem[];
    const uint32_t sb = smem_u32(smem);
    if (threadIdx.x == 0) {
        for (int i = 0; i < MB_N; i++) mbar_init(sb + R_BAR + 8 * i, i == MB_V ? 4 : 1);
        for (int i = 0; i < GB_N; i++)
            mbar_init(sb + G_BAR + 8 * i, i >= GB_EMPTY && i < GB_KV ? 8 : (i >= GB_KVF ? 4 : (i >= GB_STG && i < GB_FREE ? 128 : 1)));
        asm volatile("fence.mbarrier_init.release.cluster;" ::: "memory");
    }
    __syncwarp();
    asm volatile("barrier.cluster.arrive.relaxed.aligned;" ::: "memory");
    if (threadIdx.x >= 352 && threadIdx.x < 352 + (int)(sizeof(Maps) / sizeof(CUtensorMap)))
        asm volatile("prefetch.tensormap [%0];" :: "l"((const CUtensorMap*)&maps + (threadIdx.x - 352)) : "memory");
    uint32_t epoch;
    asm volatile("fence.proxy.async.shared::cta;" ::: "memory");
    const int role = uni(startup(smem, x, maps, epoch, pw));
    asm volatile("barrier.cluster.wait.aligned;" ::: "memory");
    const int wg = uni(threadIdx.x >> 7);
    if (role < 64) {
#define SETREG(n) do { if ((n) < 168) asm volatile("setmaxnreg.dec.sync.aligned.u32 %0;" :: "n"(n)); if ((n) > 168) asm volatile("setmaxnreg.inc.sync.aligned.u32 %0;" :: "n"(n)); } while (0)
#define RESREG(n) do { if ((n) < 168) asm volatile("setmaxnreg.inc.sync.aligned.u32 168;"); if ((n) > 168) asm volatile("setmaxnreg.dec.sync.aligned.u32 168;"); } while (0)
        if (wg == WGA) {
            SETREG(RGA);
            rec_a(sb, role, mem0, epoch);
            RESREG(RGA);
        } else if (wg == WGB) {
            SETREG(RGB);
            rec_b(sb, role, epoch);
            RESREG(RGB);
        } else {
            SETREG(RGC);
            rec_c(sb, role, mem0, maps, epoch);
            RESREG(RGC);
        }
        ffn_phase(maps, wd, out);
        if (threadIdx.x == 0) GT(((volatile int*)(smem + SH_OFF))[8] * 8 + 6);
    } else if (role < 128) {
        if (wg < 2) {
            asm volatile("setmaxnreg.inc.sync.aligned.u32 192;");
            g_consumer(sb, role - 64, wg, epoch);
            if (threadIdx.x == 128) GT(role * 8 + 6);
        } else {
            asm volatile("setmaxnreg.dec.sync.aligned.u32 120;");
            g_producer(sb, role - 64, maps, epoch, x, wr, out);
        }
    } else {
        finalizer(64 + (threadIdx.x >> 5) * 4 + role - 128, x, wr, out, epoch);
    }
}

typedef CUresult (*EncodeFn)(CUtensorMap*, CUtensorMapDataType, cuuint32_t, void*, const cuuint64_t*, const cuuint64_t*, const cuuint32_t*, const cuuint32_t*,
                             CUtensorMapInterleave, CUtensorMapSwizzle, CUtensorMapL2promotion, CUtensorMapFloatOOBfill);
static void make_map3(EncodeFn fn, CUtensorMap* m, const void* ptr, uint64_t cols, uint64_t rows) {
    cuuint64_t dims[3] = {64, rows, cols / 64};
    cuuint64_t strides[2] = {cols * 2, 128};
    cuuint32_t box[3] = {64, 64, 2};
    cuuint32_t es[3] = {1, 1, 1};
    fn(m, CU_TENSOR_MAP_DATA_TYPE_BFLOAT16, 3, (void*)ptr, dims, strides, box, es, CU_TENSOR_MAP_INTERLEAVE_NONE, CU_TENSOR_MAP_SWIZZLE_128B,
       CU_TENSOR_MAP_L2_PROMOTION_L2_256B, CU_TENSOR_MAP_FLOAT_OOB_FILL_NONE);
}
static void make_map(EncodeFn fn, CUtensorMap* m, const void* ptr, uint64_t cols, uint64_t rows, uint32_t bcols, uint32_t brows,
                     bool f32 = false, CUtensorMapSwizzle sw = CU_TENSOR_MAP_SWIZZLE_128B) {
    cuuint64_t dims[2] = {cols, rows};
    cuuint64_t strides[1] = {cols * (f32 ? 4 : 2)};
    cuuint32_t box[2] = {bcols, brows};
    cuuint32_t es[2] = {1, 1};
    fn(m, f32 ? CU_TENSOR_MAP_DATA_TYPE_FLOAT32 : CU_TENSOR_MAP_DATA_TYPE_BFLOAT16, 2, (void*)ptr, dims, strides, box, es, CU_TENSOR_MAP_INTERLEAVE_NONE, sw,
       CU_TENSOR_MAP_L2_PROMOTION_L2_256B, CU_TENSOR_MAP_FLOAT_OOB_FILL_NONE);
}

extern "C" void kernel_launch(void* const* d_in, const int* in_sizes, int n_in, void* d_out, int out_size) {
    const bf16* x = (const bf16*)d_in[0];
    const bf16* mem0 = (const bf16*)d_in[1];
    const bf16* Wq = (const bf16*)d_in[2];
    const bf16* Wk = (const bf16*)d_in[3];
    const bf16* Wv = (const bf16*)d_in[4];
    const bf16* Wo = (const bf16*)d_in[5];
    const bf16* wr = (const bf16*)d_in[8];
    const bf16* wg = (const bf16*)d_in[9];
    const bf16* wu = (const bf16*)d_in[10];
    const bf16* wd = (const bf16*)d_in[11];
    bf16* out = (bf16*)d_out;

    static EncodeFn enc = nullptr;
    static void *pxn, *pK, *pV, *pO, *pacc;
    if (!enc) {
        cudaDriverEntryPointQueryResult qr;
        void* fn = nullptr;
        cudaGetDriverEntryPoint("cuTensorMapEncodeTiled", &fn, cudaEnableDefault, &qr);
        enc = (EncodeFn)fn;
        cudaGetSymbolAddress(&pxn, g_xn); cudaGetSymbolAddress(&pK, g_K); cudaGetSymbolAddress(&pV, g_V);
        cudaGetSymbolAddress(&pO, g_O); cudaGetSymbolAddress(&pacc, g_P);
        cudaFuncSetAttribute(main_kernel, cudaFuncAttributeMaxDynamicSharedMemorySize, SMEM_TOTAL);
    }
    Maps m;
    make_map(enc, &m.wq, Wq, HD, DM, 64, 256);
    make_map(enc, &m.wk, Wk, HD, DM, 64, 256);
    make_map(enc, &m.wv, Wv, HD, DM, 64, 256);
    make_map(enc, &m.wq4, Wq, HD, DM, 64, 128); make_map(enc, &m.wk4, Wk, HD, DM, 64, 128); make_map(enc, &m.wv4, Wv, HD, DM, 64, 128);
    make_map(enc, &m.wo, Wo, DM, HD, 64, 128);
    {
        cuuint64_t dims[5] = {DM, 2, 4, 4, HD / 32};
        cuuint64_t strides[4] = {DM * 2, 8 * DM * 2, 2 * DM * 2, 32 * DM * 2};
        cuuint32_t box[5] = {64, 2, 4, 4, 4};
        cuuint32_t es[5] = {1, 1, 1, 1, 1};
        enc(&m.wo2, CU_TENSOR_MAP_DATA_TYPE_BFLOAT16, 5, (void*)Wo, dims, strides, box, es, CU_TENSOR_MAP_INTERLEAVE_NONE, CU_TENSOR_MAP_SWIZZLE_128B,
            CU_TENSOR_MAP_L2_PROMOTION_L2_256B, CU_TENSOR_MAP_FLOAT_OOB_FILL_NONE);
    }
    make_map(enc, &m.kx, pK, HD, SQ, 64, 64);
    make_map(enc, &m.ox2, pO, HD, SQ, 64, 64);
    make_map(enc, &m.xn2, pxn, DM, SQ, 64, 64);
    make_map3(enc, &m.kx3, pK, HD, SQ); make_map3(enc, &m.vx3, pV, HD, SQ);
    make_map(enc, &m.wg, wg, FF, DM, 32, 256, false, CU_TENSOR_MAP_SWIZZLE_NONE);
    make_map(enc, &m.wu, wu, FF, DM, 32, 256, false, CU_TENSOR_MAP_SWIZZLE_NONE);

    cudaStream_t st = cudaStreamPerThread;
    main_kernel<<<NCTA, 384, SMEM_TOTAL, st>>>(m, x, mem0, wr, wd, out, WPtr{Wq, Wk, Wv, Wo});
}
```

```cpp
#include <cuda_runtime.h>
#include <cuda_bf16.h>
#include <cuda.h>
#include <stdint.h>
#include <stddef.h>

typedef __nv_bfloat16 bf16;

constexpr int SQ = 2048, DM = 512, NH = 32, DH = 128, NSEG = 64, HD = 4096, FF = 1792;

constexpr int NT = 32;
#define SPEC_TILES 30
__device__ __align__(1024) bf16 g_xn[SQ * DM];
__device__ __align__(1024) bf16 g_K[SQ * HD];
__device__ __align__(1024) bf16 g_V[SQ * HD];
__device__ __align__(1024) bf16 g_O[SQ * HD];
__device__ __align__(1024) uint32_t g_KVf[NSEG][NH][1024];
__device__ __align__(1024) bf16 g_P[8 * SQ * DM];
__device__ __align__(1024) bf16 g_h[SQ * DM];
__device__ __align__(1024) bf16 g_hn[SQ * DM];
__device__ uint8_t g_xraw[12 << 20];
#define XPG 0
__device__ __forceinline__ uint64_t xpage() { return (((uint64_t)g_xraw + (2 << 20) - 1) & ~(uint64_t)((2 << 20) - 1)) + ((uint64_t)XPG << 21); }
constexpr uint32_t XR3 = (1u << 20) | (1u << 19) | (1u << 12);
__device__ __forceinline__ uint32_t aslot(uint32_t s) { return ((s & 1) << 18) | ((s & 2) << 19) | ((s & 4) * 0xc000u); }
__device__ __forceinline__ uint32_t acc_base(uint32_t W) { return ((W & 2) ? 0x3000u : 0u) + ((W & 4) << 12) + (W & 1) * 2048; }
__device__ __forceinline__ uint32_t ext_base(uint32_t W) { return 0x8000u + ((W & 4) << 12) + (W & 3) * 1024; }
#define XHS 256
#define XSS 32
__device__ __forceinline__ uint32_t zero_off(uint32_t c, uint32_t ln) {
    return ln < 8 ? acc_base(c >> 3) + (c & 7) * 256 + ln * 16 : ext_base(c >> 3) + ((c >> 2) & 1) * XHS + ((c >> 1) & 1) * XSS + (c & 1) * 16;
}
struct Flags {
    uint32_t kv[NT][NH][2];
    uint32_t o[NT][8][32];
    uint32_t rec[64];
    uint32_t xn[128];
    uint32_t p[NT][32];
    uint32_t rows[2][128];
    uint4 cand[2][128];
    uint4 norm[64];
};
__device__ __align__(1024) Flags g_f;
__device__ __align__(1024) uint4 g_yp[2][FF / 32][DM];
__device__ __align__(1024) uint32_t g_table[66 * 8];
__device__ __align__(256) uint32_t g_ticket[64];
__device__ uint32_t g_epoch;
#define NS3 6
#define HSPLIT 26
#define PFK 0
#define NWAITLN 8
#define WGA 0
#define WGB 1
#define WGC (3 - WGA - WGB)
#define PFF 1
#define NPROBE 3
constexpr int NCTA = 132;
constexpr int NFW = 112;
__device__ uint32_t g_abort;
__device__ long long g_dbg[4096];
#define TR(slot, v)

__device__ __forceinline__ uint32_t smem_u32(const void* p) { return (uint32_t)__cvta_generic_to_shared(p); }
__device__ __forceinline__ void mbar_init(uint32_t a, uint32_t c) { asm volatile("mbarrier.init.shared::cta.b64 [%0], %1;" :: "r"(a), "r"(c) : "memory"); }
__device__ __forceinline__ void mbar_expect_tx(uint32_t a, uint32_t tx) { asm volatile("mbarrier.arrive.expect_tx.shared::cta.b64 _, [%0], %1;" :: "r"(a), "r"(tx) : "memory"); }
__device__ __forceinline__ void mbar_arrive(uint32_t a) { asm volatile("mbarrier.arrive.shared::cta.b64 _, [%0];" :: "r"(a) : "memory"); }
__device__ __forceinline__ void mbar_arrive_if(uint32_t a, uint32_t pred) {
    asm volatile("{\n.reg .pred p;\nsetp.ne.u32 p, %1, 0;\n@p mbarrier.arrive.shared::cta.b64 _, [%0];\n}" :: "r"(a), "r"(pred) : "memory");
}
__device__ __forceinline__ bool mbar_try(uint32_t a, uint32_t ph) {
    uint32_t ok;
    asm volatile("{\n.reg .pred p;\nmbarrier.try_wait.parity.shared::cta.b64 p, [%1], %2;\nselp.u32 %0, 1, 0, p;\n}" : "=r"(ok) : "r"(a), "r"(ph) : "memory");
    return ok != 0;
}
#define SPINLOG 20
constexpr uint32_t SPIN_LIMIT = 1u << SPINLOG;
#define ABORT(code_) atomicCAS(&g_abort, 0u, (code_))
__device__ __forceinline__ void mbar_wait(uint32_t a, uint32_t ph) {
    uint32_t n = 0;
#pragma unroll 1
    while (!mbar_try(a, ph)) { if (++n > SPIN_LIMIT) { ABORT(1); break; } }
}
__device__ __forceinline__ void bar_sync(int id, int n) { asm volatile("bar.sync %0, %1;" :: "r"(id), "r"(n) : "memory"); }
__device__ __forceinline__ void bar_arrive(int id, int n) { asm volatile("bar.arrive %0, %1;" :: "r"(id), "r"(n) : "memory"); }

__device__ __forceinline__ void ldsm4(uint32_t* r, uint32_t a) {
    asm volatile("ldmatrix.sync.aligned.m8n8.x4.shared.b16 {%0,%1,%2,%3}, [%4];" : "=r"(r[0]), "=r"(r[1]), "=r"(r[2]), "=r"(r[3]) : "r"(a) : "memory");
}
__device__ __forceinline__ void ldsm4t(uint32_t* r, uint32_t a) {
    asm volatile("ldmatrix.sync.aligned.m8n8.x4.trans.shared.b16 {%0,%1,%2,%3}, [%4];" : "=r"(r[0]), "=r"(r[1]), "=r"(r[2]), "=r"(r[3]) : "r"(a) : "memory");
}
__device__ __forceinline__ void stsm4t(uint32_t a, uint32_t r0, uint32_t r1, uint32_t r2, uint32_t r3) {
    asm volatile("stmatrix.sync.aligned.m8n8.x4.trans.shared.b16 [%0], {%1,%2,%3,%4};" :: "r"(a), "r"(r0), "r"(r1), "r"(r2), "r"(r3) : "memory");
}
__device__ __forceinline__ void stsm4(uint32_t a, uint32_t r0, uint32_t r1, uint32_t r2, uint32_t r3) {
    asm volatile("stmatrix.sync.aligned.m8n8.x4.shared.b16 [%0], {%1,%2,%3,%4};" :: "r"(a), "r"(r0), "r"(r1), "r"(r2), "r"(r3) : "memory");
}
__device__ __forceinline__ uint32_t movm(uint32_t a) { uint32_t d; asm volatile("movmatrix.sync.aligned.m8n8.trans.b16 %0, %1;" : "=r"(d) : "r"(a)); return d; }
__device__ __forceinline__ void mma16816(float* d, uint32_t a0, uint32_t a1, uint32_t a2, uint32_t a3, uint32_t b0, uint32_t b1) {
    asm volatile("mma.sync.aligned.m16n8k16.row.col.f32.bf16.bf16.f32 {%0,%1,%2,%3}, {%4,%5,%6,%7}, {%8,%9}, {%0,%1,%2,%3};"
        : "+f"(d[0]), "+f"(d[1]), "+f"(d[2]), "+f"(d[3]) : "r"(a0), "r"(a1), "r"(a2), "r"(a3), "r"(b0), "r"(b1));
}
__device__ __forceinline__ void mma1688(float* d, uint32_t a0, uint32_t a1, uint32_t b0) {
    asm volatile("mma.sync.aligned.m16n8k8.row.col.f32.bf16.bf16.f32 {%0,%1,%2,%3}, {%4,%5}, {%6}, {%0,%1,%2,%3};"
        : "+f"(d[0]), "+f"(d[1]), "+f"(d[2]), "+f"(d[3]) : "r"(a0), "r"(a1), "r"(b0));
}
__device__ __forceinline__ uint32_t pack2(float a, float b) { uint32_t d; asm("cvt.rn.bf16x2.f32 %0, %1, %2;" : "=r"(d) : "f"(b), "f"(a)); return d; }
__device__ __forceinline__ float bf_lo(uint32_t w) { return __uint_as_float(w << 16); }
__device__ __forceinline__ float bf_hi(uint32_t w) { return __uint_as_float(w & 0xffff0000u); }
__device__ __forceinline__ float rbf(float x) { return __bfloat162float(__float2bfloat16_rn(x)); }

__device__ __forceinline__ void sts128(uint32_t a, float x, float y, float z, float w) { asm volatile("st.shared.v4.f32 [%0], {%1,%2,%3,%4};" :: "r"(a), "f"(x), "f"(y), "f"(z), "f"(w) : "memory"); }
__device__ __forceinline__ void sts128u(uint32_t a, uint32_t x, uint32_t y, uint32_t z, uint32_t w) { asm volatile("st.shared.v4.b32 [%0], {%1,%2,%3,%4};" :: "r"(a), "r"(x), "r"(y), "r"(z), "r"(w) : "memory"); }
__device__ __forceinline__ void sts64(uint32_t a, float x, float y) { asm volatile("st.shared.v2.f32 [%0], {%1,%2};" :: "r"(a), "f"(x), "f"(y) : "memory"); }
__device__ __forceinline__ float4 lds128(uint32_t a) { float4 v; asm volatile("ld.shared.v4.f32 {%0,%1,%2,%3}, [%4];" : "=f"(v.x), "=f"(v.y), "=f"(v.z), "=f"(v.w) : "r"(a) : "memory"); return v; }
__device__ __forceinline__ float2 lds64(uint32_t a) { float2 v; asm volatile("ld.shared.v2.f32 {%0,%1}, [%2];" : "=f"(v.x), "=f"(v.y) : "r"(a) : "memory"); return v; }
__device__ __forceinline__ uint2 lds64u(uint32_t a) { uint2 v; asm volatile("ld.shared.v2.b32 {%0,%1}, [%2];" : "=r"(v.x), "=r"(v.y) : "r"(a) : "memory"); return v; }
__device__ __forceinline__ float4 lds128v(uint32_t a) { float4 v; asm volatile("ld.volatile.shared.v4.f32 {%0,%1,%2,%3}, [%4];" : "=f"(v.x), "=f"(v.y), "=f"(v.z), "=f"(v.w) : "r"(a) : "memory"); return v; }
__device__ __forceinline__ float2 lds64v(uint32_t a) { float2 v; asm volatile("ld.volatile.shared.v2.f32 {%0,%1}, [%2];" : "=f"(v.x), "=f"(v.y) : "r"(a) : "memory"); return v; }
__device__ __forceinline__ uint4 lds128uv(uint32_t a) { uint4 v; asm volatile("ld.volatile.shared.v4.b32 {%0,%1,%2,%3}, [%4];" : "=r"(v.x), "=r"(v.y), "=r"(v.z), "=r"(v.w) : "r"(a) : "memory"); return v; }
__device__ __forceinline__ void st_async4(uint32_t a, float x, float y, float z, float w, uint32_t mb) {
    asm volatile("st.async.weak.shared::cluster.mbarrier::complete_tx::bytes.v4.f32 [%0], {%1,%2,%3,%4}, [%5];" :: "r"(a), "f"(x), "f"(y), "f"(z), "f"(w), "r"(mb) : "memory");
}
__device__ __forceinline__ void st_async2(uint32_t a, uint32_t x, uint32_t y, uint32_t mb) {
    asm volatile("st.async.weak.shared::cluster.mbarrier::complete_tx::bytes.v2.b32 [%0], {%1,%2}, [%3];" :: "r"(a), "r"(x), "r"(y), "r"(mb) : "memory");
}
__device__ __forceinline__ uint32_t ldg_rlx(const uint32_t* p) { uint32_t v; asm volatile("ld.relaxed.gpu.global.b32 %0, [%1];" : "=r"(v) : "l"(p) : "memory"); return v; }
__device__ __forceinline__ uint4 ldg_rlx4(const uint32_t* p) { uint4 v; asm volatile("ld.relaxed.gpu.global.v4.b32 {%0,%1,%2,%3}, [%4];" : "=r"(v.x), "=r"(v.y), "=r"(v.z), "=r"(v.w) : "l"(p) : "memory"); return v; }
__device__ __forceinline__ uint4 ldg_rlx4_if(const uint32_t* p, bool c) {
    uint4 v;
    asm volatile("{\n.reg .pred p;\nsetp.ne.u32 p, %5, 0;\nmov.b32 %0, 0;\nmov.b32 %1, 0;\nmov.b32 %2, 0;\nmov.b32 %3, 0;\n@p ld.relaxed.gpu.global.v4.b32 {%0,%1,%2,%3}, [%4];\n}"
                 : "=r"(v.x), "=r"(v.y), "=r"(v.z), "=r"(v.w) : "l"(p), "r"((uint32_t)c) : "memory");
    return v;
}
__device__ __forceinline__ void stg_rlx(uint32_t* p, uint32_t v) { asm volatile("st.relaxed.gpu.global.b32 [%0], %1;" :: "l"(p), "r"(v) : "memory"); }
__device__ __forceinline__ void tma2d(uint32_t dst, const CUtensorMap* tm, int c0, int c1, uint32_t mb) {
    asm volatile("cp.async.bulk.tensor.2d.shared::cluster.global.mbarrier::complete_tx::bytes [%0], [%1, {%3, %4}], [%2];"
        :: "r"(dst), "l"((uint64_t)tm), "r"(mb), "r"(c0), "r"(c1) : "memory");
}

__device__ __forceinline__ void tma3d(uint32_t dst, const CUtensorMap* tm, int row, int chunk, uint32_t mb) {
    asm volatile("cp.async.bulk.tensor.3d.shared::cluster.global.mbarrier::complete_tx::bytes [%0], [%1, {%3, %4, %5}], [%2];"
        :: "r"(dst), "l"((uint64_t)tm), "r"(mb), "r"(0), "r"(row), "r"(chunk) : "memory");
}
#define EF 0xff
__device__ __forceinline__ uint64_t pol_ef(int bit) {
    uint64_t p;
    if ((EF >> bit) & 1) asm("createpolicy.fractional.L2::evict_first.b64 %0, 1.0;" : "=l"(p));
    else asm("createpolicy.fractional.L2::evict_normal.b64 %0, 1.0;" : "=l"(p));
    return p;
}
__device__ __forceinline__ void tma3d_h(uint32_t dst, const CUtensorMap* tm, int row, int chunk, uint32_t mb, uint64_t pol) {
    asm volatile("cp.async.bulk.tensor.3d.shared::cluster.global.mbarrier::complete_tx::bytes.L2::cache_hint [%0], [%1, {%3, %4, %5}], [%2], %6;"
        :: "r"(dst), "l"((uint64_t)tm), "r"(mb), "r"(0), "r"(row), "r"(chunk), "l"(pol) : "memory");
}
__device__ __forceinline__ void tma2d_h(uint32_t dst, const CUtensorMap* tm, int c0, int c1, uint32_t mb, uint64_t pol) {
    asm volatile("cp.async.bulk.tensor.2d.shared::cluster.global.mbarrier::complete_tx::bytes.L2::cache_hint [%0], [%1, {%3, %4}], [%2], %5;"
        :: "r"(dst), "l"((uint64_t)tm), "r"(mb), "r"(c0), "r"(c1), "l"(pol) : "memory");
}
__device__ __forceinline__ void tma2d_mc_h(uint32_t dst, const CUtensorMap* tm, int c0, int c1, uint32_t mb, uint64_t pol) {
    asm volatile("cp.async.bulk.tensor.2d.shared::cluster.global.mbarrier::complete_tx::bytes.multicast::cluster.L2::cache_hint [%0], [%1, {%3, %4}], [%2], %5, %6;"
        :: "r"(dst), "l"((uint64_t)tm), "r"(mb), "r"(c0), "r"(c1), "h"((uint16_t)3), "l"(pol) : "memory");
}
__device__ __forceinline__ uint4 ldg4_h(const void* p, uint64_t pol) {
    uint4 v;
    asm volatile("ld.relaxed.gpu.global.L2::cache_hint.v4.b32 {%0,%1,%2,%3}, [%4], %5;" : "=r"(v.x), "=r"(v.y), "=r"(v.z), "=r"(v.w) : "l"(p), "l"(pol) : "memory");
    return v;
}
__device__ __forceinline__ void stg4_h(void* p, uint4 v, uint64_t pol) {
    asm volatile("st.relaxed.gpu.global.L2::cache_hint.v4.b32 [%0], {%1,%2,%3,%4}, %5;" :: "l"(p), "r"(v.x), "r"(v.y), "r"(v.z), "r"(v.w), "l"(pol) : "memory");
}
__device__ __forceinline__ void tma2d_mc(uint32_t dst, const CUtensorMap* tm, int c0, int c1, uint32_t mb) {
    asm volatile("cp.async.bulk.tensor.2d.shared::cluster.global.mbarrier::complete_tx::bytes.multicast::cluster [%0], [%1, {%3, %4}], [%2], %5;"
        :: "r"(dst), "l"((uint64_t)tm), "r"(mb), "r"(c0), "r"(c1), "h"((uint16_t)3) : "memory");
}
__device__ __forceinline__ void mbar_arrive2_if(uint32_t a, uint32_t pred) {
    asm volatile("{\n.reg .pred p;\nsetp.ne.u32 p, %1, 0;\n@p mbarrier.arrive.shared::cta.b64 _, [%0];\n@p mbarrier.arrive.shared::cluster.b64 _, [%2];\n}"
                 :: "r"(a), "r"(pred), "r"(a ^ 0x01000000u) : "memory");
}
__device__ __forceinline__ void tma_pf3d(const CUtensorMap* tm, int row, int chunk) {
    asm volatile("cp.async.bulk.prefetch.tensor.3d.L2.global.tile [%0, {%1, %2, %3}];" :: "l"((uint64_t)tm), "r"(0), "r"(row), "r"(chunk) : "memory");
}
__device__ __forceinline__ void tma_pf2d(const CUtensorMap* tm, int c0, int c1) {
    asm volatile("cp.async.bulk.prefetch.tensor.2d.L2.global.tile [%0, {%1, %2}];" :: "l"((uint64_t)tm), "r"(c0), "r"(c1) : "memory");
}
__device__ __forceinline__ void tma_store3d(const CUtensorMap* tm, uint32_t src, int row, int chunk) {
    asm volatile("cp.async.bulk.tensor.3d.global.shared::cta.bulk_group [%0, {%2, %3, %4}], [%1];" :: "l"((uint64_t)tm), "r"(src), "r"(0), "r"(row), "r"(chunk) : "memory");
}
__device__ __forceinline__ void bulk_store(void* dst, uint32_t src, uint32_t bytes) {
    asm volatile("cp.async.bulk.global.shared::cta.bulk_group [%0], [%1], %2;" :: "l"(dst), "r"(src), "r"(bytes) : "memory");
}
#define GT(slot)
#define CNT(k)
#define CNT2(k, c)
#define TS(i, dep)
#define TSACC()
#define TSDECL
struct Maps { CUtensorMap wq, wk, wv, wo, wo2, kx, ox2, kx3, vx3, xn2, wg, wu, wd, wq4, wk4, wv4; };
typedef Maps RecMaps;
__device__ __forceinline__ void st_rel(uint32_t* p, uint32_t v) { asm volatile("st.release.gpu.global.u32 [%0], %1;" :: "l"(p), "r"(v) : "memory"); }
#define PUBLISH(p, v) st_rel(p, v)
__device__ __forceinline__ uint2 ldg_rlx2(const uint32_t* p) { uint2 v; asm volatile("ld.relaxed.gpu.global.v2.b32 {%0,%1}, [%2];" : "=r"(v.x), "=r"(v.y) : "l"(p) : "memory"); return v; }
__device__ __forceinline__ void wait_eq2(const uint32_t* p, uint32_t e, int code) {
    uint32_t n = 0;
#pragma unroll 1
    while (true) { uint2 v = ldg_rlx2(p); if (v.x == e && v.y == e) break; __nanosleep(64); if (++n > SPIN_LIMIT) { ABORT(code); break; } }
}
__device__ __forceinline__ void wait_eq4(const uint32_t* p, uint32_t e, int code) {
    uint32_t n = 0;
#pragma unroll 1
    while (true) { uint4 v = ldg_rlx4(p); if (v.x == e && v.y == e && v.z == e && v.w == e) break; __nanosleep(64); if (++n > SPIN_LIMIT) { ABORT(code); break; } }
}
__device__ __forceinline__ void wait_rec(const uint32_t* p, uint32_t e, uint32_t steps) {
    uint32_t n = 0;
#pragma unroll 1
    while (true) {
        uint2 v = ldg_rlx2(p);
        if (__all_sync(0xffffffffu, (v.x >> 8) == e && (v.y >> 8) == e && (v.x & 255) >= steps && (v.y & 255) >= steps)) break;
        __nanosleep(64); if (++n > SPIN_LIMIT) { ABORT(8); break; }
    }
}

constexpr int R_QK1 = 0;
constexpr int R_WO = 65536;
constexpr int R_T = 131072;
constexpr int R_SLOT1 = R_T;
constexpr int R_MEMB = R_T + 24576;
constexpr int R_QP = R_MEMB + 8192;
constexpr int R_VRED = R_QP + 4096;
constexpr int R_STG = R_VRED + 2048;
constexpr int R_AX = R_STG + 2048;
constexpr int R_SLOT0 = 196608;
constexpr int R_SLOC = R_SLOT0 + 24576;
constexpr int R_SREM = R_SLOC + 1536;
constexpr int R_VB = R_SREM + 1536;
constexpr int R_MISC = R_VB + 2048;
constexpr int R_LT = R_MISC + 128;
constexpr int R_BAR = 229888;
constexpr int R_TS = 229888 + 128;
static_assert(R_AX + 24576 <= R_SLOT0 && R_LT + 2560 <= 229376, "smem map");
enum { MB_W0 = 0, MB_W1, MB_WV, MB_WO, MB_S, MB_FULL0, MB_FULL1, MB_V, MB_N };

__device__ __forceinline__ float ex2(float x) { float y; asm("ex2.approx.ftz.f32 %0, %1;" : "=f"(y) : "f"(x)); return y; }
__device__ __forceinline__ float rcpf(float x) { float y; asm("rcp.approx.ftz.f32 %0, %1;" : "=f"(y) : "f"(x)); return y; }
__device__ __forceinline__ void mma16816z(float* d, uint32_t a0, uint32_t a1, uint32_t a2, uint32_t a3, uint32_t b0, uint32_t b1) {
    asm volatile("mma.sync.aligned.m16n8k16.row.col.f32.bf16.bf16.f32 {%0,%1,%2,%3}, {%4,%5,%6,%7}, {%8,%9}, {%10,%10,%10,%10};"
        : "=f"(d[0]), "=f"(d[1]), "=f"(d[2]), "=f"(d[3]) : "r"(a0), "r"(a1), "r"(a2), "r"(a3), "r"(b0), "r"(b1), "f"(0.f));
}
__device__ __forceinline__ void mma1688hz(float* d, uint32_t a0, uint32_t a1, uint32_t b0) {
    asm volatile("mma.sync.aligned.m16n8k8.row.col.f32.f16.f16.f32 {%0,%1,%2,%3}, {%4,%5}, {%6}, {%7,%7,%7,%7};"
        : "=f"(d[0]), "=f"(d[1]), "=f"(d[2]), "=f"(d[3]) : "r"(a0), "r"(a1), "r"(b0), "f"(0.f));
}
#define MMA(d, a, b0, b1) mma16816(d, a[0], a[1], a[2], a[3], b0, b1)
#define MMAZ(d, a, b0, b1) mma16816z(d, a[0], a[1], a[2], a[3], b0, b1)
#define MMAF(first, d, a, b0, b1) do { if (first) MMAZ(d, a, b0, b1); else MMA(d, a, b0, b1); } while (0)

__device__ __forceinline__ uint32_t uni(uint32_t x) { return __reduce_max_sync(0xffffffffu, x); }
__device__ __forceinline__ void mbar_wait_u(uint32_t a, uint32_t ph) {
    uint32_t n = 0;
#pragma unroll 1
    while (!__all_sync(0xffffffffu, mbar_try(a, ph))) { if (++n > SPIN_LIMIT) { ABORT(1); break; } }
}
__device__ __forceinline__ void mbar_wait_p(uint32_t a, uint32_t ph) {
    asm volatile("{\n.reg .pred p, q;\n.reg .u32 n;\nmov.u32 n, 0;\nWL: mbarrier.try_wait.parity.shared::cta.b64 p, [%0], %1;\nadd.u32 n, n, 1;\n"
                 "setp.lt.and.u32 q, n, %2, !p;\n@q bra.uni WL;\n}" :: "r"(a), "r"(ph), "n"(SPIN_LIMIT) : "memory");
}
__device__ __forceinline__ uint32_t mbar_test(uint32_t a, uint32_t ph) {
    uint32_t ok;
    asm volatile("{\n.reg .pred p;\nmbarrier.test_wait.parity.shared::cta.b64 p, [%1], %2;\nselp.u32 %0, 1, 0, p;\n}" : "=r"(ok) : "r"(a), "r"(ph) : "memory");
    return ok;
}
__device__ __forceinline__ uint32_t opaque(uint32_t x) { return __shfl_sync(0xffffffffu, x, threadIdx.x & 31); }
__device__ __forceinline__ const uint32_t* mkptr(uint32_t lo, uint32_t hi) { uint64_t r; asm("mov.b64 %0, {%1, %2};" : "=l"(r) : "r"(lo), "r"(hi)); return (const uint32_t*)r; }
__device__ __forceinline__ uint32_t prmt(uint32_t a, uint32_t b, uint32_t s) { uint32_t d; asm("prmt.b32 %0, %1, %2, %3;" : "=r"(d) : "r"(a), "r"(b), "r"(s)); return d; }
__device__ __forceinline__ uint32_t packh2(float a, float b) { uint32_t d; asm("cvt.rn.f16x2.f32 %0, %1, %2;" : "=r"(d) : "f"(b), "f"(a)); return d; }
__device__ __forceinline__ uint32_t hadd2b(uint32_t a, uint32_t b) { uint32_t d; asm("add.rn.bf16x2 %0, %1, %2;" : "=r"(d) : "r"(a), "r"(b)); return d; }
__device__ __forceinline__ uint32_t hmul2b(uint32_t a, uint32_t b) { uint32_t d; asm("mul.rn.bf16x2 %0, %1, %2;" : "=r"(d) : "r"(a), "r"(b)); return d; }
__device__ __forceinline__ uint32_t amax2b(uint32_t a, uint32_t b) { uint32_t d; asm("max.xorsign.abs.bf16x2 %0, %1, %2;" : "=r"(d) : "r"(a), "r"(b)); return d; }
__device__ __forceinline__ uint32_t amax2h(uint32_t a, uint32_t b) { uint32_t d; asm("max.xorsign.abs.f16x2 %0, %1, %2;" : "=r"(d) : "r"(a), "r"(b)); return d; }
__device__ __forceinline__ void sts32(uint32_t a, uint32_t x) { asm volatile("st.shared.b32 [%0], %1;" :: "r"(a), "r"(x) : "memory"); }
__device__ __forceinline__ uint32_t lds32v_(uint32_t a) { uint32_t v; asm volatile("ld.volatile.shared.b32 %0, [%1];" : "=r"(v) : "r"(a) : "memory"); return v; }
__device__ __forceinline__ void stg4(void* p, uint4 v) { asm volatile("st.relaxed.gpu.global.v4.b32 [%0], {%1,%2,%3,%4};" :: "l"(p), "r"(v.x), "r"(v.y), "r"(v.z), "r"(v.w) : "memory"); }
__device__ __forceinline__ void lds_frag(uint32_t* r, uint32_t a) {
    asm volatile("ld.shared.v4.b32 {%0,%1,%2,%3}, [%4];" : "=r"(r[0]), "=r"(r[1]), "=r"(r[2]), "=r"(r[3]) : "r"(a) : "memory");
}
__device__ __forceinline__ void lds_fragv(uint32_t* r, uint32_t a) {
    asm volatile("ld.volatile.shared.v4.b32 {%0,%1,%2,%3}, [%4];" : "=r"(r[0]), "=r"(r[1]), "=r"(r[2]), "=r"(r[3]) : "r"(a) : "memory");
}
__device__ __forceinline__ uint32_t xorv(uint32_t a, uint32_t b) { uint32_t d; asm volatile("xor.b32 %0, %1, %2;" : "=r"(d) : "r"(a), "r"(b)); return d; }
#define SCHED(k) asm volatile("{\n.reg .pred p;\nsetp.ne.u32 p, %0, %1;\n@p bra.uni SD;\nSL: nanosleep.u32 64;\nbra.uni SL;\nSD:\n}" :: "r"(sbu - s), "n"(k) : "memory")
#define PINM() asm volatile("{\n.reg .pred p;\nsetp.eq.u32 p, %0, 1;\n@p st.shared.u32 [%0], 0;\n}" :: "r"(sbu) : "memory")
__device__ __forceinline__ uint32_t or_and(uint32_t a, uint32_t b, uint32_t c) { uint32_t d; asm("lop3.b32 %0, %1, %2, %3, 0xF8;" : "=r"(d) : "r"(a), "r"(b), "r"(c)); return d; }
__device__ __forceinline__ uint32_t pack2v(float a, float b) { uint32_t d; asm volatile("cvt.rn.bf16x2.f32 %0, %1, %2;" : "=r"(d) : "f"(b), "f"(a)); return d; }
#define FU(x) __float_as_uint(x)
__device__ __forceinline__ uint32_t clk32() { uint32_t t; asm volatile("mov.u32 %0, %%clock;" : "=r"(t) :: "memory"); return t; }
__device__ __forceinline__ void spin_until(uint32_t t0, uint32_t d) {
    if (d) {
#pragma unroll 1
        while (__any_sync(0xffffffffu, clk32() - t0 < d)) {}
    }
}
constexpr int SH_OFF = 229376 + 384;
constexpr uint32_t HONE2 = 0x3c003c00u, HCNT2 = 0x50005000u;

__device__ __forceinline__ uint64_t desc_sw128(uint32_t addr, uint32_t lbo, uint32_t sbo) {
    return (uint64_t)((addr & 0x3FFFF) >> 4) | ((uint64_t)(lbo >> 4) << 16) | ((uint64_t)(sbo >> 4) << 32) | (1ull << 62);
}
#define DP 390
#define NAX 3
#define NXL 0
#define NCX 2
#define NCL 1
#define DC 0
#define FLIP 1
#define VTA 1
#define KXB 4
#define KXI 5
#define ANB 3
#define BNB 3
#define CNB 3
#define SMA 0
#define SMB 0
#define SMC 0x01
#define IVA 0
#define RGA 160
#define RGC 160
#define RGB (504 - RGA - RGC)
#define NRW 8
#define NBR 16
#define E0 0
#define E1 6
#define E2 4
#define E3 8
#define IV 2
#define DEX 0
#define G2V 0
#define G2K 2
#define VDEP 0
#define AEARLY 0
#define VTP 2
#define LORD 1
#define TRK 1
#define TW 0
#define T2N 14
#define TEARLY 1
#define DT 0
#define NB0 0
#define NB1 9
#define DB2 80
#define DITHER 0
#define DA 40
#define DB 40
#define DS 200

__device__ __forceinline__ uint32_t wrow_off(int kk, int ch) {
    const int lane = threadIdx.x & 31, r = lane & 7;
    const int row = 64 * (kk >> 2) + 32 * (r & 1) + 16 * (kk & 1) + 8 * (lane >> 4) + 4 * ((kk >> 1) & 1) + (r >> 1);
    return row * 128 + ((ch ^ (row & 7)) << 4);
}
template <int K> __device__ __forceinline__ void sched(uint32_t key) {
    asm volatile("{\n.reg .pred p;\nsetp.ne.u32 p, %0, %1;\n@p bra.uni SD;\nSL: nanosleep.u32 64;\nbra.uni SL;\nSD:\n}" :: "r"(key), "n"(K) : "memory");
}
__device__ __forceinline__ void sched_i(int i, uint32_t key) {
    if (i == -1) sched<20>(key); if (i == 0) sched<21>(key); if (i == 1) sched<22>(key); if (i == 2) sched<23>(key);
    if (i == 3) sched<24>(key); if (i == 4) sched<25>(key); if (i == 5) sched<26>(key); if (i == 6) sched<27>(key);
}
template <int NB, int SM, class F>
__device__ __forceinline__ void g1(float* q0, float* k0, uint32_t (*wq)[4], uint32_t (*wk)[4], uint32_t ga, uint32_t key, F&& hook) {
    float q1[4], k1[4];
    uint32_t b[NB][4];
#pragma unroll
    for (int i = 0; i < NB; i++) ldsm4(b[i], ga + i * 512);
    hook(-1, b[0]);
    if (SM & 1) sched_i(-1, key);
#pragma unroll
    for (int i = 0; i < 8; i++) {
        uint32_t* c = b[i % NB];
        MMAF(i == 0, q0, wq[2 * i], c[0], c[1]); MMAF(i == 0, k0, wk[2 * i], c[0], c[1]);
        MMAF(i == 0, q1, wq[2 * i + 1], c[2], c[3]); MMAF(i == 0, k1, wk[2 * i + 1], c[2], c[3]);
        const uint32_t cc_[4] = {c[0], c[1], c[2], c[3]};
        if (i + NB < 8) ldsm4(b[i % NB], ga + (i + NB) * 512);
        hook(i, cc_);
        if ((SM >> (i + 1)) & 1) sched_i(i, key);
    }
#pragma unroll
    for (int i = 0; i < 4; i++) { q0[i] += q1[i]; k0[i] += k1[i]; }
}
__device__ __forceinline__ float frag_norm2(uint32_t (*w)[4]) {
    float d0[4], d1[4];
#pragma unroll
    for (int i = 0; i < 32; i++) { MMAF(i == 0, d0, w[i], w[i][0], w[i][2]); MMAF(i == 0, d1, w[i], w[i][1], w[i][3]); }
    const int lane = threadIdx.x & 31, g = lane >> 2, t = lane & 3;
    float v = g == 2 * t ? d0[0] + d1[2] : (g == 2 * t + 1 ? d0[1] + d1[3] : 0.f);
#pragma unroll
    for (int o = 16; o; o >>= 1) v += __shfl_xor_sync(0xffffffffu, v, o);
    return v;
}
__device__ __forceinline__ void load_slot(uint32_t sb, int c, int tile, const Maps& maps) {
    const uint32_t dst = sb + ((tile & 1) ? R_SLOT1 : R_SLOT0), mb = sb + R_BAR + 8 * (MB_FULL0 + (tile & 1));
    mbar_expect_tx(mb, 24576);
    if ((EF >> 8) & 1) {
        tma2d_h(dst + 16384, &maps.kx, c * 64, tile * 64, mb, pol_ef(8));
        tma3d_h(dst, &maps.vx3, tile * 64, (c >> 1) * 2, mb, pol_ef(8));
    } else {
        tma2d(dst + 16384, &maps.kx, c * 64, tile * 64, mb);
        tma3d(dst, &maps.vx3, tile * 64, (c >> 1) * 2, mb);
    }
}
__device__ __forceinline__ uint32_t put_mem0(uint32_t sb, int W, const bf16* __restrict__ mem0) {
    const int lane = threadIdx.x & 31;
    const uint4 a = *(const uint4*)(mem0 + (lane & 7) * DM + W * 64 + (lane >> 3) * 8), b = *(const uint4*)(mem0 + (lane & 7) * DM + W * 64 + 32 + (lane >> 3) * 8);
    const uint4 m0 = make_uint4(prmt(a.x, b.x, 0x5410u), prmt(a.x, b.x, 0x7632u), prmt(a.y, b.y, 0x5410u), prmt(a.y, b.y, 0x7632u));
    const uint4 m1 = make_uint4(prmt(a.z, b.z, 0x5410u), prmt(a.z, b.z, 0x7632u), prmt(a.w, b.w, 0x5410u), prmt(a.w, b.w, 0x7632u));
    bar_sync(3, 256);
    sts128u(sb + R_MEMB + W * 1024 + lane * 16, m0.x, m0.y, m0.z, m0.w);
    sts128u(sb + R_MEMB + W * 1024 + 512 + lane * 16, m1.x, m1.y, m1.z, m1.w);
    return amax2b(amax2b(amax2b(m0.x, m0.y), amax2b(m0.z, m0.w)), amax2b(amax2b(m1.x, m1.y), amax2b(m1.z, m1.w)));
}
#define PUT_MAX(rL, W) sts32(rL + R_STG + 1024 + ((W) >> 2) * 512 + ((W) & 3) * 4, amax2b(amax2b(mx, my), mz));
__device__ __forceinline__ uint32_t h2b(uint32_t w) {
    uint32_t d;
    asm("{\n.reg .f16 l, h;\n.reg .f32 a, b;\nmov.b32 {l, h}, %1;\ncvt.f32.f16 a, l;\ncvt.f32.f16 b, h;\ncvt.rn.bf16x2.f32 %0, b, a;\n}" : "=r"(d) : "r"(w));
    return d;
}
#define GATHER1(HALF)                                                                                           \
        {                                                                                                       \
            const uint4 x0 = ldg_rlx4(pm), x1 = ldg_rlx4(pm + 256); const uint2 y = ldg_rlx2(px);                 \
            cw = (sel & 0x4000u) ? prmt(x0.w, x1.w, 0x7632u) : prmt(y.x, y.y, 0x5410u);                         \
            const uint32_t p0 = h2b(x0.x), p1 = h2b(x0.y), p2 = h2b(x0.z), p3 = h2b(prmt(x0.w, y.x, sel));      \
            stsm4t(rG + R_MEMB + HALF * 4096, p0, p1, p2, p3);                                                  \
            const uint32_t p4 = h2b(x1.x), p5 = h2b(x1.y), p6 = h2b(x1.z), p7 = h2b(prmt(x1.w, y.y, sel));      \
            stsm4t(rG + R_MEMB + HALF * 4096 + 512, p4, p5, p6, p7);                                            \
            mx = amax2b(amax2b(p0, p1), amax2b(p2, p3)); my = amax2b(p4, p5); mz = amax2b(p6, p7);              \
        }
#define GATHER(HALF, PRE, SYNC, AFTER)                                                                                      \
        {                                                                                                       \
            const uint32_t so = aslot(s);                                                                       \
            const uint32_t ua = (glo + acc_base(HALF * 4 + fo)) ^ so, ux = (glo + ext_base(HALF * 4 + fo)) ^ so; \
            uint2 lt;                                                                                           \
            lt.x = lds32v_(rL + R_LT); lt.y = lds32v_(rL + R_LT + 4);                                           \
            const uint32_t sel = 0x7610u - ((lt.x ^ (lt.x >> 2)) & 16) * 0x440u;                                \
            const uint32_t* pm = mkptr(ua + lt.x, ghi);                                                         \
            const uint32_t* px = mkptr(ux + lt.y, ghi);                                                         \
            PRE                                                                                                 \
            bar_sync(5, 384);                                                                                   \
            const uint32_t t0 = clk32();                                                                        \
            TSACC();                                                                        \
            SYNC                                                                                                \
            spin_until(t0, DP + DITHER);                                                                                 \
            \
            TS(10, 0);                                                                                          \
            uint32_t cw, nr = 0;                                                                                \
            _Pragma("unroll 1") do {                                                                            \
                GATHER1(HALF)                                                                                   \
                nr++;                                                                                           \
            } while (__any_sync(0xffffffffu, cw != HCNT2 && nr < SPIN_LIMIT));                                  \
            TS(11, cw);                                                                                         \
            AFTER                                                                                               \
            CNT2(HALF * 4 + (s & 1) * 2 + (nr > 2), nr > 1);                                                    \
            \
        }
#define GOBAR (fo == 3 ? 14 : 10 + fo)

__device__ __forceinline__ void rec_a(uint32_t sb, int c, const bf16* __restrict__ mem0, uint32_t epoch) {
    const int tid = threadIdx.x - WGA * 128, lane = tid & 31, f = tid >> 5;
    uint32_t wq[16][4], wk[16][4], mx, my = 0, mz = 0;
    const int lrow = ((lane >> 4) << 3) + (lane & 7), lsel = (lane >> 3) & 1;
    {
        mbar_wait(sb + R_BAR + 8 * MB_W0, 0);
        if (c == 7 && tid == 0) GT(1421);
#pragma unroll
        for (int kk = 0; kk < 16; kk++) { const uint32_t a = sb + R_T + wrow_off(kk, 2 * f + lsel); ldsm4t(wq[kk], a); ldsm4t(wk[kk], a + 32768); }
        __syncwarp();
        mx = put_mem0(sb, f, mem0);
    }
    const uint32_t rL = opaque(sb + lane * 16), rG = opaque(sb + lane * 16 + f * 1024);
    const uint32_t sbu = uni(sb), fo = uni(f), cc = uni(c);
    const uint64_t gx = xpage();
    const uint32_t ghi = uni((uint32_t)(gx >> 32)), glo = uni((uint32_t)gx);
#pragma unroll
    for (int i = 0; i < NAX; i++) {
        sts128u(rG + R_AX + 4096 * i, wq[i][0], wq[i][1], wq[i][2], wq[i][3]);
        sts128u(rG + R_AX + 4096 * i + 512, wk[i][0], wk[i][1], wk[i][2], wk[i][3]);
    }
    sts128u(rL + R_LT + 512 + f * 512, (sb + R_SREM + (f >= 2 ? lane * 8 + f * 256 : lane * 16 + f * 1024)) ^ 0x01000000u, (sb + R_BAR + 8 * MB_S) ^ 0x01000000u,
            sb + R_QP + (lane >> 4) * 128 + lsel * 512 + (lane & 7) * 16 + (f == 3 ? 2048 : 0), sb + R_SLOT0 + lrow * 128 + ((lsel ^ (lane & 7)) << 4));
    __syncwarp();
    if (tid == 0) GT(c * 8 + 1);
    TSDECL;
    const float cexp = 0.08838834764831845f * 1.4426950408889634f;
    float cs = cexp;
    auto step = [&](int s, bool first) -> bool {
        bar_sync(1, 128);
        float q0[4], k0[4];
        uint4 ta;
        uint32_t zr, rl2;
        g1<ANB, SMA>(q0, k0, wq, wk, rL + R_MEMB, sbu - s, [&](int i, const uint32_t* c_) {
            if (i == 0) TS(0, c_[0]);
            if (i == -1) {
#pragma unroll
                for (int n = NAX - NXL; n < NAX; n++) { lds_fragv(wq[n], rG + R_AX + 4096 * n); lds_fragv(wk[n], rG + R_AX + 4096 * n + 512); }
                ta = lds128uv(rL + R_LT + 512 + fo * 512);
                zr = ta.w & 1; rl2 = rL | zr;
            }
            if (i == IVA) { PUT_MAX(rl2, fo) bar_arrive(15, 256); bar_arrive(GOBAR, 96); }
        });
        stsm4t(rG + R_QP, pack2(q0[0], q0[1]), pack2(q0[2], q0[3]), pack2(k0[0], k0[1]), pack2(k0[2], k0[3]));
        TS(1, FU(k0[3]));
        if (first) mbar_wait_p(sbu + R_BAR + 8 * MB_FULL0, 0);
        if (fo >= 2) {
            bar_sync(3, 256);
            uint32_t kb[4], kc[4], qa[4], qc[4];
            ldsm4(kb, ta.z + 256); ldsm4(qa, ta.z);
            ldsm4(kc, ta.z + 1280); ldsm4(qc, ta.z + 1024);
            const uint32_t k0_ = hadd2b(kb[0], kb[1]), k1_ = hadd2b(kb[2], kb[3]), k2_ = hadd2b(kc[0], kc[1]), k3_ = hadd2b(kc[2], kc[3]);
            float s0[4], s2[4];
            MMAZ(s0, qa, k0_, k1_); MMAZ(s2, qc, k2_, k3_);
            const float x = ((s0[0] + s0[2]) + (s2[0] + s2[2])) * cs, y = ((s0[1] + s0[3]) + (s2[1] + s2[3])) * cs;
            st_async2(ta.x, FU(x), FU(y), ta.y);
            TS(3, FU(y));
            sts64((ta.x ^ 0x01000000u) + (R_SLOC - R_SREM), x, y);
            sts128u(rl2 + R_STG + (fo & 1) * 512, k0_, k1_, k2_, k3_);
            bar_arrive(9, 192);
        } else {
            uint32_t qa[4][4], kx[4][4];
#pragma unroll
            for (int kk = 0; kk < KXB; kk++) ldsm4(kx[kk], (ta.w ^ (kk * 32)) + (16384 + fo * 2048));
            bar_sync(3, 256);
#pragma unroll
            for (int kk = 0; kk < 4; kk++) {
                if (kk >= KXB) ldsm4(kx[kk], (ta.w ^ (kk * 32)) + (16384 + fo * 2048));
                ldsm4(qa[kk], ta.z + kk * 1024);
            }
            float s0[4], s1[4], s2[4], s3[4];
            MMAZ(s0, qa[0], kx[0][0], kx[0][1]); MMAZ(s1, qa[0], kx[0][2], kx[0][3]);
            MMAZ(s2, qa[1], kx[1][0], kx[1][1]); MMAZ(s3, qa[1], kx[1][2], kx[1][3]);
            MMA(s0, qa[2], kx[2][0], kx[2][1]); MMA(s1, qa[2], kx[2][2], kx[2][3]);
            MMA(s2, qa[3], kx[3][0], kx[3][1]); MMA(s3, qa[3], kx[3][2], kx[3][3]);
            const float x = ((s0[0] + s0[2]) + (s2[0] + s2[2])) * cs, y = ((s0[1] + s0[3]) + (s2[1] + s2[3])) * cs;
            const float z = ((s1[0] + s1[2]) + (s3[0] + s3[2])) * cs, w = ((s1[1] + s1[3]) + (s3[1] + s3[3])) * cs;
            st_async4(ta.x, x, y, z, w, ta.y);
            TS(3, FU(w));
            sts128(rG + R_SLOC, x, y, z, w);
        }
        const uint32_t r8 = (rl2 + sbu) >> 1;
        uint32_t vt00[4], vt01[4], vt10[4], vt11[4];
        const uint32_t rV = ta.w ^ ((fo & 1) * 64), vo = (fo >> 1) * 8192;
        if (!VTA && VTP < 2) { ldsm4t(vt00, rV + vo); ldsm4t(vt10, (rV ^ 32) + vo); }
        if (!VTA && VTP < 1) { ldsm4t(vt01, rV + vo + 2048); ldsm4t(vt11, (rV ^ 32) + vo + 2048); }
        bar_sync(4, 128);
        const float2 l2 = lds64v(r8 + R_SLOC + 512), l3 = lds64v(r8 + R_SLOC + 768);
        const float4 l0 = lds128v(rL + R_SLOC), l1 = lds128v(rL + R_SLOC + 1024);
        if (VTA && VTP < 2) { ldsm4t(vt00, rV + vo); ldsm4t(vt10, (rV ^ 32) + vo); }
        if (VTA && VTP < 1) { ldsm4t(vt01, rV + vo + 2048); ldsm4t(vt11, (rV ^ 32) + vo + 2048); }

        if (s == NSEG - 1) { mbar_wait_u(sbu + R_BAR + 8 * MB_S, 1); mbar_wait_u(sbu + R_BAR + 8 * MB_V, 1); return true; }
        TS(2, FU(l3.y));
        mbar_wait_p(sbu + R_BAR + 8 * MB_S, s & 1);
        TS(4, 0);
        {
            const float2 r2 = lds64v(r8 + R_SREM + 512), r3 = lds64v(r8 + R_SREM + 768);
            const float4 r0 = lds128v(rL + R_SREM), r1 = lds128v(rL + R_SREM + 1024);
            if (VTP >= 1) PINM();
            if (VTP >= 2) { ldsm4t(vt00, rV + vo); ldsm4t(vt10, (rV ^ 32) + vo); }
            if (VTP >= 1) { ldsm4t(vt01, rV + vo + 2048); ldsm4t(vt11, (rV ^ 32) + vo + 2048); }
            float sv[10];
            sv[0] = l0.x + r0.x; sv[1] = l0.y + r0.y; sv[2] = l0.z + r0.z; sv[3] = l0.w + r0.w;
            sv[4] = l1.x + r1.x; sv[5] = l1.y + r1.y; sv[6] = l1.z + r1.z; sv[7] = l1.w + r1.w;
            sv[8] = ((l2.x + l3.x) + r2.x) + r3.x; sv[9] = ((l2.y + l3.y) + r2.y) + r3.y;
            float m = fmaxf(fmaxf(fmaxf(fmaxf(sv[8], sv[9]), sv[0]), fmaxf(fmaxf(sv[2], sv[3]), sv[1])), fmaxf(fmaxf(sv[4], sv[5]), fmaxf(sv[6], sv[7])));
            {
                const float m1 = __shfl_xor_sync(0xffffffffu, m, 1), m2 = __shfl_xor_sync(0xffffffffu, m, 2), m3 = __shfl_xor_sync(0xffffffffu, m, 3);
                m = fmaxf(fmaxf(m, m1), fmaxf(m2, m3));
            }
            TS(5, FU(m));
            const uint32_t ONE2 = 0x3f803f80u;
            float o0[4], o1[4], sm[4];
            const uint32_t pb0 = pack2(ex2(sv[0] - m), ex2(sv[1] - m)), pb1 = pack2(ex2(sv[2] - m), ex2(sv[3] - m));
            mma16816z(sm, ONE2, ONE2, ONE2, ONE2, pb0, pb1);
            MMAZ(o0, vt00, pb0, pb1); MMAZ(o1, vt10, pb0, pb1);
            const uint32_t z = (VDEP == 0 ? FU(m) : pb0) & zr;
            const uint32_t vok = mbar_test(sbu + R_BAR + 8 * MB_V + z, s & 1);
            const uint32_t rv = r8 + vok * 8;
            float2 va = lds64v(rv + R_VB - 8 + fo * 512);
            float2 vb = lds64v(rv + R_VB - 8 + fo * 512 + 256);
            float sig = __uint_as_float(lds32v_(sbu + R_MISC + 40));
            const uint32_t pb2 = pack2(ex2(sv[4] - m), ex2(sv[5] - m)), pb3 = pack2(ex2(sv[6] - m), ex2(sv[7] - m));
            mma16816(sm, ONE2, ONE2, ONE2, ONE2, pb2, pb3);
            const uint32_t pb4 = pack2(ex2(sv[8] - m), ex2(sv[9] - m));
            MMA(o0, vt01, pb2, pb3); MMA(o1, vt11, pb2, pb3);
            mma1688(sm, ONE2, ONE2, pb4);
            const float z0 = rcpf(sm[0]), z1 = rcpf(sm[1]);
#define PUT_O()                                                                                                   \
            {                                                                                                     \
                float a0[4] = {o0[0], o0[1], o0[2], o0[3]}, a1[4] = {o1[0], o1[1], o1[2], o1[3]};                 \
                mma1688(a0, FU(va.x), FU(va.y), pb4); mma1688(a1, FU(vb.x), FU(vb.y), pb4);                       \
                const float i0 = z0 * sig, i1 = z1 * sig;                                                         \
                stsm4t(rG + R_QP, pack2(a0[0] * i0, a0[1] * i1), pack2(a0[2] * i0, a0[3] * i1), pack2(a1[0] * i0, a1[1] * i1), pack2(a1[2] * i0, a1[3] * i1)); \
            }
            PUT_O()
            asm volatile("{\n.reg .pred p;\nsetp.ne.u32 p, %0, 0;\n@p bar.arrive 8, 256;\n}" :: "r"(vok) : "memory");
            if (__builtin_expect(__any_sync(0xffffffffu, vok == 0), 0)) {
                mbar_wait_p(sbu + R_BAR + 8 * MB_V, s & 1);
                va = lds64v(r8 + R_VB + fo * 512); vb = lds64v(r8 + R_VB + fo * 512 + 256);
                sig = __uint_as_float(lds32v_(sbu + R_MISC + 40));
                PUT_O()
                bar_arrive(8, 256);
                CNT(8);
            }
            TS(6, 0);
            const float r = __uint_as_float(0x7f000000u - FU(sig));
            cs = cexp * r * (fo >= 2 ? r : 1.f);
        }
        return false;
    };
    step(0, true);
#pragma unroll 1
    for (int s = 0;; s++) {
        if (s & 1) mbar_wait_p(sbu + R_BAR + 8 * (MB_FULL0 + (((s + 1) >> 1) & 1)), ((s + 1) >> 2) & 1);
        {
            const uint32_t a = rL + R_LT + 512 + 12 + fo * 512;
            sts32(a, lds32v_(a) + ((s & 1) ? ((s & 2) ? R_SLOT0 - R_SLOT1 - 4096 : R_SLOT1 - R_SLOT0 - 4096) : 4096));
        }
        auto early = [&]() {
            SCHED(13);
#pragma unroll
            for (int i = 0; i < NAX - NXL; i++) { lds_fragv(wq[i], rG + R_AX + 4096 * i); lds_fragv(wk[i], rG + R_AX + 4096 * i + 512); }
        };
        GATHER(0, , early();, )
        if (step(s + 1, false)) break;
    }
    CNT(9);
    if (rG == sbu) GT(cc * 8 + 4);
}

__device__ __forceinline__ void rec_b(uint32_t sb, int c, uint32_t epoch) {
    const int tid = threadIdx.x - WGB * 128, lane = tid & 31, f = tid >> 5;
    uint32_t wq[16][4], wk[16][4], wo[32][4];
    const int lrow = ((lane >> 4) << 3) + (lane & 7), lsel = (lane >> 3) & 1;
    const uint32_t rL = opaque(sb + lane * 16), rW = opaque(sb + lane * 16 + f * 16384);
    const uint32_t sbu = uni(sb), fo = uni(f), cc = uni(c), po = cc & 1, ep = uni(epoch);
    {
        mbar_wait(sb + R_BAR + 8 * MB_WO, 0);
        if (c == 7 && tid == 0) GT(1426);
        const uint32_t aO = sb + R_WO + f * 16384 + lrow * 128 + ((lsel ^ (lane & 7)) << 4);
#pragma unroll
        for (int i = 0; i < 32; i++) {
            const int tile = (i >> 4) * 2 + (i & 1), kk = (i >> 1) & 7;
            ldsm4t(wo[i], (aO ^ (32 * tile)) + kk * 2048);
        }
        const float no = frag_norm2(wo);
        if (lane == 0) sts32(sb + R_MISC + 80 + f * 4, FU(no));
        __syncwarp();
        bar_sync(0, 256);
        if (tid == 0) {
            const float4 a = lds128(sb + R_MISC + 64), b = lds128(sb + R_MISC + 80);
            stg4(&g_f.norm[c], make_uint4(FU((a.x + a.y) + (a.z + a.w)), epoch, FU((b.x + b.y) + (b.z + b.w)), epoch));
        }
        __syncwarp();
#pragma unroll
        for (int i = NRW; i < 32; i++) sts128u(rW + R_WO + i * 512, wo[i][0], wo[i][1], wo[i][2], wo[i][3]);
        mbar_wait(sb + R_BAR + 8 * MB_W1, 0);
        if (c == 7 && tid == 0) GT(1422);
        __syncwarp();
#pragma unroll
        for (int kk = 0; kk < 16; kk++) { const uint32_t a = sb + R_QK1 + wrow_off(kk, 2 * f + lsel); ldsm4t(wq[kk], a); ldsm4t(wk[kk], a + 32768); }
        bar_sync(13, 128);
#pragma unroll
        for (int i = 0; i < 16; i++) {
            sts128u(rW + R_QK1 + i * 1024, wq[i][0], wq[i][1], wq[i][2], wq[i][3]);
            sts128u(rW + R_QK1 + i * 1024 + 512, wk[i][0], wk[i][1], wk[i][2], wk[i][3]);
        }
        __syncwarp();
    }
    const uint64_t gx = xpage();
    const uint32_t ghi = uni((uint32_t)(gx >> 32)), glo = uni((uint32_t)gx);
    TSDECL;
#pragma unroll 1
    for (int s = 0;; s++) {
        bar_sync(2, 256);
        float q0[4], k0[4];
        g1<BNB, SMB>(q0, k0, wq, wk, rL + R_MEMB + 4096, sbu - s, [&](int i, const uint32_t* c_) {
            if (i == 0) TS(0, c_[0]);
            if (i >= 2 && i < 6) {
#pragma unroll
                for (int n = NRW + (i - 2) * E0 / 4; n < NRW + (i - 1) * E0 / 4; n++) lds_fragv(wo[n], rW + R_WO + n * 512);
            }
            if (i == IV) bar_arrive(GOBAR, 96);
        });
        stsm4t(rL + fo * 1024 + R_QP + 512, pack2(q0[0], q0[1]), pack2(q0[2], q0[3]), pack2(k0[0], k0[1]), pack2(k0[2], k0[3]));
        bar_arrive(3, 256);
        TS(1, FU(k0[3]));
        const uint32_t so = aslot(s);
        uint2 lt;
        { const float2 t = lds64v(rL + R_LT + 8); lt.x = FU(t.x); lt.y = FU(t.y); }
        const uint32_t sel = 0x3210u + (lt.x & 16) * 0x440u;
        uint32_t* pm = (uint32_t*)mkptr(((glo + acc_base(po * 4 + fo)) ^ so) + lt.x, ghi);
        uint32_t* px = (uint32_t*)mkptr(((glo + ext_base(po * 4 + fo)) ^ so) + lt.y, ghi);
        if (s == NSEG - 1) break;
        {
            const uint32_t z = lt.x & 1;
#pragma unroll
            for (int n = NRW; n < NRW + E0 + E1 + E2 + E3; n++) {
                const int d = n - (n < NRW + T2N ? TRK + 1 : TRK);
                lds_fragv(wo[n], (d >= NRW ? or_and(rW, wo[d][0], z) : rW) + R_WO + n * 512);
            }
        }
        TS(2, wo[NRW + E0 + E1 + E2 + E3 - 1][0]);
        SCHED(4);
        bar_sync(8, 256);
        {
            float o[4][4];
            uint32_t b[4][4];
#pragma unroll
            for (int i = 0; i < 4; i++) ldsm4(b[i], rL + R_QP + i * 1024);
            PINM();
#pragma unroll
            for (int n = NRW + E0 + E1 + E2 + E3; n < 32; n++) lds_fragv(wo[n], rW + R_WO + n * 512);
            float p[4][4];
#define G2_STEP(o, hf, kk) _Pragma("unroll") for (int i = 0; i < 2; i++) MMAF((kk) < 2, o[((kk) & 1) * 2 + i], wo[(hf) * 16 + (kk) * 2 + i], b[(kk) >> 1][((kk) & 1) * 2], b[(kk) >> 1][((kk) & 1) * 2 + 1])
#define G2_RED(o, wl, h) const uint32_t wl = packh2(o[1][2] + o[3][2], o[1][3] + o[3][3]);                            \
                asm volatile("red.relaxed.gpu.global.add.noftz.v4.f16x2 [%0], {%1,%2,%3,%4};" :: "l"(pm + (h) * 16),  \
                    "r"(packh2(o[0][0] + o[2][0], o[0][1] + o[2][1])), "r"(packh2(o[0][2] + o[2][2], o[0][3] + o[2][3])), \
                    "r"(packh2(o[1][0] + o[3][0], o[1][1] + o[3][1])), "r"(prmt(wl, HONE2, (h) ? sel : sel ^ 0x4400u)) : "memory")
            if (G2V == 1) SCHED(11);
#pragma unroll
            for (int kk = 0; kk < 8; kk++) { G2_STEP(o, 0, kk); }
            TS(7, b[0][0]);
            if (G2V == 0) SCHED(11);
            else {
#pragma unroll
                for (int i = 0; i < 4; i++) wo[16 + i][0] = or_and(wo[16 + i][0], FU(o[i][0]), lt.x & 1);
            }
#pragma unroll
            for (int kk = 0; kk < G2K; kk++) { G2_STEP(p, 1, kk); }
#pragma unroll
            for (int i = 0; i < NB0; i++) { lds_fragv(wq[i], rW + R_QK1 + i * 1024); lds_fragv(wk[i], rW + R_QK1 + i * 1024 + 512); }
            G2_RED(o, w3, 0);
            TS(8, w3);
            if (G2V == 0) SCHED(12);
#pragma unroll
            for (int kk = G2K; kk < 8; kk++) { G2_STEP(p, 1, kk); }
            G2_RED(p, w7, 1);
            asm volatile("red.relaxed.gpu.global.add.noftz.f16x2 [%0], %1;" :: "l"(px), "r"(prmt((w3 & 0xffff0000u) | 0x3c00u, w7, sel)) : "memory");
            TS(9, w7);
        }
        bar_arrive(5, 384);
        asm volatile("{\n.reg .pred p;\nsetp.eq.u32 p, %0, %1;\n@p mbarrier.arrive.expect_tx.shared::cta.b64 _, [%2], 1536;\n}"
                     :: "r"(rW), "r"(sbu), "r"(sbu + R_BAR + 8 * MB_S) : "memory");
        const uint32_t tb = clk32();
        TSACC();
        spin_until(tb, DB);
#pragma unroll
        for (int i = NB0; i < NBR; i++) {
            if (i == NB1) spin_until(tb, DP + DB2);
            lds_fragv(wq[i], rW + R_QK1 + i * 1024); lds_fragv(wk[i], rW + R_QK1 + i * 1024 + 512);
        }
    }
}

#undef lds_fragv
__device__ __forceinline__ void rec_first_loads(uint32_t sb, int c, const Maps& maps) {
    const uint32_t bar = sb + R_BAR;
    const int F0 = c * 64;
    mbar_expect_tx(bar + 8 * MB_W0, 65536); mbar_expect_tx(bar + 8 * MB_WO, 65536); mbar_expect_tx(bar + 8 * MB_WV, 65536);
    tma2d(sb + R_QK1, &maps.wv, F0, 0, bar + 8 * MB_WV); tma2d(sb + R_QK1 + 32768, &maps.wv, F0, 256, bar + 8 * MB_WV);
    tma2d(sb + R_T + 32768, &maps.wk, F0, 0, bar + 8 * MB_W0);
    if (!LORD) {
        for (int i = 0; i < 4; i++) tma2d(sb + R_WO + i * 16384, &maps.wo, (c & 1) * 256 + i * 64, (c >> 1) * 128, bar + 8 * MB_WO);
        tma2d(sb + R_T, &maps.wq, F0, 0, bar + 8 * MB_W0);
    }
    mbar_expect_tx(bar + 8 * MB_S, 1536);
}
__device__ __forceinline__ void rec_c(uint32_t sb, int c, const bf16* __restrict__ mem0, const Maps& maps, uint32_t epoch) {
    const int tid = threadIdx.x - WGC * 128, lane = tid & 31, u = tid >> 5;
    const uint32_t bar = sb + R_BAR;
    const int lrow = ((lane >> 4) << 3) + (lane & 7), lsel = (lane >> 3) & 1;
    const int kh = u >> 1, j = u & 1;
    uint32_t wv[32][4], mx, my = 0, mz = 0;
    {
        if (u == 0) {
            sts128u(sb + lane * 16 + R_LT, (lane >> 3) * 256 + (lane & 7) * 16, ((lane >> 2) & 1) * XHS + (lane >> 4) * XSS + (lane & 8) * 2 + (lane & 2) * 4,
                    (lane >> 2) * 256 + (lane & 3) * 16, (lane & 1) * XHS + ((lane >> 3) & 1) * XSS + (lane & 6) * 4 + (lane >> 4) * 4);
        }
        mbar_wait(bar + 8 * MB_WV, 0);
        if (c == 7 && tid == 0) GT(1425);
        if (LORD && tid == 32) {
            for (int i = 0; i < 4; i++) tma2d(sb + R_WO + i * 16384, &maps.wo, (c & 1) * 256 + i * 64, (c >> 1) * 128, bar + 8 * MB_WO);
            tma2d(sb + R_T, &maps.wq, c * 64, 0, bar + 8 * MB_W0);
        }
        __syncwarp();
#pragma unroll
        for (int kk = 0; kk < 16; kk++) {
            const uint32_t aa = sb + R_QK1 + kh * 32768 + wrow_off(kk, 4 * j + 2 * kh + lsel);
            ldsm4t(wv[kk], aa); ldsm4t(wv[16 + kk], aa ^ 32);
        }
        {
            uint32_t x = 0;
#pragma unroll
            for (int i = 0; i < 32; i++) x ^= wv[i][0];
            sts32(sb + R_MISC + 96 + u * 4, __reduce_xor_sync(0xffffffffu, x));
        }
        bar_sync(9, 128);
        if (c == 7 && tid == 0) GT(1423);
        if (tid == 0) {
            mbar_expect_tx(bar + 8 * MB_W1, 65536);
            tma2d(sb + R_QK1 + 32768, &maps.wk, c * 64, 256, bar + 8 * MB_W1); tma2d(sb + R_QK1, &maps.wq, c * 64, 256, bar + 8 * MB_W1);
        }
        __syncwarp();
        const float nv = frag_norm2(wv);
        if (lane == 0) sts32(sb + R_MISC + 64 + u * 4, FU(nv));
        __syncwarp();
        bar_arrive(0, 256);
        mx = put_mem0(sb, 4 + u, mem0);
    }
    const uint32_t rL = opaque(sb + lane * 16), rG = opaque(sb + lane * 16 + u * 1024);
    const uint32_t sbu = uni(sb), fo = uni(u), cc = uni(c), ep = uni(epoch);
    const uint64_t gx = xpage();
    const uint32_t ghi = uni((uint32_t)(gx >> 32)), glo = uni((uint32_t)gx);
    constexpr int CX = R_AX + NAX * 4096;
    static_assert(NAX + NCX <= 6, "AX");
#pragma unroll
    for (int i = 0; i < NCX; i++) {
        sts128u(rG + CX + 4096 * i, wv[i][0], wv[i][1], wv[i][2], wv[i][3]);
        sts128u(rG + CX + 4096 * i + 512, wv[16 + i][0], wv[16 + i][1], wv[16 + i][2], wv[16 + i][3]);
    }
    __syncwarp();
    TSDECL;
    uint32_t rpb = 0x3f800000u;
    bar_arrive(2, 256);
    if (fo == 3) {
        uint32_t n = 0;
#pragma unroll 1
        while (true) {
            const uint2 v = ldg_rlx2(&g_f.kv[0][cc >> 1][0]);
            if (__all_sync(0xffffffffu, v.x == ep && v.y == ep)) break;
            __nanosleep(32);
            if (++n > SPIN_LIMIT) { ABORT(6); break; }
        }
        if (rL == sbu) load_slot(sbu, cc, 0, maps);
        __syncwarp();
        if (cc == 7 && rL == sbu) GT(1427);
    }
#pragma unroll 1
    for (int s = 0;; s++) {
        if (TEARLY && fo == 3 && !(s & 1) && s > 0 && s + 2 < NSEG) {
            if (rL == sbu) load_slot(sbu, cc, (s + 2) >> 1, maps);
            __syncwarp();
        } else spin_until(clk32(), DC);
#pragma unroll
        for (int i = NCX - NCL; i < NCX; i++) { lds_fragv(wv[i], rG + CX + 4096 * i); lds_fragv(wv[16 + i], rG + CX + 4096 * i + 512); }
        PUT_MAX(rL, 4 + fo)
        if (fo == 0) {
                bar_sync(15, 256);
                if (s == 0) {
                    const uint32_t* np = (const uint32_t*)&g_f.norm[0] + ((rL ^ sbu) >> 2);
                    uint4 r, q; uint32_t n = 0;
#pragma unroll 1
                    while (true) {
                        r = ldg_rlx4(np); q = ldg_rlx4(np + 128);
                        const uint2 z = ldg_rlx2(&g_f.xn[(rL ^ sbu) >> 3]);
                        if (__all_sync(0xffffffffu, r.y == ep && r.w == ep && q.y == ep && q.w == ep && z.x == ep && z.y == ep)) break;
                        if (++n > SPIN_LIMIT) { ABORT(5); break; }
                    }
                    float nv = __uint_as_float(r.x) + __uint_as_float(q.x), no = __uint_as_float(r.z) + __uint_as_float(q.z);
#pragma unroll
                    for (int o = 16; o; o >>= 1) { nv += __shfl_xor_sync(0xffffffffu, nv, o); no += __shfl_xor_sync(0xffffffffu, no, o); }
                    const int lc = ((int)(FU(nv) >> 23) + (int)(FU(no) >> 23) - 252 + 9 + 1) >> 1;
                    sts32(sbu + R_MISC + 32, 140 - lc);
                    __syncwarp();
                }
                const uint4 ma = lds128uv(rL + R_STG + 1024), mb = lds128uv(rL + R_STG + 1536);
                const uint32_t m_ = amax2b(amax2b(amax2b(ma.x, ma.y), amax2b(ma.z, ma.w)), amax2b(amax2b(mb.x, mb.y), amax2b(mb.z, mb.w)));
                const int em = (int)(__reduce_max_sync(0xffffffffu, amax2b(m_, m_ << 16) & 0x7f800000u) >> 23) + (int)(rpb >> 23) - 127;
                const int es = min(max((int)lds32v_(sbu + R_MISC + 32) - max(em, 127), -60), 60);
                sts32(sbu + R_MISC + 40, (127 + es) << 23);
                TS(4, es);
        } else bar_arrive(15, 256);
        bar_sync(GOBAR, 96);
        float v0[4], v1[4];
        g1<CNB, SMC>(v0, v1, wv, wv + 16, rL + R_MEMB + (fo >> 1) * 4096, sbu - s, [&](int i, const uint32_t* c_) { if (i == 0) TS(0, c_[0]); });
        TS(1, FU(v1[3]));
        const uint32_t l16 = (rL ^ sbu) | (lds32v_(rL + R_LT + 4) & 1);
        const uint32_t r8 = sbu + (l16 >> 1);
        {
            sts128(rL + R_VRED + fo * 512, v1[0], v1[1], v1[2], v1[3]);
            const uint32_t d = r8 + R_VB + ((cc & 1) * 4 + (fo & 1) * 2 + (fo >> 1)) * 256;
            const uint32_t dr = xorv(d, 0x01000000u), br = xorv(sbu + R_BAR + 8 * MB_V, 0x01000000u);
            bar_sync(6 + (fo & 1), 64);
            const float4 a0 = lds128(rL + R_VRED + (fo ^ 2) * 512);
            const float rp = __uint_as_float(rpb);
            const uint32_t w0 = pack2((v0[0] + a0.x) * rp, (v0[1] + a0.y) * rp), w1 = pack2((v0[2] + a0.z) * rp, (v0[3] + a0.w) * rp);
            st_async2(dr, w0, w1, br);
            TS(3, w1);
            sts64(d, __uint_as_float(w0), __uint_as_float(w1));
            __syncwarp();
            asm volatile("{\n.reg .pred p;\nsetp.eq.u32 p, %0, %1;\n@p mbarrier.arrive.expect_tx.shared::cta.b64 _, [%2], 256;\n}"
                         :: "r"(rL), "r"(sbu), "r"(sbu + R_BAR + 8 * MB_V) : "memory");
        }
        if (fo == 1) {
            bar_sync(9, 192);
            uint8_t* dst = (uint8_t*)&g_KVf[s][cc >> 1][(cc & 1) * 256] + l16;
            const uint32_t r2 = prmt(rpb, 0, 0x3232u);
#pragma unroll
            for (int i = 0; i < 2; i++) {
                const uint4 a = lds128uv(rL + R_STG + i * 512);
                stg4(dst + i * 512, make_uint4(~hmul2b(a.x, r2), ~hmul2b(a.y, r2), ~hmul2b(a.z, r2), ~hmul2b(a.w, r2)));
                const float2 b0 = lds64v(r8 + R_VB + (cc & 1) * 1024 + i * 512), b1 = lds64v(r8 + R_VB + (cc & 1) * 1024 + i * 512 + 256);
                stg4(dst + 2048 + i * 512, make_uint4(~FU(b0.x), ~FU(b0.y), ~FU(b1.x), ~FU(b1.y)));
            }
            __syncwarp();
            if (l16 == 0) { stg_rlx(&g_f.rec[cc], (ep << 8) | (s + 1)); if (s == NSEG - 1) GT(1500 + cc); }
            __syncwarp();
        } else {
            bar_arrive(9, 192);
            if (fo == 2) {
                if (l16 < 144) stg4((void*)mkptr((glo + zero_off(cc, l16 >> 4)) ^ aslot(s + 4), ghi), make_uint4(0, 0, 0, 0));
                __syncwarp();
            } else if (fo == 3) {
                if (((s & 1) || s == 0) && s + 3 < NSEG) {
                    const uint32_t* fp = &g_f.kv[(s + 3) >> 1][cc >> 1][0];
                    uint32_t n = 0;
#pragma unroll 1
                    while (true) {
                        const uint2 v = ldg_rlx2(fp);
                        if (__all_sync(0xffffffffu, v.x == ep && v.y == ep)) break;
                        __nanosleep(64);
                        if (++n > SPIN_LIMIT) { ABORT(6); break; }
                    }
                }
                if (!(s & 1) && s + 2 < NSEG && (!TEARLY || s == 0)) {
                    spin_until(clk32(), DT);
                    if (l16 == 0) load_slot(sbu, cc, (s + 2) >> 1, maps);
                    __syncwarp();
                }
            }
        }
        if (s == NSEG - 1) break;
        auto early = [&]() {
#pragma unroll
            for (int i = 0; i < NCX - NCL; i++) { lds_fragv(wv[i], rG + CX + 4096 * i); lds_fragv(wv[16 + i], rG + CX + 4096 * i + 512); }
        };
        GATHER(1, , early(); rpb = 0x7f000000u - lds32v_(sbu + R_MISC + 40);, bar_arrive(2, 256);)
    }
}

__device__ __forceinline__ bool cand_better(float v, int i, float bv, int bi) { return v > bv || (v == bv && i < bi); }
constexpr int F_WG = 0, F_WU = 32768, F_WD = 65536, F_X = 98304, F_RED = F_X + 4096, F_ACT = F_RED + 8192, F_SEL = F_ACT + 256;

__device__ __noinline__ void ffn_phase(const Maps& maps, bf16* __restrict__ out) {
    extern __shared__ __align__(1024) uint8_t smem[];
    const uint32_t sb = smem_u32(smem);
    const int c = ((volatile int*)(smem + SH_OFF))[8];
    const uint32_t epoch = ((volatile uint32_t*)(smem + SH_OFF))[9];
    const int tid = threadIdx.x;
    constexpr int NWK = FF / 32;
    const bool worker = c < NWK;
    bar_sync(0, 384);
    const uint32_t mb = sb + R_BAR + 8 * MB_W0;
    if (tid == 32 && worker) {
        asm volatile("fence.proxy.async.shared::cta;" ::: "memory");
        mbar_expect_tx(mb, 98304);
        tma2d(sb + F_WG, &maps.wg, c * 32, 0, mb); tma2d(sb + F_WG + 16384, &maps.wg, c * 32, 256, mb);
        tma2d(sb + F_WU, &maps.wu, c * 32, 0, mb); tma2d(sb + F_WU + 16384, &maps.wu, c * 32, 256, mb);
        for (int i = 0; i < 8; i++) tma2d(sb + F_WD + i * 4096, &maps.wd, i * 64, c * 32, mb);
    }
    int p0 = -1, p1 = -1;
#pragma unroll 1
    for (int pass = 0; pass < 2; pass++) {
        if (tid < 32) {
            const uint32_t tag = epoch & 0xfffffu;
            uint4 r[4]; uint32_t n = 0;
            const int t3 = tid + 96 < NFW ? tid + 96 : tid;
#pragma unroll 1
            while (true) {
                bool ok = true;
#pragma unroll
                for (int i = 0; i < 4; i++) r[i] = ldg_rlx4((const uint32_t*)&g_f.cand[pass][i < 3 ? tid + 32 * i : t3]);
#pragma unroll
                for (int i = 0; i < 4; i++) ok = ok && (r[i].y >> 12) == tag && (r[i].w >> 12) == tag;
                if (__all_sync(0xffffffffu, ok)) break;
                __nanosleep(32);
                if (++n > SPIN_LIMIT) { ABORT(7); break; }
            }
            float b0 = __uint_as_float(r[0].x), b1 = __uint_as_float(r[0].z); int i0 = r[0].y & 4095, i1 = r[0].w & 4095;
#pragma unroll
            for (int i = 1; i < 4; i++) {
                if (i < 3 || t3 != tid) {
                    float c0 = __uint_as_float(r[i].x), c1 = __uint_as_float(r[i].z); int j0 = r[i].y & 4095, j1 = r[i].w & 4095;
                    if (cand_better(c0, j0, b0, i0)) {
                        if (cand_better(c1, j1, b0, i0)) { b1 = c1; i1 = j1; } else { b1 = b0; i1 = i0; }
                        b0 = c0; i0 = j0;
                    } else if (cand_better(c0, j0, b1, i1)) { b1 = c0; i1 = j0; }
                }
            }
#pragma unroll
            for (int o = 16; o; o >>= 1) {
                float c0 = __shfl_xor_sync(0xffffffffu, b0, o), c1 = __shfl_xor_sync(0xffffffffu, b1, o);
                int j0 = __shfl_xor_sync(0xffffffffu, i0, o), j1 = __shfl_xor_sync(0xffffffffu, i1, o);
                if (cand_better(c0, j0, b0, i0)) {
                    if (cand_better(c1, j1, b0, i0)) { b1 = c1; i1 = j1; } else { b1 = b0; i1 = i0; }
                    b0 = c0; i0 = j0;
                } else if (cand_better(c0, j0, b1, i1)) { b1 = c0; i1 = j0; }
            }
            i0 = min(i0, SQ - 1); i1 = min(i1, SQ - 1);
            if (i0 != p0 || i1 != p1) {
                n = 0;
#pragma unroll 1
                while (!__all_sync(0xffffffffu, (ldg_rlx(&g_f.rows[pass][tid]) == epoch) & (ldg_rlx(&g_f.rows[pass][tid + 32]) == epoch) &
                                                   (ldg_rlx(&g_f.rows[pass][tid + 64]) == epoch) & (ldg_rlx(&g_f.rows[pass][t3]) == epoch))) { __nanosleep(32); if (++n > SPIN_LIMIT) { ABORT(7); break; } }
            }
            int* sel = (int*)(smem + F_SEL);
            if (pass && tid == 0) GT(c * 8 + 5);
            if (tid == 0) { sel[0] = i0; sel[1] = i1; ((float*)sel)[2] = b0; ((float*)sel)[3] = b1; }
        }
        bar_sync(0, 384);
        const int t0 = ((int*)(smem + F_SEL))[0], t1 = ((int*)(smem + F_SEL))[1];
        if (c == 3 && tid == 0 && pass == 0) GT(1430);
        if (t0 == p0 && t1 == p1) break;
        const uint32_t ytag = epoch * 2 + pass + 1;
        if (worker) {
            const int lane = tid & 31, w = tid >> 5, g = lane >> 2, t = lane & 3;
            const int lrow = ((lane >> 4) << 3) + (lane & 7), lsel = (lane >> 3) & 1;
            float2* red = (float2*)(smem + F_RED);
            if (w < 8) {
                const uint32_t* xp = (const uint32_t*)(g_hn + (size_t)((g & 1) ? t1 : t0) * DM) + w * 32 + t;
                uint32_t xb[8];
#pragma unroll
                for (int i = 0; i < 8; i++) xb[i] = __ldcg(xp + i * 4);
                mbar_wait(mb, 1);
                if (c == 3 && tid == 0 && pass == 0) GT(1431);
                float d[4][4];
#pragma unroll
                for (int kk = 0; kk < 4; kk++) {
                    const int row = w * 64 + kk * 16 + lrow;
#pragma unroll
                    for (int m = 0; m < 4; m++) {
                        uint32_t a[4];
                        ldsm4t(a, sb + (m >> 1) * F_WU + row * 64 + ((((m & 1) * 2 + lsel) ^ ((row >> 1) & 3)) << 4));
                        MMAF(kk == 0, d[m], a, xb[2 * kk], xb[2 * kk + 1]);
                    }
                }
                const float e0 = t == 0 ? d[0][0] : (t == 1 ? d[1][0] : (t == 2 ? d[2][0] : d[3][0])), e1 = t == 0 ? d[0][1] : (t == 1 ? d[1][1] : (t == 2 ? d[2][1] : d[3][1]));
                const float e2 = t == 0 ? d[0][2] : (t == 1 ? d[1][2] : (t == 2 ? d[2][2] : d[3][2])), e3 = t == 0 ? d[0][3] : (t == 1 ? d[1][3] : (t == 2 ? d[2][3] : d[3][3]));
                red[w * 64 + t * 16 + g] = make_float2(e0, e1); red[w * 64 + t * 16 + g + 8] = make_float2(e2, e3);
            }
            bar_sync(0, 384);
            if (tid < 64) {
                const float* r = (const float*)red + tid;
                float gsum = 0.f, usum = 0.f;
#pragma unroll
                for (int kg = 0; kg < 8; kg++) { gsum += r[kg * 128]; usum += r[kg * 128 + 64]; }
                gsum = rbf(gsum); usum = rbf(usum);
                const float sg = rbf(gsum / (1.f + __expf(-gsum)));
                ((bf16*)(smem + F_ACT))[(tid & 1) * 32 + (tid >> 1)] = __float2bfloat16_rn(sg * usum);
            }
            bar_sync(0, 384);
            if (w < 8) {
                const uint32_t* ap = (const uint32_t*)(smem + F_ACT) + (g & 1) * 16 + t;
                float d[4][4];
#pragma unroll
                for (int kk = 0; kk < 2; kk++) {
                    const uint32_t b0 = ap[kk * 8], b1 = ap[kk * 8 + 4];
#pragma unroll
                    for (int m = 0; m < 4; m++) {
                        uint32_t a[4];
                        ldsm4t(a, sb + F_WD + w * 4096 + (kk * 16 + lrow) * 128 + (((m * 2 + lsel) ^ (lane & 7)) << 4));
                        MMAF(kk == 0, d[m], a, b0, b1);
                    }
                }
                const float e0 = t == 0 ? d[0][0] : (t == 1 ? d[1][0] : (t == 2 ? d[2][0] : d[3][0])), e1 = t == 0 ? d[0][1] : (t == 1 ? d[1][1] : (t == 2 ? d[2][1] : d[3][1]));
                const float e2 = t == 0 ? d[0][2] : (t == 1 ? d[1][2] : (t == 2 ? d[2][2] : d[3][2])), e3 = t == 0 ? d[0][3] : (t == 1 ? d[1][3] : (t == 2 ? d[2][3] : d[3][3]));
                uint4* yp = &g_yp[pass][c][w * 64 + t * 16 + g];
                stg4(yp, make_uint4(FU(e0), ytag, FU(e1), ytag)); stg4(yp + 8, make_uint4(FU(e2), ytag, FU(e3), ytag));
            }
            if (c == 3 && tid == 0 && pass == 0) GT(1432);
        } else {
            const int j = tid & 63, part = tid >> 6, col = (c - NWK) * 64 + j;
            const int tok = part ? t1 : t0, old = part ? p1 : p0;
            float hv = 0.f, nv = 0.f;
            if (part < 2) {
                hv = __bfloat162float(__ldcg(g_h + (size_t)tok * DM + col)); nv = __bfloat162float(__ldcg(g_hn + (size_t)tok * DM + col));
                if (old >= 0 && old != t0 && old != t1)
                    out[(size_t)old * DM + col] = __float2bfloat16_rn(__bfloat162float(__ldcg(g_h + (size_t)old * DM + col)) + __bfloat162float(__ldcg(g_hn + (size_t)old * DM + col)));
            }
            float s0 = 0.f, s1 = 0.f;
            uint4 v[10]; uint32_t n = 0;
            bool ok;
#pragma unroll 1
            do {
                ok = true;
#pragma unroll
                for (int i = 0; i < 10; i++) {
                    const int src = part + 6 * i;
                    v[i] = src < NWK ? ldg_rlx4((const uint32_t*)&g_yp[pass][src][col]) : make_uint4(0, ytag, 0, ytag);
                }
#pragma unroll
                for (int i = 0; i < 10; i++) ok = ok && v[i].y == ytag && v[i].w == ytag;
                if (!ok) __nanosleep(100);
                if (++n > SPIN_LIMIT) { ABORT(7); break; }
            } while (!ok);
#pragma unroll
            for (int i = 0; i < 10; i++) { s0 += __uint_as_float(v[i].x); s1 += __uint_as_float(v[i].z); }
            float2* red = (float2*)(smem + F_RED);
            red[part * 64 + j] = make_float2(s0, s1);
            bar_sync(0, 384);
            if (part < 2) {
                float y = 0.f;
#pragma unroll
                for (int i = 0; i < 6; i++) y += ((const float*)red)[(i * 64 + j) * 2 + part];
                const float rs = rbf(1.f / (1.f + __expf(-((float*)(smem + F_SEL))[2 + part])));
                out[(size_t)tok * DM + col] = __float2bfloat16_rn(hv + rbf(nv + rbf(rbf(y) * rs)));
            }
            if (tid == 0 && pass == 0 && c == NWK) GT(1434);
        }
        p0 = t0; p1 = t1;
        if (c == 3 && tid == 0 && pass == 0) GT(1433);
        bar_sync(0, 384);
    }
}

constexpr int G_W = 0;
constexpr int G_RING = 131072;
constexpr int G_BUF = 163840;
constexpr int G_BAR = 229376;
constexpr int G_SMEM = G_BAR + 512;
enum { GB_FULL = 0, GB_EMPTY = GB_FULL + 8, GB_KV = GB_EMPTY + 8, GB_STG = GB_KV + 2, GB_FREE = GB_STG + 2, GB_XN = GB_FREE + 2, GB_T1D, GB_VV, GB_KVF = GB_VV + 2, GB_VF, GB_N };
constexpr int SMEM_TOTAL = 232448;

__device__ __forceinline__ void wgmma_n128(float* d, uint64_t da, uint64_t db, int scale_d) {
    asm volatile("{\n.reg .pred p;\nsetp.ne.b32 p, %66, 0;\n"
        "wgmma.mma_async.sync.aligned.m64n128k16.f32.bf16.bf16 "
        "{%0,%1,%2,%3,%4,%5,%6,%7,%8,%9,%10,%11,%12,%13,%14,%15,%16,%17,%18,%19,%20,%21,%22,%23,%24,%25,%26,%27,%28,%29,%30,%31,"
        "%32,%33,%34,%35,%36,%37,%38,%39,%40,%41,%42,%43,%44,%45,%46,%47,%48,%49,%50,%51,%52,%53,%54,%55,%56,%57,%58,%59,%60,%61,%62,%63}, "
        "%64, %65, p, 1, 1, 0, 1;\n}"
        : "+f"(d[0]), "+f"(d[1]), "+f"(d[2]), "+f"(d[3]), "+f"(d[4]), "+f"(d[5]), "+f"(d[6]), "+f"(d[7]), "+f"(d[8]), "+f"(d[9]), "+f"(d[10]), "+f"(d[11]),
          "+f"(d[12]), "+f"(d[13]), "+f"(d[14]), "+f"(d[15]), "+f"(d[16]), "+f"(d[17]), "+f"(d[18]), "+f"(d[19]), "+f"(d[20]), "+f"(d[21]), "+f"(d[22]), "+f"(d[23]),
          "+f"(d[24]), "+f"(d[25]), "+f"(d[26]), "+f"(d[27]), "+f"(d[28]), "+f"(d[29]), "+f"(d[30]), "+f"(d[31]), "+f"(d[32]), "+f"(d[33]), "+f"(d[34]), "+f"(d[35]),
          "+f"(d[36]), "+f"(d[37]), "+f"(d[38]), "+f"(d[39]), "+f"(d[40]), "+f"(d[41]), "+f"(d[42]), "+f"(d[43]), "+f"(d[44]), "+f"(d[45]), "+f"(d[46]), "+f"(d[47]),
          "+f"(d[48]), "+f"(d[49]), "+f"(d[50]), "+f"(d[51]), "+f"(d[52]), "+f"(d[53]), "+f"(d[54]), "+f"(d[55]), "+f"(d[56]), "+f"(d[57]), "+f"(d[58]), "+f"(d[59]),
          "+f"(d[60]), "+f"(d[61]), "+f"(d[62]), "+f"(d[63])
        : "l"(da), "l"(db), "r"(scale_d));
}

__device__ __forceinline__ constexpr uint32_t slot_off(int slot) {
    return slot < 2 ? G_RING + slot * 16384 : G_BUF + (slot & 1) * 32768 + (slot < 4 ? 16384 : 0);
}
constexpr int PO = (HSPLIT / 2) & 1;
template <int NSLOT, class F>
__device__ __forceinline__ void gemm_tile(float* acc, uint32_t sb, int tile, int it, int wg, bool pass, uint32_t l0, F&& hook) {
    const uint32_t bar = sb + G_BAR;
    bar_sync(3 + wg, 256);
    int prev = 0;
#pragma unroll
    for (int k = 0; k < 4; k++) {
        const int n = tile * 4 + k, slot = NSLOT == 4 ? k : n % NSLOT;
        const uint32_t sz = sb + (((it + k) << 4) & sb & 0x3f0);
        const uint64_t da = desc_sw128(sz + slot_off(slot), 16, 1024), db0 = desc_sw128(sz + G_W, 65536, 1024);
        mbar_wait_p(bar + 8 * (GB_FULL + slot), NSLOT == 4 ? (tile & 1) : ((n / NSLOT) & 1));
        if (k == 3 && pass) bar_arrive(3 + (wg ^ 1), 256);
        asm volatile("wgmma.fence.sync.aligned;" ::: "memory");
#pragma unroll
        for (int kk = 0; kk < 4; kk++) wgmma_n128(acc, da + kk * 2, db0 + k * 1024 + kk * 128, (k | kk) != 0);
        asm volatile("wgmma.commit_group.sync.aligned;" ::: "memory");
        if (k > 0) {
            asm volatile("wgmma.wait_group.sync.aligned 1;" ::: "memory");
            mbar_arrive2_if(bar + 8 * (GB_EMPTY + prev), l0);
        }
#pragma unroll
        for (int kk = 0; kk < 4; kk++) wgmma_n128(acc, da + 512 + kk * 2, db0 + k * 1024 + 512 + kk * 128, 1);
        asm volatile("wgmma.commit_group.sync.aligned;" ::: "memory");
        if (k == 1) hook();
        prev = slot;
    }
    asm volatile("wgmma.wait_group.sync.aligned 0;" ::: "memory");
    mbar_arrive2_if(bar + 8 * (GB_EMPTY + prev), l0);
}
__device__ __forceinline__ void stage_bf16(const float* acc, uint32_t buf, float s0, float s1) {
    const int lane = threadIdx.x & 31, wq = (threadIdx.x >> 5) & 3;
    const int row = wq * 16 + (lane & 7) + ((lane >> 3) & 1) * 8;
    const uint32_t base = buf + row * 128;
#pragma unroll
    for (int j = 0; j < 16; j += 2) {
        const int ch = (j & 7) + (lane >> 4);
        stsm4(base + (j >> 3) * 8192 + ((ch ^ (row & 7)) << 4),
              pack2(acc[4 * j] * s0, acc[4 * j + 1] * s0), pack2(acc[4 * j + 2] * s1, acc[4 * j + 3] * s1),
              pack2(acc[4 * j + 4] * s0, acc[4 * j + 5] * s0), pack2(acc[4 * j + 6] * s1, acc[4 * j + 7] * s1));
    }
}

__device__ __forceinline__ void store_perm(const float* acc, bf16* dst, int ld, float s0, float s1) {
#pragma unroll
    for (int i = 0; i < 4; i++) {
        const float* a = acc + 16 * i;
        *(uint4*)(dst + i * 32) = make_uint4(pack2(a[0] * s0, a[1] * s0), pack2(a[4] * s0, a[5] * s0), pack2(a[8] * s0, a[9] * s0), pack2(a[12] * s0, a[13] * s0));
        *(uint4*)(dst + 8 * ld + i * 32) = make_uint4(pack2(a[2] * s1, a[3] * s1), pack2(a[6] * s1, a[7] * s1), pack2(a[10] * s1, a[11] * s1), pack2(a[14] * s1, a[15] * s1));
    }
}
template <int ACC>
__device__ __forceinline__ void wgmma_rs64(float* d, const uint32_t* a, uint64_t db) {
    asm volatile("{\n.reg .pred p;\nsetp.ne.b32 p, %37, 0;\n"
        "wgmma.mma_async.sync.aligned.m64n64k16.f32.bf16.bf16 {%0,%1,%2,%3,%4,%5,%6,%7,%8,%9,%10,%11,%12,%13,%14,%15,%16,%17,%18,%19,%20,%21,%22,%23,%24,%25,%26,%27,%28,%29,%30,%31}, {%32,%33,%34,%35}, %36, p, 1, 1, 0;\n}"
        : "+f"(d[0]), "+f"(d[1]), "+f"(d[2]), "+f"(d[3]), "+f"(d[4]), "+f"(d[5]), "+f"(d[6]), "+f"(d[7]), "+f"(d[8]), "+f"(d[9]), "+f"(d[10]), "+f"(d[11]), "+f"(d[12]), "+f"(d[13]), "+f"(d[14]), "+f"(d[15]), "+f"(d[16]), "+f"(d[17]), "+f"(d[18]), "+f"(d[19]), "+f"(d[20]), "+f"(d[21]), "+f"(d[22]), "+f"(d[23]), "+f"(d[24]), "+f"(d[25]), "+f"(d[26]), "+f"(d[27]), "+f"(d[28]), "+f"(d[29]), "+f"(d[30]), "+f"(d[31])
        : "r"(a[0]), "r"(a[1]), "r"(a[2]), "r"(a[3]), "l"(db), "n"(ACC));
}
template <int ACC>
__device__ __forceinline__ void wgmma_rs128t(float* d, const uint32_t* a, uint64_t db) {
    asm volatile("{\n.reg .pred p;\nsetp.ne.b32 p, %69, 0;\n"
        "wgmma.mma_async.sync.aligned.m64n128k16.f32.bf16.bf16 {%0,%1,%2,%3,%4,%5,%6,%7,%8,%9,%10,%11,%12,%13,%14,%15,%16,%17,%18,%19,%20,%21,%22,%23,%24,%25,%26,%27,%28,%29,%30,%31,%32,%33,%34,%35,%36,%37,%38,%39,%40,%41,%42,%43,%44,%45,%46,%47,%48,%49,%50,%51,%52,%53,%54,%55,%56,%57,%58,%59,%60,%61,%62,%63}, {%64,%65,%66,%67}, %68, p, 1, 1, 1;\n}"
        : "+f"(d[0]), "+f"(d[1]), "+f"(d[2]), "+f"(d[3]), "+f"(d[4]), "+f"(d[5]), "+f"(d[6]), "+f"(d[7]), "+f"(d[8]), "+f"(d[9]), "+f"(d[10]), "+f"(d[11]), "+f"(d[12]), "+f"(d[13]), "+f"(d[14]), "+f"(d[15]), "+f"(d[16]), "+f"(d[17]), "+f"(d[18]), "+f"(d[19]), "+f"(d[20]), "+f"(d[21]), "+f"(d[22]), "+f"(d[23]), "+f"(d[24]), "+f"(d[25]), "+f"(d[26]), "+f"(d[27]), "+f"(d[28]), "+f"(d[29]), "+f"(d[30]), "+f"(d[31]), "+f"(d[32]), "+f"(d[33]), "+f"(d[34]), "+f"(d[35]), "+f"(d[36]), "+f"(d[37]), "+f"(d[38]), "+f"(d[39]), "+f"(d[40]), "+f"(d[41]), "+f"(d[42]), "+f"(d[43]), "+f"(d[44]), "+f"(d[45]), "+f"(d[46]), "+f"(d[47]), "+f"(d[48]), "+f"(d[49]), "+f"(d[50]), "+f"(d[51]), "+f"(d[52]), "+f"(d[53]), "+f"(d[54]), "+f"(d[55]), "+f"(d[56]), "+f"(d[57]), "+f"(d[58]), "+f"(d[59]), "+f"(d[60]), "+f"(d[61]), "+f"(d[62]), "+f"(d[63])
        : "r"(a[0]), "r"(a[1]), "r"(a[2]), "r"(a[3]), "l"(db), "n"(ACC));
}
__device__ __forceinline__ void attention_tile(float* acc, uint32_t sb, int tile, int h, int wg, int wq, uint32_t l0, uint32_t epoch, uint4* km, uint4* vm) {
    const uint32_t buf = sb + G_BUF + ((tile << 4) & sb & 0x3f0);
    const int lane = threadIdx.x & 31, g = lane >> 2, t = lane & 3;
    const int sg = wq >> 1, hf = wq & 1, seg = tile * 2 + sg;
    uint32_t qf[8][4];
#pragma unroll
    for (int kk = 0; kk < 8; kk++) {
        qf[kk][0] = pack2(acc[8 * kk], acc[8 * kk + 1]); qf[kk][1] = pack2(acc[8 * kk + 2], acc[8 * kk + 3]);
        qf[kk][2] = pack2(acc[8 * kk + 4], acc[8 * kk + 5]); qf[kk][3] = pack2(acc[8 * kk + 6], acc[8 * kk + 7]);
    }
    uint32_t* kvf = &g_KVf[seg][h][lane * 4];
    auto kv_valid = [&]() {
        uint32_t mn = 0xffffffffu;
#pragma unroll
        for (int i = 0; i < 4; i++) mn = min(min(min(mn, min(km[i].x, km[i].y)), min(km[i].z, km[i].w)), min(min(vm[i].x, vm[i].y), min(vm[i].z, vm[i].w)));
        return __all_sync(0xffffffffu, mn != 0);
    };
    float sc[5][4];
    auto mem_scores = [&]() {
        float sb_[4];
#pragma unroll
        for (int i = 0; i < 4; i++) { MMAF(i == 0, sc[4], qf[2 * i], ~km[i].x, ~km[i].y); MMAF(i == 0, sb_, qf[2 * i + 1], ~km[i].z, ~km[i].w); }
#pragma unroll
        for (int i = 0; i < 4; i++) sc[4][i] += sb_[i];
    };
    mbar_wait_p(sb + G_BAR + 8 * (GB_KV + wg), (tile >> 1) & 1);
    if (h == 5 && (threadIdx.x & 127) == 0 && tile < 6) GT(1750 + tile * 8 + 2);
    bool fast;
    {
        const uint64_t dk = desc_sw128(buf, 16, 1024);
        asm volatile("wgmma.fence.sync.aligned;" ::: "memory");
#pragma unroll
        for (int kk = 0; kk < 8; kk++) {
            if (kk == 0) wgmma_rs64<0>(acc, qf[kk], dk); else wgmma_rs64<1>(acc, qf[kk], dk + (kk >> 2) * 512 + (kk & 3) * 2);
        }
        asm volatile("wgmma.commit_group.sync.aligned;" ::: "memory");
        mem_scores();
        fast = kv_valid();
        asm volatile("wgmma.wait_group.sync.aligned 0;" ::: "memory");
        mbar_arrive_if(sb + G_BAR + 8 * GB_KVF, l0);
#pragma unroll
        for (int i = 0; i < 32; i++) asm volatile("" : "+f"(acc[i]) :: "memory");
#pragma unroll
        for (int b = 0; b < 4; b++)
#pragma unroll
            for (int i = 0; i < 4; i++) sc[b][i] = sg ? acc[16 + 4 * b + i] : acc[4 * b + i];
#pragma unroll
        for (int i = 0; i < 4; i++) sc[4][i] = fast ? sc[4][i] : -INFINITY;
    }
    const float cexp = 0.08838834764831845f * 1.4426950408889634f;
    const int r0 = hf * 16 + g, r1 = r0 + 8;
#pragma unroll
    for (int b = 0; b < 4; b++) {
        const int j = b * 8 + 2 * t;
        if (j > r0) sc[b][0] = -INFINITY;
        if (j + 1 > r0) sc[b][1] = -INFINITY;
        if (j > r1) sc[b][2] = -INFINITY;
        if (j + 1 > r1) sc[b][3] = -INFINITY;
    }
    float m0 = -INFINITY, m1 = -INFINITY;
#pragma unroll
    for (int b = 0; b < 5; b++) { m0 = fmaxf(m0, fmaxf(sc[b][0], sc[b][1])); m1 = fmaxf(m1, fmaxf(sc[b][2], sc[b][3])); }
    m0 = fmaxf(m0, __shfl_xor_sync(0xffffffffu, m0, 1)); m1 = fmaxf(m1, __shfl_xor_sync(0xffffffffu, m1, 1));
    m0 = fmaxf(m0, __shfl_xor_sync(0xffffffffu, m0, 2)); m1 = fmaxf(m1, __shfl_xor_sync(0xffffffffu, m1, 2));
    float z0 = 0.f, z1 = 0.f;
    uint32_t p0, p1;
    {
        const float c0 = -m0 * cexp, c1 = -m1 * cexp;
        uint32_t pf[5][2];
#pragma unroll
        for (int b = 0; b < 5; b++) {
            pf[b][0] = pack2(ex2(fmaf(sc[b][0], cexp, c0)), ex2(fmaf(sc[b][1], cexp, c0)));
            pf[b][1] = pack2(ex2(fmaf(sc[b][2], cexp, c1)), ex2(fmaf(sc[b][3], cexp, c1)));
        }
        p0 = pf[4][0]; p1 = pf[4][1];
        uint32_t pa[4][4];
#pragma unroll
        for (int kk = 0; kk < 4; kk++)
#pragma unroll
            for (int i = 0; i < 4; i++) pa[kk][i] = (kk >> 1) == sg ? pf[(kk & 1) * 2 + (i >> 1)][i & 1] : 0u;
        const uint64_t dv = desc_sw128(buf + 32768, 8192, 1024);
        mbar_wait_p(sb + G_BAR + 8 * (GB_VV + wg), (tile >> 1) & 1);
        asm volatile("wgmma.fence.sync.aligned;" ::: "memory");
#pragma unroll
        for (int kk = 0; kk < 4; kk++) { if (kk == 0) wgmma_rs128t<0>(acc, pa[kk], dv); else wgmma_rs128t<1>(acc, pa[kk], dv + kk * 128); }
        asm volatile("wgmma.commit_group.sync.aligned;" ::: "memory");
#pragma unroll
        for (int b = 0; b < 5; b++) { z0 += bf_lo(pf[b][0]) + bf_hi(pf[b][0]); z1 += bf_lo(pf[b][1]) + bf_hi(pf[b][1]); }
        asm volatile("wgmma.wait_group.sync.aligned 0;" ::: "memory");
#pragma unroll
        for (int i = 0; i < 64; i++) asm volatile("" : "+f"(acc[i]) :: "memory");
    }
    mbar_arrive_if(sb + G_BAR + 8 * GB_VF, l0);
    if (h == 5 && (threadIdx.x & 127) == 0 && tile < 6) GT(1750 + tile * 8 + 3);
    if (!fast) {
        wait_rec(&g_f.rec[2 * h], epoch, seg + 1);
        if (seg == 63 && (threadIdx.x & 63) == 0) GT(1570 + h);
        uint32_t n = 0;
#pragma unroll 1
        do {
#pragma unroll
            for (int i = 0; i < 4; i++) { km[i] = ldg_rlx4(kvf + i * 128); vm[i] = ldg_rlx4(kvf + 512 + i * 128); }
            if (++n > SPIN_LIMIT) { ABORT(4); break; }
        } while (!kv_valid());
        mem_scores();
        float n0 = fmaxf(sc[4][0], sc[4][1]), n1 = fmaxf(sc[4][2], sc[4][3]);
        n0 = fmaxf(n0, __shfl_xor_sync(0xffffffffu, n0, 1)); n1 = fmaxf(n1, __shfl_xor_sync(0xffffffffu, n1, 1));
        n0 = fmaxf(n0, __shfl_xor_sync(0xffffffffu, n0, 2)); n1 = fmaxf(n1, __shfl_xor_sync(0xffffffffu, n1, 2));
        n0 = fmaxf(n0, m0); n1 = fmaxf(n1, m1);
        const float a0 = ex2((m0 - n0) * cexp), a1 = ex2((m1 - n1) * cexp);
        const float c0 = -n0 * cexp, c1 = -n1 * cexp;
        p0 = pack2(ex2(fmaf(sc[4][0], cexp, c0)), ex2(fmaf(sc[4][1], cexp, c0)));
        p1 = pack2(ex2(fmaf(sc[4][2], cexp, c1)), ex2(fmaf(sc[4][3], cexp, c1)));
        z0 = fmaf(z0, a0, bf_lo(p0) + bf_hi(p0)); z1 = fmaf(z1, a1, bf_lo(p1) + bf_hi(p1));
#pragma unroll
        for (int j = 0; j < 16; j++) { float* o = acc + 4 * j; o[0] *= a0; o[1] *= a0; o[2] *= a1; o[3] *= a1; }
    }
    if (h == 5 && (threadIdx.x & 127) == 0 && tile < 6) GT(1750 + tile * 8 + 4);
    if (hf) bar_arrive(5 + wg * 2 + sg, 64);
#pragma unroll
    for (int i = 0; i < 4; i++) {
        mma1688(acc + 16 * i, p0, p1, ~vm[i].x); mma1688(acc + 16 * i + 4, p0, p1, ~vm[i].y);
        mma1688(acc + 16 * i + 8, p0, p1, ~vm[i].z); mma1688(acc + 16 * i + 12, p0, p1, ~vm[i].w);
    }
    z0 += __shfl_xor_sync(0xffffffffu, z0, 1); z1 += __shfl_xor_sync(0xffffffffu, z1, 1);
    z0 += __shfl_xor_sync(0xffffffffu, z0, 2); z1 += __shfl_xor_sync(0xffffffffu, z1, 2);
    if (h == 5 && (threadIdx.x & 127) == 0 && tile < 6) GT(1750 + tile * 8 + 5);
    if (tile >= 2) mbar_wait_p(sb + G_BAR + 8 * (GB_FREE + wg), ((tile >> 1) - 1 + PO) & 1);
    store_perm(acc, g_O + (size_t)(tile * 64 + wq * 16 + g) * HD + h * 128 + t * 8, HD, rcpf(z0), rcpf(z1));
    mbar_arrive(sb + G_BAR + 8 * (GB_STG + wg));
    if (!hf) {
        bar_sync(5 + wg * 2 + sg, 64);
#pragma unroll
        for (int i = 0; i < 8; i++) stg4_h(kvf + i * 128, make_uint4(0, 0, 0, 0), pol_ef(3));
    }
}

__device__ __forceinline__ void g_consumer(uint32_t sb_, int g_, int wg_, uint32_t epoch) {
    const uint32_t sb = uni(sb_);
    const int g = uni(g_), wg = uni(wg_), wq = uni((threadIdx.x >> 5) & 3);
    const uint32_t l0 = opaque((threadIdx.x & 31) == 0);
    const uint32_t bar = sb + G_BAR, buf = sb + G_BUF + wg * 32768;
    const int lane = threadIdx.x & 31;
    float acc[64];
    if (wg == 1) bar_arrive(3, 256);
    const int n1 = g < 32 ? HSPLIT / 2 : NT - HSPLIT / 2;
#pragma unroll 1
    for (int i = 0; i < n1; i++) {
        gemm_tile<4>(acc, sb, wg, i, wg, true, l0, []() {});
        if (threadIdx.x == 0 && i == 0) GT((64 + g) * 8 + 1);
        if (threadIdx.x == 128 && i == 3) GT((64 + g) * 8 + 2);
        if (i > 0) mbar_wait_p(bar + 8 * (GB_FREE + wg), (i - 1) & 1);
        stage_bf16(acc, buf, 1.f, 1.f);
        asm volatile("fence.proxy.async.shared::cta;" ::: "memory");
        mbar_arrive(bar + 8 * (GB_STG + wg));
    }
    if (threadIdx.x == 128) GT((64 + g) * 8 + 3);
    if (g < 32) {
#pragma unroll 1
        for (int i = 0; i < NT / 2; i++) {
            const int tile = 2 * i + wg;
            const uint2 rec = ldg_rlx2(&g_f.rec[2 * g]);
            uint4 km[4], vm[4];
            gemm_tile<4>(acc, sb, tile, i, wg, tile != NT - 1, l0, [&]() {
                const uint32_t seg = tile * 2 + (wq >> 1);
                const uint32_t* kvf = &g_KVf[seg][g][lane * 4];
                const bool early = (rec.x >> 8) == epoch && (rec.y >> 8) == epoch && (rec.x & 255) > seg && (rec.y & 255) > seg;
#pragma unroll
                for (int j = 0; j < 4; j++) { km[j] = ldg_rlx4_if(kvf + j * 128, early); vm[j] = ldg_rlx4_if(kvf + 512 + j * 128, early); }
            });
            if (threadIdx.x == 0 && i == 0) GT((64 + g) * 8 + 4);
            if (threadIdx.x == 128 && i == 3) GT((64 + g) * 8 + 5);
            if (g == 5 && (threadIdx.x & 127) == 0 && tile < 6) GT(1750 + tile * 8 + 1);
            attention_tile(acc, sb, tile, g, wg, wq, l0, epoch, km, vm);
            if (g == 5 && (threadIdx.x & 127) == 0 && tile < 6) GT(1750 + tile * 8 + 6);
        }
    } else {
#pragma unroll 1
        for (int i = 0; i < NT / 2; i++) {
            const int tile = 2 * i + wg;
            gemm_tile<NS3>(acc, sb, tile, i, wg, tile != NT - 1, l0, []() {});
            if (threadIdx.x == 0 && i == 0) GT((64 + g) * 8 + 4);
            if (threadIdx.x == 128 && i == 3) GT((64 + g) * 8 + 5);
            mbar_wait_p(bar + 8 * (GB_FREE + wg), (i - 1 + PO) & 1);
            store_perm(acc, g_P + (size_t)(((g - 32) >> 2) * SQ + tile * 64 + wq * 16 + (lane >> 2)) * DM + ((g - 32) & 3) * 128 + (lane & 3) * 8, DM, 1.f, 1.f);
            mbar_arrive(bar + 8 * (GB_STG + wg));
        }
    }
}

__device__ __forceinline__ void load_w(uint32_t sb, const CUtensorMap* tm, int col, int k) {
    tma2d_h(sb + G_W + k * 16384, tm, col, k * 128, sb + G_BAR + 8 * (GB_FULL + k), pol_ef(5));
    tma2d_h(sb + G_W + 65536 + k * 16384, tm, col + 64, k * 128, sb + G_BAR + 8 * (GB_FULL + k), pol_ef(5));
}

__device__ __forceinline__ void rbf2(float& a, float& b) { uint32_t w = pack2(a, b); a = bf_lo(w); b = bf_hi(w); }
__device__ __forceinline__ void warp_sum2(float& a, float& b) {
#pragma unroll
    for (int o = 16; o; o >>= 1) { float c = __shfl_xor_sync(0xffffffffu, a, o), d = __shfl_xor_sync(0xffffffffu, b, o); a += c; b += d; }
}
__device__ __forceinline__ float sum16(const float* v) {
    return (((v[0] + v[1]) + (v[2] + v[3])) + ((v[4] + v[5]) + (v[6] + v[7]))) + (((v[8] + v[9]) + (v[10] + v[11])) + ((v[12] + v[13]) + (v[14] + v[15])));
}
__device__ __forceinline__ void ln_row2(float* v, float* u) {
    float sv = sum16(v), su = sum16(u);
    warp_sum2(sv, su);
    const float mv = sv * (1.f / DM), mu = su * (1.f / DM);
    float qv = 0.f, qu = 0.f, qv2 = 0.f, qu2 = 0.f;
#pragma unroll
    for (int i = 0; i < 16; i += 2) {
        float d0 = v[i] - mv, d1 = v[i + 1] - mv, e0 = u[i] - mu, e1 = u[i + 1] - mu;
        qv = fmaf(d0, d0, qv); qv2 = fmaf(d1, d1, qv2); qu = fmaf(e0, e0, qu); qu2 = fmaf(e1, e1, qu2);
    }
    qv += qv2; qu += qu2;
    warp_sum2(qv, qu);
    const float rv = rbf(mv), ru = rbf(mu);
    const float iv = __frcp_rn(rbf(sqrtf(rbf(rbf(qv * (1.f / DM)) + 1e-5f)))), iu = __frcp_rn(rbf(sqrtf(rbf(rbf(qu * (1.f / DM)) + 1e-5f))));
#pragma unroll
    for (int i = 0; i < 16; i += 2) {
        float a = v[i] - rv, b = v[i + 1] - rv, c = u[i] - ru, d = u[i + 1] - ru;
        rbf2(a, b); rbf2(c, d);
        a *= iv; b *= iv; c *= iu; d *= iu;
        rbf2(a, b); rbf2(c, d);
        v[i] = a; v[i + 1] = b; u[i] = c; u[i + 1] = d;
    }
}

__device__ __forceinline__ void ln_row1(float* v) {
    float sv = sum16(v);
#pragma unroll
    for (int o = 16; o; o >>= 1) sv += __shfl_xor_sync(0xffffffffu, sv, o);
    const float mv = sv * (1.f / DM);
    float qv = 0.f, qv2 = 0.f;
#pragma unroll
    for (int i = 0; i < 16; i += 2) { float d0 = v[i] - mv, d1 = v[i + 1] - mv; qv = fmaf(d0, d0, qv); qv2 = fmaf(d1, d1, qv2); }
    qv += qv2;
#pragma unroll
    for (int o = 16; o; o >>= 1) qv += __shfl_xor_sync(0xffffffffu, qv, o);
    const float rv = rbf(mv);
    float sq, iv;
    asm("sqrt.approx.f32 %0, %1;" : "=f"(sq) : "f"(rbf(rbf(qv * (1.f / DM)) + 1e-5f)));
    asm("rcp.approx.f32 %0, %1;" : "=f"(iv) : "f"(rbf(sq)));
#pragma unroll
    for (int i = 0; i < 16; i += 2) {
        float a = v[i] - rv, b = v[i + 1] - rv;
        rbf2(a, b);
        a *= iv; b *= iv;
        rbf2(a, b);
        v[i] = a; v[i + 1] = b;
    }
}
constexpr int FSPLIT = 28;
__device__ __forceinline__ int fin_row(int id, int i) {
    if (id < 64) { const int tile = i < FSPLIT / 2 ? 2 * i : i + FSPLIT / 2; return tile < NT ? tile * 64 + id : -1; }
    const int j = id - 64 + i * 48;
    return j < FSPLIT * 32 ? (j >> 6) * 128 + 64 + (j & 63) : -1;
}
__device__ __forceinline__ void finalizer(int id, const bf16* __restrict__ x, const bf16* __restrict__ wr, bf16* __restrict__ out, uint32_t epoch) {
    const int lane = threadIdx.x & 31;
    float b0 = -INFINITY, b1 = -INFINITY; int i0 = 0x7fffffff, i1 = 0x7fffffff;
    const uint32_t tag = (epoch & 0xfffffu) << 12;
    uint32_t fl = ~epoch;
    int row = fin_row(id, 0);
    const uint4 ra = *(const uint4*)(wr + lane * 8), rb = *(const uint4*)(wr + 256 + lane * 8);
    uint4 xa = *(const uint4*)(x + (size_t)row * DM + lane * 8), xb = *(const uint4*)(x + (size_t)row * DM + lane * 8 + 256);
#pragma unroll 1
    for (int it = 0; row >= 0; it++) {
        const int tile = row >> 6, nxt = fin_row(id, it + 1);
        const size_t o0 = (size_t)row * DM + lane * 8;
        uint32_t n = 0;
#pragma unroll 1
        while (!__all_sync(0xffffffffu, fl == epoch)) {
            if (n) __nanosleep(it ? 64 : 1000);
            fl = ldg_rlx(&g_f.p[tile][lane]);
            if (++n > SPIN_LIMIT) { ABORT(12); break; }
        }
        if (tile == NT - 1 && id == 63 && lane == 0) GT(1438);
        if ((id == 63 || id == 3 || id == 70) && lane == 0) GT(1800 + (id == 3) * 32 + tile);
        float v[16];
        {
            uint4 pa[8][2];
#pragma unroll
            for (int k = 0; k < 8; k++) {
                pa[k][0] = ldg4_h(g_P + (size_t)k * SQ * DM + o0, pol_ef(2));
                pa[k][1] = ldg4_h(g_P + (size_t)k * SQ * DM + o0 + 256, pol_ef(2));
            }
            fl = ldg_rlx(&g_f.p[max(nxt, 0) >> 6][lane]);
#pragma unroll
            for (int j = 0; j < 2; j++) {
#pragma unroll
                for (int i = 0; i < 4; i++) {
                    uint32_t w[8];
#pragma unroll
                    for (int k = 0; k < 8; k++) w[k] = i == 0 ? pa[k][j].x : (i == 1 ? pa[k][j].y : (i == 2 ? pa[k][j].z : pa[k][j].w));
                    v[j * 8 + 2 * i] = ((bf_lo(w[0]) + bf_lo(w[1])) + (bf_lo(w[2]) + bf_lo(w[3]))) + ((bf_lo(w[4]) + bf_lo(w[5])) + (bf_lo(w[6]) + bf_lo(w[7])));
                    v[j * 8 + 2 * i + 1] = ((bf_hi(w[0]) + bf_hi(w[1])) + (bf_hi(w[2]) + bf_hi(w[3]))) + ((bf_hi(w[4]) + bf_hi(w[5])) + (bf_hi(w[6]) + bf_hi(w[7])));
                }
            }
        }
        uint32_t hw[8];
        {
            const uint32_t xw[8] = {xa.x, xa.y, xa.z, xa.w, xb.x, xb.y, xb.z, xb.w};
            uint32_t aw[8];
#pragma unroll
            for (int i = 0; i < 8; i++) aw[i] = pack2(v[2 * i], v[2 * i + 1]);
#pragma unroll
            for (int d = 1; d <= 2; d++) {
                const bool up = lane & d;
#pragma unroll
                for (int i = 0; i < 8; i++) {
                    if (!(i & d)) {
                        const uint32_t r = __shfl_xor_sync(0xffffffffu, up ? aw[i] : aw[i | d], d);
                        if (up) aw[i] = r; else aw[i | d] = r;
                    }
                }
            }
#pragma unroll
            for (int i = 0; i < 8; i++) {
                hw[i] = pack2(bf_lo(aw[i]) + bf_lo(xw[i]), bf_hi(aw[i]) + bf_hi(xw[i]));
                v[2 * i] = bf_lo(hw[i]); v[2 * i + 1] = bf_hi(hw[i]);
            }
        }
        xa = *(const uint4*)(x + (size_t)max(nxt, 0) * DM + lane * 8); xb = *(const uint4*)(x + (size_t)max(nxt, 0) * DM + lane * 8 + 256);
        ln_row1(v);
        float r0 = 0.f, r1 = 0.f;
        {
            const uint32_t ww[8] = {ra.x, ra.y, ra.z, ra.w, rb.x, rb.y, rb.z, rb.w};
#pragma unroll
            for (int i = 0; i < 8; i++) { r0 = fmaf(v[2 * i], bf_lo(ww[i]), r0); r1 = fmaf(v[2 * i + 1], bf_hi(ww[i]), r1); }
        }
        r0 += r1;
#pragma unroll
        for (int o = 16; o; o >>= 1) r0 += __shfl_xor_sync(0xffffffffu, r0, o);
        r0 = rbf(r0);
        if (cand_better(r0, row, b0, i0)) { b1 = b0; i1 = i0; b0 = r0; i0 = row; }
        else if (cand_better(r0, row, b1, i1)) { b1 = r0; i1 = row; }
        if (tile == NT - 1 && id == 63 && lane == 0) GT(1439);
        const bool last = nxt < 0, spec = tile < SPEC_TILES && (last || (nxt >> 6) >= SPEC_TILES);
        const bool pub = (lane == 0 && spec) || (lane == 1 && last);
        if (pub)
            asm volatile("st.relaxed.gpu.global.v4.b32 [%0], {%1,%2,%3,%4};" :: "l"(&g_f.cand[lane][id]),
                         "r"(FU(b0)), "r"(tag | (uint32_t)min(i0, 4095)), "r"(FU(b1)), "r"(tag | (uint32_t)min(i1, 4095)) : "memory");
#pragma unroll
        for (int j = 0; j < 2; j++) {
            const uint32_t* hh = hw + j * 4; const float* nn = v + j * 8;
            stg4_h(out + o0 + j * 256, make_uint4(pack2(bf_lo(hh[0]) + nn[0], bf_hi(hh[0]) + nn[1]), pack2(bf_lo(hh[1]) + nn[2], bf_hi(hh[1]) + nn[3]),
                                                  pack2(bf_lo(hh[2]) + nn[4], bf_hi(hh[2]) + nn[5]), pack2(bf_lo(hh[3]) + nn[6], bf_hi(hh[3]) + nn[7])), pol_ef(4));
            if (i0 == row || i1 == row || i1 >= SQ || row == SQ - 1) {
                *(uint4*)(g_h + o0 + j * 256) = make_uint4(hh[0], hh[1], hh[2], hh[3]);
                *(uint4*)(g_hn + o0 + j * 256) = make_uint4(pack2(nn[0], nn[1]), pack2(nn[2], nn[3]), pack2(nn[4], nn[5]), pack2(nn[6], nn[7]));
            }
        }
        if (last || spec) {
            __threadfence();
            __syncwarp();
            if (pub) stg_rlx(&g_f.rows[lane][id], epoch);
        }
        row = nxt;
    }
    if (id == 0 && lane == 0) { g_epoch = epoch; if (epoch == 0xffffffu) { g_ticket[0] = 0; g_ticket[32] = 0; } }
}

__device__ __forceinline__ void g_producer(uint32_t sb, int g, const Maps& maps, uint32_t epoch, const bf16* __restrict__ x, const bf16* __restrict__ wr, bf16* __restrict__ out) {
    const uint32_t bar = sb + G_BAR;
    const int warp = (threadIdx.x >> 5) - 8;
    if (threadIdx.x == 256 && g == 5) GT(1410);
    if (threadIdx.x == 256 && g == 5) GT(1411);
    if (warp == 3) {
        wait_eq4(&g_f.xn[(threadIdx.x & 31) * 4], epoch, 13);
        __syncwarp();
        if ((threadIdx.x & 31) == 0) mbar_arrive(bar + 8 * GB_XN);
        finalizer(g, x, wr, out, epoch);
        if (g == 63 && (threadIdx.x & 31) == 0) GT(128 * 8 + 6);
    }
    if ((threadIdx.x & 31) != 0) return;
    if (threadIdx.x == 256 && g == 5) GT(1412);
    if (warp == 0) {
        wait_eq4(&g_f.xn[0], epoch, 13);
        const int rk = g & 1;
        const int m1 = g < 32 ? HSPLIT : 2 * NT - HSPLIT;
        const int mx = g < 32 ? m1 + NT : m1;
#pragma unroll 1
        for (int it = 0; it < mx; it++) {
            const int tile = g < 32 ? (it < m1 ? it : it - m1) : (it < NT ? it : it - NT + HSPLIT);
            if (it == 1) wait_eq4(&g_f.xn[4], epoch, 13);
            if (it == 2) mbar_wait(bar + 8 * GB_XN, 0);
            const bool nw = it == 0 || it == (g < 32 ? m1 : NT);
#pragma unroll
            for (int k = 0; k < 4; k++) {
                mbar_wait(bar + 8 * (GB_EMPTY + k), (it & 1) ^ 1);
                mbar_expect_tx(bar + 8 * (GB_FULL + k), nw ? 49152 : 16384);
                tma2d_mc(sb + slot_off(k) + rk * 8192, &maps.xn2, (k * 2 + rk) * 64, tile * 64, bar + 8 * (GB_FULL + k));
                if (nw && (it > 0 || k >= 2))
                    load_w(sb, it > 0 && g < 32 ? &maps.wq4 : ((g & 1) ? &maps.wv4 : &maps.wk4), it == 0 ? (g >> 1) * 128 : (g < 32 ? g * 128 : ((g - 32) >> 1) * 128), k);
            }
        }
        if (g >= 32) {
            const int u = g - 32, ks = u >> 2, ns = u & 3;
            int slot = 0, ph = 1;
#pragma unroll 1
            for (int tile = 0; tile < NT; tile++) {
                if (tile > 0) wait_eq4(&g_f.o[tile][ks][0], epoch, 9);
                if (g == 40 && tile == NT - 1) GT(1437);
                if (tile == NT - 1) GT(1690 + g - 32);
#pragma unroll 1
                for (int k = 0; k < 4; k++) {
                    mbar_wait(bar + 8 * (GB_EMPTY + slot), slot < 4 ? ph : ph ^ 1);
                    mbar_expect_tx(bar + 8 * (GB_FULL + slot), tile == 0 ? 49152 : 16384);
                    if (tile == 0) {
#pragma unroll
                        for (int nh = 0; nh < 2; nh++)
                            asm volatile("cp.async.bulk.tensor.5d.shared::cluster.global.mbarrier::complete_tx::bytes [%0], [%1, {%3, %4, %4, %4, %5}], [%2];"
                                :: "r"(sb + G_W + nh * 65536 + k * 16384), "l"((uint64_t)&maps.wo2), "r"(bar + 8 * (GB_FULL + k)), "r"(ns * 128 + nh * 64), "r"(0), "r"(ks * 16 + k * 4) : "memory");
                        if (k == 0) wait_eq4(&g_f.o[0][ks][0], epoch, 9);
                    }
                    tma2d_mc_h(sb + slot_off(slot) + rk * 8192, &maps.ox2, (ks * 8 + k * 2 + rk) * 64, tile * 64, bar + 8 * (GB_FULL + slot), pol_ef(1));
                    if (++slot == NS3) { slot = 0; ph ^= 1; }
                }
            }
        }
    } else if (warp < 3) {
        const int wg = warp - 1;
        const uint32_t buf = sb + G_BUF + wg * 32768;
        const CUtensorMap* tkv = (g & 1) ? &maps.vx3 : &maps.kx3;
        const int n1 = g < 32 ? HSPLIT / 2 : NT - HSPLIT / 2;
#pragma unroll 1
        for (int i = 0; i < n1; i++) {
            const int tile = (i < NT / 2 ? 2 * i : 2 * i - NT + HSPLIT) + wg, hd = (i < NT / 2 ? g : g - 32) >> 1;
            mbar_wait(bar + 8 * (GB_STG + wg), i & 1);
            tma_store3d(tkv, buf, tile * 64, hd * 2);
            asm volatile("cp.async.bulk.commit_group;" ::: "memory");
            asm volatile("cp.async.bulk.wait_group.read 0;" ::: "memory");
            mbar_arrive(bar + 8 * (GB_FREE + wg));
            asm volatile("cp.async.bulk.wait_group 0;" ::: "memory");
            PUBLISH(&g_f.kv[tile][hd][g & 1], epoch);
        }
        if (wg == 0) mbar_arrive(bar + 8 * GB_T1D);
        if (g >= 32) for (int i = 0; i < 4; i++) mbar_arrive2_if(bar + 8 * (GB_EMPTY + 4 + wg), 1);
        if (g < 32 && wg == 1) {
            mbar_wait(bar + 8 * GB_T1D, 0);
#pragma unroll 1
            for (int tile = 0; tile < NT; tile++) {
                wait_eq2(&g_f.kv[tile][g][0], epoch, 10);
                if (tile > 0) mbar_wait(bar + 8 * GB_KVF, (tile - 1) & 1);
                mbar_expect_tx(bar + 8 * (GB_KV + (tile & 1)), 16384);
                tma3d_h(sb + G_BUF, &maps.kx3, tile * 64, g * 2, bar + 8 * (GB_KV + (tile & 1)), pol_ef(0));
                if (tile > 0) mbar_wait(bar + 8 * GB_VF, (tile - 1) & 1);
                mbar_expect_tx(bar + 8 * (GB_VV + (tile & 1)), 16384);
                tma3d_h(sb + G_BUF + 32768, &maps.vx3, tile * 64, g * 2, bar + 8 * (GB_VV + (tile & 1)), pol_ef(0));
                if (PFK && tile + PFK < NT) {
                    const uint2 v = ldg_rlx2(&g_f.kv[tile + PFK][g][0]);
                    if (v.x == epoch && v.y == epoch) { tma_pf3d(&maps.kx3, (tile + PFK) * 64, g * 2); tma_pf3d(&maps.vx3, (tile + PFK) * 64, g * 2); }
                }
            }
        } else {
#pragma unroll 1
            for (int tile = g < 32 ? 0 : wg; tile < NT; tile += g < 32 ? 1 : 2) {
                mbar_wait(bar + 8 * (GB_STG + (tile & 1)), ((tile >> 1) + PO) & 1);
                mbar_arrive(bar + 8 * (GB_FREE + (tile & 1)));
                PUBLISH(g < 32 ? &g_f.o[tile][g >> 2][g & 3] : &g_f.p[tile][g - 32], epoch);
                if (g == 3 && tile == NT - 1) GT(1436);
                if (g == 3) GT(1896 + tile);
                if (g < 32 && tile == NT - 1) GT(1610 + g);
                if (g == 40 && tile == NT - 1) GT(1435);
                if (g == 40) GT(1864 + tile);
                if (g >= 32 && tile == NT - 1) GT(1650 + g - 32);
            }
        }
    }
}

struct WPtr { const bf16 *q, *k, *v, *o, *g, *u; };
__device__ __forceinline__ int startup(uint8_t* smem, const bf16* __restrict__ x, const Maps& maps, uint32_t& epoch, const WPtr& pw) {
    const int tid = threadIdx.x, lane = tid & 31, w = tid >> 5, cta = blockIdx.x;
    volatile uint32_t* sh = (volatile uint32_t*)(smem + SH_OFF);
    if (cta == 4 && tid == 0) GT(1399);
    epoch = (ldg_rlx(&g_epoch) + 1) & 0x00ffffffu;
    if (w < 4) {
        if (!(cta & 1)) {
            uint32_t* pp = (uint32_t*)(xpage() + ((XR3 ^ 0x3000u) ^ ((w == 1 || w == 2) ? 0x1000u : 0u) ^ ((w & 2) << 13))) + (cta >> 1) * 8;
            if (lane < 8) stg_rlx(pp + lane, 0u);
            __syncwarp();
            if (lane == 0) {
                uint32_t best = 0xffffffffu, a = 0;
#pragma unroll 1
                for (int r = 0; r < NPROBE; r++) {
                    uint32_t t0 = clk32();
                    asm volatile("atom.relaxed.gpu.global.add.u32 %0, [%1], %2;" : "=r"(a) : "l"(pp), "r"(a + 1) : "memory");
                    if (a == 0x7fffffffu) ABORT(15);
                    uint32_t t1 = clk32();
                    if (r > 0) best = min(best, t1 - t0);
                    else if (w == 0) {
                        asm volatile("red.relaxed.gpu.global.max.u32 [%0], %1;" :: "l"(&g_ticket[0]), "r"(epoch << 8) : "memory");
                        asm volatile("red.relaxed.gpu.global.max.u32 [%0], %1;" :: "l"(&g_ticket[32]), "r"(epoch << 8) : "memory");
                    }
                }
                sh[w] = best;
            }
        }
        if (!(cta & 1)) bar_sync(1, 128);
        if (cta == 4 && tid == 0) GT(1400);
        if (w == 0) {
            if (lane == 0) {
                uint32_t rp;
                if (!(cta & 1)) {
                    uint32_t a = sh[0], b = sh[1], c = sh[2], d = sh[3];
                    uint32_t mid = (min(min(a, b), min(c, d)) + max(max(a, b), max(c, d))) >> 1;
                    const int dd = (int)min(a, d) - (int)min(b, c);
                    uint32_t cls = abs(dd) > 60 ? dd > 0 : a > mid;
                    uint32_t t = atomicAdd(&g_ticket[cls * 32], 1u) & 255;
                    if (t >= (cls ? 34u : 32u)) { cls ^= 1; t = atomicAdd(&g_ticket[cls * 32], 1u) & 255; }
                    rp = min(cls ? 32 + t : t, 65u);
                    stg_rlx(&g_table[(cta >> 1) * 8], (epoch << 8) | rp);
                } else {
                    uint32_t v, n = 0;
#pragma unroll 1
                    while (((v = ldg_rlx(&g_table[(cta >> 1) * 8])) >> 8) != epoch) { if (++n > SPIN_LIMIT) { ABORT(14); break; } }
                    rp = v & 255;
                }
                const int role = rp * 2 + (cta & 1);
                sh[8] = role; sh[9] = epoch;
                while (sh[10] != epoch + 1 && cta < NWAITLN) {}
                if (role < 64) rec_first_loads(smem_u32(smem), role, maps);
                else if (role < 128) for (int k = 0; k < 2; k++) load_w(smem_u32(smem), (role & 1) ? &maps.wv4 : &maps.wk4, ((role - 64) >> 1) * 128, k);
                if (cta == 4) GT(1401);
            }
        }
    } else if (cta < 128) {
        uint4 u[2][2];
        const int row0 = cta * 16 + (w - 4) * 2;
#pragma unroll
        for (int r = 0; r < 2; r++)
#pragma unroll
            for (int j = 0; j < 2; j++) u[r][j] = *(const uint4*)(x + (size_t)(row0 + r) * DM + j * 256 + lane * 8);
        if (cta < 48) {
            const uint32_t b = cta >> 3, off = (b >= 4 ? 0x8000u + (b & 1) * 0x4000u : ((b & 1) ? 0x3000u : 0u) + ((b & 2) << 13)) ^ aslot(cta & 7);
            *(uint4*)(xpage() + off + (tid - 128) * 16) = make_uint4(0, 0, 0, 0);
        }
        float v[2][16];
#pragma unroll
        for (int r = 0; r < 2; r++)
#pragma unroll
            for (int j = 0; j < 2; j++) {
                uint32_t ww[4] = {u[r][j].x, u[r][j].y, u[r][j].z, u[r][j].w};
#pragma unroll
                for (int i = 0; i < 4; i++) { v[r][j * 8 + 2 * i] = bf_lo(ww[i]); v[r][j * 8 + 2 * i + 1] = bf_hi(ww[i]); }
            }
        ln_row2(v[0], v[1]);
#pragma unroll
        for (int r = 0; r < 2; r++)
#pragma unroll
            for (int j = 0; j < 2; j++)
                *(uint4*)(g_xn + (size_t)(row0 + r) * DM + j * 256 + lane * 8) =
                    make_uint4(pack2(v[r][j * 8], v[r][j * 8 + 1]), pack2(v[r][j * 8 + 2], v[r][j * 8 + 3]), pack2(v[r][j * 8 + 4], v[r][j * 8 + 5]), pack2(v[r][j * 8 + 6], v[r][j * 8 + 7]));
        bar_sync(2, 256);
        if (tid == 160 && cta < NWAITLN) { st_rel(&g_f.xn[cta], epoch); sh[10] = epoch + 1; }
        if (cta == 4 && tid == 160) GT(1403);
        __syncwarp();
    }
    if (cta == 4 && tid == 128) GT(1402);
    __syncthreads();
    if (tid == 160 && cta >= NWAITLN && cta < 128) st_rel(&g_f.xn[cta], epoch);
    __syncwarp();
    const int role = sh[8];
    return role;
}

__global__ void __cluster_dims__(2, 1, 1) __launch_bounds__(384, 1)
main_kernel(const __grid_constant__ Maps maps, const bf16* __restrict__ x, const bf16* __restrict__ mem0, const bf16* __restrict__ wr,
            const bf16* __restrict__ wd, bf16* __restrict__ out, const WPtr pw) {
    extern __shared__ __align__(1024) uint8_t smem[];
    const uint32_t sb = smem_u32(smem);
    if (threadIdx.x == 0) {
        for (int i = 0; i < MB_N; i++) mbar_init(sb + R_BAR + 8 * i, i == MB_V ? 4 : 1);
        for (int i = 0; i < GB_N; i++)
            mbar_init(sb + G_BAR + 8 * i, i >= GB_EMPTY && i < GB_KV ? 8 : (i >= GB_KVF ? 4 : (i >= GB_STG && i < GB_FREE ? 128 : 1)));
        asm volatile("fence.mbarrier_init.release.cluster;" ::: "memory");
    }
    __syncwarp();
    asm volatile("barrier.cluster.arrive.relaxed.aligned;" ::: "memory");
    if (threadIdx.x >= 352 && threadIdx.x < 352 + (int)(sizeof(Maps) / sizeof(CUtensorMap)))
        asm volatile("prefetch.tensormap [%0];" :: "l"((const CUtensorMap*)&maps + (threadIdx.x - 352)) : "memory");
    uint32_t epoch;
    asm volatile("fence.proxy.async.shared::cta;" ::: "memory");
    const int role = uni(startup(smem, x, maps, epoch, pw));
    asm volatile("barrier.cluster.wait.aligned;" ::: "memory");
    const int wg = uni(threadIdx.x >> 7);
    if (role < 64) {
#define SETREG(n) do { if ((n) < 168) asm volatile("setmaxnreg.dec.sync.aligned.u32 %0;" :: "n"(n)); if ((n) > 168) asm volatile("setmaxnreg.inc.sync.aligned.u32 %0;" :: "n"(n)); } while (0)
#define RESREG(n) do { if ((n) < 168) asm volatile("setmaxnreg.inc.sync.aligned.u32 168;"); if ((n) > 168) asm volatile("setmaxnreg.dec.sync.aligned.u32 168;"); } while (0)
        if (wg == WGA) {
            SETREG(RGA);
            rec_a(sb, role, mem0, epoch);
            RESREG(RGA);
        } else if (wg == WGB) {
            SETREG(RGB);
            rec_b(sb, role, epoch);
            RESREG(RGB);
        } else {
            SETREG(RGC);
            rec_c(sb, role, mem0, maps, epoch);
            RESREG(RGC);
        }
        ffn_phase(maps, out);
        if (threadIdx.x == 0) GT(((volatile int*)(smem + SH_OFF))[8] * 8 + 6);
    } else if (role < 128) {
        if (wg < 2) {
            asm volatile("setmaxnreg.inc.sync.aligned.u32 192;");
            g_consumer(sb, role - 64, wg, epoch);
            if (threadIdx.x == 128) GT(role * 8 + 6);
        } else {
            asm volatile("setmaxnreg.dec.sync.aligned.u32 120;");
            g_producer(sb, role - 64, maps, epoch, x, wr, out);
        }
    } else {
        const int id = (threadIdx.x >> 5) * 4 + role - 128;
        finalizer(64 + id, x, wr, out, epoch);
        if (PFF && id < 42 && (threadIdx.x & 31) < 8) {
            const int j = id * 8 + (threadIdx.x & 31);
            const bf16* w = j < 112 ? pw.g : (j < 224 ? pw.u : wd);
            asm volatile("cp.async.bulk.prefetch.L2.global [%0], %1;" :: "l"(w + (size_t)(j % 112) * 8192), "r"(16384) : "memory");
        }
    }
}

typedef CUresult (*EncodeFn)(CUtensorMap*, CUtensorMapDataType, cuuint32_t, void*, const cuuint64_t*, const cuuint64_t*, const cuuint32_t*, const cuuint32_t*,
                             CUtensorMapInterleave, CUtensorMapSwizzle, CUtensorMapL2promotion, CUtensorMapFloatOOBfill);
static void make_map3(EncodeFn fn, CUtensorMap* m, const void* ptr, uint64_t cols, uint64_t rows) {
    cuuint64_t dims[3] = {64, rows, cols / 64};
    cuuint64_t strides[2] = {cols * 2, 128};
    cuuint32_t box[3] = {64, 64, 2};
    cuuint32_t es[3] = {1, 1, 1};
    fn(m, CU_TENSOR_MAP_DATA_TYPE_BFLOAT16, 3, (void*)ptr, dims, strides, box, es, CU_TENSOR_MAP_INTERLEAVE_NONE, CU_TENSOR_MAP_SWIZZLE_128B,
       CU_TENSOR_MAP_L2_PROMOTION_L2_256B, CU_TENSOR_MAP_FLOAT_OOB_FILL_NONE);
}
static void make_map(EncodeFn fn, CUtensorMap* m, const void* ptr, uint64_t cols, uint64_t rows, uint32_t bcols, uint32_t brows,
                     bool f32 = false, CUtensorMapSwizzle sw = CU_TENSOR_MAP_SWIZZLE_128B) {
    cuuint64_t dims[2] = {cols, rows};
    cuuint64_t strides[1] = {cols * (f32 ? 4 : 2)};
    cuuint32_t box[2] = {bcols, brows};
    cuuint32_t es[2] = {1, 1};
    fn(m, f32 ? CU_TENSOR_MAP_DATA_TYPE_FLOAT32 : CU_TENSOR_MAP_DATA_TYPE_BFLOAT16, 2, (void*)ptr, dims, strides, box, es, CU_TENSOR_MAP_INTERLEAVE_NONE, sw,
       CU_TENSOR_MAP_L2_PROMOTION_L2_256B, CU_TENSOR_MAP_FLOAT_OOB_FILL_NONE);
}

extern "C" void kernel_launch(void* const* d_in, const int* in_sizes, int n_in, void* d_out, int out_size) {
    const bf16* x = (const bf16*)d_in[0];
    const bf16* mem0 = (const bf16*)d_in[1];
    const bf16* Wq = (const bf16*)d_in[2];
    const bf16* Wk = (const bf16*)d_in[3];
    const bf16* Wv = (const bf16*)d_in[4];
    const bf16* Wo = (const bf16*)d_in[5];
    const bf16* wr = (const bf16*)d_in[8];
    const bf16* wg = (const bf16*)d_in[9];
    const bf16* wu = (const bf16*)d_in[10];
    const bf16* wd = (const bf16*)d_in[11];
    bf16* out = (bf16*)d_out;

    static EncodeFn enc = nullptr;
    static void *pxn, *pK, *pV, *pO, *pacc;
    if (!enc) {
        cudaDriverEntryPointQueryResult qr;
        void* fn = nullptr;
        cudaGetDriverEntryPoint("cuTensorMapEncodeTiled", &fn, cudaEnableDefault, &qr);
        enc = (EncodeFn)fn;
        cudaGetSymbolAddress(&pxn, g_xn); cudaGetSymbolAddress(&pK, g_K); cudaGetSymbolAddress(&pV, g_V);
        cudaGetSymbolAddress(&pO, g_O); cudaGetSymbolAddress(&pacc, g_P);
        cudaFuncSetAttribute(main_kernel, cudaFuncAttributeMaxDynamicSharedMemorySize, SMEM_TOTAL);
    }
    Maps m;
    make_map(enc, &m.wq, Wq, HD, DM, 64, 256);
    make_map(enc, &m.wk, Wk, HD, DM, 64, 256);
    make_map(enc, &m.wv, Wv, HD, DM, 64, 256);
    make_map(enc, &m.wq4, Wq, HD, DM, 64, 128); make_map(enc, &m.wk4, Wk, HD, DM, 64, 128); make_map(enc, &m.wv4, Wv, HD, DM, 64, 128);
    make_map(enc, &m.wo, Wo, DM, HD, 64, 128);
    {
        cuuint64_t dims[5] = {DM, 2, 4, 4, HD / 32};
        cuuint64_t strides[4] = {DM * 2, 8 * DM * 2, 2 * DM * 2, 32 * DM * 2};
        cuuint32_t box[5] = {64, 2, 4, 4, 4};
        cuuint32_t es[5] = {1, 1, 1, 1, 1};
        enc(&m.wo2, CU_TENSOR_MAP_DATA_TYPE_BFLOAT16, 5, (void*)Wo, dims, strides, box, es, CU_TENSOR_MAP_INTERLEAVE_NONE, CU_TENSOR_MAP_SWIZZLE_128B,
            CU_TENSOR_MAP_L2_PROMOTION_L2_256B, CU_TENSOR_MAP_FLOAT_OOB_FILL_NONE);
    }
    make_map(enc, &m.kx, pK, HD, SQ, 64, 64);
    make_map(enc, &m.ox2, pO, HD, SQ, 64, 64);
    make_map(enc, &m.xn2, pxn, DM, SQ, 64, 64);
    make_map3(enc, &m.kx3, pK, HD, SQ); make_map3(enc, &m.vx3, pV, HD, SQ);
    make_map(enc, &m.wg, wg, FF, DM, 32, 256, false, CU_TENSOR_MAP_SWIZZLE_64B);
    make_map(enc, &m.wu, wu, FF, DM, 32, 256, false, CU_TENSOR_MAP_SWIZZLE_64B);
    make_map(enc, &m.wd, wd, DM, FF, 64, 32);

    cudaStream_t st = cudaStreamPerThread;
    main_kernel<<<NCTA, 384, SMEM_TOTAL, st>>>(m, x, mem0, wr, wd, out, WPtr{Wq, Wk, Wv, Wo, wg, wu});
}
```

```cpp
#include <cuda_runtime.h>
#include <cuda_bf16.h>
#include <cuda.h>
#include <stdint.h>
#include <stddef.h>

typedef __nv_bfloat16 bf16;

constexpr int SQ = 2048, DM = 512, NH = 32, DH = 128, NSEG = 64, HD = 4096, FF = 1792;

constexpr int NT = 32;
#define SPEC_TILES 30
__device__ __align__(1024) bf16 g_xn[SQ * DM];
__device__ __align__(1024) bf16 g_K[SQ * HD];
__device__ __align__(1024) bf16 g_V[SQ * HD];
__device__ __align__(1024) bf16 g_O[SQ * HD];
__device__ __align__(1024) uint32_t g_KVf[NSEG][NH][1024];
__device__ __align__(1024) bf16 g_P[8 * SQ * DM];
__device__ __align__(1024) bf16 g_h[SQ * DM];
__device__ __align__(1024) bf16 g_hn[SQ * DM];
__device__ uint8_t g_xraw[12 << 20];
#define XPG 0
__device__ __forceinline__ uint64_t xpage() { return (((uint64_t)g_xraw + (2 << 20) - 1) & ~(uint64_t)((2 << 20) - 1)) + ((uint64_t)XPG << 21); }
constexpr uint32_t XR3 = (1u << 20) | (1u << 19) | (1u << 12);
__device__ __forceinline__ uint32_t aslot(uint32_t s) { return ((s & 1) << 18) | ((s & 2) << 19) | ((s & 4) * 0xc000u); }
__device__ __forceinline__ uint32_t acc_base(uint32_t W) { return ((W & 2) ? 0x3000u : 0u) + ((W & 4) << 12) + (W & 1) * 2048; }
__device__ __forceinline__ uint32_t ext_base(uint32_t W) { return 0x8000u + ((W & 4) << 12) + (W & 3) * 1024; }
#define XHS 256
#define XSS 32
__device__ __forceinline__ uint32_t zero_off(uint32_t c, uint32_t ln) {
    return ln < 8 ? acc_base(c >> 3) + (c & 7) * 256 + ln * 16 : ext_base(c >> 3) + ((c >> 2) & 1) * XHS + ((c >> 1) & 1) * XSS + (c & 1) * 16;
}
struct Flags {
    uint32_t kv[NT][NH][2];
    uint32_t o[NT][8][32];
    uint32_t rec[64];
    uint32_t xn[128];
    uint32_t p[NT][32];
    uint32_t rows[2][128];
    uint4 cand[2][128];
    uint4 norm[64];
};
__device__ __align__(1024) Flags g_f;
__device__ __align__(1024) uint4 g_yp[2][FF / 64][DM];
__device__ __align__(1024) uint32_t g_table[66 * 8];
__device__ __align__(256) uint32_t g_ticket[64];
__device__ uint32_t g_epoch;
#define NS3 6
#define HSPLIT 26
#define PFK 0
#define NWAITLN 8
#define WGA 0
#define WGB 1
#define WGC (3 - WGA - WGB)
#define PFF 10
#define FFD 2
#define NPROBE 3
constexpr int NCTA = 132;
constexpr int NFW = 112;
__device__ uint32_t g_abort;
__device__ long long g_dbg[4096];
#define TR(slot, v)

__device__ __forceinline__ uint32_t smem_u32(const void* p) { return (uint32_t)__cvta_generic_to_shared(p); }
__device__ __forceinline__ void mbar_init(uint32_t a, uint32_t c) { asm volatile("mbarrier.init.shared::cta.b64 [%0], %1;" :: "r"(a), "r"(c) : "memory"); }
__device__ __forceinline__ void mbar_expect_tx(uint32_t a, uint32_t tx) { asm volatile("mbarrier.arrive.expect_tx.shared::cta.b64 _, [%0], %1;" :: "r"(a), "r"(tx) : "memory"); }
__device__ __forceinline__ void mbar_arrive(uint32_t a) { asm volatile("mbarrier.arrive.shared::cta.b64 _, [%0];" :: "r"(a) : "memory"); }
__device__ __forceinline__ void mbar_arrive_if(uint32_t a, uint32_t pred) {
    asm volatile("{\n.reg .pred p;\nsetp.ne.u32 p, %1, 0;\n@p mbarrier.arrive.shared::cta.b64 _, [%0];\n}" :: "r"(a), "r"(pred) : "memory");
}
__device__ __forceinline__ bool mbar_try(uint32_t a, uint32_t ph) {
    uint32_t ok;
    asm volatile("{\n.reg .pred p;\nmbarrier.try_wait.parity.shared::cta.b64 p, [%1], %2;\nselp.u32 %0, 1, 0, p;\n}" : "=r"(ok) : "r"(a), "r"(ph) : "memory");
    return ok != 0;
}
#define SPINLOG 20
constexpr uint32_t SPIN_LIMIT = 1u << SPINLOG;
#define ABORT(code_) atomicCAS(&g_abort, 0u, (code_))
__device__ __forceinline__ void mbar_wait(uint32_t a, uint32_t ph) {
    uint32_t n = 0;
#pragma unroll 1
    while (!mbar_try(a, ph)) { if (++n > SPIN_LIMIT) { ABORT(1); break; } }
}
__device__ __forceinline__ void bar_sync(int id, int n) { asm volatile("bar.sync %0, %1;" :: "r"(id), "r"(n) : "memory"); }
__device__ __forceinline__ void bar_arrive(int id, int n) { asm volatile("bar.arrive %0, %1;" :: "r"(id), "r"(n) : "memory"); }

__device__ __forceinline__ void ldsm4(uint32_t* r, uint32_t a) {
    asm volatile("ldmatrix.sync.aligned.m8n8.x4.shared.b16 {%0,%1,%2,%3}, [%4];" : "=r"(r[0]), "=r"(r[1]), "=r"(r[2]), "=r"(r[3]) : "r"(a) : "memory");
}
__device__ __forceinline__ void ldsm4t(uint32_t* r, uint32_t a) {
    asm volatile("ldmatrix.sync.aligned.m8n8.x4.trans.shared.b16 {%0,%1,%2,%3}, [%4];" : "=r"(r[0]), "=r"(r[1]), "=r"(r[2]), "=r"(r[3]) : "r"(a) : "memory");
}
__device__ __forceinline__ void stsm4t(uint32_t a, uint32_t r0, uint32_t r1, uint32_t r2, uint32_t r3) {
    asm volatile("stmatrix.sync.aligned.m8n8.x4.trans.shared.b16 [%0], {%1,%2,%3,%4};" :: "r"(a), "r"(r0), "r"(r1), "r"(r2), "r"(r3) : "memory");
}
__device__ __forceinline__ void stsm4(uint32_t a, uint32_t r0, uint32_t r1, uint32_t r2, uint32_t r3) {
    asm volatile("stmatrix.sync.aligned.m8n8.x4.shared.b16 [%0], {%1,%2,%3,%4};" :: "r"(a), "r"(r0), "r"(r1), "r"(r2), "r"(r3) : "memory");
}
__device__ __forceinline__ uint32_t movm(uint32_t a) { uint32_t d; asm volatile("movmatrix.sync.aligned.m8n8.trans.b16 %0, %1;" : "=r"(d) : "r"(a)); return d; }
__device__ __forceinline__ void mma16816(float* d, uint32_t a0, uint32_t a1, uint32_t a2, uint32_t a3, uint32_t b0, uint32_t b1) {
    asm volatile("mma.sync.aligned.m16n8k16.row.col.f32.bf16.bf16.f32 {%0,%1,%2,%3}, {%4,%5,%6,%7}, {%8,%9}, {%0,%1,%2,%3};"
        : "+f"(d[0]), "+f"(d[1]), "+f"(d[2]), "+f"(d[3]) : "r"(a0), "r"(a1), "r"(a2), "r"(a3), "r"(b0), "r"(b1));
}
__device__ __forceinline__ void mma1688(float* d, uint32_t a0, uint32_t a1, uint32_t b0) {
    asm volatile("mma.sync.aligned.m16n8k8.row.col.f32.bf16.bf16.f32 {%0,%1,%2,%3}, {%4,%5}, {%6}, {%0,%1,%2,%3};"
        : "+f"(d[0]), "+f"(d[1]), "+f"(d[2]), "+f"(d[3]) : "r"(a0), "r"(a1), "r"(b0));
}
__device__ __forceinline__ uint32_t pack2(float a, float b) { uint32_t d; asm("cvt.rn.bf16x2.f32 %0, %1, %2;" : "=r"(d) : "f"(b), "f"(a)); return d; }
__device__ __forceinline__ float bf_lo(uint32_t w) { return __uint_as_float(w << 16); }
__device__ __forceinline__ float bf_hi(uint32_t w) { return __uint_as_float(w & 0xffff0000u); }
__device__ __forceinline__ float rbf(float x) { return __bfloat162float(__float2bfloat16_rn(x)); }

__device__ __forceinline__ void sts128(uint32_t a, float x, float y, float z, float w) { asm volatile("st.shared.v4.f32 [%0], {%1,%2,%3,%4};" :: "r"(a), "f"(x), "f"(y), "f"(z), "f"(w) : "memory"); }
__device__ __forceinline__ void sts128u(uint32_t a, uint32_t x, uint32_t y, uint32_t z, uint32_t w) { asm volatile("st.shared.v4.b32 [%0], {%1,%2,%3,%4};" :: "r"(a), "r"(x), "r"(y), "r"(z), "r"(w) : "memory"); }
__device__ __forceinline__ void sts64(uint32_t a, float x, float y) { asm volatile("st.shared.v2.f32 [%0], {%1,%2};" :: "r"(a), "f"(x), "f"(y) : "memory"); }
__device__ __forceinline__ float4 lds128(uint32_t a) { float4 v; asm volatile("ld.shared.v4.f32 {%0,%1,%2,%3}, [%4];" : "=f"(v.x), "=f"(v.y), "=f"(v.z), "=f"(v.w) : "r"(a) : "memory"); return v; }
__device__ __forceinline__ float2 lds64(uint32_t a) { float2 v; asm volatile("ld.shared.v2.f32 {%0,%1}, [%2];" : "=f"(v.x), "=f"(v.y) : "r"(a) : "memory"); return v; }
__device__ __forceinline__ uint2 lds64u(uint32_t a) { uint2 v; asm volatile("ld.shared.v2.b32 {%0,%1}, [%2];" : "=r"(v.x), "=r"(v.y) : "r"(a) : "memory"); return v; }
__device__ __forceinline__ float4 lds128v(uint32_t a) { float4 v; asm volatile("ld.volatile.shared.v4.f32 {%0,%1,%2,%3}, [%4];" : "=f"(v.x), "=f"(v.y), "=f"(v.z), "=f"(v.w) : "r"(a) : "memory"); return v; }
__device__ __forceinline__ float2 lds64v(uint32_t a) { float2 v; asm volatile("ld.volatile.shared.v2.f32 {%0,%1}, [%2];" : "=f"(v.x), "=f"(v.y) : "r"(a) : "memory"); return v; }
__device__ __forceinline__ uint4 lds128uv(uint32_t a) { uint4 v; asm volatile("ld.volatile.shared.v4.b32 {%0,%1,%2,%3}, [%4];" : "=r"(v.x), "=r"(v.y), "=r"(v.z), "=r"(v.w) : "r"(a) : "memory"); return v; }
__device__ __forceinline__ void st_async4(uint32_t a, float x, float y, float z, float w, uint32_t mb) {
    asm volatile("st.async.weak.shared::cluster.mbarrier::complete_tx::bytes.v4.f32 [%0], {%1,%2,%3,%4}, [%5];" :: "r"(a), "f"(x), "f"(y), "f"(z), "f"(w), "r"(mb) : "memory");
}
__device__ __forceinline__ void st_async2(uint32_t a, uint32_t x, uint32_t y, uint32_t mb) {
    asm volatile("st.async.weak.shared::cluster.mbarrier::complete_tx::bytes.v2.b32 [%0], {%1,%2}, [%3];" :: "r"(a), "r"(x), "r"(y), "r"(mb) : "memory");
}
__device__ __forceinline__ uint32_t ldg_rlx(const uint32_t* p) { uint32_t v; asm volatile("ld.relaxed.gpu.global.b32 %0, [%1];" : "=r"(v) : "l"(p) : "memory"); return v; }
__device__ __forceinline__ uint4 ldg_rlx4(const uint32_t* p) { uint4 v; asm volatile("ld.relaxed.gpu.global.v4.b32 {%0,%1,%2,%3}, [%4];" : "=r"(v.x), "=r"(v.y), "=r"(v.z), "=r"(v.w) : "l"(p) : "memory"); return v; }
__device__ __forceinline__ uint4 ldg_rlx4_if(const uint32_t* p, bool c) {
    uint4 v;
    asm volatile("{\n.reg .pred p;\nsetp.ne.u32 p, %5, 0;\nmov.b32 %0, 0;\nmov.b32 %1, 0;\nmov.b32 %2, 0;\nmov.b32 %3, 0;\n@p ld.relaxed.gpu.global.v4.b32 {%0,%1,%2,%3}, [%4];\n}"
                 : "=r"(v.x), "=r"(v.y), "=r"(v.z), "=r"(v.w) : "l"(p), "r"((uint32_t)c) : "memory");
    return v;
}
__device__ __forceinline__ void stg_rlx(uint32_t* p, uint32_t v) { asm volatile("st.relaxed.gpu.global.b32 [%0], %1;" :: "l"(p), "r"(v) : "memory"); }
__device__ __forceinline__ void tma2d(uint32_t dst, const CUtensorMap* tm, int c0, int c1, uint32_t mb) {
    asm volatile("cp.async.bulk.tensor.2d.shared::cluster.global.mbarrier::complete_tx::bytes [%0], [%1, {%3, %4}], [%2];"
        :: "r"(dst), "l"((uint64_t)tm), "r"(mb), "r"(c0), "r"(c1) : "memory");
}

__device__ __forceinline__ void tma3d(uint32_t dst, const CUtensorMap* tm, int row, int chunk, uint32_t mb) {
    asm volatile("cp.async.bulk.tensor.3d.shared::cluster.global.mbarrier::complete_tx::bytes [%0], [%1, {%3, %4, %5}], [%2];"
        :: "r"(dst), "l"((uint64_t)tm), "r"(mb), "r"(0), "r"(row), "r"(chunk) : "memory");
}
#define EF 0xff
__device__ __forceinline__ uint64_t pol_ef(int bit) {
    uint64_t p;
    if ((EF >> bit) & 1) asm("createpolicy.fractional.L2::evict_first.b64 %0, 1.0;" : "=l"(p));
    else asm("createpolicy.fractional.L2::evict_normal.b64 %0, 1.0;" : "=l"(p));
    return p;
}
__device__ __forceinline__ void tma3d_h(uint32_t dst, const CUtensorMap* tm, int row, int chunk, uint32_t mb, uint64_t pol) {
    asm volatile("cp.async.bulk.tensor.3d.shared::cluster.global.mbarrier::complete_tx::bytes.L2::cache_hint [%0], [%1, {%3, %4, %5}], [%2], %6;"
        :: "r"(dst), "l"((uint64_t)tm), "r"(mb), "r"(0), "r"(row), "r"(chunk), "l"(pol) : "memory");
}
__device__ __forceinline__ void tma2d_h(uint32_t dst, const CUtensorMap* tm, int c0, int c1, uint32_t mb, uint64_t pol) {
    asm volatile("cp.async.bulk.tensor.2d.shared::cluster.global.mbarrier::complete_tx::bytes.L2::cache_hint [%0], [%1, {%3, %4}], [%2], %5;"
        :: "r"(dst), "l"((uint64_t)tm), "r"(mb), "r"(c0), "r"(c1), "l"(pol) : "memory");
}
__device__ __forceinline__ void tma2d_mc_h(uint32_t dst, const CUtensorMap* tm, int c0, int c1, uint32_t mb, uint64_t pol) {
    asm volatile("cp.async.bulk.tensor.2d.shared::cluster.global.mbarrier::complete_tx::bytes.multicast::cluster.L2::cache_hint [%0], [%1, {%3, %4}], [%2], %5, %6;"
        :: "r"(dst), "l"((uint64_t)tm), "r"(mb), "r"(c0), "r"(c1), "h"((uint16_t)3), "l"(pol) : "memory");
}
__device__ __forceinline__ uint4 ldg4_h(const void* p, uint64_t pol) {
    uint4 v;
    asm volatile("ld.relaxed.gpu.global.L2::cache_hint.v4.b32 {%0,%1,%2,%3}, [%4], %5;" : "=r"(v.x), "=r"(v.y), "=r"(v.z), "=r"(v.w) : "l"(p), "l"(pol) : "memory");
    return v;
}
__device__ __forceinline__ void stg4_h(void* p, uint4 v, uint64_t pol) {
    asm volatile("st.relaxed.gpu.global.L2::cache_hint.v4.b32 [%0], {%1,%2,%3,%4}, %5;" :: "l"(p), "r"(v.x), "r"(v.y), "r"(v.z), "r"(v.w), "l"(pol) : "memory");
}
__device__ __forceinline__ void tma2d_mc(uint32_t dst, const CUtensorMap* tm, int c0, int c1, uint32_t mb) {
    asm volatile("cp.async.bulk.tensor.2d.shared::cluster.global.mbarrier::complete_tx::bytes.multicast::cluster [%0], [%1, {%3, %4}], [%2], %5;"
        :: "r"(dst), "l"((uint64_t)tm), "r"(mb), "r"(c0), "r"(c1), "h"((uint16_t)3) : "memory");
}
__device__ __forceinline__ void mbar_arrive2_if(uint32_t a, uint32_t pred) {
    asm volatile("{\n.reg .pred p;\nsetp.ne.u32 p, %1, 0;\n@p mbarrier.arrive.shared::cta.b64 _, [%0];\n@p mbarrier.arrive.shared::cluster.b64 _, [%2];\n}"
                 :: "r"(a), "r"(pred), "r"(a ^ 0x01000000u) : "memory");
}
__device__ __forceinline__ void tma_pf3d(const CUtensorMap* tm, int row, int chunk) {
    asm volatile("cp.async.bulk.prefetch.tensor.3d.L2.global.tile [%0, {%1, %2, %3}];" :: "l"((uint64_t)tm), "r"(0), "r"(row), "r"(chunk) : "memory");
}
__device__ __forceinline__ void tma_pf2d(const CUtensorMap* tm, int c0, int c1) {
    asm volatile("cp.async.bulk.prefetch.tensor.2d.L2.global.tile [%0, {%1, %2}];" :: "l"((uint64_t)tm), "r"(c0), "r"(c1) : "memory");
}
__device__ __forceinline__ void tma_store3d(const CUtensorMap* tm, uint32_t src, int row, int chunk) {
    asm volatile("cp.async.bulk.tensor.3d.global.shared::cta.bulk_group [%0, {%2, %3, %4}], [%1];" :: "l"((uint64_t)tm), "r"(src), "r"(0), "r"(row), "r"(chunk) : "memory");
}
__device__ __forceinline__ void bulk_store(void* dst, uint32_t src, uint32_t bytes) {
    asm volatile("cp.async.bulk.global.shared::cta.bulk_group [%0], [%1], %2;" :: "l"(dst), "r"(src), "r"(bytes) : "memory");
}
#define GT(slot)
#define CNT(k)
#define CNT2(k, c)
#define TS(i, dep)
#define TSACC()
#define TSDECL
struct Maps { CUtensorMap wq, wk, wv, wo, wo2, kx, ox2, kx3, vx3, xn2, wg, wu, wd, wq4, wk4, wv4; };
typedef Maps RecMaps;
__device__ __forceinline__ void st_rel(uint32_t* p, uint32_t v) { asm volatile("st.release.gpu.global.u32 [%0], %1;" :: "l"(p), "r"(v) : "memory"); }
#define PUBLISH(p, v) st_rel(p, v)
__device__ __forceinline__ uint2 ldg_rlx2(const uint32_t* p) { uint2 v; asm volatile("ld.relaxed.gpu.global.v2.b32 {%0,%1}, [%2];" : "=r"(v.x), "=r"(v.y) : "l"(p) : "memory"); return v; }
__device__ __forceinline__ void wait_eq2(const uint32_t* p, uint32_t e, int code) {
    uint32_t n = 0;
#pragma unroll 1
    while (true) { uint2 v = ldg_rlx2(p); if (v.x == e && v.y == e) break; __nanosleep(64); if (++n > SPIN_LIMIT) { ABORT(code); break; } }
}
__device__ __forceinline__ void wait_eq4(const uint32_t* p, uint32_t e, int code) {
    uint32_t n = 0;
#pragma unroll 1
    while (true) { uint4 v = ldg_rlx4(p); if (v.x == e && v.y == e && v.z == e && v.w == e) break; __nanosleep(64); if (++n > SPIN_LIMIT) { ABORT(code); break; } }
}
__device__ __forceinline__ void wait_rec(const uint32_t* p, uint32_t e, uint32_t steps) {
    uint32_t n = 0;
#pragma unroll 1
    while (true) {
        uint2 v = ldg_rlx2(p);
        if (__all_sync(0xffffffffu, (v.x >> 8) == e && (v.y >> 8) == e && (v.x & 255) >= steps && (v.y & 255) >= steps)) break;
        __nanosleep(64); if (++n > SPIN_LIMIT) { ABORT(8); break; }
    }
}

constexpr int R_QK1 = 0;
constexpr int R_WO = 65536;
constexpr int R_T = 131072;
constexpr int R_SLOT1 = R_T;
constexpr int R_MEMB = R_T + 24576;
constexpr int R_QP = R_MEMB + 8192;
constexpr int R_VRED = R_QP + 4096;
constexpr int R_STG = R_VRED + 2048;
constexpr int R_AX = R_STG + 2048;
constexpr int R_SLOT0 = 196608;
constexpr int R_SLOC = R_SLOT0 + 24576;
constexpr int R_SREM = R_SLOC + 1536;
constexpr int R_VB = R_SREM + 1536;
constexpr int R_MISC = R_VB + 2048;
constexpr int R_LT = R_MISC + 128;
constexpr int R_BAR = 229888;
constexpr int R_TS = 229888 + 128;
static_assert(R_AX + 24576 <= R_SLOT0 && R_LT + 2560 <= 229376, "smem map");
enum { MB_W0 = 0, MB_W1, MB_WV, MB_WO, MB_S, MB_FULL0, MB_FULL1, MB_V, MB_N };

__device__ __forceinline__ float ex2(float x) { float y; asm("ex2.approx.ftz.f32 %0, %1;" : "=f"(y) : "f"(x)); return y; }
__device__ __forceinline__ float rcpf(float x) { float y; asm("rcp.approx.ftz.f32 %0, %1;" : "=f"(y) : "f"(x)); return y; }
__device__ __forceinline__ void mma16816z(float* d, uint32_t a0, uint32_t a1, uint32_t a2, uint32_t a3, uint32_t b0, uint32_t b1) {
    asm volatile("mma.sync.aligned.m16n8k16.row.col.f32.bf16.bf16.f32 {%0,%1,%2,%3}, {%4,%5,%6,%7}, {%8,%9}, {%10,%10,%10,%10};"
        : "=f"(d[0]), "=f"(d[1]), "=f"(d[2]), "=f"(d[3]) : "r"(a0), "r"(a1), "r"(a2), "r"(a3), "r"(b0), "r"(b1), "f"(0.f));
}
__device__ __forceinline__ void mma1688hz(float* d, uint32_t a0, uint32_t a1, uint32_t b0) {
    asm volatile("mma.sync.aligned.m16n8k8.row.col.f32.f16.f16.f32 {%0,%1,%2,%3}, {%4,%5}, {%6}, {%7,%7,%7,%7};"
        : "=f"(d[0]), "=f"(d[1]), "=f"(d[2]), "=f"(d[3]) : "r"(a0), "r"(a1), "r"(b0), "f"(0.f));
}
#define MMA(d, a, b0, b1) mma16816(d, a[0], a[1], a[2], a[3], b0, b1)
#define MMAZ(d, a, b0, b1) mma16816z(d, a[0], a[1], a[2], a[3], b0, b1)
#define MMAF(first, d, a, b0, b1) do { if (first) MMAZ(d, a, b0, b1); else MMA(d, a, b0, b1); } while (0)

__device__ __forceinline__ uint32_t uni(uint32_t x) { return __reduce_max_sync(0xffffffffu, x); }
__device__ __forceinline__ void mbar_wait_u(uint32_t a, uint32_t ph) {
    uint32_t n = 0;
#pragma unroll 1
    while (!__all_sync(0xffffffffu, mbar_try(a, ph))) { if (++n > SPIN_LIMIT) { ABORT(1); break; } }
}
__device__ __forceinline__ void mbar_wait_p(uint32_t a, uint32_t ph) {
    asm volatile("{\n.reg .pred p, q;\n.reg .u32 n;\nmov.u32 n, 0;\nWL: mbarrier.try_wait.parity.shared::cta.b64 p, [%0], %1;\nadd.u32 n, n, 1;\n"
                 "setp.lt.and.u32 q, n, %2, !p;\n@q bra.uni WL;\n}" :: "r"(a), "r"(ph), "n"(SPIN_LIMIT) : "memory");
}
__device__ __forceinline__ uint32_t mbar_test(uint32_t a, uint32_t ph) {
    uint32_t ok;
    asm volatile("{\n.reg .pred p;\nmbarrier.test_wait.parity.shared::cta.b64 p, [%1], %2;\nselp.u32 %0, 1, 0, p;\n}" : "=r"(ok) : "r"(a), "r"(ph) : "memory");
    return ok;
}
__device__ __forceinline__ uint32_t opaque(uint32_t x) { return __shfl_sync(0xffffffffu, x, threadIdx.x & 31); }
__device__ __forceinline__ const uint32_t* mkptr(uint32_t lo, uint32_t hi) { uint64_t r; asm("mov.b64 %0, {%1, %2};" : "=l"(r) : "r"(lo), "r"(hi)); return (const uint32_t*)r; }
__device__ __forceinline__ uint32_t prmt(uint32_t a, uint32_t b, uint32_t s) { uint32_t d; asm("prmt.b32 %0, %1, %2, %3;" : "=r"(d) : "r"(a), "r"(b), "r"(s)); return d; }
__device__ __forceinline__ uint32_t packh2(float a, float b) { uint32_t d; asm("cvt.rn.f16x2.f32 %0, %1, %2;" : "=r"(d) : "f"(b), "f"(a)); return d; }
__device__ __forceinline__ uint32_t hadd2b(uint32_t a, uint32_t b) { uint32_t d; asm("add.rn.bf16x2 %0, %1, %2;" : "=r"(d) : "r"(a), "r"(b)); return d; }
__device__ __forceinline__ uint32_t hmul2b(uint32_t a, uint32_t b) { uint32_t d; asm("mul.rn.bf16x2 %0, %1, %2;" : "=r"(d) : "r"(a), "r"(b)); return d; }
__device__ __forceinline__ uint32_t amax2b(uint32_t a, uint32_t b) { uint32_t d; asm("max.xorsign.abs.bf16x2 %0, %1, %2;" : "=r"(d) : "r"(a), "r"(b)); return d; }
__device__ __forceinline__ uint32_t amax2h(uint32_t a, uint32_t b) { uint32_t d; asm("max.xorsign.abs.f16x2 %0, %1, %2;" : "=r"(d) : "r"(a), "r"(b)); return d; }
__device__ __forceinline__ void sts32(uint32_t a, uint32_t x) { asm volatile("st.shared.b32 [%0], %1;" :: "r"(a), "r"(x) : "memory"); }
__device__ __forceinline__ uint32_t lds32v_(uint32_t a) { uint32_t v; asm volatile("ld.volatile.shared.b32 %0, [%1];" : "=r"(v) : "r"(a) : "memory"); return v; }
__device__ __forceinline__ void stg4(void* p, uint4 v) { asm volatile("st.relaxed.gpu.global.v4.b32 [%0], {%1,%2,%3,%4};" :: "l"(p), "r"(v.x), "r"(v.y), "r"(v.z), "r"(v.w) : "memory"); }
__device__ __forceinline__ void lds_frag(uint32_t* r, uint32_t a) {
    asm volatile("ld.shared.v4.b32 {%0,%1,%2,%3}, [%4];" : "=r"(r[0]), "=r"(r[1]), "=r"(r[2]), "=r"(r[3]) : "r"(a) : "memory");
}
__device__ __forceinline__ void lds_fragv(uint32_t* r, uint32_t a) {
    asm volatile("ld.volatile.shared.v4.b32 {%0,%1,%2,%3}, [%4];" : "=r"(r[0]), "=r"(r[1]), "=r"(r[2]), "=r"(r[3]) : "r"(a) : "memory");
}
__device__ __forceinline__ uint32_t xorv(uint32_t a, uint32_t b) { uint32_t d; asm volatile("xor.b32 %0, %1, %2;" : "=r"(d) : "r"(a), "r"(b)); return d; }
#define SCHED(k) asm volatile("{\n.reg .pred p;\nsetp.ne.u32 p, %0, %1;\n@p bra.uni SD;\nSL: nanosleep.u32 64;\nbra.uni SL;\nSD:\n}" :: "r"(sbu - s), "n"(k) : "memory")
#define PINM() asm volatile("{\n.reg .pred p;\nsetp.eq.u32 p, %0, 1;\n@p st.shared.u32 [%0], 0;\n}" :: "r"(sbu) : "memory")
__device__ __forceinline__ uint32_t or_and(uint32_t a, uint32_t b, uint32_t c) { uint32_t d; asm("lop3.b32 %0, %1, %2, %3, 0xF8;" : "=r"(d) : "r"(a), "r"(b), "r"(c)); return d; }
__device__ __forceinline__ uint32_t pack2v(float a, float b) { uint32_t d; asm volatile("cvt.rn.bf16x2.f32 %0, %1, %2;" : "=r"(d) : "f"(b), "f"(a)); return d; }
#define FU(x) __float_as_uint(x)
__device__ __forceinline__ uint32_t clk32() { uint32_t t; asm volatile("mov.u32 %0, %%clock;" : "=r"(t) :: "memory"); return t; }
__device__ __forceinline__ void spin_until(uint32_t t0, uint32_t d) {
    if (d) {
#pragma unroll 1
        while (__any_sync(0xffffffffu, clk32() - t0 < d)) {}
    }
}
constexpr int SH_OFF = 229376 + 384;
constexpr uint32_t HONE2 = 0x3c003c00u, HCNT2 = 0x50005000u;

__device__ __forceinline__ uint64_t desc_sw128(uint32_t addr, uint32_t lbo, uint32_t sbo) {
    return (uint64_t)((addr & 0x3FFFF) >> 4) | ((uint64_t)(lbo >> 4) << 16) | ((uint64_t)(sbo >> 4) << 32) | (1ull << 62);
}
#define DP 390
#define NAX 3
#define NXL 0
#define NCX 2
#define NCL 1
#define FLIP 1
#define VTA 1
#define KXB 4
#define ANB 3
#define BNB 3
#define CNB 3
#define SMA 0
#define SMB 0
#define SMC 0x01
#define IVA 0
#define RGA 160
#define RGC 160
#define RGB (504 - RGA - RGC)
#define NRW 8
#define NBR 16
#define E0 0
#define E1 6
#define E2 4
#define E3 8
#define IV 2
#define G2V 0
#define G2K 2
#define VDEP 0
#define AEARLY 0
#define VTP 2
#define LORD 1
#define TRK 1
#define T2N 14
#define NB0 0
#define NB1 9
#define DB2 80
#define DITHER 0
#define DB 40

__device__ __forceinline__ uint32_t wrow_off(int kk, int ch) {
    const int lane = threadIdx.x & 31, r = lane & 7;
    const int row = 64 * (kk >> 2) + 32 * (r & 1) + 16 * (kk & 1) + 8 * (lane >> 4) + 4 * ((kk >> 1) & 1) + (r >> 1);
    return row * 128 + ((ch ^ (row & 7)) << 4);
}
template <int K> __device__ __forceinline__ void sched(uint32_t key) {
    asm volatile("{\n.reg .pred p;\nsetp.ne.u32 p, %0, %1;\n@p bra.uni SD;\nSL: nanosleep.u32 64;\nbra.uni SL;\nSD:\n}" :: "r"(key), "n"(K) : "memory");
}
__device__ __forceinline__ void sched_i(int i, uint32_t key) {
    if (i == -1) sched<20>(key); if (i == 0) sched<21>(key); if (i == 1) sched<22>(key); if (i == 2) sched<23>(key);
    if (i == 3) sched<24>(key); if (i == 4) sched<25>(key); if (i == 5) sched<26>(key); if (i == 6) sched<27>(key);
}
template <int NB, int SM, class F>
__device__ __forceinline__ void g1(float* q0, float* k0, uint32_t (*wq)[4], uint32_t (*wk)[4], uint32_t ga, uint32_t key, F&& hook) {
    float q1[4], k1[4];
    uint32_t b[NB][4];
#pragma unroll
    for (int i = 0; i < NB; i++) ldsm4(b[i], ga + i * 512);
    hook(-1, b[0]);
    if (SM & 1) sched_i(-1, key);
#pragma unroll
    for (int i = 0; i < 8; i++) {
        uint32_t* c = b[i % NB];
        MMAF(i == 0, q0, wq[2 * i], c[0], c[1]); MMAF(i == 0, k0, wk[2 * i], c[0], c[1]);
        MMAF(i == 0, q1, wq[2 * i + 1], c[2], c[3]); MMAF(i == 0, k1, wk[2 * i + 1], c[2], c[3]);
        const uint32_t cc_[4] = {c[0], c[1], c[2], c[3]};
        if (i + NB < 8) ldsm4(b[i % NB], ga + (i + NB) * 512);
        hook(i, cc_);
        if ((SM >> (i + 1)) & 1) sched_i(i, key);
    }
#pragma unroll
    for (int i = 0; i < 4; i++) { q0[i] += q1[i]; k0[i] += k1[i]; }
}
__device__ __forceinline__ float frag_norm2(uint32_t (*w)[4]) {
    float d0[4], d1[4];
#pragma unroll
    for (int i = 0; i < 32; i++) { MMAF(i == 0, d0, w[i], w[i][0], w[i][2]); MMAF(i == 0, d1, w[i], w[i][1], w[i][3]); }
    const int lane = threadIdx.x & 31, g = lane >> 2, t = lane & 3;
    float v = g == 2 * t ? d0[0] + d1[2] : (g == 2 * t + 1 ? d0[1] + d1[3] : 0.f);
#pragma unroll
    for (int o = 16; o; o >>= 1) v += __shfl_xor_sync(0xffffffffu, v, o);
    return v;
}
__device__ __forceinline__ void load_slot(uint32_t sb, int c, int tile, const Maps& maps) {
    const uint32_t dst = sb + ((tile & 1) ? R_SLOT1 : R_SLOT0), mb = sb + R_BAR + 8 * (MB_FULL0 + (tile & 1));
    mbar_expect_tx(mb, 24576);
    if ((EF >> 8) & 1) {
        tma2d_h(dst + 16384, &maps.kx, c * 64, tile * 64, mb, pol_ef(8));
        tma3d_h(dst, &maps.vx3, tile * 64, (c >> 1) * 2, mb, pol_ef(8));
    } else {
        tma2d(dst + 16384, &maps.kx, c * 64, tile * 64, mb);
        tma3d(dst, &maps.vx3, tile * 64, (c >> 1) * 2, mb);
    }
}
__device__ __forceinline__ uint32_t put_mem0(uint32_t sb, int W, const bf16* __restrict__ mem0) {
    const int lane = threadIdx.x & 31;
    const uint4 a = *(const uint4*)(mem0 + (lane & 7) * DM + W * 64 + (lane >> 3) * 8), b = *(const uint4*)(mem0 + (lane & 7) * DM + W * 64 + 32 + (lane >> 3) * 8);
    const uint4 m0 = make_uint4(prmt(a.x, b.x, 0x5410u), prmt(a.x, b.x, 0x7632u), prmt(a.y, b.y, 0x5410u), prmt(a.y, b.y, 0x7632u));
    const uint4 m1 = make_uint4(prmt(a.z, b.z, 0x5410u), prmt(a.z, b.z, 0x7632u), prmt(a.w, b.w, 0x5410u), prmt(a.w, b.w, 0x7632u));
    bar_sync(3, 256);
    sts128u(sb + R_MEMB + W * 1024 + lane * 16, m0.x, m0.y, m0.z, m0.w);
    sts128u(sb + R_MEMB + W * 1024 + 512 + lane * 16, m1.x, m1.y, m1.z, m1.w);
    return amax2b(amax2b(amax2b(m0.x, m0.y), amax2b(m0.z, m0.w)), amax2b(amax2b(m1.x, m1.y), amax2b(m1.z, m1.w)));
}
#define PUT_MAX(rL, W) sts32(rL + R_STG + 1024 + ((W) >> 2) * 512 + ((W) & 3) * 4, amax2b(amax2b(mx, my), mz));
__device__ __forceinline__ uint32_t h2b(uint32_t w) {
    uint32_t d;
    asm("{\n.reg .f16 l, h;\n.reg .f32 a, b;\nmov.b32 {l, h}, %1;\ncvt.f32.f16 a, l;\ncvt.f32.f16 b, h;\ncvt.rn.bf16x2.f32 %0, b, a;\n}" : "=r"(d) : "r"(w));
    return d;
}
#define GATHER1(HALF)                                                                                           \
        {                                                                                                       \
            const uint4 x0 = ldg_rlx4(pm), x1 = ldg_rlx4(pm + 256); const uint2 y = ldg_rlx2(px);                 \
            cw = (sel & 0x4000u) ? prmt(x0.w, x1.w, 0x7632u) : prmt(y.x, y.y, 0x5410u);                         \
            const uint32_t p0 = h2b(x0.x), p1 = h2b(x0.y), p2 = h2b(x0.z), p3 = h2b(prmt(x0.w, y.x, sel));      \
            stsm4t(rG + R_MEMB + HALF * 4096, p0, p1, p2, p3);                                                  \
            const uint32_t p4 = h2b(x1.x), p5 = h2b(x1.y), p6 = h2b(x1.z), p7 = h2b(prmt(x1.w, y.y, sel));      \
            stsm4t(rG + R_MEMB + HALF * 4096 + 512, p4, p5, p6, p7);                                            \
            mx = amax2b(amax2b(p0, p1), amax2b(p2, p3)); my = amax2b(p4, p5); mz = amax2b(p6, p7);              \
        }
#define GATHER(HALF, PRE, SYNC, AFTER)                                                                                      \
        {                                                                                                       \
            const uint32_t so = aslot(s);                                                                       \
            const uint32_t ua = (glo + acc_base(HALF * 4 + fo)) ^ so, ux = (glo + ext_base(HALF * 4 + fo)) ^ so; \
            uint2 lt;                                                                                           \
            lt.x = lds32v_(rL + R_LT); lt.y = lds32v_(rL + R_LT + 4);                                           \
            const uint32_t sel = 0x7610u - ((lt.x ^ (lt.x >> 2)) & 16) * 0x440u;                                \
            const uint32_t* pm = mkptr(ua + lt.x, ghi);                                                         \
            const uint32_t* px = mkptr(ux + lt.y, ghi);                                                         \
            PRE                                                                                                 \
            bar_sync(5, 384);                                                                                   \
            const uint32_t t0 = clk32();                                                                        \
            TSACC();                                                                        \
            SYNC                                                                                                \
            spin_until(t0, DP + DITHER);                                                                                 \
            \
            TS(10, 0);                                                                                          \
            uint32_t cw, nr = 0;                                                                                \
            _Pragma("unroll 1") do {                                                                            \
                GATHER1(HALF)                                                                                   \
                nr++;                                                                                           \
            } while (__any_sync(0xffffffffu, cw != HCNT2 && nr < SPIN_LIMIT));                                  \
            TS(11, cw);                                                                                         \
            AFTER                                                                                               \
            CNT2(HALF * 4 + (s & 1) * 2 + (nr > 2), nr > 1);                                                    \
            \
        }
#define GOBAR (fo == 3 ? 14 : 10 + fo)

__device__ __forceinline__ void rec_a(uint32_t sb, int c, const bf16* __restrict__ mem0, uint32_t epoch) {
    const int tid = threadIdx.x - WGA * 128, lane = tid & 31, f = tid >> 5;
    uint32_t wq[16][4], wk[16][4], mx, my = 0, mz = 0;
    const int lrow = ((lane >> 4) << 3) + (lane & 7), lsel = (lane >> 3) & 1;
    {
        mbar_wait(sb + R_BAR + 8 * MB_W0, 0);
        if (c == 7 && tid == 0) GT(1421);
#pragma unroll
        for (int kk = 0; kk < 16; kk++) { const uint32_t a = sb + R_T + wrow_off(kk, 2 * f + lsel); ldsm4t(wq[kk], a); ldsm4t(wk[kk], a + 32768); }
        __syncwarp();
        mx = put_mem0(sb, f, mem0);
    }
    const uint32_t rL = opaque(sb + lane * 16), rG = opaque(sb + lane * 16 + f * 1024);
    const uint32_t sbu = uni(sb), fo = uni(f), cc = uni(c);
    const uint64_t gx = xpage();
    const uint32_t ghi = uni((uint32_t)(gx >> 32)), glo = uni((uint32_t)gx);
#pragma unroll
    for (int i = 0; i < NAX; i++) {
        sts128u(rG + R_AX + 4096 * i, wq[i][0], wq[i][1], wq[i][2], wq[i][3]);
        sts128u(rG + R_AX + 4096 * i + 512, wk[i][0], wk[i][1], wk[i][2], wk[i][3]);
    }
    sts128u(rL + R_LT + 512 + f * 512, (sb + R_SREM + (f >= 2 ? lane * 8 + f * 256 : lane * 16 + f * 1024)) ^ 0x01000000u, (sb + R_BAR + 8 * MB_S) ^ 0x01000000u,
            sb + R_QP + (lane >> 4) * 128 + lsel * 512 + (lane & 7) * 16 + (f == 3 ? 2048 : 0), sb + R_SLOT0 + lrow * 128 + ((lsel ^ (lane & 7)) << 4));
    __syncwarp();
    if (tid == 0) GT(c * 8 + 1);
    TSDECL;
    const float cexp = 0.08838834764831845f * 1.4426950408889634f;
    float cs = cexp;
    auto step = [&](int s, bool first) -> bool {
        bar_sync(1, 128);
        float q0[4], k0[4];
        uint4 ta;
        uint32_t zr, rl2;
        g1<ANB, SMA>(q0, k0, wq, wk, rL + R_MEMB, sbu - s, [&](int i, const uint32_t* c_) {
            if (i == 0) TS(0, c_[0]);
            if (i == -1) {
#pragma unroll
                for (int n = NAX - NXL; n < NAX; n++) { lds_fragv(wq[n], rG + R_AX + 4096 * n); lds_fragv(wk[n], rG + R_AX + 4096 * n + 512); }
                ta = lds128uv(rL + R_LT + 512 + fo * 512);
                zr = ta.w & 1; rl2 = rL | zr;
            }
            if (i == IVA) { PUT_MAX(rl2, fo) bar_arrive(15, 256); bar_arrive(GOBAR, 96); }
        });
        stsm4t(rG + R_QP, pack2(q0[0], q0[1]), pack2(q0[2], q0[3]), pack2(k0[0], k0[1]), pack2(k0[2], k0[3]));
        TS(1, FU(k0[3]));
        if (first) mbar_wait_p(sbu + R_BAR + 8 * MB_FULL0, 0);
        if (fo >= 2) {
            bar_sync(3, 256);
            uint32_t kb[4], kc[4], qa[4], qc[4];
            ldsm4(kb, ta.z + 256); ldsm4(qa, ta.z);
            ldsm4(kc, ta.z + 1280); ldsm4(qc, ta.z + 1024);
            const uint32_t k0_ = hadd2b(kb[0], kb[1]), k1_ = hadd2b(kb[2], kb[3]), k2_ = hadd2b(kc[0], kc[1]), k3_ = hadd2b(kc[2], kc[3]);
            float s0[4], s2[4];
            MMAZ(s0, qa, k0_, k1_); MMAZ(s2, qc, k2_, k3_);
            const float x = ((s0[0] + s0[2]) + (s2[0] + s2[2])) * cs, y = ((s0[1] + s0[3]) + (s2[1] + s2[3])) * cs;
            st_async2(ta.x, FU(x), FU(y), ta.y);
            TS(3, FU(y));
            sts64((ta.x ^ 0x01000000u) + (R_SLOC - R_SREM), x, y);
            sts128u(rl2 + R_STG + (fo & 1) * 512, k0_, k1_, k2_, k3_);
            bar_arrive(9, 192);
        } else {
            uint32_t qa[4][4], kx[4][4];
#pragma unroll
            for (int kk = 0; kk < KXB; kk++) ldsm4(kx[kk], (ta.w ^ (kk * 32)) + (16384 + fo * 2048));
            bar_sync(3, 256);
#pragma unroll
            for (int kk = 0; kk < 4; kk++) {
                if (kk >= KXB) ldsm4(kx[kk], (ta.w ^ (kk * 32)) + (16384 + fo * 2048));
                ldsm4(qa[kk], ta.z + kk * 1024);
            }
            float s0[4], s1[4], s2[4], s3[4];
            MMAZ(s0, qa[0], kx[0][0], kx[0][1]); MMAZ(s1, qa[0], kx[0][2], kx[0][3]);
            MMAZ(s2, qa[1], kx[1][0], kx[1][1]); MMAZ(s3, qa[1], kx[1][2], kx[1][3]);
            MMA(s0, qa[2], kx[2][0], kx[2][1]); MMA(s1, qa[2], kx[2][2], kx[2][3]);
            MMA(s2, qa[3], kx[3][0], kx[3][1]); MMA(s3, qa[3], kx[3][2], kx[3][3]);
            const float x = ((s0[0] + s0[2]) + (s2[0] + s2[2])) * cs, y = ((s0[1] + s0[3]) + (s2[1] + s2[3])) * cs;
            const float z = ((s1[0] + s1[2]) + (s3[0] + s3[2])) * cs, w = ((s1[1] + s1[3]) + (s3[1] + s3[3])) * cs;
            st_async4(ta.x, x, y, z, w, ta.y);
            TS(3, FU(w));
            sts128(rG + R_SLOC, x, y, z, w);
        }
        const uint32_t r8 = (rl2 + sbu) >> 1;
        uint32_t vt00[4], vt01[4], vt10[4], vt11[4];
        const uint32_t rV = ta.w ^ ((fo & 1) * 64), vo = (fo >> 1) * 8192;
        if (!VTA && VTP < 2) { ldsm4t(vt00, rV + vo); ldsm4t(vt10, (rV ^ 32) + vo); }
        if (!VTA && VTP < 1) { ldsm4t(vt01, rV + vo + 2048); ldsm4t(vt11, (rV ^ 32) + vo + 2048); }
        bar_sync(4, 128);
        const float2 l2 = lds64v(r8 + R_SLOC + 512), l3 = lds64v(r8 + R_SLOC + 768);
        const float4 l0 = lds128v(rL + R_SLOC), l1 = lds128v(rL + R_SLOC + 1024);
        if (VTA && VTP < 2) { ldsm4t(vt00, rV + vo); ldsm4t(vt10, (rV ^ 32) + vo); }
        if (VTA && VTP < 1) { ldsm4t(vt01, rV + vo + 2048); ldsm4t(vt11, (rV ^ 32) + vo + 2048); }

        if (s == NSEG - 1) { mbar_wait_u(sbu + R_BAR + 8 * MB_S, 1); mbar_wait_u(sbu + R_BAR + 8 * MB_V, 1); return true; }
        TS(2, FU(l3.y));
        mbar_wait_p(sbu + R_BAR + 8 * MB_S, s & 1);
        TS(4, 0);
        {
            const float2 r2 = lds64v(r8 + R_SREM + 512), r3 = lds64v(r8 + R_SREM + 768);
            const float4 r0 = lds128v(rL + R_SREM), r1 = lds128v(rL + R_SREM + 1024);
            if (VTP >= 1) PINM();
            if (VTP >= 2) { ldsm4t(vt00, rV + vo); ldsm4t(vt10, (rV ^ 32) + vo); }
            if (VTP >= 1) { ldsm4t(vt01, rV + vo + 2048); ldsm4t(vt11, (rV ^ 32) + vo + 2048); }
            float sv[10];
            sv[0] = l0.x + r0.x; sv[1] = l0.y + r0.y; sv[2] = l0.z + r0.z; sv[3] = l0.w + r0.w;
            sv[4] = l1.x + r1.x; sv[5] = l1.y + r1.y; sv[6] = l1.z + r1.z; sv[7] = l1.w + r1.w;
            sv[8] = ((l2.x + l3.x) + r2.x) + r3.x; sv[9] = ((l2.y + l3.y) + r2.y) + r3.y;
            float m = fmaxf(fmaxf(fmaxf(fmaxf(sv[8], sv[9]), sv[0]), fmaxf(fmaxf(sv[2], sv[3]), sv[1])), fmaxf(fmaxf(sv[4], sv[5]), fmaxf(sv[6], sv[7])));
            {
                const float m1 = __shfl_xor_sync(0xffffffffu, m, 1), m2 = __shfl_xor_sync(0xffffffffu, m, 2), m3 = __shfl_xor_sync(0xffffffffu, m, 3);
                m = fmaxf(fmaxf(m, m1), fmaxf(m2, m3));
            }
            TS(5, FU(m));
            const uint32_t ONE2 = 0x3f803f80u;
            float o0[4], o1[4], sm[4];
            const uint32_t pb0 = pack2(ex2(sv[0] - m), ex2(sv[1] - m)), pb1 = pack2(ex2(sv[2] - m), ex2(sv[3] - m));
            mma16816z(sm, ONE2, ONE2, ONE2, ONE2, pb0, pb1);
            MMAZ(o0, vt00, pb0, pb1); MMAZ(o1, vt10, pb0, pb1);
            const uint32_t z = (VDEP == 0 ? FU(m) : pb0) & zr;
            const uint32_t vok = mbar_test(sbu + R_BAR + 8 * MB_V + z, s & 1);
            const uint32_t rv = r8 + vok * 8;
            float2 va = lds64v(rv + R_VB - 8 + fo * 512);
            float2 vb = lds64v(rv + R_VB - 8 + fo * 512 + 256);
            float sig = __uint_as_float(lds32v_(sbu + R_MISC + 40));
            const uint32_t pb2 = pack2(ex2(sv[4] - m), ex2(sv[5] - m)), pb3 = pack2(ex2(sv[6] - m), ex2(sv[7] - m));
            mma16816(sm, ONE2, ONE2, ONE2, ONE2, pb2, pb3);
            const uint32_t pb4 = pack2(ex2(sv[8] - m), ex2(sv[9] - m));
            MMA(o0, vt01, pb2, pb3); MMA(o1, vt11, pb2, pb3);
            mma1688(sm, ONE2, ONE2, pb4);
            const float z0 = rcpf(sm[0]), z1 = rcpf(sm[1]);
#define PUT_O()                                                                                                   \
            {                                                                                                     \
                float a0[4] = {o0[0], o0[1], o0[2], o0[3]}, a1[4] = {o1[0], o1[1], o1[2], o1[3]};                 \
                mma1688(a0, FU(va.x), FU(va.y), pb4); mma1688(a1, FU(vb.x), FU(vb.y), pb4);                       \
                const float i0 = z0 * sig, i1 = z1 * sig;                                                         \
                stsm4t(rG + R_QP, pack2(a0[0] * i0, a0[1] * i1), pack2(a0[2] * i0, a0[3] * i1), pack2(a1[0] * i0, a1[1] * i1), pack2(a1[2] * i0, a1[3] * i1)); \
            }
            PUT_O()
            asm volatile("{\n.reg .pred p;\nsetp.ne.u32 p, %0, 0;\n@p bar.arrive 8, 256;\n}" :: "r"(vok) : "memory");
            if (__builtin_expect(__any_sync(0xffffffffu, vok == 0), 0)) {
                mbar_wait_p(sbu + R_BAR + 8 * MB_V, s & 1);
                va = lds64v(r8 + R_VB + fo * 512); vb = lds64v(r8 + R_VB + fo * 512 + 256);
                sig = __uint_as_float(lds32v_(sbu + R_MISC + 40));
                PUT_O()
                bar_arrive(8, 256);
                CNT(8);
            }
            TS(6, 0);
            const float r = __uint_as_float(0x7f000000u - FU(sig));
            cs = cexp * r * (fo >= 2 ? r : 1.f);
        }
        return false;
    };
    step(0, true);
#pragma unroll 1
    for (int s = 0;; s++) {
        if (s & 1) mbar_wait_p(sbu + R_BAR + 8 * (MB_FULL0 + (((s + 1) >> 1) & 1)), ((s + 1) >> 2) & 1);
        {
            const uint32_t a = rL + R_LT + 512 + 12 + fo * 512;
            sts32(a, lds32v_(a) + ((s & 1) ? ((s & 2) ? R_SLOT0 - R_SLOT1 - 4096 : R_SLOT1 - R_SLOT0 - 4096) : 4096));
        }
        auto early = [&]() {
            SCHED(13);
#pragma unroll
            for (int i = 0; i < NAX - NXL; i++) { lds_fragv(wq[i], rG + R_AX + 4096 * i); lds_fragv(wk[i], rG + R_AX + 4096 * i + 512); }
        };
        GATHER(0, , early();, )
        if (step(s + 1, false)) break;
    }
    CNT(9);
    if (rG == sbu) GT(cc * 8 + 4);
}

__device__ __forceinline__ void rec_b(uint32_t sb, int c, uint32_t epoch) {
    const int tid = threadIdx.x - WGB * 128, lane = tid & 31, f = tid >> 5;
    uint32_t wq[16][4], wk[16][4], wo[32][4];
    const int lrow = ((lane >> 4) << 3) + (lane & 7), lsel = (lane >> 3) & 1;
    const uint32_t rL = opaque(sb + lane * 16), rW = opaque(sb + lane * 16 + f * 16384);
    const uint32_t sbu = uni(sb), fo = uni(f), cc = uni(c), po = cc & 1, ep = uni(epoch);
    {
        mbar_wait(sb + R_BAR + 8 * MB_WO, 0);
        if (c == 7 && tid == 0) GT(1426);
        const uint32_t aO = sb + R_WO + f * 16384 + lrow * 128 + ((lsel ^ (lane & 7)) << 4);
#pragma unroll
        for (int i = 0; i < 32; i++) {
            const int tile = (i >> 4) * 2 + (i & 1), kk = (i >> 1) & 7;
            ldsm4t(wo[i], (aO ^ (32 * tile)) + kk * 2048);
        }
        const float no = frag_norm2(wo);
        if (lane == 0) sts32(sb + R_MISC + 80 + f * 4, FU(no));
        __syncwarp();
        bar_sync(0, 256);
        if (tid == 0) {
            const float4 a = lds128(sb + R_MISC + 64), b = lds128(sb + R_MISC + 80);
            stg4(&g_f.norm[c], make_uint4(FU((a.x + a.y) + (a.z + a.w)), epoch, FU((b.x + b.y) + (b.z + b.w)), epoch));
        }
        __syncwarp();
#pragma unroll
        for (int i = NRW; i < 32; i++) sts128u(rW + R_WO + i * 512, wo[i][0], wo[i][1], wo[i][2], wo[i][3]);
        mbar_wait(sb + R_BAR + 8 * MB_W1, 0);
        if (c == 7 && tid == 0) GT(1422);
        __syncwarp();
#pragma unroll
        for (int kk = 0; kk < 16; kk++) { const uint32_t a = sb + R_QK1 + wrow_off(kk, 2 * f + lsel); ldsm4t(wq[kk], a); ldsm4t(wk[kk], a + 32768); }
        bar_sync(13, 128);
#pragma unroll
        for (int i = 0; i < 16; i++) {
            sts128u(rW + R_QK1 + i * 1024, wq[i][0], wq[i][1], wq[i][2], wq[i][3]);
            sts128u(rW + R_QK1 + i * 1024 + 512, wk[i][0], wk[i][1], wk[i][2], wk[i][3]);
        }
        __syncwarp();
    }
    const uint64_t gx = xpage();
    const uint32_t ghi = uni((uint32_t)(gx >> 32)), glo = uni((uint32_t)gx);
    TSDECL;
#pragma unroll 1
    for (int s = 0;; s++) {
        bar_sync(2, 256);
        float q0[4], k0[4];
        g1<BNB, SMB>(q0, k0, wq, wk, rL + R_MEMB + 4096, sbu - s, [&](int i, const uint32_t* c_) {
            if (i == 0) TS(0, c_[0]);
            if (i >= 2 && i < 6) {
#pragma unroll
                for (int n = NRW + (i - 2) * E0 / 4; n < NRW + (i - 1) * E0 / 4; n++) lds_fragv(wo[n], rW + R_WO + n * 512);
            }
            if (i == IV) bar_arrive(GOBAR, 96);
        });
        stsm4t(rL + fo * 1024 + R_QP + 512, pack2(q0[0], q0[1]), pack2(q0[2], q0[3]), pack2(k0[0], k0[1]), pack2(k0[2], k0[3]));
        bar_arrive(3, 256);
        TS(1, FU(k0[3]));
        const uint32_t so = aslot(s);
        uint2 lt;
        { const float2 t = lds64v(rL + R_LT + 8); lt.x = FU(t.x); lt.y = FU(t.y); }
        const uint32_t sel = 0x3210u + (lt.x & 16) * 0x440u;
        uint32_t* pm = (uint32_t*)mkptr(((glo + acc_base(po * 4 + fo)) ^ so) + lt.x, ghi);
        uint32_t* px = (uint32_t*)mkptr(((glo + ext_base(po * 4 + fo)) ^ so) + lt.y, ghi);
        if (s == NSEG - 1) break;
        {
            const uint32_t z = lt.x & 1;
#pragma unroll
            for (int n = NRW; n < NRW + E0 + E1 + E2 + E3; n++) {
                const int d = n - (n < NRW + T2N ? TRK + 1 : TRK);
                lds_fragv(wo[n], (d >= NRW ? or_and(rW, wo[d][0], z) : rW) + R_WO + n * 512);
            }
        }
        TS(2, wo[NRW + E0 + E1 + E2 + E3 - 1][0]);
        SCHED(4);
        bar_sync(8, 256);
        {
            float o[4][4];
            uint32_t b[4][4];
#pragma unroll
            for (int i = 0; i < 4; i++) ldsm4(b[i], rL + R_QP + i * 1024);
            PINM();
#pragma unroll
            for (int n = NRW + E0 + E1 + E2 + E3; n < 32; n++) lds_fragv(wo[n], rW + R_WO + n * 512);
            float p[4][4];
#define G2_STEP(o, hf, kk) _Pragma("unroll") for (int i = 0; i < 2; i++) MMAF((kk) < 2, o[((kk) & 1) * 2 + i], wo[(hf) * 16 + (kk) * 2 + i], b[(kk) >> 1][((kk) & 1) * 2], b[(kk) >> 1][((kk) & 1) * 2 + 1])
#define G2_RED(o, wl, h) const uint32_t wl = packh2(o[1][2] + o[3][2], o[1][3] + o[3][3]);                            \
                asm volatile("red.relaxed.gpu.global.add.noftz.v4.f16x2 [%0], {%1,%2,%3,%4};" :: "l"(pm + (h) * 16),  \
                    "r"(packh2(o[0][0] + o[2][0], o[0][1] + o[2][1])), "r"(packh2(o[0][2] + o[2][2], o[0][3] + o[2][3])), \
                    "r"(packh2(o[1][0] + o[3][0], o[1][1] + o[3][1])), "r"(prmt(wl, HONE2, (h) ? sel : sel ^ 0x4400u)) : "memory")
            if (G2V == 1) SCHED(11);
#pragma unroll
            for (int kk = 0; kk < 8; kk++) { G2_STEP(o, 0, kk); }
            TS(7, b[0][0]);
            if (G2V == 0) SCHED(11);
            else {
#pragma unroll
                for (int i = 0; i < 4; i++) wo[16 + i][0] = or_and(wo[16 + i][0], FU(o[i][0]), lt.x & 1);
            }
#pragma unroll
            for (int kk = 0; kk < G2K; kk++) { G2_STEP(p, 1, kk); }
#pragma unroll
            for (int i = 0; i < NB0; i++) { lds_fragv(wq[i], rW + R_QK1 + i * 1024); lds_fragv(wk[i], rW + R_QK1 + i * 1024 + 512); }
            G2_RED(o, w3, 0);
            TS(8, w3);
            if (G2V == 0) SCHED(12);
#pragma unroll
            for (int kk = G2K; kk < 8; kk++) { G2_STEP(p, 1, kk); }
            G2_RED(p, w7, 1);
            asm volatile("red.relaxed.gpu.global.add.noftz.f16x2 [%0], %1;" :: "l"(px), "r"(prmt((w3 & 0xffff0000u) | 0x3c00u, w7, sel)) : "memory");
            TS(9, w7);
        }
        bar_arrive(5, 384);
        asm volatile("{\n.reg .pred p;\nsetp.eq.u32 p, %0, %1;\n@p mbarrier.arrive.expect_tx.shared::cta.b64 _, [%2], 1536;\n}"
                     :: "r"(rW), "r"(sbu), "r"(sbu + R_BAR + 8 * MB_S) : "memory");
        const uint32_t tb = clk32();
        TSACC();
        spin_until(tb, DB);
#pragma unroll
        for (int i = NB0; i < NBR; i++) {
            if (i == NB1) spin_until(tb, DP + DB2);
            lds_fragv(wq[i], rW + R_QK1 + i * 1024); lds_fragv(wk[i], rW + R_QK1 + i * 1024 + 512);
        }
    }
}

#undef lds_fragv
__device__ __forceinline__ void rec_first_loads(uint32_t sb, int c, const Maps& maps) {
    const uint32_t bar = sb + R_BAR;
    const int F0 = c * 64;
    mbar_expect_tx(bar + 8 * MB_W0, 65536); mbar_expect_tx(bar + 8 * MB_WO, 65536); mbar_expect_tx(bar + 8 * MB_WV, 65536);
    tma2d(sb + R_QK1, &maps.wv, F0, 0, bar + 8 * MB_WV); tma2d(sb + R_QK1 + 32768, &maps.wv, F0, 256, bar + 8 * MB_WV);
    tma2d(sb + R_T + 32768, &maps.wk, F0, 0, bar + 8 * MB_W0);
    if (!LORD) {
        for (int i = 0; i < 4; i++) tma2d(sb + R_WO + i * 16384, &maps.wo, (c & 1) * 256 + i * 64, (c >> 1) * 128, bar + 8 * MB_WO);
        tma2d(sb + R_T, &maps.wq, F0, 0, bar + 8 * MB_W0);
    }
    mbar_expect_tx(bar + 8 * MB_S, 1536);
}
__device__ __forceinline__ void rec_c(uint32_t sb, int c, const bf16* __restrict__ mem0, const Maps& maps, uint32_t epoch) {
    const int tid = threadIdx.x - WGC * 128, lane = tid & 31, u = tid >> 5;
    const uint32_t bar = sb + R_BAR;
    const int lrow = ((lane >> 4) << 3) + (lane & 7), lsel = (lane >> 3) & 1;
    const int kh = u >> 1, j = u & 1;
    uint32_t wv[32][4], mx, my = 0, mz = 0;
    {
        if (u == 0) {
            sts128u(sb + lane * 16 + R_LT, (lane >> 3) * 256 + (lane & 7) * 16, ((lane >> 2) & 1) * XHS + (lane >> 4) * XSS + (lane & 8) * 2 + (lane & 2) * 4,
                    (lane >> 2) * 256 + (lane & 3) * 16, (lane & 1) * XHS + ((lane >> 3) & 1) * XSS + (lane & 6) * 4 + (lane >> 4) * 4);
        }
        mbar_wait(bar + 8 * MB_WV, 0);
        if (c == 7 && tid == 0) GT(1425);
        if (LORD && tid == 32) {
            for (int i = 0; i < 4; i++) tma2d(sb + R_WO + i * 16384, &maps.wo, (c & 1) * 256 + i * 64, (c >> 1) * 128, bar + 8 * MB_WO);
            tma2d(sb + R_T, &maps.wq, c * 64, 0, bar + 8 * MB_W0);
        }
        __syncwarp();
#pragma unroll
        for (int kk = 0; kk < 16; kk++) {
            const uint32_t aa = sb + R_QK1 + kh * 32768 + wrow_off(kk, 4 * j + 2 * kh + lsel);
            ldsm4t(wv[kk], aa); ldsm4t(wv[16 + kk], aa ^ 32);
        }
        {
            uint32_t x = 0;
#pragma unroll
            for (int i = 0; i < 32; i++) x ^= wv[i][0];
            sts32(sb + R_MISC + 96 + u * 4, __reduce_xor_sync(0xffffffffu, x));
        }
        bar_sync(9, 128);
        if (c == 7 && tid == 0) GT(1423);
        if (tid == 0) {
            mbar_expect_tx(bar + 8 * MB_W1, 65536);
            tma2d(sb + R_QK1 + 32768, &maps.wk, c * 64, 256, bar + 8 * MB_W1); tma2d(sb + R_QK1, &maps.wq, c * 64, 256, bar + 8 * MB_W1);
        }
        __syncwarp();
        const float nv = frag_norm2(wv);
        if (lane == 0) sts32(sb + R_MISC + 64 + u * 4, FU(nv));
        __syncwarp();
        bar_arrive(0, 256);
        mx = put_mem0(sb, 4 + u, mem0);
    }
    const uint32_t rL = opaque(sb + lane * 16), rG = opaque(sb + lane * 16 + u * 1024);
    const uint32_t sbu = uni(sb), fo = uni(u), cc = uni(c), ep = uni(epoch);
    const uint64_t gx = xpage();
    const uint32_t ghi = uni((uint32_t)(gx >> 32)), glo = uni((uint32_t)gx);
    constexpr int CX = R_AX + NAX * 4096;
    static_assert(NAX + NCX <= 6, "AX");
#pragma unroll
    for (int i = 0; i < NCX; i++) {
        sts128u(rG + CX + 4096 * i, wv[i][0], wv[i][1], wv[i][2], wv[i][3]);
        sts128u(rG + CX + 4096 * i + 512, wv[16 + i][0], wv[16 + i][1], wv[16 + i][2], wv[16 + i][3]);
    }
    __syncwarp();
    TSDECL;
    uint32_t rpb = 0x3f800000u;
    bar_arrive(2, 256);
    uint32_t kvq = ~ep;
    auto ring = [&](int s) {
        uint32_t n = 0;
#pragma unroll 1
        while (!__all_sync(0xffffffffu, kvq == ep)) {
            kvq = ldg_rlx(&g_f.kv[(s + 2) >> 1][cc >> 1][(rL >> 4) & 1]);
            if (++n > SPIN_LIMIT) { ABORT(6); break; }
        }
        if (rL == sbu) load_slot(sbu, cc, (s + 2) >> 1, maps);
        __syncwarp();
    };
    if (fo == 3) { ring(-2); if (cc == 7 && rL == sbu) GT(1427); }
#pragma unroll 1
    for (int s = 0;; s++) {
        if (fo == 3 && !(s & 1) && s > 0 && s + 2 < NSEG) ring(s);
#pragma unroll
        for (int i = NCX - NCL; i < NCX; i++) { lds_fragv(wv[i], rG + CX + 4096 * i); lds_fragv(wv[16 + i], rG + CX + 4096 * i + 512); }
        PUT_MAX(rL, 4 + fo)
        if (fo == 0) {
                bar_sync(15, 256);
                if (s == 0) {
                    const uint32_t* np = (const uint32_t*)&g_f.norm[0] + ((rL ^ sbu) >> 2);
                    uint4 r, q; uint32_t n = 0;
#pragma unroll 1
                    while (true) {
                        r = ldg_rlx4(np); q = ldg_rlx4(np + 128);
                        const uint2 z = ldg_rlx2(&g_f.xn[(rL ^ sbu) >> 3]);
                        if (__all_sync(0xffffffffu, r.y == ep && r.w == ep && q.y == ep && q.w == ep && z.x == ep && z.y == ep)) break;
                        if (++n > SPIN_LIMIT) { ABORT(5); break; }
                    }
                    float nv = __uint_as_float(r.x) + __uint_as_float(q.x), no = __uint_as_float(r.z) + __uint_as_float(q.z);
#pragma unroll
                    for (int o = 16; o; o >>= 1) { nv += __shfl_xor_sync(0xffffffffu, nv, o); no += __shfl_xor_sync(0xffffffffu, no, o); }
                    const int lc = ((int)(FU(nv) >> 23) + (int)(FU(no) >> 23) - 252 + 9 + 1) >> 1;
                    sts32(sbu + R_MISC + 32, 140 - lc);
                    __syncwarp();
                }
                const uint4 ma = lds128uv(rL + R_STG + 1024), mb = lds128uv(rL + R_STG + 1536);
                const uint32_t m_ = amax2b(amax2b(amax2b(ma.x, ma.y), amax2b(ma.z, ma.w)), amax2b(amax2b(mb.x, mb.y), amax2b(mb.z, mb.w)));
                const int em = (int)(__reduce_max_sync(0xffffffffu, amax2b(m_, m_ << 16) & 0x7f800000u) >> 23) + (int)(rpb >> 23) - 127;
                const int es = min(max((int)lds32v_(sbu + R_MISC + 32) - max(em, 127), -60), 60);
                sts32(sbu + R_MISC + 40, (127 + es) << 23);
                TS(4, es);
        } else bar_arrive(15, 256);
        bar_sync(GOBAR, 96);
        float v0[4], v1[4];
        g1<CNB, SMC>(v0, v1, wv, wv + 16, rL + R_MEMB + (fo >> 1) * 4096, sbu - s, [&](int i, const uint32_t* c_) { if (i == 0) TS(0, c_[0]); });
        TS(1, FU(v1[3]));
        const uint32_t l16 = (rL ^ sbu) | (lds32v_(rL + R_LT + 4) & 1);
        const uint32_t r8 = sbu + (l16 >> 1);
        {
            sts128(rL + R_VRED + fo * 512, v1[0], v1[1], v1[2], v1[3]);
            const uint32_t d = r8 + R_VB + ((cc & 1) * 4 + (fo & 1) * 2 + (fo >> 1)) * 256;
            const uint32_t dr = xorv(d, 0x01000000u), br = xorv(sbu + R_BAR + 8 * MB_V, 0x01000000u);
            bar_sync(6 + (fo & 1), 64);
            const float4 a0 = lds128(rL + R_VRED + (fo ^ 2) * 512);
            const float rp = __uint_as_float(rpb);
            const uint32_t w0 = pack2((v0[0] + a0.x) * rp, (v0[1] + a0.y) * rp), w1 = pack2((v0[2] + a0.z) * rp, (v0[3] + a0.w) * rp);
            st_async2(dr, w0, w1, br);
            TS(3, w1);
            sts64(d, __uint_as_float(w0), __uint_as_float(w1));
            __syncwarp();
            asm volatile("{\n.reg .pred p;\nsetp.eq.u32 p, %0, %1;\n@p mbarrier.arrive.expect_tx.shared::cta.b64 _, [%2], 256;\n}"
                         :: "r"(rL), "r"(sbu), "r"(sbu + R_BAR + 8 * MB_V) : "memory");
        }
        if (fo == 1) {
            bar_sync(9, 192);
            uint8_t* dst = (uint8_t*)&g_KVf[s][cc >> 1][(cc & 1) * 256] + l16;
            const uint32_t r2 = prmt(rpb, 0, 0x3232u);
#pragma unroll
            for (int i = 0; i < 2; i++) {
                const uint4 a = lds128uv(rL + R_STG + i * 512);
                stg4(dst + i * 512, make_uint4(~hmul2b(a.x, r2), ~hmul2b(a.y, r2), ~hmul2b(a.z, r2), ~hmul2b(a.w, r2)));
                const float2 b0 = lds64v(r8 + R_VB + (cc & 1) * 1024 + i * 512), b1 = lds64v(r8 + R_VB + (cc & 1) * 1024 + i * 512 + 256);
                stg4(dst + 2048 + i * 512, make_uint4(~FU(b0.x), ~FU(b0.y), ~FU(b1.x), ~FU(b1.y)));
            }
            __syncwarp();
            if (l16 == 0) { stg_rlx(&g_f.rec[cc], (ep << 8) | (s + 1)); if (s == NSEG - 1) GT(1500 + cc); }
            __syncwarp();
        } else {
            bar_arrive(9, 192);
            if (fo == 2) {
                if (l16 < 144) stg4((void*)mkptr((glo + zero_off(cc, l16 >> 4)) ^ aslot(s + 4), ghi), make_uint4(0, 0, 0, 0));
                __syncwarp();
            } else if (fo == 3) {
                kvq = ldg_rlx(&g_f.kv[min((s + 3) >> 1, NT - 1)][cc >> 1][(l16 >> 4) & 1]);
                if (s == 0) ring(s);
            }
        }
        if (s == NSEG - 1) break;
        auto early = [&]() {
#pragma unroll
            for (int i = 0; i < NCX - NCL; i++) { lds_fragv(wv[i], rG + CX + 4096 * i); lds_fragv(wv[16 + i], rG + CX + 4096 * i + 512); }
        };
        GATHER(1, , early(); rpb = 0x7f000000u - lds32v_(sbu + R_MISC + 40);, bar_arrive(2, 256);)
    }
}

__device__ __forceinline__ bool cand_better(float v, int i, float bv, int bi) { return v > bv || (v == bv && i < bi); }

constexpr int G_W = 0;
constexpr int G_RING = 131072;
constexpr int G_BUF = 163840;
constexpr int G_BAR = 229376;
constexpr int G_SMEM = G_BAR + 512;
enum { GB_FULL = 0, GB_EMPTY = GB_FULL + 8, GB_KV = GB_EMPTY + 8, GB_STG = GB_KV + 2, GB_FREE = GB_STG + 2, GB_XN = GB_FREE + 2, GB_T1D, GB_FFN, GB_VV, GB_KVF = GB_VV + 2, GB_VF, GB_N };
constexpr int SMEM_TOTAL = 232448;

__device__ __forceinline__ void wgmma_n128(float* d, uint64_t da, uint64_t db, int scale_d) {
    asm volatile("{\n.reg .pred p;\nsetp.ne.b32 p, %66, 0;\n"
        "wgmma.mma_async.sync.aligned.m64n128k16.f32.bf16.bf16 "
        "{%0,%1,%2,%3,%4,%5,%6,%7,%8,%9,%10,%11,%12,%13,%14,%15,%16,%17,%18,%19,%20,%21,%22,%23,%24,%25,%26,%27,%28,%29,%30,%31,"
        "%32,%33,%34,%35,%36,%37,%38,%39,%40,%41,%42,%43,%44,%45,%46,%47,%48,%49,%50,%51,%52,%53,%54,%55,%56,%57,%58,%59,%60,%61,%62,%63}, "
        "%64, %65, p, 1, 1, 0, 1;\n}"
        : "+f"(d[0]), "+f"(d[1]), "+f"(d[2]), "+f"(d[3]), "+f"(d[4]), "+f"(d[5]), "+f"(d[6]), "+f"(d[7]), "+f"(d[8]), "+f"(d[9]), "+f"(d[10]), "+f"(d[11]),
          "+f"(d[12]), "+f"(d[13]), "+f"(d[14]), "+f"(d[15]), "+f"(d[16]), "+f"(d[17]), "+f"(d[18]), "+f"(d[19]), "+f"(d[20]), "+f"(d[21]), "+f"(d[22]), "+f"(d[23]),
          "+f"(d[24]), "+f"(d[25]), "+f"(d[26]), "+f"(d[27]), "+f"(d[28]), "+f"(d[29]), "+f"(d[30]), "+f"(d[31]), "+f"(d[32]), "+f"(d[33]), "+f"(d[34]), "+f"(d[35]),
          "+f"(d[36]), "+f"(d[37]), "+f"(d[38]), "+f"(d[39]), "+f"(d[40]), "+f"(d[41]), "+f"(d[42]), "+f"(d[43]), "+f"(d[44]), "+f"(d[45]), "+f"(d[46]), "+f"(d[47]),
          "+f"(d[48]), "+f"(d[49]), "+f"(d[50]), "+f"(d[51]), "+f"(d[52]), "+f"(d[53]), "+f"(d[54]), "+f"(d[55]), "+f"(d[56]), "+f"(d[57]), "+f"(d[58]), "+f"(d[59]),
          "+f"(d[60]), "+f"(d[61]), "+f"(d[62]), "+f"(d[63])
        : "l"(da), "l"(db), "r"(scale_d));
}

__device__ __forceinline__ constexpr uint32_t slot_off(int slot) {
    return slot < 2 ? G_RING + slot * 16384 : G_BUF + (slot & 1) * 32768 + (slot < 4 ? 16384 : 0);
}
constexpr int PO = (HSPLIT / 2) & 1;
template <int NSLOT, class F>
__device__ __forceinline__ void gemm_tile(float* acc, uint32_t sb, int tile, int it, int wg, bool pass, uint32_t l0, F&& hook) {
    const uint32_t bar = sb + G_BAR;
    bar_sync(3 + wg, 256);
    int prev = 0;
#pragma unroll
    for (int k = 0; k < 4; k++) {
        const int n = tile * 4 + k, slot = NSLOT == 4 ? k : n % NSLOT;
        const uint32_t sz = sb + (((it + k) << 4) & sb & 0x3f0);
        const uint64_t da = desc_sw128(sz + slot_off(slot), 16, 1024), db0 = desc_sw128(sz + G_W, 65536, 1024);
        mbar_wait_p(bar + 8 * (GB_FULL + slot), NSLOT == 4 ? (tile & 1) : ((n / NSLOT) & 1));
        if (k == 3 && pass) bar_arrive(3 + (wg ^ 1), 256);
        asm volatile("wgmma.fence.sync.aligned;" ::: "memory");
#pragma unroll
        for (int kk = 0; kk < 4; kk++) wgmma_n128(acc, da + kk * 2, db0 + k * 1024 + kk * 128, (k | kk) != 0);
        asm volatile("wgmma.commit_group.sync.aligned;" ::: "memory");
        if (k > 0) {
            asm volatile("wgmma.wait_group.sync.aligned 1;" ::: "memory");
            mbar_arrive2_if(bar + 8 * (GB_EMPTY + prev), l0);
        }
#pragma unroll
        for (int kk = 0; kk < 4; kk++) wgmma_n128(acc, da + 512 + kk * 2, db0 + k * 1024 + 512 + kk * 128, 1);
        asm volatile("wgmma.commit_group.sync.aligned;" ::: "memory");
        if (k == 1) hook();
        prev = slot;
    }
    asm volatile("wgmma.wait_group.sync.aligned 0;" ::: "memory");
    mbar_arrive2_if(bar + 8 * (GB_EMPTY + prev), l0);
}
__device__ __forceinline__ void stage_bf16(const float* acc, uint32_t buf, float s0, float s1) {
    const int lane = threadIdx.x & 31, wq = (threadIdx.x >> 5) & 3;
    const int row = wq * 16 + (lane & 7) + ((lane >> 3) & 1) * 8;
    const uint32_t base = buf + row * 128;
#pragma unroll
    for (int j = 0; j < 16; j += 2) {
        const int ch = (j & 7) + (lane >> 4);
        stsm4(base + (j >> 3) * 8192 + ((ch ^ (row & 7)) << 4),
              pack2(acc[4 * j] * s0, acc[4 * j + 1] * s0), pack2(acc[4 * j + 2] * s1, acc[4 * j + 3] * s1),
              pack2(acc[4 * j + 4] * s0, acc[4 * j + 5] * s0), pack2(acc[4 * j + 6] * s1, acc[4 * j + 7] * s1));
    }
}

__device__ __forceinline__ void store_perm(const float* acc, bf16* dst, int ld, float s0, float s1) {
#pragma unroll
    for (int i = 0; i < 4; i++) {
        const float* a = acc + 16 * i;
        *(uint4*)(dst + i * 32) = make_uint4(pack2(a[0] * s0, a[1] * s0), pack2(a[4] * s0, a[5] * s0), pack2(a[8] * s0, a[9] * s0), pack2(a[12] * s0, a[13] * s0));
        *(uint4*)(dst + 8 * ld + i * 32) = make_uint4(pack2(a[2] * s1, a[3] * s1), pack2(a[6] * s1, a[7] * s1), pack2(a[10] * s1, a[11] * s1), pack2(a[14] * s1, a[15] * s1));
    }
}
template <int ACC>
__device__ __forceinline__ void wgmma_rs64(float* d, const uint32_t* a, uint64_t db) {
    asm volatile("{\n.reg .pred p;\nsetp.ne.b32 p, %37, 0;\n"
        "wgmma.mma_async.sync.aligned.m64n64k16.f32.bf16.bf16 {%0,%1,%2,%3,%4,%5,%6,%7,%8,%9,%10,%11,%12,%13,%14,%15,%16,%17,%18,%19,%20,%21,%22,%23,%24,%25,%26,%27,%28,%29,%30,%31}, {%32,%33,%34,%35}, %36, p, 1, 1, 0;\n}"
        : "+f"(d[0]), "+f"(d[1]), "+f"(d[2]), "+f"(d[3]), "+f"(d[4]), "+f"(d[5]), "+f"(d[6]), "+f"(d[7]), "+f"(d[8]), "+f"(d[9]), "+f"(d[10]), "+f"(d[11]), "+f"(d[12]), "+f"(d[13]), "+f"(d[14]), "+f"(d[15]), "+f"(d[16]), "+f"(d[17]), "+f"(d[18]), "+f"(d[19]), "+f"(d[20]), "+f"(d[21]), "+f"(d[22]), "+f"(d[23]), "+f"(d[24]), "+f"(d[25]), "+f"(d[26]), "+f"(d[27]), "+f"(d[28]), "+f"(d[29]), "+f"(d[30]), "+f"(d[31])
        : "r"(a[0]), "r"(a[1]), "r"(a[2]), "r"(a[3]), "l"(db), "n"(ACC));
}
template <int ACC>
__device__ __forceinline__ void wgmma_rs128t(float* d, const uint32_t* a, uint64_t db) {
    asm volatile("{\n.reg .pred p;\nsetp.ne.b32 p, %69, 0;\n"
        "wgmma.mma_async.sync.aligned.m64n128k16.f32.bf16.bf16 {%0,%1,%2,%3,%4,%5,%6,%7,%8,%9,%10,%11,%12,%13,%14,%15,%16,%17,%18,%19,%20,%21,%22,%23,%24,%25,%26,%27,%28,%29,%30,%31,%32,%33,%34,%35,%36,%37,%38,%39,%40,%41,%42,%43,%44,%45,%46,%47,%48,%49,%50,%51,%52,%53,%54,%55,%56,%57,%58,%59,%60,%61,%62,%63}, {%64,%65,%66,%67}, %68, p, 1, 1, 1;\n}"
        : "+f"(d[0]), "+f"(d[1]), "+f"(d[2]), "+f"(d[3]), "+f"(d[4]), "+f"(d[5]), "+f"(d[6]), "+f"(d[7]), "+f"(d[8]), "+f"(d[9]), "+f"(d[10]), "+f"(d[11]), "+f"(d[12]), "+f"(d[13]), "+f"(d[14]), "+f"(d[15]), "+f"(d[16]), "+f"(d[17]), "+f"(d[18]), "+f"(d[19]), "+f"(d[20]), "+f"(d[21]), "+f"(d[22]), "+f"(d[23]), "+f"(d[24]), "+f"(d[25]), "+f"(d[26]), "+f"(d[27]), "+f"(d[28]), "+f"(d[29]), "+f"(d[30]), "+f"(d[31]), "+f"(d[32]), "+f"(d[33]), "+f"(d[34]), "+f"(d[35]), "+f"(d[36]), "+f"(d[37]), "+f"(d[38]), "+f"(d[39]), "+f"(d[40]), "+f"(d[41]), "+f"(d[42]), "+f"(d[43]), "+f"(d[44]), "+f"(d[45]), "+f"(d[46]), "+f"(d[47]), "+f"(d[48]), "+f"(d[49]), "+f"(d[50]), "+f"(d[51]), "+f"(d[52]), "+f"(d[53]), "+f"(d[54]), "+f"(d[55]), "+f"(d[56]), "+f"(d[57]), "+f"(d[58]), "+f"(d[59]), "+f"(d[60]), "+f"(d[61]), "+f"(d[62]), "+f"(d[63])
        : "r"(a[0]), "r"(a[1]), "r"(a[2]), "r"(a[3]), "l"(db), "n"(ACC));
}
__device__ __forceinline__ void attention_tile(float* acc, uint32_t sb, int tile, int h, int wg, int wq, uint32_t l0, uint32_t epoch, uint4* km, uint4* vm) {
    const uint32_t buf = sb + G_BUF + ((tile << 4) & sb & 0x3f0);
    const int lane = threadIdx.x & 31, g = lane >> 2, t = lane & 3;
    const int sg = wq >> 1, hf = wq & 1, seg = tile * 2 + sg;
    uint32_t qf[8][4];
#pragma unroll
    for (int kk = 0; kk < 8; kk++) {
        qf[kk][0] = pack2(acc[8 * kk], acc[8 * kk + 1]); qf[kk][1] = pack2(acc[8 * kk + 2], acc[8 * kk + 3]);
        qf[kk][2] = pack2(acc[8 * kk + 4], acc[8 * kk + 5]); qf[kk][3] = pack2(acc[8 * kk + 6], acc[8 * kk + 7]);
    }
    uint32_t* kvf = &g_KVf[seg][h][lane * 4];
    auto kv_valid = [&]() {
        uint32_t mn = 0xffffffffu;
#pragma unroll
        for (int i = 0; i < 4; i++) mn = min(min(min(mn, min(km[i].x, km[i].y)), min(km[i].z, km[i].w)), min(min(vm[i].x, vm[i].y), min(vm[i].z, vm[i].w)));
        return __all_sync(0xffffffffu, mn != 0);
    };
    float sc[5][4];
    auto mem_scores = [&]() {
        float sb_[4];
#pragma unroll
        for (int i = 0; i < 4; i++) { MMAF(i == 0, sc[4], qf[2 * i], ~km[i].x, ~km[i].y); MMAF(i == 0, sb_, qf[2 * i + 1], ~km[i].z, ~km[i].w); }
#pragma unroll
        for (int i = 0; i < 4; i++) sc[4][i] += sb_[i];
    };
    mbar_wait_p(sb + G_BAR + 8 * (GB_KV + wg), (tile >> 1) & 1);
    if (h == 5 && (threadIdx.x & 127) == 0 && tile < 6) GT(1750 + tile * 8 + 2);
    bool fast;
    {
        const uint64_t dk = desc_sw128(buf, 16, 1024);
        asm volatile("wgmma.fence.sync.aligned;" ::: "memory");
#pragma unroll
        for (int kk = 0; kk < 8; kk++) {
            if (kk == 0) wgmma_rs64<0>(acc, qf[kk], dk); else wgmma_rs64<1>(acc, qf[kk], dk + (kk >> 2) * 512 + (kk & 3) * 2);
        }
        asm volatile("wgmma.commit_group.sync.aligned;" ::: "memory");
        mem_scores();
        fast = kv_valid();
        asm volatile("wgmma.wait_group.sync.aligned 0;" ::: "memory");
        mbar_arrive_if(sb + G_BAR + 8 * GB_KVF, l0);
#pragma unroll
        for (int i = 0; i < 32; i++) asm volatile("" : "+f"(acc[i]) :: "memory");
#pragma unroll
        for (int b = 0; b < 4; b++)
#pragma unroll
            for (int i = 0; i < 4; i++) sc[b][i] = sg ? acc[16 + 4 * b + i] : acc[4 * b + i];
#pragma unroll
        for (int i = 0; i < 4; i++) sc[4][i] = fast ? sc[4][i] : -INFINITY;
    }
    const float cexp = 0.08838834764831845f * 1.4426950408889634f;
    const int r0 = hf * 16 + g, r1 = r0 + 8;
#pragma unroll
    for (int b = 0; b < 4; b++) {
        const int j = b * 8 + 2 * t;
        if (j > r0) sc[b][0] = -INFINITY;
        if (j + 1 > r0) sc[b][1] = -INFINITY;
        if (j > r1) sc[b][2] = -INFINITY;
        if (j + 1 > r1) sc[b][3] = -INFINITY;
    }
    float m0 = -INFINITY, m1 = -INFINITY;
#pragma unroll
    for (int b = 0; b < 5; b++) { m0 = fmaxf(m0, fmaxf(sc[b][0], sc[b][1])); m1 = fmaxf(m1, fmaxf(sc[b][2], sc[b][3])); }
    m0 = fmaxf(m0, __shfl_xor_sync(0xffffffffu, m0, 1)); m1 = fmaxf(m1, __shfl_xor_sync(0xffffffffu, m1, 1));
    m0 = fmaxf(m0, __shfl_xor_sync(0xffffffffu, m0, 2)); m1 = fmaxf(m1, __shfl_xor_sync(0xffffffffu, m1, 2));
    float z0 = 0.f, z1 = 0.f;
    uint32_t p0, p1;
    {
        const float c0 = -m0 * cexp, c1 = -m1 * cexp;
        uint32_t pf[5][2];
#pragma unroll
        for (int b = 0; b < 5; b++) {
            pf[b][0] = pack2(ex2(fmaf(sc[b][0], cexp, c0)), ex2(fmaf(sc[b][1], cexp, c0)));
            pf[b][1] = pack2(ex2(fmaf(sc[b][2], cexp, c1)), ex2(fmaf(sc[b][3], cexp, c1)));
        }
        p0 = pf[4][0]; p1 = pf[4][1];
        uint32_t pa[4][4];
#pragma unroll
        for (int kk = 0; kk < 4; kk++)
#pragma unroll
            for (int i = 0; i < 4; i++) pa[kk][i] = (kk >> 1) == sg ? pf[(kk & 1) * 2 + (i >> 1)][i & 1] : 0u;
        const uint64_t dv = desc_sw128(buf + 32768, 8192, 1024);
        mbar_wait_p(sb + G_BAR + 8 * (GB_VV + wg), (tile >> 1) & 1);
        asm volatile("wgmma.fence.sync.aligned;" ::: "memory");
#pragma unroll
        for (int kk = 0; kk < 4; kk++) { if (kk == 0) wgmma_rs128t<0>(acc, pa[kk], dv); else wgmma_rs128t<1>(acc, pa[kk], dv + kk * 128); }
        asm volatile("wgmma.commit_group.sync.aligned;" ::: "memory");
#pragma unroll
        for (int b = 0; b < 5; b++) { z0 += bf_lo(pf[b][0]) + bf_hi(pf[b][0]); z1 += bf_lo(pf[b][1]) + bf_hi(pf[b][1]); }
        asm volatile("wgmma.wait_group.sync.aligned 0;" ::: "memory");
#pragma unroll
        for (int i = 0; i < 64; i++) asm volatile("" : "+f"(acc[i]) :: "memory");
    }
    mbar_arrive_if(sb + G_BAR + 8 * GB_VF, l0);
    if (h == 5 && (threadIdx.x & 127) == 0 && tile < 6) GT(1750 + tile * 8 + 3);
    if (!fast) {
        wait_rec(&g_f.rec[2 * h], epoch, seg + 1);
        if (seg == 63 && (threadIdx.x & 63) == 0) GT(1570 + h);
        uint32_t n = 0;
#pragma unroll 1
        do {
#pragma unroll
            for (int i = 0; i < 4; i++) { km[i] = ldg_rlx4(kvf + i * 128); vm[i] = ldg_rlx4(kvf + 512 + i * 128); }
            if (++n > SPIN_LIMIT) { ABORT(4); break; }
        } while (!kv_valid());
        mem_scores();
        float n0 = fmaxf(sc[4][0], sc[4][1]), n1 = fmaxf(sc[4][2], sc[4][3]);
        n0 = fmaxf(n0, __shfl_xor_sync(0xffffffffu, n0, 1)); n1 = fmaxf(n1, __shfl_xor_sync(0xffffffffu, n1, 1));
        n0 = fmaxf(n0, __shfl_xor_sync(0xffffffffu, n0, 2)); n1 = fmaxf(n1, __shfl_xor_sync(0xffffffffu, n1, 2));
        n0 = fmaxf(n0, m0); n1 = fmaxf(n1, m1);
        const float a0 = ex2((m0 - n0) * cexp), a1 = ex2((m1 - n1) * cexp);
        const float c0 = -n0 * cexp, c1 = -n1 * cexp;
        p0 = pack2(ex2(fmaf(sc[4][0], cexp, c0)), ex2(fmaf(sc[4][1], cexp, c0)));
        p1 = pack2(ex2(fmaf(sc[4][2], cexp, c1)), ex2(fmaf(sc[4][3], cexp, c1)));
        z0 = fmaf(z0, a0, bf_lo(p0) + bf_hi(p0)); z1 = fmaf(z1, a1, bf_lo(p1) + bf_hi(p1));
#pragma unroll
        for (int j = 0; j < 16; j++) { float* o = acc + 4 * j; o[0] *= a0; o[1] *= a0; o[2] *= a1; o[3] *= a1; }
    }
    if (h == 5 && (threadIdx.x & 127) == 0 && tile < 6) GT(1750 + tile * 8 + 4);
    if (hf) bar_arrive(5 + wg * 2 + sg, 64);
#pragma unroll
    for (int i = 0; i < 4; i++) {
        mma1688(acc + 16 * i, p0, p1, ~vm[i].x); mma1688(acc + 16 * i + 4, p0, p1, ~vm[i].y);
        mma1688(acc + 16 * i + 8, p0, p1, ~vm[i].z); mma1688(acc + 16 * i + 12, p0, p1, ~vm[i].w);
    }
    z0 += __shfl_xor_sync(0xffffffffu, z0, 1); z1 += __shfl_xor_sync(0xffffffffu, z1, 1);
    z0 += __shfl_xor_sync(0xffffffffu, z0, 2); z1 += __shfl_xor_sync(0xffffffffu, z1, 2);
    if (h == 5 && (threadIdx.x & 127) == 0 && tile < 6) GT(1750 + tile * 8 + 5);
    if (tile >= 2) mbar_wait_p(sb + G_BAR + 8 * (GB_FREE + wg), ((tile >> 1) - 1 + PO) & 1);
    store_perm(acc, g_O + (size_t)(tile * 64 + wq * 16 + g) * HD + h * 128 + t * 8, HD, rcpf(z0), rcpf(z1));
    mbar_arrive(sb + G_BAR + 8 * (GB_STG + wg));
    if (!hf) {
        bar_sync(5 + wg * 2 + sg, 64);
#pragma unroll
        for (int i = 0; i < 8; i++) stg4_h(kvf + i * 128, make_uint4(0, 0, 0, 0), pol_ef(3));
    }
}

constexpr int NWK = FF / 64;
constexpr int F_X = 229888, F_ACT = F_X + 2080, F_SEL = F_ACT + 288;
static_assert(F_SEL + 32 <= SMEM_TOTAL, "smem");
__device__ __noinline__ void ffn_phase(int c, uint32_t epoch, bf16* __restrict__ out) {
    extern __shared__ __align__(1024) uint8_t smem[];
    const uint32_t sb = smem_u32(smem);
    const int tid = threadIdx.x;
    const bool worker = c < NWK;
    const int nthr = worker ? 128 : 384;
    int p0 = -1, p1 = -1;
    float pb = 0.f;
#pragma unroll 1
    for (int pass = 0; pass < 2; pass++) {
        if (tid < 32) {
            const uint32_t tag = epoch & 0xfffffu;
            uint4 r[4]; uint32_t n = 0;
            const int t3 = tid + 96 < NFW ? tid + 96 : tid;
#pragma unroll 1
            while (true) {
                bool ok = true;
#pragma unroll
                for (int i = 0; i < 4; i++) r[i] = ldg_rlx4((const uint32_t*)&g_f.cand[pass][i < 3 ? tid + 32 * i : t3]);
#pragma unroll
                for (int i = 0; i < 4; i++) ok = ok && (r[i].y >> 12) == tag && (r[i].w >> 12) == tag;
                if (__all_sync(0xffffffffu, ok)) break;
                if (pass == 0) __nanosleep(100);
                if (++n > SPIN_LIMIT) { ABORT(7); break; }
            }
            bool chg = pass == 0;
#pragma unroll
            for (int i = 0; i < 4; i++) {
                const int j0 = r[i].y & 4095, j1 = r[i].w & 4095;
                chg = chg || (j0 != p0 && cand_better(__uint_as_float(r[i].x), j0, pb, p1)) || (j1 != p0 && cand_better(__uint_as_float(r[i].z), j1, pb, p1));
            }
            int* sel = (int*)(smem + F_SEL);
            if (__any_sync(0xffffffffu, chg)) {
                float b0 = __uint_as_float(r[0].x), b1 = __uint_as_float(r[0].z); int i0 = r[0].y & 4095, i1 = r[0].w & 4095;
#pragma unroll
                for (int i = 1; i < 9; i++) {
                    float c0, c1; int j0, j1;
                    if (i < 4) { c0 = __uint_as_float(r[i].x); c1 = __uint_as_float(r[i].z); j0 = r[i].y & 4095; j1 = r[i].w & 4095; }
                    else {
                        const int o = 1 << (i - 4);
                        c0 = __shfl_xor_sync(0xffffffffu, b0, o); c1 = __shfl_xor_sync(0xffffffffu, b1, o);
                        j0 = __shfl_xor_sync(0xffffffffu, i0, o); j1 = __shfl_xor_sync(0xffffffffu, i1, o);
                    }
                    if (i != 3 || t3 != tid) {
                        if (cand_better(c0, j0, b0, i0)) {
                            if (cand_better(c1, j1, b0, i0)) { b1 = c1; i1 = j1; } else { b1 = b0; i1 = i0; }
                            b0 = c0; i0 = j0;
                        } else if (cand_better(c0, j0, b1, i1)) { b1 = c0; i1 = j0; }
                    }
                }
                n = 0;
#pragma unroll 1
                while (!__all_sync(0xffffffffu, (ldg_rlx(&g_f.rows[pass][tid]) == epoch) & (ldg_rlx(&g_f.rows[pass][tid + 32]) == epoch) &
                                                   (ldg_rlx(&g_f.rows[pass][tid + 64]) == epoch) & (ldg_rlx(&g_f.rows[pass][t3]) == epoch))) { if (++n > SPIN_LIMIT) { ABORT(7); break; } }
                if (tid == 0) { sel[0] = min(i0, SQ - 1); sel[1] = min(i1, SQ - 1); ((float*)sel)[2] = b0; ((float*)sel)[3] = b1; }
            }
            if (pass && tid == 0 && c == 3) GT(1440);
        }
        bar_sync(1, nthr);
        const int t0 = ((int*)(smem + F_SEL))[0], t1 = ((int*)(smem + F_SEL))[1];
        if (c == 3 && tid == 0 && pass == 0) GT(1430);
        if (t0 == p0 && t1 == p1) break;
        pb = ((float*)(smem + F_SEL))[3];
        const uint32_t ytag = epoch * 2 + pass + 1;
        if (worker) {
            const int lane = tid & 31, w = tid >> 5, g = lane >> 2, t = lane & 3;
            const int lrow = ((lane >> 4) << 3) + (lane & 7), lsel = (lane >> 3) & 1;
            *(uint4*)(smem + F_X + (tid >> 6) * 1040 + (tid & 63) * 16) = __ldcg((const uint4*)(g_hn + (size_t)(tid >> 6 ? t1 : t0) * DM) + (tid & 63));
            mbar_wait(sb + G_BAR + 8 * GB_FFN, 0);
            if (c == 3 && tid == 0 && pass == 0) GT(1431);
            bar_sync(1, 128);
            {
                float dg[2][4], du[2][4];
                const uint32_t wa = sb + G_W + lrow * 128 + (((2 * w + lsel) ^ (lane & 7)) << 4), xa = sb + F_X + (lane & 1) * 1040 + (lane >> 3) * 16;
#pragma unroll 4
                for (int k2 = 0; k2 < 16; k2++) {
                    uint32_t xb[4], a0[4], a1[4], a2[4], a3[4];
                    ldsm4(xb, xa + k2 * 64);
                    ldsm4t(a0, wa + k2 * 4096); ldsm4t(a1, wa + k2 * 4096 + 65536); ldsm4t(a2, wa + k2 * 4096 + 2048); ldsm4t(a3, wa + k2 * 4096 + 67584);
                    if (k2 == 0) { for (int i = 0; i < 4; i++) dg[0][i] = dg[1][i] = du[0][i] = du[1][i] = 0.f; }
                    MMA(dg[0], a0, xb[0], xb[1]); MMA(du[0], a1, xb[0], xb[1]); MMA(dg[1], a2, xb[2], xb[3]); MMA(du[1], a3, xb[2], xb[3]);
                }
                const float gs = rbf(t == 0 ? dg[0][0] + dg[1][0] : (t == 1 ? dg[0][1] + dg[1][1] : (t == 2 ? dg[0][2] + dg[1][2] : dg[0][3] + dg[1][3])));
                const float us = rbf(t == 0 ? du[0][0] + du[1][0] : (t == 1 ? du[0][1] + du[1][1] : (t == 2 ? du[0][2] + du[1][2] : du[0][3] + du[1][3])));
                ((bf16*)(smem + F_ACT))[(t & 1) * 72 + w * 16 + (t >> 1) * 8 + g] = __float2bfloat16_rn(rbf(gs / (1.f + __expf(-gs))) * us);
            }
            bar_sync(1, 128);
            uint32_t ab[2][4];
            ldsm4(ab[0], sb + F_ACT + (lane & 1) * 144 + (lane >> 3) * 16); ldsm4(ab[1], sb + F_ACT + (lane & 1) * 144 + (lane >> 3) * 16 + 64);
#pragma unroll
            for (int h = 0; h < 2; h++) {
                float d[4][4];
#pragma unroll
                for (int kk = 0; kk < 4; kk++) {
#pragma unroll
                    for (int m = 0; m < 4; m++) {
                        uint32_t a[4];
                        ldsm4t(a, sb + slot_off(w) + h * 8192 + (kk * 16 + lrow) * 128 + (((m * 2 + lsel) ^ (lane & 7)) << 4));
                        MMAF(kk == 0, d[m], a, ab[kk >> 1][(kk & 1) * 2], ab[kk >> 1][(kk & 1) * 2 + 1]);
                    }
                }
                const float e0 = t == 0 ? d[0][0] : (t == 1 ? d[1][0] : (t == 2 ? d[2][0] : d[3][0])), e1 = t == 0 ? d[0][1] : (t == 1 ? d[1][1] : (t == 2 ? d[2][1] : d[3][1]));
                const float e2 = t == 0 ? d[0][2] : (t == 1 ? d[1][2] : (t == 2 ? d[2][2] : d[3][2])), e3 = t == 0 ? d[0][3] : (t == 1 ? d[1][3] : (t == 2 ? d[2][3] : d[3][3]));
                uint4* yp = &g_yp[pass][c][w * 128 + h * 64 + t * 16 + g];
                stg4(yp, make_uint4(FU(e0), ytag, FU(e1), ytag)); stg4(yp + 8, make_uint4(FU(e2), ytag, FU(e3), ytag));
            }
            if (c == 3 && tid == 0 && pass == 0) GT(1432);
        } else {
            const int j = tid & 127, part = tid >> 7, col = (c - NWK) * 128 + j;
            const int tok = part ? t1 : t0, old = part ? p1 : p0;
            float hv = 0.f, nv = 0.f;
            if (part < 2) {
                hv = __bfloat162float(__ldcg(g_h + (size_t)tok * DM + col)); nv = __bfloat162float(__ldcg(g_hn + (size_t)tok * DM + col));
                if (old >= 0 && old != t0 && old != t1)
                    out[(size_t)old * DM + col] = __float2bfloat16_rn(__bfloat162float(__ldcg(g_h + (size_t)old * DM + col)) + __bfloat162float(__ldcg(g_hn + (size_t)old * DM + col)));
            }
            float s0 = 0.f, s1 = 0.f;
            uint4 v[10]; uint32_t n = 0;
            bool ok;
#pragma unroll 1
            do {
                ok = true;
#pragma unroll
                for (int i = 0; i < 10; i++) {
                    const int src = part + 3 * i;
                    v[i] = src < NWK ? ldg_rlx4((const uint32_t*)&g_yp[pass][src][col]) : make_uint4(0, ytag, 0, ytag);
                }
#pragma unroll
                for (int i = 0; i < 10; i++) ok = ok && v[i].y == ytag && v[i].w == ytag;
                if (!ok) __nanosleep(100);
                if (++n > SPIN_LIMIT) { ABORT(7); break; }
            } while (!ok);
#pragma unroll
            for (int i = 0; i < 10; i++) { s0 += __uint_as_float(v[i].x); s1 += __uint_as_float(v[i].z); }
            float2* red = (float2*)smem;
            red[part * 128 + j] = make_float2(s0, s1);
            bar_sync(1, 384);
            if (part < 2) {
                float y = 0.f;
#pragma unroll
                for (int i = 0; i < 3; i++) y += ((const float*)red)[(i * 128 + j) * 2 + part];
                const float rs = rbf(1.f / (1.f + __expf(-((float*)(smem + F_SEL))[2 + part])));
                out[(size_t)tok * DM + col] = __float2bfloat16_rn(hv + rbf(nv + rbf(rbf(y) * rs)));
            }
            if (tid == 0 && pass == 0 && c == NWK) GT(1434);
        }
        p0 = t0; p1 = t1;
        if (c == 3 && tid == 0 && pass == 0) GT(1433);
        bar_sync(1, nthr);
    }
}

__device__ __forceinline__ void g_consumer(uint32_t sb_, int g_, int wg_, uint32_t epoch) {
    const uint32_t sb = uni(sb_);
    const int g = uni(g_), wg = uni(wg_), wq = uni((threadIdx.x >> 5) & 3);
    const uint32_t l0 = opaque((threadIdx.x & 31) == 0);
    const uint32_t bar = sb + G_BAR, buf = sb + G_BUF + wg * 32768;
    const int lane = threadIdx.x & 31;
    float acc[64];
    if (wg == 1) bar_arrive(3, 256);
    const int n1 = g < 32 ? HSPLIT / 2 : NT - HSPLIT / 2;
#pragma unroll 1
    for (int i = 0; i < n1; i++) {
        gemm_tile<4>(acc, sb, wg, i, wg, true, l0, []() {});
        if (threadIdx.x == 0 && i == 0) GT((64 + g) * 8 + 1);
        if (threadIdx.x == 128 && i == 3) GT((64 + g) * 8 + 2);
        if (i > 0) mbar_wait_p(bar + 8 * (GB_FREE + wg), (i - 1) & 1);
        stage_bf16(acc, buf, 1.f, 1.f);
        asm volatile("fence.proxy.async.shared::cta;" ::: "memory");
        mbar_arrive(bar + 8 * (GB_STG + wg));
    }
    if (threadIdx.x == 128) GT((64 + g) * 8 + 3);
    if (g < 32) {
#pragma unroll 1
        for (int i = 0; i < NT / 2; i++) {
            const int tile = 2 * i + wg;
            const uint2 rec = ldg_rlx2(&g_f.rec[2 * g]);
            uint4 km[4], vm[4];
            gemm_tile<4>(acc, sb, tile, i, wg, tile != NT - 1, l0, [&]() {
                const uint32_t seg = tile * 2 + (wq >> 1);
                const uint32_t* kvf = &g_KVf[seg][g][lane * 4];
                const bool early = (rec.x >> 8) == epoch && (rec.y >> 8) == epoch && (rec.x & 255) > seg && (rec.y & 255) > seg;
#pragma unroll
                for (int j = 0; j < 4; j++) { km[j] = ldg_rlx4_if(kvf + j * 128, early); vm[j] = ldg_rlx4_if(kvf + 512 + j * 128, early); }
            });
            if (threadIdx.x == 0 && i == 0) GT((64 + g) * 8 + 4);
            if (threadIdx.x == 128 && i == 3) GT((64 + g) * 8 + 5);
            if (g == 5 && (threadIdx.x & 127) == 0 && tile < 6) GT(1750 + tile * 8 + 1);
            attention_tile(acc, sb, tile, g, wg, wq, l0, epoch, km, vm);
            if (g == 5 && (threadIdx.x & 127) == 0 && tile < 6) GT(1750 + tile * 8 + 6);
        }
    } else {
#pragma unroll 1
        for (int i = 0; i < NT / 2; i++) {
            const int tile = 2 * i + wg;
            gemm_tile<NS3>(acc, sb, tile, i, wg, tile != NT - 1, l0, []() {});
            if (threadIdx.x == 0 && i == 0) GT((64 + g) * 8 + 4);
            if (threadIdx.x == 128 && i == 3) GT((64 + g) * 8 + 5);
            mbar_wait_p(bar + 8 * (GB_FREE + wg), (i - 1 + PO) & 1);
            store_perm(acc, g_P + (size_t)(((g - 32) >> 2) * SQ + tile * 64 + wq * 16 + (lane >> 2)) * DM + ((g - 32) & 3) * 128 + (lane & 3) * 8, DM, 1.f, 1.f);
            mbar_arrive(bar + 8 * (GB_STG + wg));
        }
    }
}

__device__ __forceinline__ void load_w(uint32_t sb, const CUtensorMap* tm, int col, int k) {
    tma2d_h(sb + G_W + k * 16384, tm, col, k * 128, sb + G_BAR + 8 * (GB_FULL + k), pol_ef(5));
    tma2d_h(sb + G_W + 65536 + k * 16384, tm, col + 64, k * 128, sb + G_BAR + 8 * (GB_FULL + k), pol_ef(5));
}

__device__ __forceinline__ void rbf2(float& a, float& b) { uint32_t w = pack2(a, b); a = bf_lo(w); b = bf_hi(w); }
__device__ __forceinline__ void warp_sum2(float& a, float& b) {
#pragma unroll
    for (int o = 16; o; o >>= 1) { float c = __shfl_xor_sync(0xffffffffu, a, o), d = __shfl_xor_sync(0xffffffffu, b, o); a += c; b += d; }
}
__device__ __forceinline__ float sum16(const float* v) {
    return (((v[0] + v[1]) + (v[2] + v[3])) + ((v[4] + v[5]) + (v[6] + v[7]))) + (((v[8] + v[9]) + (v[10] + v[11])) + ((v[12] + v[13]) + (v[14] + v[15])));
}
__device__ __forceinline__ void ln_row2(float* v, float* u) {
    float sv = sum16(v), su = sum16(u);
    warp_sum2(sv, su);
    const float mv = sv * (1.f / DM), mu = su * (1.f / DM);
    float qv = 0.f, qu = 0.f, qv2 = 0.f, qu2 = 0.f;
#pragma unroll
    for (int i = 0; i < 16; i += 2) {
        float d0 = v[i] - mv, d1 = v[i + 1] - mv, e0 = u[i] - mu, e1 = u[i + 1] - mu;
        qv = fmaf(d0, d0, qv); qv2 = fmaf(d1, d1, qv2); qu = fmaf(e0, e0, qu); qu2 = fmaf(e1, e1, qu2);
    }
    qv += qv2; qu += qu2;
    warp_sum2(qv, qu);
    const float rv = rbf(mv), ru = rbf(mu);
    const float iv = __frcp_rn(rbf(sqrtf(rbf(rbf(qv * (1.f / DM)) + 1e-5f)))), iu = __frcp_rn(rbf(sqrtf(rbf(rbf(qu * (1.f / DM)) + 1e-5f))));
#pragma unroll
    for (int i = 0; i < 16; i += 2) {
        float a = v[i] - rv, b = v[i + 1] - rv, c = u[i] - ru, d = u[i + 1] - ru;
        rbf2(a, b); rbf2(c, d);
        a *= iv; b *= iv; c *= iu; d *= iu;
        rbf2(a, b); rbf2(c, d);
        v[i] = a; v[i + 1] = b; u[i] = c; u[i + 1] = d;
    }
}

__device__ __forceinline__ void ln_row1(float* v) {
    float sv = sum16(v);
#pragma unroll
    for (int o = 16; o; o >>= 1) sv += __shfl_xor_sync(0xffffffffu, sv, o);
    const float mv = sv * (1.f / DM);
    float qv = 0.f, qv2 = 0.f;
#pragma unroll
    for (int i = 0; i < 16; i += 2) { float d0 = v[i] - mv, d1 = v[i + 1] - mv; qv = fmaf(d0, d0, qv); qv2 = fmaf(d1, d1, qv2); }
    qv += qv2;
#pragma unroll
    for (int o = 16; o; o >>= 1) qv += __shfl_xor_sync(0xffffffffu, qv, o);
    const float rv = rbf(mv);
    float sq, iv;
    asm("sqrt.approx.f32 %0, %1;" : "=f"(sq) : "f"(rbf(rbf(qv * (1.f / DM)) + 1e-5f)));
    asm("rcp.approx.f32 %0, %1;" : "=f"(iv) : "f"(rbf(sq)));
#pragma unroll
    for (int i = 0; i < 16; i += 2) {
        float a = v[i] - rv, b = v[i + 1] - rv;
        rbf2(a, b);
        a *= iv; b *= iv;
        rbf2(a, b);
        v[i] = a; v[i + 1] = b;
    }
}
constexpr int FSPLIT = 28;
__device__ __forceinline__ int fin_row(int id, int i) {
    if (id < 64) { const int tile = i < FSPLIT / 2 ? 2 * i : i + FSPLIT / 2; return tile < NT ? tile * 64 + id : -1; }
    const int j = id - 64 + i * 48;
    return j < FSPLIT * 32 ? (j >> 6) * 128 + 64 + (j & 63) : -1;
}
__device__ __forceinline__ void finalizer(int id, const bf16* __restrict__ x, const bf16* __restrict__ wr, bf16* __restrict__ out, uint32_t epoch, const bf16* pf) {
    const int lane = threadIdx.x & 31;
    float b0 = -INFINITY, b1 = -INFINITY; int i0 = 0x7fffffff, i1 = 0x7fffffff;
    const uint32_t tag = (epoch & 0xfffffu) << 12;
    uint32_t fl = ~epoch;
    int row = fin_row(id, 0);
    const uint4 ra = *(const uint4*)(wr + lane * 8), rb = *(const uint4*)(wr + 256 + lane * 8);
    uint4 xa = *(const uint4*)(x + (size_t)row * DM + lane * 8), xb = *(const uint4*)(x + (size_t)row * DM + lane * 8 + 256);
#pragma unroll 1
    for (int it = 0; row >= 0; it++) {
        const int tile = row >> 6, nxt = fin_row(id, it + 1);
        const size_t o0 = (size_t)row * DM + lane * 8;
        uint32_t n = 0;
#pragma unroll 1
        while (!__all_sync(0xffffffffu, fl == epoch)) {
            if (n) __nanosleep(it ? 64 : 1000);
            fl = ldg_rlx(&g_f.p[tile][lane]);
            if (++n > SPIN_LIMIT) { ABORT(12); break; }
        }
        if (tile == NT - 1 && id == 63 && lane == 0) GT(1438);
        if ((id == 63 || id == 3 || id == 70) && lane == 0) GT(1800 + (id == 3) * 32 + tile);
        if (PFF && pf && lane == 0 && (unsigned)(it - PFF) < 7u)
            asm volatile("cp.async.bulk.prefetch.L2.global [%0], %1;" :: "l"(pf + (size_t)((id & 15) * 7 + it - PFF) * 8192), "r"(16384) : "memory");
        float v[16];
        {
            uint4 pa[8][2];
#pragma unroll
            for (int k = 0; k < 8; k++) {
                pa[k][0] = ldg4_h(g_P + (size_t)k * SQ * DM + o0, pol_ef(2));
                pa[k][1] = ldg4_h(g_P + (size_t)k * SQ * DM + o0 + 256, pol_ef(2));
            }
            fl = ldg_rlx(&g_f.p[max(nxt, 0) >> 6][lane]);
#pragma unroll
            for (int j = 0; j < 2; j++) {
#pragma unroll
                for (int i = 0; i < 4; i++) {
                    uint32_t w[8];
#pragma unroll
                    for (int k = 0; k < 8; k++) w[k] = i == 0 ? pa[k][j].x : (i == 1 ? pa[k][j].y : (i == 2 ? pa[k][j].z : pa[k][j].w));
                    v[j * 8 + 2 * i] = ((bf_lo(w[0]) + bf_lo(w[1])) + (bf_lo(w[2]) + bf_lo(w[3]))) + ((bf_lo(w[4]) + bf_lo(w[5])) + (bf_lo(w[6]) + bf_lo(w[7])));
                    v[j * 8 + 2 * i + 1] = ((bf_hi(w[0]) + bf_hi(w[1])) + (bf_hi(w[2]) + bf_hi(w[3]))) + ((bf_hi(w[4]) + bf_hi(w[5])) + (bf_hi(w[6]) + bf_hi(w[7])));
                }
            }
        }
        uint32_t hw[8];
        {
            const uint32_t xw[8] = {xa.x, xa.y, xa.z, xa.w, xb.x, xb.y, xb.z, xb.w};
            uint32_t aw[8];
#pragma unroll
            for (int i = 0; i < 8; i++) aw[i] = pack2(v[2 * i], v[2 * i + 1]);
#pragma unroll
            for (int d = 1; d <= 2; d++) {
                const bool up = lane & d;
#pragma unroll
                for (int i = 0; i < 8; i++) {
                    if (!(i & d)) {
                        const uint32_t r = __shfl_xor_sync(0xffffffffu, up ? aw[i] : aw[i | d], d);
                        if (up) aw[i] = r; else aw[i | d] = r;
                    }
                }
            }
#pragma unroll
            for (int i = 0; i < 8; i++) {
                hw[i] = pack2(bf_lo(aw[i]) + bf_lo(xw[i]), bf_hi(aw[i]) + bf_hi(xw[i]));
                v[2 * i] = bf_lo(hw[i]); v[2 * i + 1] = bf_hi(hw[i]);
            }
        }
        xa = *(const uint4*)(x + (size_t)max(nxt, 0) * DM + lane * 8); xb = *(const uint4*)(x + (size_t)max(nxt, 0) * DM + lane * 8 + 256);
        ln_row1(v);
        float r0 = 0.f, r1 = 0.f;
        {
            const uint32_t ww[8] = {ra.x, ra.y, ra.z, ra.w, rb.x, rb.y, rb.z, rb.w};
#pragma unroll
            for (int i = 0; i < 8; i++) { r0 = fmaf(v[2 * i], bf_lo(ww[i]), r0); r1 = fmaf(v[2 * i + 1], bf_hi(ww[i]), r1); }
        }
        r0 += r1;
#pragma unroll
        for (int o = 16; o; o >>= 1) r0 += __shfl_xor_sync(0xffffffffu, r0, o);
        r0 = rbf(r0);
        if (cand_better(r0, row, b0, i0)) { b1 = b0; i1 = i0; b0 = r0; i0 = row; }
        else if (cand_better(r0, row, b1, i1)) { b1 = r0; i1 = row; }
        if (tile == NT - 1 && id == 63 && lane == 0) GT(1439);
        const bool keep = i0 == row || i1 == row || i1 >= SQ || row == SQ - 1;
        const bool last = nxt < 0, spec = tile < SPEC_TILES && (last || (nxt >> 6) >= SPEC_TILES);
        const bool pub = (lane == 0 && spec) || (lane == 1 && last);
        if (pub)
            asm volatile("st.relaxed.gpu.global.v4.b32 [%0], {%1,%2,%3,%4};" :: "l"(&g_f.cand[lane][id]),
                         "r"(FU(b0)), "r"(tag | (uint32_t)min(i0, 4095)), "r"(FU(b1)), "r"(tag | (uint32_t)min(i1, 4095)) : "memory");
#pragma unroll
        for (int j = 0; j < 2; j++) {
            const uint32_t* hh = hw + j * 4; const float* nn = v + j * 8;
            stg4_h(out + o0 + j * 256, make_uint4(pack2(bf_lo(hh[0]) + nn[0], bf_hi(hh[0]) + nn[1]), pack2(bf_lo(hh[1]) + nn[2], bf_hi(hh[1]) + nn[3]),
                                                  pack2(bf_lo(hh[2]) + nn[4], bf_hi(hh[2]) + nn[5]), pack2(bf_lo(hh[3]) + nn[6], bf_hi(hh[3]) + nn[7])), pol_ef(4));
            if (keep) {
                *(uint4*)(g_h + o0 + j * 256) = make_uint4(hh[0], hh[1], hh[2], hh[3]);
                *(uint4*)(g_hn + o0 + j * 256) = make_uint4(pack2(nn[0], nn[1]), pack2(nn[2], nn[3]), pack2(nn[4], nn[5]), pack2(nn[6], nn[7]));
            }
        }
        if (keep) { __threadfence(); __syncwarp(); }
        if (pub) stg_rlx(&g_f.rows[lane][id], epoch);
        row = nxt;
    }
    if (id == 0 && lane == 0) { g_epoch = epoch; if (epoch == 0xffffffu) { g_ticket[0] = 0; g_ticket[32] = 0; } }
}

__device__ __forceinline__ void g_producer(uint32_t sb, int g, const Maps& maps, uint32_t epoch, const bf16* __restrict__ x, const bf16* __restrict__ wr, bf16* __restrict__ out) {
    const uint32_t bar = sb + G_BAR;
    const int warp = (threadIdx.x >> 5) - 8;
    if (threadIdx.x == 256 && g == 5) GT(1410);
    if (threadIdx.x == 256 && g == 5) GT(1411);
    if (warp == 3) {
        wait_eq4(&g_f.xn[(threadIdx.x & 31) * 4], epoch, 13);
        __syncwarp();
        if ((threadIdx.x & 31) == 0) mbar_arrive(bar + 8 * GB_XN);
        finalizer(g, x, wr, out, epoch, nullptr);
        if (g == 63 && (threadIdx.x & 31) == 0) GT(128 * 8 + 6);
    }
    if ((threadIdx.x & 31) != 0) return;
    if (threadIdx.x == 256 && g == 5) GT(1412);
    if (warp == 0) {
        wait_eq4(&g_f.xn[0], epoch, 13);
        const int rk = g & 1;
        const int m1 = g < 32 ? HSPLIT : 2 * NT - HSPLIT;
        const int mx = g < 32 ? m1 + NT : m1;
#pragma unroll 1
        for (int it = 0; it < mx; it++) {
            const int tile = g < 32 ? (it < m1 ? it : it - m1) : (it < NT ? it : it - NT + HSPLIT);
            if (it == 1) wait_eq4(&g_f.xn[4], epoch, 13);
            if (it == 2) mbar_wait(bar + 8 * GB_XN, 0);
            const bool nw = it == 0 || it == (g < 32 ? m1 : NT);
#pragma unroll
            for (int k = 0; k < 4; k++) {
                mbar_wait(bar + 8 * (GB_EMPTY + k), (it & 1) ^ 1);
                mbar_expect_tx(bar + 8 * (GB_FULL + k), nw ? 49152 : 16384);
                tma2d_mc(sb + slot_off(k) + rk * 8192, &maps.xn2, (k * 2 + rk) * 64, tile * 64, bar + 8 * (GB_FULL + k));
                if (nw && (it > 0 || k >= 2))
                    load_w(sb, it > 0 && g < 32 ? &maps.wq4 : ((g & 1) ? &maps.wv4 : &maps.wk4), it == 0 ? (g >> 1) * 128 : (g < 32 ? g * 128 : ((g - 32) >> 1) * 128), k);
            }
        }
        if (g < NWK) {
#pragma unroll 1
            for (int j = 0; j < 12 + FFD; j++) {
                if (j >= FFD) mbar_wait(bar + 8 * (GB_FULL + ((j - FFD) & 3)), (mx + ((j - FFD) >> 2)) & 1);
                if (j < 12) {
                    const int k = j & 3;
                    const uint32_t mb = bar + 8 * (GB_FULL + k);
                    if (j < 4) mbar_wait(bar + 8 * (GB_EMPTY + k), (mx & 1) ^ 1);
                    mbar_expect_tx(mb, 16384);
                    if (j < 8) tma2d_h(sb + G_W + (j >> 2) * 65536 + k * 16384, j < 4 ? &maps.wg : &maps.wu, g * 64, k * 128, mb, pol_ef(5));
                    else { tma2d_h(sb + slot_off(k), &maps.wd, k * 128, g * 64, mb, pol_ef(5)); tma2d_h(sb + slot_off(k) + 8192, &maps.wd, k * 128 + 64, g * 64, mb, pol_ef(5)); }
                }
            }
            mbar_arrive(bar + 8 * GB_FFN);
            if (g == 3) GT(1442);
        }
        if (g >= 32) {
            const int u = g - 32, ks = u >> 2, ns = u & 3;
            int slot = 0, ph = 1;
#pragma unroll 1
            for (int tile = 0; tile < NT; tile++) {
                if (tile > 0) wait_eq4(&g_f.o[tile][ks][0], epoch, 9);
                if (g == 40 && tile == NT - 1) GT(1437);
                if (tile == NT - 1) GT(1690 + g - 32);
#pragma unroll 1
                for (int k = 0; k < 4; k++) {
                    mbar_wait(bar + 8 * (GB_EMPTY + slot), slot < 4 ? ph : ph ^ 1);
                    mbar_expect_tx(bar + 8 * (GB_FULL + slot), tile == 0 ? 49152 : 16384);
                    if (tile == 0) {
#pragma unroll
                        for (int nh = 0; nh < 2; nh++)
                            asm volatile("cp.async.bulk.tensor.5d.shared::cluster.global.mbarrier::complete_tx::bytes [%0], [%1, {%3, %4, %4, %4, %5}], [%2];"
                                :: "r"(sb + G_W + nh * 65536 + k * 16384), "l"((uint64_t)&maps.wo2), "r"(bar + 8 * (GB_FULL + k)), "r"(ns * 128 + nh * 64), "r"(0), "r"(ks * 16 + k * 4) : "memory");
                        if (k == 0) wait_eq4(&g_f.o[0][ks][0], epoch, 9);
                    }
                    tma2d_mc_h(sb + slot_off(slot) + rk * 8192, &maps.ox2, (ks * 8 + k * 2 + rk) * 64, tile * 64, bar + 8 * (GB_FULL + slot), pol_ef(1));
                    if (++slot == NS3) { slot = 0; ph ^= 1; }
                }
            }
        }
    } else if (warp < 3) {
        const int wg = warp - 1;
        const uint32_t buf = sb + G_BUF + wg * 32768;
        const CUtensorMap* tkv = (g & 1) ? &maps.vx3 : &maps.kx3;
        const int n1 = g < 32 ? HSPLIT / 2 : NT - HSPLIT / 2;
#pragma unroll 1
        for (int i = 0; i < n1; i++) {
            const int tile = (i < NT / 2 ? 2 * i : 2 * i - NT + HSPLIT) + wg, hd = (i < NT / 2 ? g : g - 32) >> 1;
            mbar_wait(bar + 8 * (GB_STG + wg), i & 1);
            tma_store3d(tkv, buf, tile * 64, hd * 2);
            asm volatile("cp.async.bulk.commit_group;" ::: "memory");
            asm volatile("cp.async.bulk.wait_group.read 0;" ::: "memory");
            mbar_arrive(bar + 8 * (GB_FREE + wg));
            asm volatile("cp.async.bulk.wait_group 0;" ::: "memory");
            PUBLISH(&g_f.kv[tile][hd][g & 1], epoch);
        }
        if (wg == 0) mbar_arrive(bar + 8 * GB_T1D);
        if (g >= 32) for (int i = 0; i < 4; i++) mbar_arrive2_if(bar + 8 * (GB_EMPTY + 4 + wg), 1);
        if (g < 32 && wg == 1) {
            mbar_wait(bar + 8 * GB_T1D, 0);
#pragma unroll 1
            for (int tile = 0; tile < NT; tile++) {
                wait_eq2(&g_f.kv[tile][g][0], epoch, 10);
                if (tile > 0) mbar_wait(bar + 8 * GB_KVF, (tile - 1) & 1);
                mbar_expect_tx(bar + 8 * (GB_KV + (tile & 1)), 16384);
                tma3d_h(sb + G_BUF, &maps.kx3, tile * 64, g * 2, bar + 8 * (GB_KV + (tile & 1)), pol_ef(0));
                if (tile > 0) mbar_wait(bar + 8 * GB_VF, (tile - 1) & 1);
                mbar_expect_tx(bar + 8 * (GB_VV + (tile & 1)), 16384);
                tma3d_h(sb + G_BUF + 32768, &maps.vx3, tile * 64, g * 2, bar + 8 * (GB_VV + (tile & 1)), pol_ef(0));
                if (PFK && tile + PFK < NT) {
                    const uint2 v = ldg_rlx2(&g_f.kv[tile + PFK][g][0]);
                    if (v.x == epoch && v.y == epoch) { tma_pf3d(&maps.kx3, (tile + PFK) * 64, g * 2); tma_pf3d(&maps.vx3, (tile + PFK) * 64, g * 2); }
                }
            }
        } else {
#pragma unroll 1
            for (int tile = g < 32 ? 0 : wg; tile < NT; tile += g < 32 ? 1 : 2) {
                mbar_wait(bar + 8 * (GB_STG + (tile & 1)), ((tile >> 1) + PO) & 1);
                mbar_arrive(bar + 8 * (GB_FREE + (tile & 1)));
                PUBLISH(g < 32 ? &g_f.o[tile][g >> 2][g & 3] : &g_f.p[tile][g - 32], epoch);
                if (g == 3 && tile == NT - 1) GT(1436);
                if (g == 3) GT(1896 + tile);
                if (g < 32 && tile == NT - 1) GT(1610 + g);
                if (g == 40 && tile == NT - 1) GT(1435);
                if (g == 40) GT(1864 + tile);
                if (g >= 32 && tile == NT - 1) GT(1650 + g - 32);
            }
        }
    }
}

struct WPtr { const bf16 *q, *k, *v, *o, *g, *u; };
__device__ __forceinline__ int startup(uint8_t* smem, const bf16* __restrict__ x, const Maps& maps, uint32_t& epoch, const WPtr& pw) {
    const int tid = threadIdx.x, lane = tid & 31, w = tid >> 5, cta = blockIdx.x;
    volatile uint32_t* sh = (volatile uint32_t*)(smem + SH_OFF);
    if (cta == 4 && tid == 0) GT(1399);
    epoch = (ldg_rlx(&g_epoch) + 1) & 0x00ffffffu;
    if (w < 4) {
        if (!(cta & 1)) {
            uint32_t* pp = (uint32_t*)(xpage() + ((XR3 ^ 0x3000u) ^ ((w == 1 || w == 2) ? 0x1000u : 0u) ^ ((w & 2) << 13))) + (cta >> 1) * 8;
            if (lane < 8) stg_rlx(pp + lane, 0u);
            __syncwarp();
            if (lane == 0) {
                uint32_t best = 0xffffffffu, a = 0;
#pragma unroll 1
                for (int r = 0; r < NPROBE; r++) {
                    uint32_t t0 = clk32();
                    asm volatile("atom.relaxed.gpu.global.add.u32 %0, [%1], %2;" : "=r"(a) : "l"(pp), "r"(a + 1) : "memory");
                    if (a == 0x7fffffffu) ABORT(15);
                    uint32_t t1 = clk32();
                    if (r > 0) best = min(best, t1 - t0);
                    else if (w == 0) {
                        asm volatile("red.relaxed.gpu.global.max.u32 [%0], %1;" :: "l"(&g_ticket[0]), "r"(epoch << 8) : "memory");
                        asm volatile("red.relaxed.gpu.global.max.u32 [%0], %1;" :: "l"(&g_ticket[32]), "r"(epoch << 8) : "memory");
                    }
                }
                sh[w] = best;
            }
        }
        if (!(cta & 1)) bar_sync(1, 128);
        if (cta == 4 && tid == 0) GT(1400);
        if (w == 0) {
            if (lane == 0) {
                uint32_t rp;
                if (!(cta & 1)) {
                    uint32_t a = sh[0], b = sh[1], c = sh[2], d = sh[3];
                    uint32_t mid = (min(min(a, b), min(c, d)) + max(max(a, b), max(c, d))) >> 1;
                    const int dd = (int)min(a, d) - (int)min(b, c);
                    uint32_t cls = abs(dd) > 60 ? dd > 0 : a > mid;
                    uint32_t t = atomicAdd(&g_ticket[cls * 32], 1u) & 255;
                    if (t >= (cls ? 34u : 32u)) { cls ^= 1; t = atomicAdd(&g_ticket[cls * 32], 1u) & 255; }
                    rp = min(cls ? 32 + t : t, 65u);
                    stg_rlx(&g_table[(cta >> 1) * 8], (epoch << 8) | rp);
                } else {
                    uint32_t v, n = 0;
#pragma unroll 1
                    while (((v = ldg_rlx(&g_table[(cta >> 1) * 8])) >> 8) != epoch) { if (++n > SPIN_LIMIT) { ABORT(14); break; } }
                    rp = v & 255;
                }
                const int role = rp * 2 + (cta & 1);
                sh[8] = role; sh[9] = epoch;
                while (sh[10] != epoch + 1 && cta < NWAITLN) {}
                if (role < 64) rec_first_loads(smem_u32(smem), role, maps);
                else if (role < 128) for (int k = 0; k < 2; k++) load_w(smem_u32(smem), (role & 1) ? &maps.wv4 : &maps.wk4, ((role - 64) >> 1) * 128, k);
                if (cta == 4) GT(1401);
            }
        }
    } else if (cta < 128) {
        uint4 u[2][2];
        const int row0 = cta * 16 + (w - 4) * 2;
#pragma unroll
        for (int r = 0; r < 2; r++)
#pragma unroll
            for (int j = 0; j < 2; j++) u[r][j] = *(const uint4*)(x + (size_t)(row0 + r) * DM + j * 256 + lane * 8);
        if (cta < 48) {
            const uint32_t b = cta >> 3, off = (b >= 4 ? 0x8000u + (b & 1) * 0x4000u : ((b & 1) ? 0x3000u : 0u) + ((b & 2) << 13)) ^ aslot(cta & 7);
            *(uint4*)(xpage() + off + (tid - 128) * 16) = make_uint4(0, 0, 0, 0);
        }
        float v[2][16];
#pragma unroll
        for (int r = 0; r < 2; r++)
#pragma unroll
            for (int j = 0; j < 2; j++) {
                uint32_t ww[4] = {u[r][j].x, u[r][j].y, u[r][j].z, u[r][j].w};
#pragma unroll
                for (int i = 0; i < 4; i++) { v[r][j * 8 + 2 * i] = bf_lo(ww[i]); v[r][j * 8 + 2 * i + 1] = bf_hi(ww[i]); }
            }
        ln_row2(v[0], v[1]);
#pragma unroll
        for (int r = 0; r < 2; r++)
#pragma unroll
            for (int j = 0; j < 2; j++)
                *(uint4*)(g_xn + (size_t)(row0 + r) * DM + j * 256 + lane * 8) =
                    make_uint4(pack2(v[r][j * 8], v[r][j * 8 + 1]), pack2(v[r][j * 8 + 2], v[r][j * 8 + 3]), pack2(v[r][j * 8 + 4], v[r][j * 8 + 5]), pack2(v[r][j * 8 + 6], v[r][j * 8 + 7]));
        bar_sync(2, 256);
        if (tid == 160 && cta < NWAITLN) { st_rel(&g_f.xn[cta], epoch); sh[10] = epoch + 1; }
        if (cta == 4 && tid == 160) GT(1403);
        __syncwarp();
    }
    if (cta == 4 && tid == 128) GT(1402);
    __syncthreads();
    if (tid == 160 && cta >= NWAITLN && cta < 128) st_rel(&g_f.xn[cta], epoch);
    __syncwarp();
    const int role = sh[8];
    return role;
}

__global__ void __cluster_dims__(2, 1, 1) __launch_bounds__(384, 1)
main_kernel(const __grid_constant__ Maps maps, const bf16* __restrict__ x, const bf16* __restrict__ mem0, const bf16* __restrict__ wr,
            const bf16* __restrict__ wd, bf16* __restrict__ out, const WPtr pw) {
    extern __shared__ __align__(1024) uint8_t smem[];
    const uint32_t sb = smem_u32(smem);
    if (threadIdx.x == 0) {
        for (int i = 0; i < MB_N; i++) mbar_init(sb + R_BAR + 8 * i, i == MB_V ? 4 : 1);
        for (int i = 0; i < GB_N; i++)
            mbar_init(sb + G_BAR + 8 * i, i >= GB_EMPTY && i < GB_KV ? 8 : (i >= GB_KVF ? 4 : (i >= GB_STG && i < GB_FREE ? 128 : 1)));
        asm volatile("fence.mbarrier_init.release.cluster;" ::: "memory");
    }
    __syncwarp();
    asm volatile("barrier.cluster.arrive.relaxed.aligned;" ::: "memory");
    if (threadIdx.x >= 352 && threadIdx.x < 352 + (int)(sizeof(Maps) / sizeof(CUtensorMap)))
        asm volatile("prefetch.tensormap [%0];" :: "l"((const CUtensorMap*)&maps + (threadIdx.x - 352)) : "memory");
    uint32_t epoch;
    asm volatile("fence.proxy.async.shared::cta;" ::: "memory");
    const int role = uni(startup(smem, x, maps, epoch, pw));
    asm volatile("barrier.cluster.wait.aligned;" ::: "memory");
    const int wg = uni(threadIdx.x >> 7);
    if (role < 64) {
#define SETREG(n) do { if ((n) < 168) asm volatile("setmaxnreg.dec.sync.aligned.u32 %0;" :: "n"(n)); if ((n) > 168) asm volatile("setmaxnreg.inc.sync.aligned.u32 %0;" :: "n"(n)); } while (0)
#define RESREG(n) do { if ((n) < 168) asm volatile("setmaxnreg.inc.sync.aligned.u32 168;"); if ((n) > 168) asm volatile("setmaxnreg.dec.sync.aligned.u32 168;"); } while (0)
        if (wg == WGA) {
            SETREG(RGA);
            rec_a(sb, role, mem0, epoch);
        } else if (wg == WGB) {
            SETREG(RGB);
            rec_b(sb, role, epoch);
        } else {
            SETREG(RGC);
            rec_c(sb, role, mem0, maps, epoch);
        }
    } else if (role < 128) {
        if (wg < 2) {
            asm volatile("setmaxnreg.inc.sync.aligned.u32 192;");
            g_consumer(sb, role - 64, wg, epoch);
            if (wg == 0 && role - 64 < NWK) { ffn_phase(role - 64, epoch, out); if (role == 67 && threadIdx.x == 0) GT(1441); }
            if (threadIdx.x == 128) GT(role * 8 + 6);
        } else {
            asm volatile("setmaxnreg.dec.sync.aligned.u32 120;");
            g_producer(sb, role - 64, maps, epoch, x, wr, out);
        }
    } else {
        const int id = (threadIdx.x >> 5) * 4 + role - 128;
        finalizer(64 + id, x, wr, out, epoch, id < 16 ? pw.g : (id < 32 ? pw.u : wd));
        __syncwarp();
        ffn_phase(NWK + role - 128, epoch, out);
        if (threadIdx.x == 0) GT(role * 8 + 5);
    }
}

typedef CUresult (*EncodeFn)(CUtensorMap*, CUtensorMapDataType, cuuint32_t, void*, const cuuint64_t*, const cuuint64_t*, const cuuint32_t*, const cuuint32_t*,
                             CUtensorMapInterleave, CUtensorMapSwizzle, CUtensorMapL2promotion, CUtensorMapFloatOOBfill);
static void make_map3(EncodeFn fn, CUtensorMap* m, const void* ptr, uint64_t cols, uint64_t rows) {
    cuuint64_t dims[3] = {64, rows, cols / 64};
    cuuint64_t strides[2] = {cols * 2, 128};
    cuuint32_t box[3] = {64, 64, 2};
    cuuint32_t es[3] = {1, 1, 1};
    fn(m, CU_TENSOR_MAP_DATA_TYPE_BFLOAT16, 3, (void*)ptr, dims, strides, box, es, CU_TENSOR_MAP_INTERLEAVE_NONE, CU_TENSOR_MAP_SWIZZLE_128B,
       CU_TENSOR_MAP_L2_PROMOTION_L2_256B, CU_TENSOR_MAP_FLOAT_OOB_FILL_NONE);
}
static void make_map(EncodeFn fn, CUtensorMap* m, const void* ptr, uint64_t cols, uint64_t rows, uint32_t bcols, uint32_t brows,
                     bool f32 = false, CUtensorMapSwizzle sw = CU_TENSOR_MAP_SWIZZLE_128B) {
    cuuint64_t dims[2] = {cols, rows};
    cuuint64_t strides[1] = {cols * (f32 ? 4 : 2)};
    cuuint32_t box[2] = {bcols, brows};
    cuuint32_t es[2] = {1, 1};
    fn(m, f32 ? CU_TENSOR_MAP_DATA_TYPE_FLOAT32 : CU_TENSOR_MAP_DATA_TYPE_BFLOAT16, 2, (void*)ptr, dims, strides, box, es, CU_TENSOR_MAP_INTERLEAVE_NONE, sw,
       CU_TENSOR_MAP_L2_PROMOTION_L2_256B, CU_TENSOR_MAP_FLOAT_OOB_FILL_NONE);
}

extern "C" void kernel_launch(void* const* d_in, const int* in_sizes, int n_in, void* d_out, int out_size) {
    const bf16* x = (const bf16*)d_in[0];
    const bf16* mem0 = (const bf16*)d_in[1];
    const bf16* Wq = (const bf16*)d_in[2];
    const bf16* Wk = (const bf16*)d_in[3];
    const bf16* Wv = (const bf16*)d_in[4];
    const bf16* Wo = (const bf16*)d_in[5];
    const bf16* wr = (const bf16*)d_in[8];
    const bf16* wg = (const bf16*)d_in[9];
    const bf16* wu = (const bf16*)d_in[10];
    const bf16* wd = (const bf16*)d_in[11];
    bf16* out = (bf16*)d_out;

    static EncodeFn enc = nullptr;
    static void *pxn, *pK, *pV, *pO, *pacc;
    if (!enc) {
        cudaDriverEntryPointQueryResult qr;
        void* fn = nullptr;
        cudaGetDriverEntryPoint("cuTensorMapEncodeTiled", &fn, cudaEnableDefault, &qr);
        enc = (EncodeFn)fn;
        cudaGetSymbolAddress(&pxn, g_xn); cudaGetSymbolAddress(&pK, g_K); cudaGetSymbolAddress(&pV, g_V);
        cudaGetSymbolAddress(&pO, g_O); cudaGetSymbolAddress(&pacc, g_P);
        cudaFuncSetAttribute(main_kernel, cudaFuncAttributeMaxDynamicSharedMemorySize, SMEM_TOTAL);
    }
    Maps m;
    make_map(enc, &m.wq, Wq, HD, DM, 64, 256);
    make_map(enc, &m.wk, Wk, HD, DM, 64, 256);
    make_map(enc, &m.wv, Wv, HD, DM, 64, 256);
    make_map(enc, &m.wq4, Wq, HD, DM, 64, 128); make_map(enc, &m.wk4, Wk, HD, DM, 64, 128); make_map(enc, &m.wv4, Wv, HD, DM, 64, 128);
    make_map(enc, &m.wo, Wo, DM, HD, 64, 128);
    {
        cuuint64_t dims[5] = {DM, 2, 4, 4, HD / 32};
        cuuint64_t strides[4] = {DM * 2, 8 * DM * 2, 2 * DM * 2, 32 * DM * 2};
        cuuint32_t box[5] = {64, 2, 4, 4, 4};
        cuuint32_t es[5] = {1, 1, 1, 1, 1};
        enc(&m.wo2, CU_TENSOR_MAP_DATA_TYPE_BFLOAT16, 5, (void*)Wo, dims, strides, box, es, CU_TENSOR_MAP_INTERLEAVE_NONE, CU_TENSOR_MAP_SWIZZLE_128B,
            CU_TENSOR_MAP_L2_PROMOTION_L2_256B, CU_TENSOR_MAP_FLOAT_OOB_FILL_NONE);
    }
    make_map(enc, &m.kx, pK, HD, SQ, 64, 64);
    make_map(enc, &m.ox2, pO, HD, SQ, 64, 64);
    make_map(enc, &m.xn2, pxn, DM, SQ, 64, 64);
    make_map3(enc, &m.kx3, pK, HD, SQ); make_map3(enc, &m.vx3, pV, HD, SQ);
    make_map(enc, &m.wg, wg, FF, DM, 64, 128);
    make_map(enc, &m.wu, wu, FF, DM, 64, 128);
    make_map(enc, &m.wd, wd, DM, FF, 64, 64);

    cudaStream_t st = cudaStreamPerThread;
    main_kernel<<<NCTA, 384, SMEM_TOTAL, st>>>(m, x, mem0, wr, wd, out, WPtr{Wq, Wk, Wv, Wo, wg, wu});
}
```

```cpp
#include <cuda_runtime.h>
#include <cuda_bf16.h>
#include <cuda.h>
#include <stdint.h>
#include <stddef.h>

typedef __nv_bfloat16 bf16;

constexpr int SQ = 2048, DM = 512, NH = 32, DH = 128, NSEG = 64, HD = 4096, FF = 1792;

constexpr int NT = 32;
#define SPEC_TILES 30
__device__ __align__(1024) bf16 g_xn[SQ * DM];
__device__ __align__(1024) bf16 g_K[SQ * HD];
__device__ __align__(1024) bf16 g_V[SQ * HD];
__device__ __align__(1024) bf16 g_O[SQ * HD];
__device__ __align__(1024) uint32_t g_KVf[NSEG][NH][1024];
__device__ __align__(1024) bf16 g_P[8 * SQ * DM];
__device__ __align__(1024) bf16 g_h[SQ * DM];
__device__ __align__(1024) bf16 g_hn[SQ * DM];
__device__ uint8_t g_xraw[12 << 20];
#define XPG 0
__device__ __forceinline__ uint64_t xpage() { return (((uint64_t)g_xraw + (2 << 20) - 1) & ~(uint64_t)((2 << 20) - 1)) + ((uint64_t)XPG << 21); }
constexpr uint32_t XR3 = (1u << 20) | (1u << 19) | (1u << 12);
__device__ __forceinline__ uint32_t aslot(uint32_t s) { return ((s & 1) << 18) | ((s & 2) << 19) | ((s & 4) * 0xc000u); }
__device__ __forceinline__ uint32_t acc_base(uint32_t W) { return ((W & 2) ? 0x3000u : 0u) + ((W & 4) << 12) + (W & 1) * 2048; }
__device__ __forceinline__ uint32_t ext_base(uint32_t W) { return 0x8000u + ((W & 4) << 12) + (W & 3) * 1024; }
#define XHS 256
#define XSS 32
__device__ __forceinline__ uint32_t zero_off(uint32_t c, uint32_t ln) {
    return ln < 8 ? acc_base(c >> 3) + (c & 7) * 256 + ln * 16 : ext_base(c >> 3) + ((c >> 2) & 1) * XHS + ((c >> 1) & 1) * XSS + (c & 1) * 16;
}
struct Flags {
    uint32_t kv[NT][NH][2];
    uint32_t o[NT][8][32];
    uint32_t rec[64];
    uint32_t xn[128];
    uint32_t p[NT][32];
    uint32_t rows[2][128];
    uint4 cand[2][128];
    uint4 norm[64];
};
__device__ __align__(1024) Flags g_f;
__device__ __align__(1024) uint4 g_yp[2][FF / 32][DM];
__device__ __align__(1024) uint32_t g_table[66 * 8];
__device__ __align__(256) uint32_t g_ticket[64];
__device__ uint32_t g_epoch;
#define NS3 6
#define HSPLIT 26
#define PFK 0
#define NWAITLN 8
#define WGA 0
#define WGB 1
#define WGC (3 - WGA - WGB)
#define PFF 10
#define FFS 0
#define LLT 31
#define NPROBE 3
constexpr int NCTA = 132;
constexpr int NFW = 112;
__device__ uint32_t g_abort;
__device__ long long g_dbg[4096];
#define TR(slot, v)

__device__ __forceinline__ uint32_t smem_u32(const void* p) { return (uint32_t)__cvta_generic_to_shared(p); }
__device__ __forceinline__ void mbar_init(uint32_t a, uint32_t c) { asm volatile("mbarrier.init.shared::cta.b64 [%0], %1;" :: "r"(a), "r"(c) : "memory"); }
__device__ __forceinline__ void mbar_expect_tx(uint32_t a, uint32_t tx) { asm volatile("mbarrier.arrive.expect_tx.shared::cta.b64 _, [%0], %1;" :: "r"(a), "r"(tx) : "memory"); }
__device__ __forceinline__ void mbar_arrive(uint32_t a) { asm volatile("mbarrier.arrive.shared::cta.b64 _, [%0];" :: "r"(a) : "memory"); }
__device__ __forceinline__ void mbar_arrive_if(uint32_t a, uint32_t pred) {
    asm volatile("{\n.reg .pred p;\nsetp.ne.u32 p, %1, 0;\n@p mbarrier.arrive.shared::cta.b64 _, [%0];\n}" :: "r"(a), "r"(pred) : "memory");
}
__device__ __forceinline__ bool mbar_try(uint32_t a, uint32_t ph) {
    uint32_t ok;
    asm volatile("{\n.reg .pred p;\nmbarrier.try_wait.parity.shared::cta.b64 p, [%1], %2;\nselp.u32 %0, 1, 0, p;\n}" : "=r"(ok) : "r"(a), "r"(ph) : "memory");
    return ok != 0;
}
#define SPINLOG 20
constexpr uint32_t SPIN_LIMIT = 1u << SPINLOG;
#define ABORT(code_) atomicCAS(&g_abort, 0u, (code_))
__device__ __forceinline__ void mbar_wait(uint32_t a, uint32_t ph) {
    uint32_t n = 0;
#pragma unroll 1
    while (!mbar_try(a, ph)) { if (++n > SPIN_LIMIT) { ABORT(1); break; } }
}
__device__ __forceinline__ void bar_sync(int id, int n) { asm volatile("bar.sync %0, %1;" :: "r"(id), "r"(n) : "memory"); }
__device__ __forceinline__ void bar_arrive(int id, int n) { asm volatile("bar.arrive %0, %1;" :: "r"(id), "r"(n) : "memory"); }

__device__ __forceinline__ void ldsm4(uint32_t* r, uint32_t a) {
    asm volatile("ldmatrix.sync.aligned.m8n8.x4.shared.b16 {%0,%1,%2,%3}, [%4];" : "=r"(r[0]), "=r"(r[1]), "=r"(r[2]), "=r"(r[3]) : "r"(a) : "memory");
}
__device__ __forceinline__ void ldsm4t(uint32_t* r, uint32_t a) {
    asm volatile("ldmatrix.sync.aligned.m8n8.x4.trans.shared.b16 {%0,%1,%2,%3}, [%4];" : "=r"(r[0]), "=r"(r[1]), "=r"(r[2]), "=r"(r[3]) : "r"(a) : "memory");
}
__device__ __forceinline__ void stsm4t(uint32_t a, uint32_t r0, uint32_t r1, uint32_t r2, uint32_t r3) {
    asm volatile("stmatrix.sync.aligned.m8n8.x4.trans.shared.b16 [%0], {%1,%2,%3,%4};" :: "r"(a), "r"(r0), "r"(r1), "r"(r2), "r"(r3) : "memory");
}
__device__ __forceinline__ void stsm4(uint32_t a, uint32_t r0, uint32_t r1, uint32_t r2, uint32_t r3) {
    asm volatile("stmatrix.sync.aligned.m8n8.x4.shared.b16 [%0], {%1,%2,%3,%4};" :: "r"(a), "r"(r0), "r"(r1), "r"(r2), "r"(r3) : "memory");
}
__device__ __forceinline__ uint32_t movm(uint32_t a) { uint32_t d; asm volatile("movmatrix.sync.aligned.m8n8.trans.b16 %0, %1;" : "=r"(d) : "r"(a)); return d; }
__device__ __forceinline__ void mma16816(float* d, uint32_t a0, uint32_t a1, uint32_t a2, uint32_t a3, uint32_t b0, uint32_t b1) {
    asm volatile("mma.sync.aligned.m16n8k16.row.col.f32.bf16.bf16.f32 {%0,%1,%2,%3}, {%4,%5,%6,%7}, {%8,%9}, {%0,%1,%2,%3};"
        : "+f"(d[0]), "+f"(d[1]), "+f"(d[2]), "+f"(d[3]) : "r"(a0), "r"(a1), "r"(a2), "r"(a3), "r"(b0), "r"(b1));
}
__device__ __forceinline__ void mma1688(float* d, uint32_t a0, uint32_t a1, uint32_t b0) {
    asm volatile("mma.sync.aligned.m16n8k8.row.col.f32.bf16.bf16.f32 {%0,%1,%2,%3}, {%4,%5}, {%6}, {%0,%1,%2,%3};"
        : "+f"(d[0]), "+f"(d[1]), "+f"(d[2]), "+f"(d[3]) : "r"(a0), "r"(a1), "r"(b0));
}
__device__ __forceinline__ uint32_t pack2(float a, float b) { uint32_t d; asm("cvt.rn.bf16x2.f32 %0, %1, %2;" : "=r"(d) : "f"(b), "f"(a)); return d; }
__device__ __forceinline__ float bf_lo(uint32_t w) { return __uint_as_float(w << 16); }
__device__ __forceinline__ float bf_hi(uint32_t w) { return __uint_as_float(w & 0xffff0000u); }
__device__ __forceinline__ float rbf(float x) { return __bfloat162float(__float2bfloat16_rn(x)); }

__device__ __forceinline__ void sts128(uint32_t a, float x, float y, float z, float w) { asm volatile("st.shared.v4.f32 [%0], {%1,%2,%3,%4};" :: "r"(a), "f"(x), "f"(y), "f"(z), "f"(w) : "memory"); }
__device__ __forceinline__ void sts128u(uint32_t a, uint32_t x, uint32_t y, uint32_t z, uint32_t w) { asm volatile("st.shared.v4.b32 [%0], {%1,%2,%3,%4};" :: "r"(a), "r"(x), "r"(y), "r"(z), "r"(w) : "memory"); }
__device__ __forceinline__ void sts64(uint32_t a, float x, float y) { asm volatile("st.shared.v2.f32 [%0], {%1,%2};" :: "r"(a), "f"(x), "f"(y) : "memory"); }
__device__ __forceinline__ float4 lds128(uint32_t a) { float4 v; asm volatile("ld.shared.v4.f32 {%0,%1,%2,%3}, [%4];" : "=f"(v.x), "=f"(v.y), "=f"(v.z), "=f"(v.w) : "r"(a) : "memory"); return v; }
__device__ __forceinline__ float2 lds64(uint32_t a) { float2 v; asm volatile("ld.shared.v2.f32 {%0,%1}, [%2];" : "=f"(v.x), "=f"(v.y) : "r"(a) : "memory"); return v; }
__device__ __forceinline__ uint2 lds64u(uint32_t a) { uint2 v; asm volatile("ld.shared.v2.b32 {%0,%1}, [%2];" : "=r"(v.x), "=r"(v.y) : "r"(a) : "memory"); return v; }
__device__ __forceinline__ float4 lds128v(uint32_t a) { float4 v; asm volatile("ld.volatile.shared.v4.f32 {%0,%1,%2,%3}, [%4];" : "=f"(v.x), "=f"(v.y), "=f"(v.z), "=f"(v.w) : "r"(a) : "memory"); return v; }
__device__ __forceinline__ float2 lds64v(uint32_t a) { float2 v; asm volatile("ld.volatile.shared.v2.f32 {%0,%1}, [%2];" : "=f"(v.x), "=f"(v.y) : "r"(a) : "memory"); return v; }
__device__ __forceinline__ uint4 lds128uv(uint32_t a) { uint4 v; asm volatile("ld.volatile.shared.v4.b32 {%0,%1,%2,%3}, [%4];" : "=r"(v.x), "=r"(v.y), "=r"(v.z), "=r"(v.w) : "r"(a) : "memory"); return v; }
__device__ __forceinline__ void st_async4(uint32_t a, float x, float y, float z, float w, uint32_t mb) {
    asm volatile("st.async.weak.shared::cluster.mbarrier::complete_tx::bytes.v4.f32 [%0], {%1,%2,%3,%4}, [%5];" :: "r"(a), "f"(x), "f"(y), "f"(z), "f"(w), "r"(mb) : "memory");
}
__device__ __forceinline__ void st_async2(uint32_t a, uint32_t x, uint32_t y, uint32_t mb) {
    asm volatile("st.async.weak.shared::cluster.mbarrier::complete_tx::bytes.v2.b32 [%0], {%1,%2}, [%3];" :: "r"(a), "r"(x), "r"(y), "r"(mb) : "memory");
}
__device__ __forceinline__ uint32_t ldg_rlx(const uint32_t* p) { uint32_t v; asm volatile("ld.relaxed.gpu.global.b32 %0, [%1];" : "=r"(v) : "l"(p) : "memory"); return v; }
__device__ __forceinline__ uint4 ldg_rlx4(const uint32_t* p) { uint4 v; asm volatile("ld.relaxed.gpu.global.v4.b32 {%0,%1,%2,%3}, [%4];" : "=r"(v.x), "=r"(v.y), "=r"(v.z), "=r"(v.w) : "l"(p) : "memory"); return v; }
__device__ __forceinline__ uint4 ldg_rlx4_if(const uint32_t* p, bool c) {
    uint4 v;
    asm volatile("{\n.reg .pred p;\nsetp.ne.u32 p, %5, 0;\nmov.b32 %0, 0;\nmov.b32 %1, 0;\nmov.b32 %2, 0;\nmov.b32 %3, 0;\n@p ld.relaxed.gpu.global.v4.b32 {%0,%1,%2,%3}, [%4];\n}"
                 : "=r"(v.x), "=r"(v.y), "=r"(v.z), "=r"(v.w) : "l"(p), "r"((uint32_t)c) : "memory");
    return v;
}
__device__ __forceinline__ void stg_rlx(uint32_t* p, uint32_t v) { asm volatile("st.relaxed.gpu.global.b32 [%0], %1;" :: "l"(p), "r"(v) : "memory"); }
__device__ __forceinline__ void tma2d(uint32_t dst, const CUtensorMap* tm, int c0, int c1, uint32_t mb) {
    asm volatile("cp.async.bulk.tensor.2d.shared::cluster.global.mbarrier::complete_tx::bytes [%0], [%1, {%3, %4}], [%2];"
        :: "r"(dst), "l"((uint64_t)tm), "r"(mb), "r"(c0), "r"(c1) : "memory");
}

__device__ __forceinline__ void tma3d(uint32_t dst, const CUtensorMap* tm, int row, int chunk, uint32_t mb) {
    asm volatile("cp.async.bulk.tensor.3d.shared::cluster.global.mbarrier::complete_tx::bytes [%0], [%1, {%3, %4, %5}], [%2];"
        :: "r"(dst), "l"((uint64_t)tm), "r"(mb), "r"(0), "r"(row), "r"(chunk) : "memory");
}
#define EF 0xff
__device__ __forceinline__ uint64_t pol_ef(int bit) {
    uint64_t p;
    if ((EF >> bit) & 1) asm("createpolicy.fractional.L2::evict_first.b64 %0, 1.0;" : "=l"(p));
    else asm("createpolicy.fractional.L2::evict_normal.b64 %0, 1.0;" : "=l"(p));
    return p;
}
__device__ __forceinline__ void tma3d_h(uint32_t dst, const CUtensorMap* tm, int row, int chunk, uint32_t mb, uint64_t pol) {
    asm volatile("cp.async.bulk.tensor.3d.shared::cluster.global.mbarrier::complete_tx::bytes.L2::cache_hint [%0], [%1, {%3, %4, %5}], [%2], %6;"
        :: "r"(dst), "l"((uint64_t)tm), "r"(mb), "r"(0), "r"(row), "r"(chunk), "l"(pol) : "memory");
}
__device__ __forceinline__ void tma2d_h(uint32_t dst, const CUtensorMap* tm, int c0, int c1, uint32_t mb, uint64_t pol) {
    asm volatile("cp.async.bulk.tensor.2d.shared::cluster.global.mbarrier::complete_tx::bytes.L2::cache_hint [%0], [%1, {%3, %4}], [%2], %5;"
        :: "r"(dst), "l"((uint64_t)tm), "r"(mb), "r"(c0), "r"(c1), "l"(pol) : "memory");
}
__device__ __forceinline__ void tma2d_mc_h(uint32_t dst, const CUtensorMap* tm, int c0, int c1, uint32_t mb, uint64_t pol) {
    asm volatile("cp.async.bulk.tensor.2d.shared::cluster.global.mbarrier::complete_tx::bytes.multicast::cluster.L2::cache_hint [%0], [%1, {%3, %4}], [%2], %5, %6;"
        :: "r"(dst), "l"((uint64_t)tm), "r"(mb), "r"(c0), "r"(c1), "h"((uint16_t)3), "l"(pol) : "memory");
}
__device__ __forceinline__ uint4 ldg4_h(const void* p, uint64_t pol) {
    uint4 v;
    asm volatile("ld.relaxed.gpu.global.L2::cache_hint.v4.b32 {%0,%1,%2,%3}, [%4], %5;" : "=r"(v.x), "=r"(v.y), "=r"(v.z), "=r"(v.w) : "l"(p), "l"(pol) : "memory");
    return v;
}
__device__ __forceinline__ void stg4_h(void* p, uint4 v, uint64_t pol) {
    asm volatile("st.relaxed.gpu.global.L2::cache_hint.v4.b32 [%0], {%1,%2,%3,%4}, %5;" :: "l"(p), "r"(v.x), "r"(v.y), "r"(v.z), "r"(v.w), "l"(pol) : "memory");
}
__device__ __forceinline__ void tma2d_mc(uint32_t dst, const CUtensorMap* tm, int c0, int c1, uint32_t mb) {
    asm volatile("cp.async.bulk.tensor.2d.shared::cluster.global.mbarrier::complete_tx::bytes.multicast::cluster [%0], [%1, {%3, %4}], [%2], %5;"
        :: "r"(dst), "l"((uint64_t)tm), "r"(mb), "r"(c0), "r"(c1), "h"((uint16_t)3) : "memory");
}
__device__ __forceinline__ void mbar_arrive2_if(uint32_t a, uint32_t pred) {
    asm volatile("{\n.reg .pred p;\nsetp.ne.u32 p, %1, 0;\n@p mbarrier.arrive.shared::cta.b64 _, [%0];\n@p mbarrier.arrive.shared::cluster.b64 _, [%2];\n}"
                 :: "r"(a), "r"(pred), "r"(a ^ 0x01000000u) : "memory");
}
__device__ __forceinline__ void tma_pf3d(const CUtensorMap* tm, int row, int chunk) {
    asm volatile("cp.async.bulk.prefetch.tensor.3d.L2.global.tile [%0, {%1, %2, %3}];" :: "l"((uint64_t)tm), "r"(0), "r"(row), "r"(chunk) : "memory");
}
__device__ __forceinline__ void tma_pf2d(const CUtensorMap* tm, int c0, int c1) {
    asm volatile("cp.async.bulk.prefetch.tensor.2d.L2.global.tile [%0, {%1, %2}];" :: "l"((uint64_t)tm), "r"(c0), "r"(c1) : "memory");
}
__device__ __forceinline__ void tma_store3d(const CUtensorMap* tm, uint32_t src, int row, int chunk) {
    asm volatile("cp.async.bulk.tensor.3d.global.shared::cta.bulk_group [%0, {%2, %3, %4}], [%1];" :: "l"((uint64_t)tm), "r"(src), "r"(0), "r"(row), "r"(chunk) : "memory");
}
__device__ __forceinline__ void bulk_store(void* dst, uint32_t src, uint32_t bytes) {
    asm volatile("cp.async.bulk.global.shared::cta.bulk_group [%0], [%1], %2;" :: "l"(dst), "r"(src), "r"(bytes) : "memory");
}
#define GT(slot)
#define CNT(k)
#define CNT2(k, c)
#define TS(i, dep)
#define TSACC()
#define TSDECL
struct Maps { CUtensorMap wq, wk, wv, wo, wo2, kx, ox2, kx3, vx3, xn2, wg, wu, wd, wq4, wk4, wv4; };
typedef Maps RecMaps;
__device__ __forceinline__ void st_rel(uint32_t* p, uint32_t v) { asm volatile("st.release.gpu.global.u32 [%0], %1;" :: "l"(p), "r"(v) : "memory"); }
#define PUBLISH(p, v) st_rel(p, v)
__device__ __forceinline__ uint2 ldg_rlx2(const uint32_t* p) { uint2 v; asm volatile("ld.relaxed.gpu.global.v2.b32 {%0,%1}, [%2];" : "=r"(v.x), "=r"(v.y) : "l"(p) : "memory"); return v; }
__device__ __forceinline__ void wait_eq2(const uint32_t* p, uint32_t e, int code) {
    uint32_t n = 0;
#pragma unroll 1
    while (true) { uint2 v = ldg_rlx2(p); if (v.x == e && v.y == e) break; __nanosleep(64); if (++n > SPIN_LIMIT) { ABORT(code); break; } }
}
__device__ __forceinline__ void wait_eq4(const uint32_t* p, uint32_t e, int code) {
    uint32_t n = 0;
#pragma unroll 1
    while (true) { uint4 v = ldg_rlx4(p); if (v.x == e && v.y == e && v.z == e && v.w == e) break; __nanosleep(64); if (++n > SPIN_LIMIT) { ABORT(code); break; } }
}
__device__ __forceinline__ void wait_rec(const uint32_t* p, uint32_t e, uint32_t steps) {
    uint32_t n = 0;
#pragma unroll 1
    while (true) {
        uint2 v = ldg_rlx2(p);
        if (__all_sync(0xffffffffu, (v.x >> 8) == e && (v.y >> 8) == e && (v.x & 255) >= steps && (v.y & 255) >= steps)) break;
        __nanosleep(64); if (++n > SPIN_LIMIT) { ABORT(8); break; }
    }
}

constexpr int R_QK1 = 0;
constexpr int R_WO = 65536;
constexpr int R_T = 131072;
constexpr int R_SLOT1 = R_T;
constexpr int R_MEMB = R_T + 24576;
constexpr int R_QP = R_MEMB + 8192;
constexpr int R_VRED = R_QP + 4096;
constexpr int R_STG = R_VRED + 2048;
constexpr int R_AX = R_STG + 2048;
constexpr int R_SLOT0 = 196608;
constexpr int R_SLOC = R_SLOT0 + 24576;
constexpr int R_SREM = R_SLOC + 1536;
constexpr int R_VB = R_SREM + 1536;
constexpr int R_MISC = R_VB + 2048;
constexpr int R_LT = R_MISC + 128;
constexpr int R_BAR = 229888;
constexpr int R_TS = 229888 + 128;
static_assert(R_AX + 24576 <= R_SLOT0 && R_LT + 2560 <= 229376, "smem map");
enum { MB_W0 = 0, MB_W1, MB_WV, MB_WO, MB_S, MB_FULL0, MB_FULL1, MB_V, MB_N };

__device__ __forceinline__ float ex2(float x) { float y; asm("ex2.approx.ftz.f32 %0, %1;" : "=f"(y) : "f"(x)); return y; }
__device__ __forceinline__ float rcpf(float x) { float y; asm("rcp.approx.ftz.f32 %0, %1;" : "=f"(y) : "f"(x)); return y; }
__device__ __forceinline__ void mma16816z(float* d, uint32_t a0, uint32_t a1, uint32_t a2, uint32_t a3, uint32_t b0, uint32_t b1) {
    asm volatile("mma.sync.aligned.m16n8k16.row.col.f32.bf16.bf16.f32 {%0,%1,%2,%3}, {%4,%5,%6,%7}, {%8,%9}, {%10,%10,%10,%10};"
        : "=f"(d[0]), "=f"(d[1]), "=f"(d[2]), "=f"(d[3]) : "r"(a0), "r"(a1), "r"(a2), "r"(a3), "r"(b0), "r"(b1), "f"(0.f));
}
__device__ __forceinline__ void mma1688hz(float* d, uint32_t a0, uint32_t a1, uint32_t b0) {
    asm volatile("mma.sync.aligned.m16n8k8.row.col.f32.f16.f16.f32 {%0,%1,%2,%3}, {%4,%5}, {%6}, {%7,%7,%7,%7};"
        : "=f"(d[0]), "=f"(d[1]), "=f"(d[2]), "=f"(d[3]) : "r"(a0), "r"(a1), "r"(b0), "f"(0.f));
}
#define MMA(d, a, b0, b1) mma16816(d, a[0], a[1], a[2], a[3], b0, b1)
#define MMAZ(d, a, b0, b1) mma16816z(d, a[0], a[1], a[2], a[3], b0, b1)
#define MMAF(first, d, a, b0, b1) do { if (first) MMAZ(d, a, b0, b1); else MMA(d, a, b0, b1); } while (0)

__device__ __forceinline__ uint32_t uni(uint32_t x) { return __reduce_max_sync(0xffffffffu, x); }
__device__ __forceinline__ void mbar_wait_u(uint32_t a, uint32_t ph) {
    uint32_t n = 0;
#pragma unroll 1
    while (!__all_sync(0xffffffffu, mbar_try(a, ph))) { if (++n > SPIN_LIMIT) { ABORT(1); break; } }
}
__device__ __forceinline__ void mbar_wait_p(uint32_t a, uint32_t ph) {
    asm volatile("{\n.reg .pred p, q;\n.reg .u32 n;\nmov.u32 n, 0;\nWL: mbarrier.try_wait.parity.shared::cta.b64 p, [%0], %1;\nadd.u32 n, n, 1;\n"
                 "setp.lt.and.u32 q, n, %2, !p;\n@q bra.uni WL;\n}" :: "r"(a), "r"(ph), "n"(SPIN_LIMIT) : "memory");
}
__device__ __forceinline__ uint32_t mbar_test(uint32_t a, uint32_t ph) {
    uint32_t ok;
    asm volatile("{\n.reg .pred p;\nmbarrier.test_wait.parity.shared::cta.b64 p, [%1], %2;\nselp.u32 %0, 1, 0, p;\n}" : "=r"(ok) : "r"(a), "r"(ph) : "memory");
    return ok;
}
__device__ __forceinline__ uint32_t opaque(uint32_t x) { return __shfl_sync(0xffffffffu, x, threadIdx.x & 31); }
__device__ __forceinline__ const uint32_t* mkptr(uint32_t lo, uint32_t hi) { uint64_t r; asm("mov.b64 %0, {%1, %2};" : "=l"(r) : "r"(lo), "r"(hi)); return (const uint32_t*)r; }
__device__ __forceinline__ uint32_t prmt(uint32_t a, uint32_t b, uint32_t s) { uint32_t d; asm("prmt.b32 %0, %1, %2, %3;" : "=r"(d) : "r"(a), "r"(b), "r"(s)); return d; }
__device__ __forceinline__ uint32_t packh2(float a, float b) { uint32_t d; asm("cvt.rn.f16x2.f32 %0, %1, %2;" : "=r"(d) : "f"(b), "f"(a)); return d; }
__device__ __forceinline__ uint32_t hadd2b(uint32_t a, uint32_t b) { uint32_t d; asm("add.rn.bf16x2 %0, %1, %2;" : "=r"(d) : "r"(a), "r"(b)); return d; }
__device__ __forceinline__ uint32_t hmul2b(uint32_t a, uint32_t b) { uint32_t d; asm("mul.rn.bf16x2 %0, %1, %2;" : "=r"(d) : "r"(a), "r"(b)); return d; }
__device__ __forceinline__ uint32_t amax2b(uint32_t a, uint32_t b) { uint32_t d; asm("max.xorsign.abs.bf16x2 %0, %1, %2;" : "=r"(d) : "r"(a), "r"(b)); return d; }
__device__ __forceinline__ uint32_t amax2h(uint32_t a, uint32_t b) { uint32_t d; asm("max.xorsign.abs.f16x2 %0, %1, %2;" : "=r"(d) : "r"(a), "r"(b)); return d; }
__device__ __forceinline__ void sts32(uint32_t a, uint32_t x) { asm volatile("st.shared.b32 [%0], %1;" :: "r"(a), "r"(x) : "memory"); }
__device__ __forceinline__ uint32_t lds32v_(uint32_t a) { uint32_t v; asm volatile("ld.volatile.shared.b32 %0, [%1];" : "=r"(v) : "r"(a) : "memory"); return v; }
__device__ __forceinline__ void stg4(void* p, uint4 v) { asm volatile("st.relaxed.gpu.global.v4.b32 [%0], {%1,%2,%3,%4};" :: "l"(p), "r"(v.x), "r"(v.y), "r"(v.z), "r"(v.w) : "memory"); }
__device__ __forceinline__ void lds_frag(uint32_t* r, uint32_t a) {
    asm volatile("ld.shared.v4.b32 {%0,%1,%2,%3}, [%4];" : "=r"(r[0]), "=r"(r[1]), "=r"(r[2]), "=r"(r[3]) : "r"(a) : "memory");
}
__device__ __forceinline__ void lds_fragv(uint32_t* r, uint32_t a) {
    asm volatile("ld.volatile.shared.v4.b32 {%0,%1,%2,%3}, [%4];" : "=r"(r[0]), "=r"(r[1]), "=r"(r[2]), "=r"(r[3]) : "r"(a) : "memory");
}
__device__ __forceinline__ uint32_t xorv(uint32_t a, uint32_t b) { uint32_t d; asm volatile("xor.b32 %0, %1, %2;" : "=r"(d) : "r"(a), "r"(b)); return d; }
#define SCHED(k) asm volatile("{\n.reg .pred p;\nsetp.ne.u32 p, %0, %1;\n@p bra.uni SD;\nSL: nanosleep.u32 64;\nbra.uni SL;\nSD:\n}" :: "r"(sbu - s), "n"(k) : "memory")
#define PINM() asm volatile("{\n.reg .pred p;\nsetp.eq.u32 p, %0, 1;\n@p st.shared.u32 [%0], 0;\n}" :: "r"(sbu) : "memory")
__device__ __forceinline__ uint32_t or_and(uint32_t a, uint32_t b, uint32_t c) { uint32_t d; asm("lop3.b32 %0, %1, %2, %3, 0xF8;" : "=r"(d) : "r"(a), "r"(b), "r"(c)); return d; }
__device__ __forceinline__ uint32_t pack2v(float a, float b) { uint32_t d; asm volatile("cvt.rn.bf16x2.f32 %0, %1, %2;" : "=r"(d) : "f"(b), "f"(a)); return d; }
#define FU(x) __float_as_uint(x)
__device__ __forceinline__ uint32_t clk32() { uint32_t t; asm volatile("mov.u32 %0, %%clock;" : "=r"(t) :: "memory"); return t; }
__device__ __forceinline__ void spin_until(uint32_t t0, uint32_t d) {
    if (d) {
#pragma unroll 1
        while (__any_sync(0xffffffffu, clk32() - t0 < d)) {}
    }
}
constexpr int SH_OFF = 229376 + 384;
constexpr uint32_t HONE2 = 0x3c003c00u, HCNT2 = 0x50005000u;

__device__ __forceinline__ uint64_t desc_sw128(uint32_t addr, uint32_t lbo, uint32_t sbo) {
    return (uint64_t)((addr & 0x3FFFF) >> 4) | ((uint64_t)(lbo >> 4) << 16) | ((uint64_t)(sbo >> 4) << 32) | (1ull << 62);
}
#define DP 390
#define NAX 3
#define NXL 0
#define NCX 2
#define NCL 1
#define FLIP 1
#define VTA 1
#define KXB 4
#define ANB 3
#define BNB 3
#define CNB 3
#define SMA 0
#define SMB 0
#define SMC 0x01
#define IVA 0
#define RGA 160
#define RGC 160
#define RGB (504 - RGA - RGC)
#define NRW 8
#define NBR 16
#define E0 0
#define E1 6
#define E2 4
#define E3 8
#define IV 2
#define G2V 0
#define G2K 2
#define VDEP 0
#define AEARLY 0
#define VTP 2
#define LORD 1
#define TRK 1
#define T2N 14
#define NB0 0
#define NB1 9
#define DB2 80
#define DITHER 0
#define DB 40

__device__ __forceinline__ uint32_t wrow_off(int kk, int ch) {
    const int lane = threadIdx.x & 31, r = lane & 7;
    const int row = 64 * (kk >> 2) + 32 * (r & 1) + 16 * (kk & 1) + 8 * (lane >> 4) + 4 * ((kk >> 1) & 1) + (r >> 1);
    return row * 128 + ((ch ^ (row & 7)) << 4);
}
template <int K> __device__ __forceinline__ void sched(uint32_t key) {
    asm volatile("{\n.reg .pred p;\nsetp.ne.u32 p, %0, %1;\n@p bra.uni SD;\nSL: nanosleep.u32 64;\nbra.uni SL;\nSD:\n}" :: "r"(key), "n"(K) : "memory");
}
__device__ __forceinline__ void sched_i(int i, uint32_t key) {
    if (i == -1) sched<20>(key); if (i == 0) sched<21>(key); if (i == 1) sched<22>(key); if (i == 2) sched<23>(key);
    if (i == 3) sched<24>(key); if (i == 4) sched<25>(key); if (i == 5) sched<26>(key); if (i == 6) sched<27>(key);
}
template <int NB, int SM, class F>
__device__ __forceinline__ void g1(float* q0, float* k0, uint32_t (*wq)[4], uint32_t (*wk)[4], uint32_t ga, uint32_t key, F&& hook) {
    float q1[4], k1[4];
    uint32_t b[NB][4];
#pragma unroll
    for (int i = 0; i < NB; i++) ldsm4(b[i], ga + i * 512);
    hook(-1, b[0]);
    if (SM & 1) sched_i(-1, key);
#pragma unroll
    for (int i = 0; i < 8; i++) {
        uint32_t* c = b[i % NB];
        MMAF(i == 0, q0, wq[2 * i], c[0], c[1]); MMAF(i == 0, k0, wk[2 * i], c[0], c[1]);
        MMAF(i == 0, q1, wq[2 * i + 1], c[2], c[3]); MMAF(i == 0, k1, wk[2 * i + 1], c[2], c[3]);
        const uint32_t cc_[4] = {c[0], c[1], c[2], c[3]};
        if (i + NB < 8) ldsm4(b[i % NB], ga + (i + NB) * 512);
        hook(i, cc_);
        if ((SM >> (i + 1)) & 1) sched_i(i, key);
    }
#pragma unroll
    for (int i = 0; i < 4; i++) { q0[i] += q1[i]; k0[i] += k1[i]; }
}
__device__ __forceinline__ float frag_norm2(uint32_t (*w)[4]) {
    float d0[4], d1[4];
#pragma unroll
    for (int i = 0; i < 32; i++) { MMAF(i == 0, d0, w[i], w[i][0], w[i][2]); MMAF(i == 0, d1, w[i], w[i][1], w[i][3]); }
    const int lane = threadIdx.x & 31, g = lane >> 2, t = lane & 3;
    float v = g == 2 * t ? d0[0] + d1[2] : (g == 2 * t + 1 ? d0[1] + d1[3] : 0.f);
#pragma unroll
    for (int o = 16; o; o >>= 1) v += __shfl_xor_sync(0xffffffffu, v, o);
    return v;
}
__device__ __forceinline__ void load_slot(uint32_t sb, int c, int tile, const Maps& maps) {
    const uint32_t dst = sb + ((tile & 1) ? R_SLOT1 : R_SLOT0), mb = sb + R_BAR + 8 * (MB_FULL0 + (tile & 1));
    mbar_expect_tx(mb, 24576);
    if ((EF >> 8) & 1) {
        tma2d_h(dst + 16384, &maps.kx, c * 64, tile * 64, mb, pol_ef(8));
        tma3d_h(dst, &maps.vx3, tile * 64, (c >> 1) * 2, mb, pol_ef(8));
    } else {
        tma2d(dst + 16384, &maps.kx, c * 64, tile * 64, mb);
        tma3d(dst, &maps.vx3, tile * 64, (c >> 1) * 2, mb);
    }
}
__device__ __forceinline__ uint32_t put_mem0(uint32_t sb, int W, const bf16* __restrict__ mem0) {
    const int lane = threadIdx.x & 31;
    const uint4 a = *(const uint4*)(mem0 + (lane & 7) * DM + W * 64 + (lane >> 3) * 8), b = *(const uint4*)(mem0 + (lane & 7) * DM + W * 64 + 32 + (lane >> 3) * 8);
    const uint4 m0 = make_uint4(prmt(a.x, b.x, 0x5410u), prmt(a.x, b.x, 0x7632u), prmt(a.y, b.y, 0x5410u), prmt(a.y, b.y, 0x7632u));
    const uint4 m1 = make_uint4(prmt(a.z, b.z, 0x5410u), prmt(a.z, b.z, 0x7632u), prmt(a.w, b.w, 0x5410u), prmt(a.w, b.w, 0x7632u));
    bar_sync(3, 256);
    sts128u(sb + R_MEMB + W * 1024 + lane * 16, m0.x, m0.y, m0.z, m0.w);
    sts128u(sb + R_MEMB + W * 1024 + 512 + lane * 16, m1.x, m1.y, m1.z, m1.w);
    return amax2b(amax2b(amax2b(m0.x, m0.y), amax2b(m0.z, m0.w)), amax2b(amax2b(m1.x, m1.y), amax2b(m1.z, m1.w)));
}
#define PUT_MAX(rL, W) sts32(rL + R_STG + 1024 + ((W) >> 2) * 512 + ((W) & 3) * 4, amax2b(amax2b(mx, my), mz));
__device__ __forceinline__ uint32_t h2b(uint32_t w) {
    uint32_t d;
    asm("{\n.reg .f16 l, h;\n.reg .f32 a, b;\nmov.b32 {l, h}, %1;\ncvt.f32.f16 a, l;\ncvt.f32.f16 b, h;\ncvt.rn.bf16x2.f32 %0, b, a;\n}" : "=r"(d) : "r"(w));
    return d;
}
#define GATHER1(HALF)                                                                                           \
        {                                                                                                       \
            const uint4 x0 = ldg_rlx4(pm), x1 = ldg_rlx4(pm + 256); const uint2 y = ldg_rlx2(px);                 \
            cw = (sel & 0x4000u) ? prmt(x0.w, x1.w, 0x7632u) : prmt(y.x, y.y, 0x5410u);                         \
            const uint32_t p0 = h2b(x0.x), p1 = h2b(x0.y), p2 = h2b(x0.z), p3 = h2b(prmt(x0.w, y.x, sel));      \
            stsm4t(rG + R_MEMB + HALF * 4096, p0, p1, p2, p3);                                                  \
            const uint32_t p4 = h2b(x1.x), p5 = h2b(x1.y), p6 = h2b(x1.z), p7 = h2b(prmt(x1.w, y.y, sel));      \
            stsm4t(rG + R_MEMB + HALF * 4096 + 512, p4, p5, p6, p7);                                            \
            mx = amax2b(amax2b(p0, p1), amax2b(p2, p3)); my = amax2b(p4, p5); mz = amax2b(p6, p7);              \
        }
#define GATHER(HALF, PRE, SYNC, AFTER)                                                                                      \
        {                                                                                                       \
            const uint32_t so = aslot(s);                                                                       \
            const uint32_t ua = (glo + acc_base(HALF * 4 + fo)) ^ so, ux = (glo + ext_base(HALF * 4 + fo)) ^ so; \
            uint2 lt;                                                                                           \
            lt.x = lds32v_(rL + R_LT); lt.y = lds32v_(rL + R_LT + 4);                                           \
            const uint32_t sel = 0x7610u - ((lt.x ^ (lt.x >> 2)) & 16) * 0x440u;                                \
            const uint32_t* pm = mkptr(ua + lt.x, ghi);                                                         \
            const uint32_t* px = mkptr(ux + lt.y, ghi);                                                         \
            PRE                                                                                                 \
            bar_sync(5, 384);                                                                                   \
            const uint32_t t0 = clk32();                                                                        \
            TSACC();                                                                        \
            SYNC                                                                                                \
            spin_until(t0, DP + DITHER);                                                                                 \
            \
            TS(10, 0);                                                                                          \
            uint32_t cw, nr = 0;                                                                                \
            _Pragma("unroll 1") do {                                                                            \
                GATHER1(HALF)                                                                                   \
                nr++;                                                                                           \
            } while (__any_sync(0xffffffffu, cw != HCNT2 && nr < SPIN_LIMIT));                                  \
            TS(11, cw);                                                                                         \
            AFTER                                                                                               \
            CNT2(HALF * 4 + (s & 1) * 2 + (nr > 2), nr > 1);                                                    \
            \
        }
#define GOBAR (fo == 3 ? 14 : 10 + fo)

__device__ __forceinline__ void rec_a(uint32_t sb, int c, const bf16* __restrict__ mem0, uint32_t epoch) {
    const int tid = threadIdx.x - WGA * 128, lane = tid & 31, f = tid >> 5;
    uint32_t wq[16][4], wk[16][4], mx, my = 0, mz = 0;
    const int lrow = ((lane >> 4) << 3) + (lane & 7), lsel = (lane >> 3) & 1;
    {
        mbar_wait(sb + R_BAR + 8 * MB_W0, 0);
        if (c == 7 && tid == 0) GT(1421);
#pragma unroll
        for (int kk = 0; kk < 16; kk++) { const uint32_t a = sb + R_T + wrow_off(kk, 2 * f + lsel); ldsm4t(wq[kk], a); ldsm4t(wk[kk], a + 32768); }
        __syncwarp();
        mx = put_mem0(sb, f, mem0);
    }
    const uint32_t rL = opaque(sb + lane * 16), rG = opaque(sb + lane * 16 + f * 1024);
    const uint32_t sbu = uni(sb), fo = uni(f), cc = uni(c);
    const uint64_t gx = xpage();
    const uint32_t ghi = uni((uint32_t)(gx >> 32)), glo = uni((uint32_t)gx);
#pragma unroll
    for (int i = 0; i < NAX; i++) {
        sts128u(rG + R_AX + 4096 * i, wq[i][0], wq[i][1], wq[i][2], wq[i][3]);
        sts128u(rG + R_AX + 4096 * i + 512, wk[i][0], wk[i][1], wk[i][2], wk[i][3]);
    }
    sts128u(rL + R_LT + 512 + f * 512, (sb + R_SREM + (f >= 2 ? lane * 8 + f * 256 : lane * 16 + f * 1024)) ^ 0x01000000u, (sb + R_BAR + 8 * MB_S) ^ 0x01000000u,
            sb + R_QP + (lane >> 4) * 128 + lsel * 512 + (lane & 7) * 16 + (f == 3 ? 2048 : 0), sb + R_SLOT0 + lrow * 128 + ((lsel ^ (lane & 7)) << 4));
    __syncwarp();
    if (tid == 0) GT(c * 8 + 1);
    TSDECL;
    const float cexp = 0.08838834764831845f * 1.4426950408889634f;
    float cs = cexp;
    auto step = [&](int s, bool first) -> bool {
        bar_sync(1, 128);
        float q0[4], k0[4];
        uint4 ta;
        uint32_t zr, rl2;
        g1<ANB, SMA>(q0, k0, wq, wk, rL + R_MEMB, sbu - s, [&](int i, const uint32_t* c_) {
            if (i == 0) TS(0, c_[0]);
            if (i == -1) {
#pragma unroll
                for (int n = NAX - NXL; n < NAX; n++) { lds_fragv(wq[n], rG + R_AX + 4096 * n); lds_fragv(wk[n], rG + R_AX + 4096 * n + 512); }
                ta = lds128uv(rL + R_LT + 512 + fo * 512);
                zr = ta.w & 1; rl2 = rL | zr;
            }
            if (i == IVA) { PUT_MAX(rl2, fo) bar_arrive(15, 256); bar_arrive(GOBAR, 96); }
        });
        stsm4t(rG + R_QP, pack2(q0[0], q0[1]), pack2(q0[2], q0[3]), pack2(k0[0], k0[1]), pack2(k0[2], k0[3]));
        TS(1, FU(k0[3]));
        if (first) mbar_wait_p(sbu + R_BAR + 8 * MB_FULL0, 0);
        if (fo >= 2) {
            bar_sync(3, 256);
            uint32_t kb[4], kc[4], qa[4], qc[4];
            ldsm4(kb, ta.z + 256); ldsm4(qa, ta.z);
            ldsm4(kc, ta.z + 1280); ldsm4(qc, ta.z + 1024);
            const uint32_t k0_ = hadd2b(kb[0], kb[1]), k1_ = hadd2b(kb[2], kb[3]), k2_ = hadd2b(kc[0], kc[1]), k3_ = hadd2b(kc[2], kc[3]);
            float s0[4], s2[4];
            MMAZ(s0, qa, k0_, k1_); MMAZ(s2, qc, k2_, k3_);
            const float x = ((s0[0] + s0[2]) + (s2[0] + s2[2])) * cs, y = ((s0[1] + s0[3]) + (s2[1] + s2[3])) * cs;
            st_async2(ta.x, FU(x), FU(y), ta.y);
            TS(3, FU(y));
            sts64((ta.x ^ 0x01000000u) + (R_SLOC - R_SREM), x, y);
            sts128u(rl2 + R_STG + (fo & 1) * 512, k0_, k1_, k2_, k3_);
            bar_arrive(9, 192);
        } else {
            uint32_t qa[4][4], kx[4][4];
#pragma unroll
            for (int kk = 0; kk < KXB; kk++) ldsm4(kx[kk], (ta.w ^ (kk * 32)) + (16384 + fo * 2048));
            bar_sync(3, 256);
#pragma unroll
            for (int kk = 0; kk < 4; kk++) {
                if (kk >= KXB) ldsm4(kx[kk], (ta.w ^ (kk * 32)) + (16384 + fo * 2048));
                ldsm4(qa[kk], ta.z + kk * 1024);
            }
            float s0[4], s1[4], s2[4], s3[4];
            MMAZ(s0, qa[0], kx[0][0], kx[0][1]); MMAZ(s1, qa[0], kx[0][2], kx[0][3]);
            MMAZ(s2, qa[1], kx[1][0], kx[1][1]); MMAZ(s3, qa[1], kx[1][2], kx[1][3]);
            MMA(s0, qa[2], kx[2][0], kx[2][1]); MMA(s1, qa[2], kx[2][2], kx[2][3]);
            MMA(s2, qa[3], kx[3][0], kx[3][1]); MMA(s3, qa[3], kx[3][2], kx[3][3]);
            const float x = ((s0[0] + s0[2]) + (s2[0] + s2[2])) * cs, y = ((s0[1] + s0[3]) + (s2[1] + s2[3])) * cs;
            const float z = ((s1[0] + s1[2]) + (s3[0] + s3[2])) * cs, w = ((s1[1] + s1[3]) + (s3[1] + s3[3])) * cs;
            st_async4(ta.x, x, y, z, w, ta.y);
            TS(3, FU(w));
            sts128(rG + R_SLOC, x, y, z, w);
        }
        const uint32_t r8 = (rl2 + sbu) >> 1;
        uint32_t vt00[4], vt01[4], vt10[4], vt11[4];
        const uint32_t rV = ta.w ^ ((fo & 1) * 64), vo = (fo >> 1) * 8192;
        if (!VTA && VTP < 2) { ldsm4t(vt00, rV + vo); ldsm4t(vt10, (rV ^ 32) + vo); }
        if (!VTA && VTP < 1) { ldsm4t(vt01, rV + vo + 2048); ldsm4t(vt11, (rV ^ 32) + vo + 2048); }
        bar_sync(4, 128);
        const float2 l2 = lds64v(r8 + R_SLOC + 512), l3 = lds64v(r8 + R_SLOC + 768);
        const float4 l0 = lds128v(rL + R_SLOC), l1 = lds128v(rL + R_SLOC + 1024);
        if (VTA && VTP < 2) { ldsm4t(vt00, rV + vo); ldsm4t(vt10, (rV ^ 32) + vo); }
        if (VTA && VTP < 1) { ldsm4t(vt01, rV + vo + 2048); ldsm4t(vt11, (rV ^ 32) + vo + 2048); }

        if (s == NSEG - 1) { mbar_wait_u(sbu + R_BAR + 8 * MB_S, 1); mbar_wait_u(sbu + R_BAR + 8 * MB_V, 1); return true; }
        TS(2, FU(l3.y));
        mbar_wait_p(sbu + R_BAR + 8 * MB_S, s & 1);
        TS(4, 0);
        {
            const float2 r2 = lds64v(r8 + R_SREM + 512), r3 = lds64v(r8 + R_SREM + 768);
            const float4 r0 = lds128v(rL + R_SREM), r1 = lds128v(rL + R_SREM + 1024);
            if (VTP >= 1) PINM();
            if (VTP >= 2) { ldsm4t(vt00, rV + vo); ldsm4t(vt10, (rV ^ 32) + vo); }
            if (VTP >= 1) { ldsm4t(vt01, rV + vo + 2048); ldsm4t(vt11, (rV ^ 32) + vo + 2048); }
            float sv[10];
            sv[0] = l0.x + r0.x; sv[1] = l0.y + r0.y; sv[2] = l0.z + r0.z; sv[3] = l0.w + r0.w;
            sv[4] = l1.x + r1.x; sv[5] = l1.y + r1.y; sv[6] = l1.z + r1.z; sv[7] = l1.w + r1.w;
            sv[8] = ((l2.x + l3.x) + r2.x) + r3.x; sv[9] = ((l2.y + l3.y) + r2.y) + r3.y;
            float m = fmaxf(fmaxf(fmaxf(fmaxf(sv[8], sv[9]), sv[0]), fmaxf(fmaxf(sv[2], sv[3]), sv[1])), fmaxf(fmaxf(sv[4], sv[5]), fmaxf(sv[6], sv[7])));
            {
                const float m1 = __shfl_xor_sync(0xffffffffu, m, 1), m2 = __shfl_xor_sync(0xffffffffu, m, 2), m3 = __shfl_xor_sync(0xffffffffu, m, 3);
                m = fmaxf(fmaxf(m, m1), fmaxf(m2, m3));
            }
            TS(5, FU(m));
            const uint32_t ONE2 = 0x3f803f80u;
            float o0[4], o1[4], sm[4];
            const uint32_t pb0 = pack2(ex2(sv[0] - m), ex2(sv[1] - m)), pb1 = pack2(ex2(sv[2] - m), ex2(sv[3] - m));
            mma16816z(sm, ONE2, ONE2, ONE2, ONE2, pb0, pb1);
            MMAZ(o0, vt00, pb0, pb1); MMAZ(o1, vt10, pb0, pb1);
            const uint32_t z = (VDEP == 0 ? FU(m) : pb0) & zr;
            const uint32_t vok = mbar_test(sbu + R_BAR + 8 * MB_V + z, s & 1);
            const uint32_t rv = r8 + vok * 8;
            float2 va = lds64v(rv + R_VB - 8 + fo * 512);
            float2 vb = lds64v(rv + R_VB - 8 + fo * 512 + 256);
            float sig = __uint_as_float(lds32v_(sbu + R_MISC + 40));
            const uint32_t pb2 = pack2(ex2(sv[4] - m), ex2(sv[5] - m)), pb3 = pack2(ex2(sv[6] - m), ex2(sv[7] - m));
            mma16816(sm, ONE2, ONE2, ONE2, ONE2, pb2, pb3);
            const uint32_t pb4 = pack2(ex2(sv[8] - m), ex2(sv[9] - m));
            MMA(o0, vt01, pb2, pb3); MMA(o1, vt11, pb2, pb3);
            mma1688(sm, ONE2, ONE2, pb4);
            const float z0 = rcpf(sm[0]), z1 = rcpf(sm[1]);
#define PUT_O()                                                                                                   \
            {                                                                                                     \
                float a0[4] = {o0[0], o0[1], o0[2], o0[3]}, a1[4] = {o1[0], o1[1], o1[2], o1[3]};                 \
                mma1688(a0, FU(va.x), FU(va.y), pb4); mma1688(a1, FU(vb.x), FU(vb.y), pb4);                       \
                const float i0 = z0 * sig, i1 = z1 * sig;                                                         \
                stsm4t(rG + R_QP, pack2(a0[0] * i0, a0[1] * i1), pack2(a0[2] * i0, a0[3] * i1), pack2(a1[0] * i0, a1[1] * i1), pack2(a1[2] * i0, a1[3] * i1)); \
            }
            PUT_O()
            asm volatile("{\n.reg .pred p;\nsetp.ne.u32 p, %0, 0;\n@p bar.arrive 8, 256;\n}" :: "r"(vok) : "memory");
            if (__builtin_expect(__any_sync(0xffffffffu, vok == 0), 0)) {
                mbar_wait_p(sbu + R_BAR + 8 * MB_V, s & 1);
                va = lds64v(r8 + R_VB + fo * 512); vb = lds64v(r8 + R_VB + fo * 512 + 256);
                sig = __uint_as_float(lds32v_(sbu + R_MISC + 40));
                PUT_O()
                bar_arrive(8, 256);
                CNT(8);
            }
            TS(6, 0);
            const float r = __uint_as_float(0x7f000000u - FU(sig));
            cs = cexp * r * (fo >= 2 ? r : 1.f);
        }
        return false;
    };
    step(0, true);
#pragma unroll 1
    for (int s = 0;; s++) {
        if (s & 1) mbar_wait_p(sbu + R_BAR + 8 * (MB_FULL0 + (((s + 1) >> 1) & 1)), ((s + 1) >> 2) & 1);
        {
            const uint32_t a = rL + R_LT + 512 + 12 + fo * 512;
            sts32(a, lds32v_(a) + ((s & 1) ? ((s & 2) ? R_SLOT0 - R_SLOT1 - 4096 : R_SLOT1 - R_SLOT0 - 4096) : 4096));
        }
        auto early = [&]() {
            SCHED(13);
#pragma unroll
            for (int i = 0; i < NAX - NXL; i++) { lds_fragv(wq[i], rG + R_AX + 4096 * i); lds_fragv(wk[i], rG + R_AX + 4096 * i + 512); }
        };
        GATHER(0, , early();, )
        if (step(s + 1, false)) break;
    }
    CNT(9);
    if (rG == sbu) GT(cc * 8 + 4);
}

__device__ __forceinline__ void rec_b(uint32_t sb, int c, uint32_t epoch) {
    const int tid = threadIdx.x - WGB * 128, lane = tid & 31, f = tid >> 5;
    uint32_t wq[16][4], wk[16][4], wo[32][4];
    const int lrow = ((lane >> 4) << 3) + (lane & 7), lsel = (lane >> 3) & 1;
    const uint32_t rL = opaque(sb + lane * 16), rW = opaque(sb + lane * 16 + f * 16384);
    const uint32_t sbu = uni(sb), fo = uni(f), cc = uni(c), po = cc & 1, ep = uni(epoch);
    {
        mbar_wait(sb + R_BAR + 8 * MB_WO, 0);
        if (c == 7 && tid == 0) GT(1426);
        const uint32_t aO = sb + R_WO + f * 16384 + lrow * 128 + ((lsel ^ (lane & 7)) << 4);
#pragma unroll
        for (int i = 0; i < 32; i++) {
            const int tile = (i >> 4) * 2 + (i & 1), kk = (i >> 1) & 7;
            ldsm4t(wo[i], (aO ^ (32 * tile)) + kk * 2048);
        }
        const float no = frag_norm2(wo);
        if (lane == 0) sts32(sb + R_MISC + 80 + f * 4, FU(no));
        __syncwarp();
        bar_sync(0, 256);
        if (tid == 0) {
            const float4 a = lds128(sb + R_MISC + 64), b = lds128(sb + R_MISC + 80);
            stg4(&g_f.norm[c], make_uint4(FU((a.x + a.y) + (a.z + a.w)), epoch, FU((b.x + b.y) + (b.z + b.w)), epoch));
        }
        __syncwarp();
#pragma unroll
        for (int i = NRW; i < 32; i++) sts128u(rW + R_WO + i * 512, wo[i][0], wo[i][1], wo[i][2], wo[i][3]);
        mbar_wait(sb + R_BAR + 8 * MB_W1, 0);
        if (c == 7 && tid == 0) GT(1422);
        __syncwarp();
#pragma unroll
        for (int kk = 0; kk < 16; kk++) { const uint32_t a = sb + R_QK1 + wrow_off(kk, 2 * f + lsel); ldsm4t(wq[kk], a); ldsm4t(wk[kk], a + 32768); }
        bar_sync(13, 128);
#pragma unroll
        for (int i = 0; i < 16; i++) {
            sts128u(rW + R_QK1 + i * 1024, wq[i][0], wq[i][1], wq[i][2], wq[i][3]);
            sts128u(rW + R_QK1 + i * 1024 + 512, wk[i][0], wk[i][1], wk[i][2], wk[i][3]);
        }
        __syncwarp();
    }
    const uint64_t gx = xpage();
    const uint32_t ghi = uni((uint32_t)(gx >> 32)), glo = uni((uint32_t)gx);
    TSDECL;
#pragma unroll 1
    for (int s = 0;; s++) {
        bar_sync(2, 256);
        float q0[4], k0[4];
        g1<BNB, SMB>(q0, k0, wq, wk, rL + R_MEMB + 4096, sbu - s, [&](int i, const uint32_t* c_) {
            if (i == 0) TS(0, c_[0]);
            if (i >= 2 && i < 6) {
#pragma unroll
                for (int n = NRW + (i - 2) * E0 / 4; n < NRW + (i - 1) * E0 / 4; n++) lds_fragv(wo[n], rW + R_WO + n * 512);
            }
            if (i == IV) bar_arrive(GOBAR, 96);
        });
        stsm4t(rL + fo * 1024 + R_QP + 512, pack2(q0[0], q0[1]), pack2(q0[2], q0[3]), pack2(k0[0], k0[1]), pack2(k0[2], k0[3]));
        bar_arrive(3, 256);
        TS(1, FU(k0[3]));
        const uint32_t so = aslot(s);
        uint2 lt;
        { const float2 t = lds64v(rL + R_LT + 8); lt.x = FU(t.x); lt.y = FU(t.y); }
        const uint32_t sel = 0x3210u + (lt.x & 16) * 0x440u;
        uint32_t* pm = (uint32_t*)mkptr(((glo + acc_base(po * 4 + fo)) ^ so) + lt.x, ghi);
        uint32_t* px = (uint32_t*)mkptr(((glo + ext_base(po * 4 + fo)) ^ so) + lt.y, ghi);
        if (s == NSEG - 1) break;
        {
            const uint32_t z = lt.x & 1;
#pragma unroll
            for (int n = NRW; n < NRW + E0 + E1 + E2 + E3; n++) {
                const int d = n - (n < NRW + T2N ? TRK + 1 : TRK);
                lds_fragv(wo[n], (d >= NRW ? or_and(rW, wo[d][0], z) : rW) + R_WO + n * 512);
            }
        }
        TS(2, wo[NRW + E0 + E1 + E2 + E3 - 1][0]);
        SCHED(4);
        bar_sync(8, 256);
        {
            float o[4][4];
            uint32_t b[4][4];
#pragma unroll
            for (int i = 0; i < 4; i++) ldsm4(b[i], rL + R_QP + i * 1024);
            PINM();
#pragma unroll
            for (int n = NRW + E0 + E1 + E2 + E3; n < 32; n++) lds_fragv(wo[n], rW + R_WO + n * 512);
            float p[4][4];
#define G2_STEP(o, hf, kk) _Pragma("unroll") for (int i = 0; i < 2; i++) MMAF((kk) < 2, o[((kk) & 1) * 2 + i], wo[(hf) * 16 + (kk) * 2 + i], b[(kk) >> 1][((kk) & 1) * 2], b[(kk) >> 1][((kk) & 1) * 2 + 1])
#define G2_RED(o, wl, h) const uint32_t wl = packh2(o[1][2] + o[3][2], o[1][3] + o[3][3]);                            \
                asm volatile("red.relaxed.gpu.global.add.noftz.v4.f16x2 [%0], {%1,%2,%3,%4};" :: "l"(pm + (h) * 16),  \
                    "r"(packh2(o[0][0] + o[2][0], o[0][1] + o[2][1])), "r"(packh2(o[0][2] + o[2][2], o[0][3] + o[2][3])), \
                    "r"(packh2(o[1][0] + o[3][0], o[1][1] + o[3][1])), "r"(prmt(wl, HONE2, (h) ? sel : sel ^ 0x4400u)) : "memory")
            if (G2V == 1) SCHED(11);
#pragma unroll
            for (int kk = 0; kk < 8; kk++) { G2_STEP(o, 0, kk); }
            TS(7, b[0][0]);
            if (G2V == 0) SCHED(11);
            else {
#pragma unroll
                for (int i = 0; i < 4; i++) wo[16 + i][0] = or_and(wo[16 + i][0], FU(o[i][0]), lt.x & 1);
            }
#pragma unroll
            for (int kk = 0; kk < G2K; kk++) { G2_STEP(p, 1, kk); }
#pragma unroll
            for (int i = 0; i < NB0; i++) { lds_fragv(wq[i], rW + R_QK1 + i * 1024); lds_fragv(wk[i], rW + R_QK1 + i * 1024 + 512); }
            G2_RED(o, w3, 0);
            TS(8, w3);
            if (G2V == 0) SCHED(12);
#pragma unroll
            for (int kk = G2K; kk < 8; kk++) { G2_STEP(p, 1, kk); }
            G2_RED(p, w7, 1);
            asm volatile("red.relaxed.gpu.global.add.noftz.f16x2 [%0], %1;" :: "l"(px), "r"(prmt((w3 & 0xffff0000u) | 0x3c00u, w7, sel)) : "memory");
            TS(9, w7);
        }
        bar_arrive(5, 384);
        asm volatile("{\n.reg .pred p;\nsetp.eq.u32 p, %0, %1;\n@p mbarrier.arrive.expect_tx.shared::cta.b64 _, [%2], 1536;\n}"
                     :: "r"(rW), "r"(sbu), "r"(sbu + R_BAR + 8 * MB_S) : "memory");
        const uint32_t tb = clk32();
        TSACC();
        spin_until(tb, DB);
#pragma unroll
        for (int i = NB0; i < NBR; i++) {
            if (i == NB1) spin_until(tb, DP + DB2);
            lds_fragv(wq[i], rW + R_QK1 + i * 1024); lds_fragv(wk[i], rW + R_QK1 + i * 1024 + 512);
        }
    }
}

#undef lds_fragv
__device__ __forceinline__ void rec_first_loads(uint32_t sb, int c, const Maps& maps) {
    const uint32_t bar = sb + R_BAR;
    const int F0 = c * 64;
    mbar_expect_tx(bar + 8 * MB_W0, 65536); mbar_expect_tx(bar + 8 * MB_WO, 65536); mbar_expect_tx(bar + 8 * MB_WV, 65536);
    tma2d(sb + R_QK1, &maps.wv, F0, 0, bar + 8 * MB_WV); tma2d(sb + R_QK1 + 32768, &maps.wv, F0, 256, bar + 8 * MB_WV);
    tma2d(sb + R_T + 32768, &maps.wk, F0, 0, bar + 8 * MB_W0);
    if (!LORD) {
        for (int i = 0; i < 4; i++) tma2d(sb + R_WO + i * 16384, &maps.wo, (c & 1) * 256 + i * 64, (c >> 1) * 128, bar + 8 * MB_WO);
        tma2d(sb + R_T, &maps.wq, F0, 0, bar + 8 * MB_W0);
    }
    mbar_expect_tx(bar + 8 * MB_S, 1536);
}
__device__ __forceinline__ void rec_c(uint32_t sb, int c, const bf16* __restrict__ mem0, const Maps& maps, uint32_t epoch) {
    const int tid = threadIdx.x - WGC * 128, lane = tid & 31, u = tid >> 5;
    const uint32_t bar = sb + R_BAR;
    const int lrow = ((lane >> 4) << 3) + (lane & 7), lsel = (lane >> 3) & 1;
    const int kh = u >> 1, j = u & 1;
    uint32_t wv[32][4], mx, my = 0, mz = 0;
    {
        if (u == 0) {
            sts128u(sb + lane * 16 + R_LT, (lane >> 3) * 256 + (lane & 7) * 16, ((lane >> 2) & 1) * XHS + (lane >> 4) * XSS + (lane & 8) * 2 + (lane & 2) * 4,
                    (lane >> 2) * 256 + (lane & 3) * 16, (lane & 1) * XHS + ((lane >> 3) & 1) * XSS + (lane & 6) * 4 + (lane >> 4) * 4);
        }
        mbar_wait(bar + 8 * MB_WV, 0);
        if (c == 7 && tid == 0) GT(1425);
        if (LORD && tid == 32) {
            for (int i = 0; i < 4; i++) tma2d(sb + R_WO + i * 16384, &maps.wo, (c & 1) * 256 + i * 64, (c >> 1) * 128, bar + 8 * MB_WO);
            tma2d(sb + R_T, &maps.wq, c * 64, 0, bar + 8 * MB_W0);
        }
        __syncwarp();
#pragma unroll
        for (int kk = 0; kk < 16; kk++) {
            const uint32_t aa = sb + R_QK1 + kh * 32768 + wrow_off(kk, 4 * j + 2 * kh + lsel);
            ldsm4t(wv[kk], aa); ldsm4t(wv[16 + kk], aa ^ 32);
        }
        {
            uint32_t x = 0;
#pragma unroll
            for (int i = 0; i < 32; i++) x ^= wv[i][0];
            sts32(sb + R_MISC + 96 + u * 4, __reduce_xor_sync(0xffffffffu, x));
        }
        bar_sync(9, 128);
        if (c == 7 && tid == 0) GT(1423);
        if (tid == 0) {
            mbar_expect_tx(bar + 8 * MB_W1, 65536);
            tma2d(sb + R_QK1 + 32768, &maps.wk, c * 64, 256, bar + 8 * MB_W1); tma2d(sb + R_QK1, &maps.wq, c * 64, 256, bar + 8 * MB_W1);
        }
        __syncwarp();
        const float nv = frag_norm2(wv);
        if (lane == 0) sts32(sb + R_MISC + 64 + u * 4, FU(nv));
        __syncwarp();
        bar_arrive(0, 256);
        mx = put_mem0(sb, 4 + u, mem0);
    }
    const uint32_t rL = opaque(sb + lane * 16), rG = opaque(sb + lane * 16 + u * 1024);
    const uint32_t sbu = uni(sb), fo = uni(u), cc = uni(c), ep = uni(epoch);
    const uint64_t gx = xpage();
    const uint32_t ghi = uni((uint32_t)(gx >> 32)), glo = uni((uint32_t)gx);
    constexpr int CX = R_AX + NAX * 4096;
    static_assert(NAX + NCX <= 6, "AX");
#pragma unroll
    for (int i = 0; i < NCX; i++) {
        sts128u(rG + CX + 4096 * i, wv[i][0], wv[i][1], wv[i][2], wv[i][3]);
        sts128u(rG + CX + 4096 * i + 512, wv[16 + i][0], wv[16 + i][1], wv[16 + i][2], wv[16 + i][3]);
    }
    __syncwarp();
    TSDECL;
    uint32_t rpb = 0x3f800000u;
    bar_arrive(2, 256);
    uint32_t kvq = ~ep;
    auto ring = [&](int s) {
        uint32_t n = 0;
#pragma unroll 1
        while (!__all_sync(0xffffffffu, kvq == ep)) {
            kvq = ldg_rlx(&g_f.kv[(s + 2) >> 1][cc >> 1][(rL >> 4) & 1]);
            if (++n > SPIN_LIMIT) { ABORT(6); break; }
        }
        if (rL == sbu) load_slot(sbu, cc, (s + 2) >> 1, maps);
        __syncwarp();
    };
    if (fo == 3) { ring(-2); if (cc == 7 && rL == sbu) GT(1427); }
#pragma unroll 1
    for (int s = 0;; s++) {
        if (fo == 3 && !(s & 1) && s > 0 && s + 2 < NSEG) ring(s);
#pragma unroll
        for (int i = NCX - NCL; i < NCX; i++) { lds_fragv(wv[i], rG + CX + 4096 * i); lds_fragv(wv[16 + i], rG + CX + 4096 * i + 512); }
        PUT_MAX(rL, 4 + fo)
        if (fo == 0) {
                bar_sync(15, 256);
                if (s == 0) {
                    const uint32_t* np = (const uint32_t*)&g_f.norm[0] + ((rL ^ sbu) >> 2);
                    uint4 r, q; uint32_t n = 0;
#pragma unroll 1
                    while (true) {
                        r = ldg_rlx4(np); q = ldg_rlx4(np + 128);
                        const uint2 z = ldg_rlx2(&g_f.xn[(rL ^ sbu) >> 3]);
                        if (__all_sync(0xffffffffu, r.y == ep && r.w == ep && q.y == ep && q.w == ep && z.x == ep && z.y == ep)) break;
                        if (++n > SPIN_LIMIT) { ABORT(5); break; }
                    }
                    float nv = __uint_as_float(r.x) + __uint_as_float(q.x), no = __uint_as_float(r.z) + __uint_as_float(q.z);
#pragma unroll
                    for (int o = 16; o; o >>= 1) { nv += __shfl_xor_sync(0xffffffffu, nv, o); no += __shfl_xor_sync(0xffffffffu, no, o); }
                    const int lc = ((int)(FU(nv) >> 23) + (int)(FU(no) >> 23) - 252 + 9 + 1) >> 1;
                    sts32(sbu + R_MISC + 32, 140 - lc);
                    __syncwarp();
                }
                const uint4 ma = lds128uv(rL + R_STG + 1024), mb = lds128uv(rL + R_STG + 1536);
                const uint32_t m_ = amax2b(amax2b(amax2b(ma.x, ma.y), amax2b(ma.z, ma.w)), amax2b(amax2b(mb.x, mb.y), amax2b(mb.z, mb.w)));
                const int em = (int)(__reduce_max_sync(0xffffffffu, amax2b(m_, m_ << 16) & 0x7f800000u) >> 23) + (int)(rpb >> 23) - 127;
                const int es = min(max((int)lds32v_(sbu + R_MISC + 32) - max(em, 127), -60), 60);
                sts32(sbu + R_MISC + 40, (127 + es) << 23);
                TS(4, es);
        } else bar_arrive(15, 256);
        bar_sync(GOBAR, 96);
        float v0[4], v1[4];
        g1<CNB, SMC>(v0, v1, wv, wv + 16, rL + R_MEMB + (fo >> 1) * 4096, sbu - s, [&](int i, const uint32_t* c_) { if (i == 0) TS(0, c_[0]); });
        TS(1, FU(v1[3]));
        const uint32_t l16 = (rL ^ sbu) | (lds32v_(rL + R_LT + 4) & 1);
        const uint32_t r8 = sbu + (l16 >> 1);
        {
            sts128(rL + R_VRED + fo * 512, v1[0], v1[1], v1[2], v1[3]);
            const uint32_t d = r8 + R_VB + ((cc & 1) * 4 + (fo & 1) * 2 + (fo >> 1)) * 256;
            const uint32_t dr = xorv(d, 0x01000000u), br = xorv(sbu + R_BAR + 8 * MB_V, 0x01000000u);
            bar_sync(6 + (fo & 1), 64);
            const float4 a0 = lds128(rL + R_VRED + (fo ^ 2) * 512);
            const float rp = __uint_as_float(rpb);
            const uint32_t w0 = pack2((v0[0] + a0.x) * rp, (v0[1] + a0.y) * rp), w1 = pack2((v0[2] + a0.z) * rp, (v0[3] + a0.w) * rp);
            st_async2(dr, w0, w1, br);
            TS(3, w1);
            sts64(d, __uint_as_float(w0), __uint_as_float(w1));
            __syncwarp();
            asm volatile("{\n.reg .pred p;\nsetp.eq.u32 p, %0, %1;\n@p mbarrier.arrive.expect_tx.shared::cta.b64 _, [%2], 256;\n}"
                         :: "r"(rL), "r"(sbu), "r"(sbu + R_BAR + 8 * MB_V) : "memory");
        }
        if (fo == 1) {
            bar_sync(9, 192);
            uint8_t* dst = (uint8_t*)&g_KVf[s][cc >> 1][(cc & 1) * 256] + l16;
            const uint32_t r2 = prmt(rpb, 0, 0x3232u);
#pragma unroll
            for (int i = 0; i < 2; i++) {
                const uint4 a = lds128uv(rL + R_STG + i * 512);
                stg4(dst + i * 512, make_uint4(~hmul2b(a.x, r2), ~hmul2b(a.y, r2), ~hmul2b(a.z, r2), ~hmul2b(a.w, r2)));
                const float2 b0 = lds64v(r8 + R_VB + (cc & 1) * 1024 + i * 512), b1 = lds64v(r8 + R_VB + (cc & 1) * 1024 + i * 512 + 256);
                stg4(dst + 2048 + i * 512, make_uint4(~FU(b0.x), ~FU(b0.y), ~FU(b1.x), ~FU(b1.y)));
            }
            __syncwarp();
            if (l16 == 0) { stg_rlx(&g_f.rec[cc], (ep << 8) | (s + 1)); if (s == NSEG - 1) GT(1500 + cc); }
            __syncwarp();
        } else {
            bar_arrive(9, 192);
            if (fo == 2) {
                if (l16 < 144) stg4((void*)mkptr((glo + zero_off(cc, l16 >> 4)) ^ aslot(s + 4), ghi), make_uint4(0, 0, 0, 0));
                __syncwarp();
            } else if (fo == 3) {
                kvq = ldg_rlx(&g_f.kv[min((s + 3) >> 1, NT - 1)][cc >> 1][(l16 >> 4) & 1]);
                if (s == 0) ring(s);
            }
        }
        if (s == NSEG - 1) break;
        auto early = [&]() {
#pragma unroll
            for (int i = 0; i < NCX - NCL; i++) { lds_fragv(wv[i], rG + CX + 4096 * i); lds_fragv(wv[16 + i], rG + CX + 4096 * i + 512); }
        };
        GATHER(1, , early(); rpb = 0x7f000000u - lds32v_(sbu + R_MISC + 40);, bar_arrive(2, 256);)
    }
}

__device__ __forceinline__ bool cand_better(float v, int i, float bv, int bi) { return v > bv || (v == bv && i < bi); }

constexpr int G_W = 0;
constexpr int G_RING = 131072;
constexpr int G_BUF = 163840;
constexpr int G_BAR = 229376;
constexpr int G_SMEM = G_BAR + 512;
enum { GB_FULL = 0, GB_EMPTY = GB_FULL + 8, GB_KV = GB_EMPTY + 8, GB_STG = GB_KV + 2, GB_FREE = GB_STG + 2, GB_XN = GB_FREE + 2, GB_T1D, GB_VV, GB_KVF = GB_VV + 2, GB_VF, GB_N };
constexpr int SMEM_TOTAL = 232448;

__device__ __forceinline__ void wgmma_n128(float* d, uint64_t da, uint64_t db, int scale_d) {
    asm volatile("{\n.reg .pred p;\nsetp.ne.b32 p, %66, 0;\n"
        "wgmma.mma_async.sync.aligned.m64n128k16.f32.bf16.bf16 "
        "{%0,%1,%2,%3,%4,%5,%6,%7,%8,%9,%10,%11,%12,%13,%14,%15,%16,%17,%18,%19,%20,%21,%22,%23,%24,%25,%26,%27,%28,%29,%30,%31,"
        "%32,%33,%34,%35,%36,%37,%38,%39,%40,%41,%42,%43,%44,%45,%46,%47,%48,%49,%50,%51,%52,%53,%54,%55,%56,%57,%58,%59,%60,%61,%62,%63}, "
        "%64, %65, p, 1, 1, 0, 1;\n}"
        : "+f"(d[0]), "+f"(d[1]), "+f"(d[2]), "+f"(d[3]), "+f"(d[4]), "+f"(d[5]), "+f"(d[6]), "+f"(d[7]), "+f"(d[8]), "+f"(d[9]), "+f"(d[10]), "+f"(d[11]),
          "+f"(d[12]), "+f"(d[13]), "+f"(d[14]), "+f"(d[15]), "+f"(d[16]), "+f"(d[17]), "+f"(d[18]), "+f"(d[19]), "+f"(d[20]), "+f"(d[21]), "+f"(d[22]), "+f"(d[23]),
          "+f"(d[24]), "+f"(d[25]), "+f"(d[26]), "+f"(d[27]), "+f"(d[28]), "+f"(d[29]), "+f"(d[30]), "+f"(d[31]), "+f"(d[32]), "+f"(d[33]), "+f"(d[34]), "+f"(d[35]),
          "+f"(d[36]), "+f"(d[37]), "+f"(d[38]), "+f"(d[39]), "+f"(d[40]), "+f"(d[41]), "+f"(d[42]), "+f"(d[43]), "+f"(d[44]), "+f"(d[45]), "+f"(d[46]), "+f"(d[47]),
          "+f"(d[48]), "+f"(d[49]), "+f"(d[50]), "+f"(d[51]), "+f"(d[52]), "+f"(d[53]), "+f"(d[54]), "+f"(d[55]), "+f"(d[56]), "+f"(d[57]), "+f"(d[58]), "+f"(d[59]),
          "+f"(d[60]), "+f"(d[61]), "+f"(d[62]), "+f"(d[63])
        : "l"(da), "l"(db), "r"(scale_d));
}

__device__ __forceinline__ constexpr uint32_t slot_off(int slot) {
    return slot < 2 ? G_RING + slot * 16384 : G_BUF + (slot & 1) * 32768 + (slot < 4 ? 16384 : 0);
}
constexpr int PO = (HSPLIT / 2) & 1;
template <int NSLOT, class F>
__device__ __forceinline__ void gemm_tile(float* acc, uint32_t sb, int tile, int it, int wg, bool pass, uint32_t l0, F&& hook) {
    const uint32_t bar = sb + G_BAR;
    bar_sync(3 + wg, 256);
    int prev = 0;
#pragma unroll
    for (int k = 0; k < 4; k++) {
        const int n = tile * 4 + k, slot = NSLOT == 4 ? k : n % NSLOT;
        const uint32_t sz = sb + (((it + k) << 4) & sb & 0x3f0);
        const uint64_t da = desc_sw128(sz + slot_off(slot), 16, 1024), db0 = desc_sw128(sz + G_W, 65536, 1024);
        mbar_wait_p(bar + 8 * (GB_FULL + slot), NSLOT == 4 ? (tile & 1) : ((n / NSLOT) & 1));
        if (k == 3 && pass) bar_arrive(3 + (wg ^ 1), 256);
        asm volatile("wgmma.fence.sync.aligned;" ::: "memory");
#pragma unroll
        for (int kk = 0; kk < 4; kk++) wgmma_n128(acc, da + kk * 2, db0 + k * 1024 + kk * 128, (k | kk) != 0);
        asm volatile("wgmma.commit_group.sync.aligned;" ::: "memory");
        if (k > 0) {
            asm volatile("wgmma.wait_group.sync.aligned 1;" ::: "memory");
            mbar_arrive2_if(bar + 8 * (GB_EMPTY + prev), l0);
        }
#pragma unroll
        for (int kk = 0; kk < 4; kk++) wgmma_n128(acc, da + 512 + kk * 2, db0 + k * 1024 + 512 + kk * 128, 1);
        asm volatile("wgmma.commit_group.sync.aligned;" ::: "memory");
        if (k == 1) hook();
        prev = slot;
    }
    asm volatile("wgmma.wait_group.sync.aligned 0;" ::: "memory");
    mbar_arrive2_if(bar + 8 * (GB_EMPTY + prev), l0);
}
__device__ __forceinline__ void stage_bf16(const float* acc, uint32_t buf, float s0, float s1) {
    const int lane = threadIdx.x & 31, wq = (threadIdx.x >> 5) & 3;
    const int row = wq * 16 + (lane & 7) + ((lane >> 3) & 1) * 8;
    const uint32_t base = buf + row * 128;
#pragma unroll
    for (int j = 0; j < 16; j += 2) {
        const int ch = (j & 7) + (lane >> 4);
        stsm4(base + (j >> 3) * 8192 + ((ch ^ (row & 7)) << 4),
              pack2(acc[4 * j] * s0, acc[4 * j + 1] * s0), pack2(acc[4 * j + 2] * s1, acc[4 * j + 3] * s1),
              pack2(acc[4 * j + 4] * s0, acc[4 * j + 5] * s0), pack2(acc[4 * j + 6] * s1, acc[4 * j + 7] * s1));
    }
}

__device__ __forceinline__ void store_perm(const float* acc, bf16* dst, int ld, float s0, float s1, uint32_t m) {
#pragma unroll
    for (int i = 0; i < 4; i++) {
        const float* a = acc + 16 * i;
        stg4(dst + i * 32, make_uint4(pack2(a[0] * s0, a[1] * s0) ^ m, pack2(a[4] * s0, a[5] * s0) ^ m, pack2(a[8] * s0, a[9] * s0) ^ m, pack2(a[12] * s0, a[13] * s0) ^ m));
        stg4(dst + 8 * ld + i * 32, make_uint4(pack2(a[2] * s1, a[3] * s1) ^ m, pack2(a[6] * s1, a[7] * s1) ^ m, pack2(a[10] * s1, a[11] * s1) ^ m, pack2(a[14] * s1, a[15] * s1) ^ m));
    }
}
template <int ACC>
__device__ __forceinline__ void wgmma_rs64(float* d, const uint32_t* a, uint64_t db) {
    asm volatile("{\n.reg .pred p;\nsetp.ne.b32 p, %37, 0;\n"
        "wgmma.mma_async.sync.aligned.m64n64k16.f32.bf16.bf16 {%0,%1,%2,%3,%4,%5,%6,%7,%8,%9,%10,%11,%12,%13,%14,%15,%16,%17,%18,%19,%20,%21,%22,%23,%24,%25,%26,%27,%28,%29,%30,%31}, {%32,%33,%34,%35}, %36, p, 1, 1, 0;\n}"
        : "+f"(d[0]), "+f"(d[1]), "+f"(d[2]), "+f"(d[3]), "+f"(d[4]), "+f"(d[5]), "+f"(d[6]), "+f"(d[7]), "+f"(d[8]), "+f"(d[9]), "+f"(d[10]), "+f"(d[11]), "+f"(d[12]), "+f"(d[13]), "+f"(d[14]), "+f"(d[15]), "+f"(d[16]), "+f"(d[17]), "+f"(d[18]), "+f"(d[19]), "+f"(d[20]), "+f"(d[21]), "+f"(d[22]), "+f"(d[23]), "+f"(d[24]), "+f"(d[25]), "+f"(d[26]), "+f"(d[27]), "+f"(d[28]), "+f"(d[29]), "+f"(d[30]), "+f"(d[31])
        : "r"(a[0]), "r"(a[1]), "r"(a[2]), "r"(a[3]), "l"(db), "n"(ACC));
}
template <int ACC>
__device__ __forceinline__ void wgmma_rs128t(float* d, const uint32_t* a, uint64_t db) {
    asm volatile("{\n.reg .pred p;\nsetp.ne.b32 p, %69, 0;\n"
        "wgmma.mma_async.sync.aligned.m64n128k16.f32.bf16.bf16 {%0,%1,%2,%3,%4,%5,%6,%7,%8,%9,%10,%11,%12,%13,%14,%15,%16,%17,%18,%19,%20,%21,%22,%23,%24,%25,%26,%27,%28,%29,%30,%31,%32,%33,%34,%35,%36,%37,%38,%39,%40,%41,%42,%43,%44,%45,%46,%47,%48,%49,%50,%51,%52,%53,%54,%55,%56,%57,%58,%59,%60,%61,%62,%63}, {%64,%65,%66,%67}, %68, p, 1, 1, 1;\n}"
        : "+f"(d[0]), "+f"(d[1]), "+f"(d[2]), "+f"(d[3]), "+f"(d[4]), "+f"(d[5]), "+f"(d[6]), "+f"(d[7]), "+f"(d[8]), "+f"(d[9]), "+f"(d[10]), "+f"(d[11]), "+f"(d[12]), "+f"(d[13]), "+f"(d[14]), "+f"(d[15]), "+f"(d[16]), "+f"(d[17]), "+f"(d[18]), "+f"(d[19]), "+f"(d[20]), "+f"(d[21]), "+f"(d[22]), "+f"(d[23]), "+f"(d[24]), "+f"(d[25]), "+f"(d[26]), "+f"(d[27]), "+f"(d[28]), "+f"(d[29]), "+f"(d[30]), "+f"(d[31]), "+f"(d[32]), "+f"(d[33]), "+f"(d[34]), "+f"(d[35]), "+f"(d[36]), "+f"(d[37]), "+f"(d[38]), "+f"(d[39]), "+f"(d[40]), "+f"(d[41]), "+f"(d[42]), "+f"(d[43]), "+f"(d[44]), "+f"(d[45]), "+f"(d[46]), "+f"(d[47]), "+f"(d[48]), "+f"(d[49]), "+f"(d[50]), "+f"(d[51]), "+f"(d[52]), "+f"(d[53]), "+f"(d[54]), "+f"(d[55]), "+f"(d[56]), "+f"(d[57]), "+f"(d[58]), "+f"(d[59]), "+f"(d[60]), "+f"(d[61]), "+f"(d[62]), "+f"(d[63])
        : "r"(a[0]), "r"(a[1]), "r"(a[2]), "r"(a[3]), "l"(db), "n"(ACC));
}
__device__ __forceinline__ void attention_tile(float* acc, uint32_t sb, int tile, int h, int wg, int wq, uint32_t l0, uint32_t epoch, uint4* km, uint4* vm) {
    const uint32_t buf = sb + G_BUF + ((tile << 4) & sb & 0x3f0);
    const int lane = threadIdx.x & 31, g = lane >> 2, t = lane & 3;
    const int sg = wq >> 1, hf = wq & 1, seg = tile * 2 + sg;
    uint32_t qf[8][4];
#pragma unroll
    for (int kk = 0; kk < 8; kk++) {
        qf[kk][0] = pack2(acc[8 * kk], acc[8 * kk + 1]); qf[kk][1] = pack2(acc[8 * kk + 2], acc[8 * kk + 3]);
        qf[kk][2] = pack2(acc[8 * kk + 4], acc[8 * kk + 5]); qf[kk][3] = pack2(acc[8 * kk + 6], acc[8 * kk + 7]);
    }
    uint32_t* kvf = &g_KVf[seg][h][lane * 4];
    auto kv_valid = [&]() {
        uint32_t mn = 0xffffffffu;
#pragma unroll
        for (int i = 0; i < 4; i++) mn = min(min(min(mn, min(km[i].x, km[i].y)), min(km[i].z, km[i].w)), min(min(vm[i].x, vm[i].y), min(vm[i].z, vm[i].w)));
        return __all_sync(0xffffffffu, mn != 0);
    };
    float sc[5][4];
    auto mem_scores = [&]() {
        float sb_[4];
#pragma unroll
        for (int i = 0; i < 4; i++) { MMAF(i == 0, sc[4], qf[2 * i], ~km[i].x, ~km[i].y); MMAF(i == 0, sb_, qf[2 * i + 1], ~km[i].z, ~km[i].w); }
#pragma unroll
        for (int i = 0; i < 4; i++) sc[4][i] += sb_[i];
    };
    mbar_wait_p(sb + G_BAR + 8 * (GB_KV + wg), (tile >> 1) & 1);
    if (h == 5 && (threadIdx.x & 127) == 0 && tile < 6) GT(1750 + tile * 8 + 2);
    bool fast;
    {
        const uint64_t dk = desc_sw128(buf, 16, 1024);
        asm volatile("wgmma.fence.sync.aligned;" ::: "memory");
#pragma unroll
        for (int kk = 0; kk < 8; kk++) {
            if (kk == 0) wgmma_rs64<0>(acc, qf[kk], dk); else wgmma_rs64<1>(acc, qf[kk], dk + (kk >> 2) * 512 + (kk & 3) * 2);
        }
        asm volatile("wgmma.commit_group.sync.aligned;" ::: "memory");
        mem_scores();
        fast = kv_valid();
        asm volatile("wgmma.wait_group.sync.aligned 0;" ::: "memory");
        mbar_arrive_if(sb + G_BAR + 8 * GB_KVF, l0);
#pragma unroll
        for (int i = 0; i < 32; i++) asm volatile("" : "+f"(acc[i]) :: "memory");
#pragma unroll
        for (int b = 0; b < 4; b++)
#pragma unroll
            for (int i = 0; i < 4; i++) sc[b][i] = sg ? acc[16 + 4 * b + i] : acc[4 * b + i];
#pragma unroll
        for (int i = 0; i < 4; i++) sc[4][i] = fast ? sc[4][i] : -INFINITY;
    }
    const float cexp = 0.08838834764831845f * 1.4426950408889634f;
    const int r0 = hf * 16 + g, r1 = r0 + 8;
#pragma unroll
    for (int b = 0; b < 4; b++) {
        const int j = b * 8 + 2 * t;
        if (j > r0) sc[b][0] = -INFINITY;
        if (j + 1 > r0) sc[b][1] = -INFINITY;
        if (j > r1) sc[b][2] = -INFINITY;
        if (j + 1 > r1) sc[b][3] = -INFINITY;
    }
    float m0 = -INFINITY, m1 = -INFINITY;
#pragma unroll
    for (int b = 0; b < 5; b++) { m0 = fmaxf(m0, fmaxf(sc[b][0], sc[b][1])); m1 = fmaxf(m1, fmaxf(sc[b][2], sc[b][3])); }
    m0 = fmaxf(m0, __shfl_xor_sync(0xffffffffu, m0, 1)); m1 = fmaxf(m1, __shfl_xor_sync(0xffffffffu, m1, 1));
    m0 = fmaxf(m0, __shfl_xor_sync(0xffffffffu, m0, 2)); m1 = fmaxf(m1, __shfl_xor_sync(0xffffffffu, m1, 2));
    float z0 = 0.f, z1 = 0.f;
    uint32_t p0, p1;
    {
        const float c0 = -m0 * cexp, c1 = -m1 * cexp;
        uint32_t pf[5][2];
#pragma unroll
        for (int b = 0; b < 5; b++) {
            pf[b][0] = pack2(ex2(fmaf(sc[b][0], cexp, c0)), ex2(fmaf(sc[b][1], cexp, c0)));
            pf[b][1] = pack2(ex2(fmaf(sc[b][2], cexp, c1)), ex2(fmaf(sc[b][3], cexp, c1)));
        }
        p0 = pf[4][0]; p1 = pf[4][1];
        uint32_t pa[4][4];
#pragma unroll
        for (int kk = 0; kk < 4; kk++)
#pragma unroll
            for (int i = 0; i < 4; i++) pa[kk][i] = (kk >> 1) == sg ? pf[(kk & 1) * 2 + (i >> 1)][i & 1] : 0u;
        const uint64_t dv = desc_sw128(buf + 32768, 8192, 1024);
        mbar_wait_p(sb + G_BAR + 8 * (GB_VV + wg), (tile >> 1) & 1);
        asm volatile("wgmma.fence.sync.aligned;" ::: "memory");
#pragma unroll
        for (int kk = 0; kk < 4; kk++) { if (kk == 0) wgmma_rs128t<0>(acc, pa[kk], dv); else wgmma_rs128t<1>(acc, pa[kk], dv + kk * 128); }
        asm volatile("wgmma.commit_group.sync.aligned;" ::: "memory");
#pragma unroll
        for (int b = 0; b < 5; b++) { z0 += bf_lo(pf[b][0]) + bf_hi(pf[b][0]); z1 += bf_lo(pf[b][1]) + bf_hi(pf[b][1]); }
        asm volatile("wgmma.wait_group.sync.aligned 0;" ::: "memory");
#pragma unroll
        for (int i = 0; i < 64; i++) asm volatile("" : "+f"(acc[i]) :: "memory");
    }
    mbar_arrive_if(sb + G_BAR + 8 * GB_VF, l0);
    if (h == 5 && (threadIdx.x & 127) == 0 && tile < 6) GT(1750 + tile * 8 + 3);
    if (!fast) {
        wait_rec(&g_f.rec[2 * h], epoch, seg + 1);
        if (seg == 63 && (threadIdx.x & 63) == 0) GT(1570 + h);
        uint32_t n = 0;
#pragma unroll 1
        do {
#pragma unroll
            for (int i = 0; i < 4; i++) { km[i] = ldg_rlx4(kvf + i * 128); vm[i] = ldg_rlx4(kvf + 512 + i * 128); }
            if (++n > SPIN_LIMIT) { ABORT(4); break; }
        } while (!kv_valid());
        mem_scores();
        float n0 = fmaxf(sc[4][0], sc[4][1]), n1 = fmaxf(sc[4][2], sc[4][3]);
        n0 = fmaxf(n0, __shfl_xor_sync(0xffffffffu, n0, 1)); n1 = fmaxf(n1, __shfl_xor_sync(0xffffffffu, n1, 1));
        n0 = fmaxf(n0, __shfl_xor_sync(0xffffffffu, n0, 2)); n1 = fmaxf(n1, __shfl_xor_sync(0xffffffffu, n1, 2));
        n0 = fmaxf(n0, m0); n1 = fmaxf(n1, m1);
        const float a0 = ex2((m0 - n0) * cexp), a1 = ex2((m1 - n1) * cexp);
        const float c0 = -n0 * cexp, c1 = -n1 * cexp;
        p0 = pack2(ex2(fmaf(sc[4][0], cexp, c0)), ex2(fmaf(sc[4][1], cexp, c0)));
        p1 = pack2(ex2(fmaf(sc[4][2], cexp, c1)), ex2(fmaf(sc[4][3], cexp, c1)));
        z0 = fmaf(z0, a0, bf_lo(p0) + bf_hi(p0)); z1 = fmaf(z1, a1, bf_lo(p1) + bf_hi(p1));
#pragma unroll
        for (int j = 0; j < 16; j++) { float* o = acc + 4 * j; o[0] *= a0; o[1] *= a0; o[2] *= a1; o[3] *= a1; }
    }
    if (h == 5 && (threadIdx.x & 127) == 0 && tile < 6) GT(1750 + tile * 8 + 4);
    if (hf) bar_arrive(5 + wg * 2 + sg, 64);
#pragma unroll
    for (int i = 0; i < 4; i++) {
        mma1688(acc + 16 * i, p0, p1, ~vm[i].x); mma1688(acc + 16 * i + 4, p0, p1, ~vm[i].y);
        mma1688(acc + 16 * i + 8, p0, p1, ~vm[i].z); mma1688(acc + 16 * i + 12, p0, p1, ~vm[i].w);
    }
    z0 += __shfl_xor_sync(0xffffffffu, z0, 1); z1 += __shfl_xor_sync(0xffffffffu, z1, 1);
    z0 += __shfl_xor_sync(0xffffffffu, z0, 2); z1 += __shfl_xor_sync(0xffffffffu, z1, 2);
    if (h == 5 && (threadIdx.x & 127) == 0 && tile < 6) GT(1750 + tile * 8 + 5);
    if (tile >= 2) mbar_wait_p(sb + G_BAR + 8 * (GB_FREE + wg), ((tile >> 1) - 1 + PO) & 1);
    store_perm(acc, g_O + (size_t)(tile * 64 + wq * 16 + g) * HD + h * 128 + t * 8, HD, rcpf(z0), rcpf(z1), 0);
    mbar_arrive(sb + G_BAR + 8 * (GB_STG + wg));
    if (!hf) {
        bar_sync(5 + wg * 2 + sg, 64);
#pragma unroll
        for (int i = 0; i < 8; i++) stg4_h(kvf + i * 128, make_uint4(0, 0, 0, 0), pol_ef(3));
    }
}

constexpr int NWK = FF / 32;
constexpr int F_WG = 0, F_WU = 32768, F_WD = 65536, F_RED = 98304, F_ACT = F_RED + 8192, F_SEL = F_ACT + 256;
__device__ __noinline__ void ffn_phase(const Maps& maps, bf16* __restrict__ out) {
    extern __shared__ __align__(1024) uint8_t smem[];
    const uint32_t sb = smem_u32(smem);
    const int c = ((volatile int*)(smem + SH_OFF))[8];
    const uint32_t epoch = ((volatile uint32_t*)(smem + SH_OFF))[9];
    const int tid = threadIdx.x;
    const bool worker = c < NWK;
    bar_sync(0, 384);
    const uint32_t mb = sb + R_BAR + 8 * MB_W0;
    if (tid == 352 && worker) {
        asm volatile("fence.proxy.async.shared::cta;" ::: "memory");
        mbar_expect_tx(mb, 98304);
#pragma unroll 1
        for (int j = 0; j < 6; j++) {
            if (j < 4) tma2d_h(sb + j * 16384, j < 2 ? &maps.wg : &maps.wu, c * 32, (j & 1) * 256, mb, pol_ef(5));
            else for (int i = 0; i < 4; i++) tma2d_h(sb + F_WD + ((j - 4) * 4 + i) * 4096, &maps.wd, ((j - 4) * 4 + i) * 64, c * 32, mb, pol_ef(5));
            if (FFS) __nanosleep(FFS);
        }
    }
    int p0 = -1, p1 = -1;
    float pb = 0.f;
#pragma unroll 1
    for (int pass = 0; pass < 2; pass++) {
        if (tid < 32) {
            const uint32_t tag = epoch & 0xfffffu;
            uint4 r[4]; uint32_t n = 0;
            const int t3 = tid + 96 < NFW ? tid + 96 : tid;
#pragma unroll 1
            while (true) {
                bool ok = true;
#pragma unroll
                for (int i = 0; i < 4; i++) r[i] = ldg_rlx4((const uint32_t*)&g_f.cand[pass][i < 3 ? tid + 32 * i : t3]);
#pragma unroll
                for (int i = 0; i < 4; i++) ok = ok && (r[i].y >> 12) == tag && (r[i].w >> 12) == tag;
                if (__all_sync(0xffffffffu, ok)) break;
                if (pass == 0) __nanosleep(100);
                if (++n > SPIN_LIMIT) { ABORT(7); break; }
            }
            bool chg = pass == 0;
#pragma unroll
            for (int i = 0; i < 4; i++) {
                const int j0 = r[i].y & 4095, j1 = r[i].w & 4095;
                chg = chg || (j0 != p0 && cand_better(__uint_as_float(r[i].x), j0, pb, p1)) || (j1 != p0 && cand_better(__uint_as_float(r[i].z), j1, pb, p1));
            }
            int* sel = (int*)(smem + F_SEL);
            if (__any_sync(0xffffffffu, chg)) {
                float b0 = __uint_as_float(r[0].x), b1 = __uint_as_float(r[0].z); int i0 = r[0].y & 4095, i1 = r[0].w & 4095;
#pragma unroll
                for (int i = 1; i < 9; i++) {
                    float c0, c1; int j0, j1;
                    if (i < 4) { c0 = __uint_as_float(r[i].x); c1 = __uint_as_float(r[i].z); j0 = r[i].y & 4095; j1 = r[i].w & 4095; }
                    else {
                        const int o = 1 << (i - 4);
                        c0 = __shfl_xor_sync(0xffffffffu, b0, o); c1 = __shfl_xor_sync(0xffffffffu, b1, o);
                        j0 = __shfl_xor_sync(0xffffffffu, i0, o); j1 = __shfl_xor_sync(0xffffffffu, i1, o);
                    }
                    if (i != 3 || t3 != tid) {
                        if (cand_better(c0, j0, b0, i0)) {
                            if (cand_better(c1, j1, b0, i0)) { b1 = c1; i1 = j1; } else { b1 = b0; i1 = i0; }
                            b0 = c0; i0 = j0;
                        } else if (cand_better(c0, j0, b1, i1)) { b1 = c0; i1 = j0; }
                    }
                }
                n = 0;
#pragma unroll 1
                while (!__all_sync(0xffffffffu, (ldg_rlx(&g_f.rows[pass][tid]) == epoch) & (ldg_rlx(&g_f.rows[pass][tid + 32]) == epoch) &
                                                   (ldg_rlx(&g_f.rows[pass][tid + 64]) == epoch) & (ldg_rlx(&g_f.rows[pass][t3]) == epoch))) { if (++n > SPIN_LIMIT) { ABORT(7); break; } }
                if (tid == 0) { sel[0] = min(i0, SQ - 1); sel[1] = min(i1, SQ - 1); ((float*)sel)[2] = b0; ((float*)sel)[3] = b1; }
            }
            if (pass && tid == 0 && c == 3) GT(1440);
        }
        bar_sync(0, 384);
        const int t0 = ((int*)(smem + F_SEL))[0], t1 = ((int*)(smem + F_SEL))[1];
        if (c == 3 && tid == 0 && pass == 0) GT(1430);
        if (t0 == p0 && t1 == p1) break;
        pb = ((float*)(smem + F_SEL))[3];
        const uint32_t ytag = epoch * 2 + pass + 1;
        if (worker) {
            const int lane = tid & 31, w = tid >> 5, g = lane >> 2, t = lane & 3;
            const int lrow = ((lane >> 4) << 3) + (lane & 7), lsel = (lane >> 3) & 1;
            float2* red = (float2*)(smem + F_RED);
            if (w < 8) {
                const uint32_t* xp = (const uint32_t*)(g_hn + (size_t)((g & 1) ? t1 : t0) * DM) + w * 32 + t;
                uint32_t xb[8];
#pragma unroll
                for (int i = 0; i < 8; i++) xb[i] = __ldcg(xp + i * 4);
                mbar_wait(mb, 1);
                if (c == 3 && tid == 0 && pass == 0) GT(1431);
                float d[4][4];
#pragma unroll
                for (int kk = 0; kk < 4; kk++) {
                    const int row = w * 64 + kk * 16 + lrow;
#pragma unroll
                    for (int m = 0; m < 4; m++) {
                        uint32_t a[4];
                        ldsm4t(a, sb + (m >> 1) * F_WU + row * 64 + ((((m & 1) * 2 + lsel) ^ ((row >> 1) & 3)) << 4));
                        MMAF(kk == 0, d[m], a, xb[2 * kk], xb[2 * kk + 1]);
                    }
                }
                const float e0 = t == 0 ? d[0][0] : (t == 1 ? d[1][0] : (t == 2 ? d[2][0] : d[3][0])), e1 = t == 0 ? d[0][1] : (t == 1 ? d[1][1] : (t == 2 ? d[2][1] : d[3][1]));
                const float e2 = t == 0 ? d[0][2] : (t == 1 ? d[1][2] : (t == 2 ? d[2][2] : d[3][2])), e3 = t == 0 ? d[0][3] : (t == 1 ? d[1][3] : (t == 2 ? d[2][3] : d[3][3]));
                red[w * 64 + t * 16 + g] = make_float2(e0, e1); red[w * 64 + t * 16 + g + 8] = make_float2(e2, e3);
            }
            bar_sync(0, 384);
            if (tid < 64) {
                const float* r = (const float*)red + tid;
                float gsum = 0.f, usum = 0.f;
#pragma unroll
                for (int kg = 0; kg < 8; kg++) { gsum += r[kg * 128]; usum += r[kg * 128 + 64]; }
                gsum = rbf(gsum); usum = rbf(usum);
                const float sg = rbf(gsum / (1.f + __expf(-gsum)));
                ((bf16*)(smem + F_ACT))[(tid & 1) * 32 + (tid >> 1)] = __float2bfloat16_rn(sg * usum);
            }
            bar_sync(0, 384);
            if (w < 8) {
                const uint32_t* ap = (const uint32_t*)(smem + F_ACT) + (g & 1) * 16 + t;
                float d[4][4];
#pragma unroll
                for (int kk = 0; kk < 2; kk++) {
                    const uint32_t b0 = ap[kk * 8], b1 = ap[kk * 8 + 4];
#pragma unroll
                    for (int m = 0; m < 4; m++) {
                        uint32_t a[4];
                        ldsm4t(a, sb + F_WD + w * 4096 + (kk * 16 + lrow) * 128 + (((m * 2 + lsel) ^ (lane & 7)) << 4));
                        MMAF(kk == 0, d[m], a, b0, b1);
                    }
                }
                const float e0 = t == 0 ? d[0][0] : (t == 1 ? d[1][0] : (t == 2 ? d[2][0] : d[3][0])), e1 = t == 0 ? d[0][1] : (t == 1 ? d[1][1] : (t == 2 ? d[2][1] : d[3][1]));
                const float e2 = t == 0 ? d[0][2] : (t == 1 ? d[1][2] : (t == 2 ? d[2][2] : d[3][2])), e3 = t == 0 ? d[0][3] : (t == 1 ? d[1][3] : (t == 2 ? d[2][3] : d[3][3]));
                uint4* yp = &g_yp[pass][c][w * 64 + t * 16 + g];
                stg4(yp, make_uint4(FU(e0), ytag, FU(e1), ytag)); stg4(yp + 8, make_uint4(FU(e2), ytag, FU(e3), ytag));
            }
            if (c == 3 && tid == 0 && pass == 0) GT(1432);
        } else {
            const int j = tid & 63, part = tid >> 6, col = (c - NWK) * 64 + j;
            const int tok = part ? t1 : t0, old = part ? p1 : p0;
            float hv = 0.f, nv = 0.f;
            if (part < 2) {
                hv = __bfloat162float(__ldcg(g_h + (size_t)tok * DM + col)); nv = __bfloat162float(__ldcg(g_hn + (size_t)tok * DM + col));
                if (old >= 0 && old != t0 && old != t1)
                    out[(size_t)old * DM + col] = __float2bfloat16_rn(__bfloat162float(__ldcg(g_h + (size_t)old * DM + col)) + __bfloat162float(__ldcg(g_hn + (size_t)old * DM + col)));
            }
            float s0 = 0.f, s1 = 0.f;
            uint4 v[10]; uint32_t n = 0;
            bool ok;
#pragma unroll 1
            do {
                ok = true;
#pragma unroll
                for (int i = 0; i < 10; i++) {
                    const int src = part + 6 * i;
                    v[i] = src < NWK ? ldg_rlx4((const uint32_t*)&g_yp[pass][src][col]) : make_uint4(0, ytag, 0, ytag);
                }
#pragma unroll
                for (int i = 0; i < 10; i++) ok = ok && v[i].y == ytag && v[i].w == ytag;
                if (!ok) __nanosleep(100);
                if (++n > SPIN_LIMIT) { ABORT(7); break; }
            } while (!ok);
#pragma unroll
            for (int i = 0; i < 10; i++) { s0 += __uint_as_float(v[i].x); s1 += __uint_as_float(v[i].z); }
            float2* red = (float2*)(smem + F_RED);
            red[part * 64 + j] = make_float2(s0, s1);
            bar_sync(0, 384);
            if (part < 2) {
                float y = 0.f;
#pragma unroll
                for (int i = 0; i < 6; i++) y += ((const float*)red)[(i * 64 + j) * 2 + part];
                const float rs = rbf(1.f / (1.f + __expf(-((float*)(smem + F_SEL))[2 + part])));
                out[(size_t)tok * DM + col] = __float2bfloat16_rn(hv + rbf(nv + rbf(rbf(y) * rs)));
            }
            if (tid == 0 && pass == 0 && c == NWK) GT(1434);
        }
        p0 = t0; p1 = t1;
        if (c == 3 && tid == 0 && pass == 0) GT(1433);
        bar_sync(0, 384);
    }
}

__device__ __forceinline__ void g_consumer(uint32_t sb_, int g_, int wg_, uint32_t epoch) {
    const uint32_t sb = uni(sb_);
    const int g = uni(g_), wg = uni(wg_), wq = uni((threadIdx.x >> 5) & 3);
    const uint32_t l0 = opaque((threadIdx.x & 31) == 0);
    const uint32_t bar = sb + G_BAR, buf = sb + G_BUF + wg * 32768;
    const int lane = threadIdx.x & 31;
    float acc[64];
    if (wg == 1) bar_arrive(3, 256);
    const int n1 = g < 32 ? HSPLIT / 2 : NT - HSPLIT / 2;
#pragma unroll 1
    for (int i = 0; i < n1; i++) {
        gemm_tile<4>(acc, sb, wg, i, wg, true, l0, []() {});
        if (threadIdx.x == 0 && i == 0) GT((64 + g) * 8 + 1);
        if (threadIdx.x == 128 && i == 3) GT((64 + g) * 8 + 2);
        if (i > 0) mbar_wait_p(bar + 8 * (GB_FREE + wg), (i - 1) & 1);
        stage_bf16(acc, buf, 1.f, 1.f);
        asm volatile("fence.proxy.async.shared::cta;" ::: "memory");
        mbar_arrive(bar + 8 * (GB_STG + wg));
    }
    if (threadIdx.x == 128) GT((64 + g) * 8 + 3);
    if (g < 32) {
#pragma unroll 1
        for (int i = 0; i < NT / 2; i++) {
            const int tile = 2 * i + wg;
            const uint2 rec = ldg_rlx2(&g_f.rec[2 * g]);
            uint4 km[4], vm[4];
            gemm_tile<4>(acc, sb, tile, i, wg, tile != NT - 1, l0, [&]() {
                const uint32_t seg = tile * 2 + (wq >> 1);
                const uint32_t* kvf = &g_KVf[seg][g][lane * 4];
                const bool early = (rec.x >> 8) == epoch && (rec.y >> 8) == epoch && (rec.x & 255) > seg && (rec.y & 255) > seg;
#pragma unroll
                for (int j = 0; j < 4; j++) { km[j] = ldg_rlx4_if(kvf + j * 128, early); vm[j] = ldg_rlx4_if(kvf + 512 + j * 128, early); }
            });
            if (threadIdx.x == 0 && i == 0) GT((64 + g) * 8 + 4);
            if (threadIdx.x == 128 && i == 3) GT((64 + g) * 8 + 5);
            if (g == 5 && (threadIdx.x & 127) == 0 && tile < 6) GT(1750 + tile * 8 + 1);
            attention_tile(acc, sb, tile, g, wg, wq, l0, epoch, km, vm);
            if (g == 5 && (threadIdx.x & 127) == 0 && tile < 6) GT(1750 + tile * 8 + 6);
        }
    } else {
#pragma unroll 1
        for (int i = 0; i < NT / 2; i++) {
            const int tile = 2 * i + wg;
            gemm_tile<NS3>(acc, sb, tile, i, wg, tile != NT - 1, l0, []() {});
            if (threadIdx.x == 0 && i == 0) GT((64 + g) * 8 + 4);
            if (threadIdx.x == 128 && i == 3) GT((64 + g) * 8 + 5);
            mbar_wait_p(bar + 8 * (GB_FREE + wg), (i - 1 + PO) & 1);
            store_perm(acc, g_P + (size_t)(((g - 32) >> 2) * SQ + tile * 64 + wq * 16 + (lane >> 2)) * DM + ((g - 32) & 3) * 128 + (lane & 3) * 8, DM, 1.f, 1.f, 0xffffffffu);
            mbar_arrive(bar + 8 * (GB_STG + wg));
        }
    }
}

__device__ __forceinline__ void load_w(uint32_t sb, const CUtensorMap* tm, int col, int k) {
    tma2d_h(sb + G_W + k * 16384, tm, col, k * 128, sb + G_BAR + 8 * (GB_FULL + k), pol_ef(5));
    tma2d_h(sb + G_W + 65536 + k * 16384, tm, col + 64, k * 128, sb + G_BAR + 8 * (GB_FULL + k), pol_ef(5));
}

__device__ __forceinline__ void rbf2(float& a, float& b) { uint32_t w = pack2(a, b); a = bf_lo(w); b = bf_hi(w); }
__device__ __forceinline__ void warp_sum2(float& a, float& b) {
#pragma unroll
    for (int o = 16; o; o >>= 1) { float c = __shfl_xor_sync(0xffffffffu, a, o), d = __shfl_xor_sync(0xffffffffu, b, o); a += c; b += d; }
}
__device__ __forceinline__ float sum16(const float* v) {
    return (((v[0] + v[1]) + (v[2] + v[3])) + ((v[4] + v[5]) + (v[6] + v[7]))) + (((v[8] + v[9]) + (v[10] + v[11])) + ((v[12] + v[13]) + (v[14] + v[15])));
}
__device__ __forceinline__ void ln_row2(float* v, float* u) {
    float sv = sum16(v), su = sum16(u);
    warp_sum2(sv, su);
    const float mv = sv * (1.f / DM), mu = su * (1.f / DM);
    float qv = 0.f, qu = 0.f, qv2 = 0.f, qu2 = 0.f;
#pragma unroll
    for (int i = 0; i < 16; i += 2) {
        float d0 = v[i] - mv, d1 = v[i + 1] - mv, e0 = u[i] - mu, e1 = u[i + 1] - mu;
        qv = fmaf(d0, d0, qv); qv2 = fmaf(d1, d1, qv2); qu = fmaf(e0, e0, qu); qu2 = fmaf(e1, e1, qu2);
    }
    qv += qv2; qu += qu2;
    warp_sum2(qv, qu);
    const float rv = rbf(mv), ru = rbf(mu);
    const float iv = __frcp_rn(rbf(sqrtf(rbf(rbf(qv * (1.f / DM)) + 1e-5f)))), iu = __frcp_rn(rbf(sqrtf(rbf(rbf(qu * (1.f / DM)) + 1e-5f))));
#pragma unroll
    for (int i = 0; i < 16; i += 2) {
        float a = v[i] - rv, b = v[i + 1] - rv, c = u[i] - ru, d = u[i + 1] - ru;
        rbf2(a, b); rbf2(c, d);
        a *= iv; b *= iv; c *= iu; d *= iu;
        rbf2(a, b); rbf2(c, d);
        v[i] = a; v[i + 1] = b; u[i] = c; u[i + 1] = d;
    }
}

__device__ __forceinline__ void ln_row1(float* v) {
    const float pv = __shfl_sync(0xffffffffu, v[0], 0);
    float sv = 0.f, sv2 = 0.f, qv = 0.f, qv2 = 0.f;
#pragma unroll
    for (int i = 0; i < 16; i += 2) { const float d0 = v[i] - pv, d1 = v[i + 1] - pv; sv += d0; sv2 += d1; qv = fmaf(d0, d0, qv); qv2 = fmaf(d1, d1, qv2); }
    sv += sv2; qv += qv2;
    warp_sum2(sv, qv);
    const float dm = sv * (1.f / DM), mv = pv + dm;
    qv = fmaxf(fmaf(-dm, sv, qv), 0.f);
    const float rv = rbf(mv);
    float sq, iv;
    asm("sqrt.approx.f32 %0, %1;" : "=f"(sq) : "f"(rbf(rbf(qv * (1.f / DM)) + 1e-5f)));
    asm("rcp.approx.f32 %0, %1;" : "=f"(iv) : "f"(rbf(sq)));
#pragma unroll
    for (int i = 0; i < 16; i += 2) {
        float a = v[i] - rv, b = v[i + 1] - rv;
        rbf2(a, b);
        a *= iv; b *= iv;
        rbf2(a, b);
        v[i] = a; v[i + 1] = b;
    }
}
constexpr int FSPLIT = 28;
__device__ __forceinline__ int fin_row(int id, int i) {
    if (id < 64) { const int tile = i < FSPLIT / 2 ? 2 * i : i + FSPLIT / 2; return tile < NT ? tile * 64 + id : -1; }
    const int j = id - 64 + i * 48;
    return j < FSPLIT * 32 ? (j >> 6) * 128 + 64 + (j & 63) : -1;
}
__device__ __forceinline__ void finalizer(int id, const bf16* __restrict__ x, const bf16* __restrict__ wr, bf16* __restrict__ out, uint32_t epoch, const bf16* pf) {
    const int lane = threadIdx.x & 31;
    float b0 = -INFINITY, b1 = -INFINITY; int i0 = 0x7fffffff, i1 = 0x7fffffff;
    const uint32_t tag = (epoch & 0xfffffu) << 12;
    uint32_t fl = ~epoch;
    int row = fin_row(id, 0);
    const uint4 ra = *(const uint4*)(wr + lane * 8), rb = *(const uint4*)(wr + 256 + lane * 8);
    uint4 xa = *(const uint4*)(x + (size_t)row * DM + lane * 8), xb = *(const uint4*)(x + (size_t)row * DM + lane * 8 + 256);
#pragma unroll 1
    for (int it = 0; row >= 0; it++) {
        const int tile = row >> 6, nxt = fin_row(id, it + 1);
        const size_t o0 = (size_t)row * DM + lane * 8;
        uint32_t n = 0;
#pragma unroll 1
        while (!__all_sync(0xffffffffu, fl == epoch)) {
            if (n && tile < NT - 1) __nanosleep(it ? 64 : 1000);
            fl = ldg_rlx(&g_f.p[tile][lane]);
            if (++n > SPIN_LIMIT) { ABORT(12); break; }
        }
        if (tile == NT - 1 && id == 63 && lane == 0) GT(1438);
        if ((id == 63 || id == 3 || id == 70) && lane == 0) GT(1800 + (id == 3) * 32 + tile);
        if (PFF && pf && lane == 0 && (unsigned)(it - PFF) < 7u)
            asm volatile("cp.async.bulk.prefetch.L2.global [%0], %1;" :: "l"(pf + (size_t)((id & 15) * 7 + it - PFF) * 8192), "r"(16384) : "memory");
        float v[16];
        {
            uint4 pa[8][2];
            n = 0;
#pragma unroll 1
            while (true) {
#pragma unroll
                for (int k = 0; k < 8; k++) {
                    pa[k][0] = ldg4_h(g_P + (size_t)k * SQ * DM + o0, pol_ef(2));
                    pa[k][1] = ldg4_h(g_P + (size_t)k * SQ * DM + o0 + 256, pol_ef(2));
                }
                fl = ldg_rlx(&g_f.p[max(nxt, 0) >> 6][lane]);
                uint32_t mn = 0xffffffffu;
#pragma unroll
                for (int k = 0; k < 8; k++) mn = min(min(min(mn, min(pa[k][0].x, pa[k][0].y)), min(pa[k][0].z, pa[k][0].w)), min(min(pa[k][1].x, pa[k][1].y), min(pa[k][1].z, pa[k][1].w)));
                if (__all_sync(0xffffffffu, mn != 0)) break;
                if (++n > SPIN_LIMIT) { ABORT(11); break; }
            }
            if (tile == NT - 1 && id == 63 && lane == 0) GT(1443);
#pragma unroll
            for (int j = 0; j < 2; j++) {
#pragma unroll
                for (int i = 0; i < 4; i++) {
                    uint32_t w[8];
#pragma unroll
                    for (int k = 0; k < 8; k++) w[k] = ~(i == 0 ? pa[k][j].x : (i == 1 ? pa[k][j].y : (i == 2 ? pa[k][j].z : pa[k][j].w)));
                    v[j * 8 + 2 * i] = ((bf_lo(w[0]) + bf_lo(w[1])) + (bf_lo(w[2]) + bf_lo(w[3]))) + ((bf_lo(w[4]) + bf_lo(w[5])) + (bf_lo(w[6]) + bf_lo(w[7])));
                    v[j * 8 + 2 * i + 1] = ((bf_hi(w[0]) + bf_hi(w[1])) + (bf_hi(w[2]) + bf_hi(w[3]))) + ((bf_hi(w[4]) + bf_hi(w[5])) + (bf_hi(w[6]) + bf_hi(w[7])));
                }
            }
        }
        uint32_t hw[8];
        {
            const uint32_t xw[8] = {xa.x, xa.y, xa.z, xa.w, xb.x, xb.y, xb.z, xb.w};
            uint32_t aw[8];
#pragma unroll
            for (int i = 0; i < 8; i++) aw[i] = pack2(v[2 * i], v[2 * i + 1]);
#pragma unroll
            for (int d = 1; d <= 2; d++) {
                const bool up = lane & d;
#pragma unroll
                for (int i = 0; i < 8; i++) {
                    if (!(i & d)) {
                        const uint32_t r = __shfl_xor_sync(0xffffffffu, up ? aw[i] : aw[i | d], d);
                        if (up) aw[i] = r; else aw[i | d] = r;
                    }
                }
            }
#pragma unroll
            for (int i = 0; i < 8; i++) {
                hw[i] = pack2(bf_lo(aw[i]) + bf_lo(xw[i]), bf_hi(aw[i]) + bf_hi(xw[i]));
                v[2 * i] = bf_lo(hw[i]); v[2 * i + 1] = bf_hi(hw[i]);
            }
        }
        xa = *(const uint4*)(x + (size_t)max(nxt, 0) * DM + lane * 8); xb = *(const uint4*)(x + (size_t)max(nxt, 0) * DM + lane * 8 + 256);
        ln_row1(v);
        float r0 = 0.f, r1 = 0.f;
        {
            const uint32_t ww[8] = {ra.x, ra.y, ra.z, ra.w, rb.x, rb.y, rb.z, rb.w};
#pragma unroll
            for (int i = 0; i < 8; i++) { r0 = fmaf(v[2 * i], bf_lo(ww[i]), r0); r1 = fmaf(v[2 * i + 1], bf_hi(ww[i]), r1); }
        }
        r0 += r1;
#pragma unroll
        for (int o = 16; o; o >>= 1) r0 += __shfl_xor_sync(0xffffffffu, r0, o);
        r0 = rbf(r0);
        if (cand_better(r0, row, b0, i0)) { b1 = b0; i1 = i0; b0 = r0; i0 = row; }
        else if (cand_better(r0, row, b1, i1)) { b1 = r0; i1 = row; }
        if (tile == NT - 1 && id == 63 && lane == 0) GT(1439);
        const bool keep = i0 == row || i1 == row || i1 >= SQ || row == SQ - 1;
        const bool last = nxt < 0, spec = tile < SPEC_TILES && (last || (nxt >> 6) >= SPEC_TILES);
        const bool pub = (lane == 0 && spec) || (lane == 1 && last);
        if (pub)
            asm volatile("st.relaxed.gpu.global.v4.b32 [%0], {%1,%2,%3,%4};" :: "l"(&g_f.cand[lane][id]),
                         "r"(FU(b0)), "r"(tag | (uint32_t)min(i0, 4095)), "r"(FU(b1)), "r"(tag | (uint32_t)min(i1, 4095)) : "memory");
#pragma unroll
        for (int j = 0; j < 2; j++) {
            const uint32_t* hh = hw + j * 4; const float* nn = v + j * 8;
            stg4_h(out + o0 + j * 256, make_uint4(pack2(bf_lo(hh[0]) + nn[0], bf_hi(hh[0]) + nn[1]), pack2(bf_lo(hh[1]) + nn[2], bf_hi(hh[1]) + nn[3]),
                                                  pack2(bf_lo(hh[2]) + nn[4], bf_hi(hh[2]) + nn[5]), pack2(bf_lo(hh[3]) + nn[6], bf_hi(hh[3]) + nn[7])), pol_ef(4));
            if (keep) {
                *(uint4*)(g_h + o0 + j * 256) = make_uint4(hh[0], hh[1], hh[2], hh[3]);
                *(uint4*)(g_hn + o0 + j * 256) = make_uint4(pack2(nn[0], nn[1]), pack2(nn[2], nn[3]), pack2(nn[4], nn[5]), pack2(nn[6], nn[7]));
            }
        }
        if (keep) { __threadfence(); __syncwarp(); }
        if (pub) stg_rlx(&g_f.rows[lane][id], epoch);
        if (tile >= LLT) {
#pragma unroll
            for (int k = 0; k < 8; k++) { stg4(g_P + (size_t)k * SQ * DM + o0, make_uint4(0, 0, 0, 0)); stg4(g_P + (size_t)k * SQ * DM + o0 + 256, make_uint4(0, 0, 0, 0)); }
        }
        row = nxt;
    }
    if (id == 0 && lane == 0) { g_epoch = epoch; if (epoch == 0xffffffu) { g_ticket[0] = 0; g_ticket[32] = 0; } }
}

__device__ __forceinline__ void g_producer(uint32_t sb, int g, const Maps& maps, uint32_t epoch, const bf16* __restrict__ x, const bf16* __restrict__ wr, bf16* __restrict__ out) {
    const uint32_t bar = sb + G_BAR;
    const int warp = (threadIdx.x >> 5) - 8;
    if (threadIdx.x == 256 && g == 5) GT(1410);
    if (threadIdx.x == 256 && g == 5) GT(1411);
    if (warp == 3) {
        wait_eq4(&g_f.xn[(threadIdx.x & 31) * 4], epoch, 13);
        __syncwarp();
        if ((threadIdx.x & 31) == 0) mbar_arrive(bar + 8 * GB_XN);
        finalizer(g, x, wr, out, epoch, nullptr);
        if (g == 63 && (threadIdx.x & 31) == 0) GT(128 * 8 + 6);
    }
    if ((threadIdx.x & 31) != 0) return;
    if (threadIdx.x == 256 && g == 5) GT(1412);
    if (warp == 0) {
        wait_eq4(&g_f.xn[0], epoch, 13);
        const int rk = g & 1;
        const int m1 = g < 32 ? HSPLIT : 2 * NT - HSPLIT;
        const int mx = g < 32 ? m1 + NT : m1;
#pragma unroll 1
        for (int it = 0; it < mx; it++) {
            const int tile = g < 32 ? (it < m1 ? it : it - m1) : (it < NT ? it : it - NT + HSPLIT);
            if (it == 1) wait_eq4(&g_f.xn[4], epoch, 13);
            if (it == 2) mbar_wait(bar + 8 * GB_XN, 0);
            const bool nw = it == 0 || it == (g < 32 ? m1 : NT);
#pragma unroll
            for (int k = 0; k < 4; k++) {
                mbar_wait(bar + 8 * (GB_EMPTY + k), (it & 1) ^ 1);
                mbar_expect_tx(bar + 8 * (GB_FULL + k), nw ? 49152 : 16384);
                tma2d_mc(sb + slot_off(k) + rk * 8192, &maps.xn2, (k * 2 + rk) * 64, tile * 64, bar + 8 * (GB_FULL + k));
                if (nw && (it > 0 || k >= 2))
                    load_w(sb, it > 0 && g < 32 ? &maps.wq4 : ((g & 1) ? &maps.wv4 : &maps.wk4), it == 0 ? (g >> 1) * 128 : (g < 32 ? g * 128 : ((g - 32) >> 1) * 128), k);
            }
        }
        if (g >= 32) {
            const int u = g - 32, ks = u >> 2, ns = u & 3;
            int slot = 0, ph = 1;
#pragma unroll 1
            for (int tile = 0; tile < NT; tile++) {
                if (tile > 0) wait_eq4(&g_f.o[tile][ks][0], epoch, 9);
                if (g == 40 && tile == NT - 1) GT(1437);
                if (tile == NT - 1) GT(1690 + g - 32);
#pragma unroll 1
                for (int k = 0; k < 4; k++) {
                    mbar_wait(bar + 8 * (GB_EMPTY + slot), slot < 4 ? ph : ph ^ 1);
                    mbar_expect_tx(bar + 8 * (GB_FULL + slot), tile == 0 ? 49152 : 16384);
                    if (tile == 0) {
#pragma unroll
                        for (int nh = 0; nh < 2; nh++)
                            asm volatile("cp.async.bulk.tensor.5d.shared::cluster.global.mbarrier::complete_tx::bytes [%0], [%1, {%3, %4, %4, %4, %5}], [%2];"
                                :: "r"(sb + G_W + nh * 65536 + k * 16384), "l"((uint64_t)&maps.wo2), "r"(bar + 8 * (GB_FULL + k)), "r"(ns * 128 + nh * 64), "r"(0), "r"(ks * 16 + k * 4) : "memory");
                        if (k == 0) wait_eq4(&g_f.o[0][ks][0], epoch, 9);
                    }
                    tma2d_mc_h(sb + slot_off(slot) + rk * 8192, &maps.ox2, (ks * 8 + k * 2 + rk) * 64, tile * 64, bar + 8 * (GB_FULL + slot), pol_ef(1));
                    if (++slot == NS3) { slot = 0; ph ^= 1; }
                }
            }
        }
    } else if (warp < 3) {
        const int wg = warp - 1;
        const uint32_t buf = sb + G_BUF + wg * 32768;
        const CUtensorMap* tkv = (g & 1) ? &maps.vx3 : &maps.kx3;
        const int n1 = g < 32 ? HSPLIT / 2 : NT - HSPLIT / 2;
#pragma unroll 1
        for (int i = 0; i < n1; i++) {
            const int tile = (i < NT / 2 ? 2 * i : 2 * i - NT + HSPLIT) + wg, hd = (i < NT / 2 ? g : g - 32) >> 1;
            mbar_wait(bar + 8 * (GB_STG + wg), i & 1);
            tma_store3d(tkv, buf, tile * 64, hd * 2);
            asm volatile("cp.async.bulk.commit_group;" ::: "memory");
            asm volatile("cp.async.bulk.wait_group.read 0;" ::: "memory");
            mbar_arrive(bar + 8 * (GB_FREE + wg));
            asm volatile("cp.async.bulk.wait_group 0;" ::: "memory");
            PUBLISH(&g_f.kv[tile][hd][g & 1], epoch);
        }
        if (wg == 0) mbar_arrive(bar + 8 * GB_T1D);
        if (g >= 32) for (int i = 0; i < 4; i++) mbar_arrive2_if(bar + 8 * (GB_EMPTY + 4 + wg), 1);
        if (g < 32 && wg == 1) {
            mbar_wait(bar + 8 * GB_T1D, 0);
#pragma unroll 1
            for (int tile = 0; tile < NT; tile++) {
                wait_eq2(&g_f.kv[tile][g][0], epoch, 10);
                if (tile > 0) mbar_wait(bar + 8 * GB_KVF, (tile - 1) & 1);
                mbar_expect_tx(bar + 8 * (GB_KV + (tile & 1)), 16384);
                tma3d_h(sb + G_BUF, &maps.kx3, tile * 64, g * 2, bar + 8 * (GB_KV + (tile & 1)), pol_ef(0));
                if (tile > 0) mbar_wait(bar + 8 * GB_VF, (tile - 1) & 1);
                mbar_expect_tx(bar + 8 * (GB_VV + (tile & 1)), 16384);
                tma3d_h(sb + G_BUF + 32768, &maps.vx3, tile * 64, g * 2, bar + 8 * (GB_VV + (tile & 1)), pol_ef(0));
                if (PFK && tile + PFK < NT) {
                    const uint2 v = ldg_rlx2(&g_f.kv[tile + PFK][g][0]);
                    if (v.x == epoch && v.y == epoch) { tma_pf3d(&maps.kx3, (tile + PFK) * 64, g * 2); tma_pf3d(&maps.vx3, (tile + PFK) * 64, g * 2); }
                }
            }
        } else {
#pragma unroll 1
            for (int tile = g < 32 ? 0 : wg; tile < NT; tile += g < 32 ? 1 : 2) {
                mbar_wait(bar + 8 * (GB_STG + (tile & 1)), ((tile >> 1) + PO) & 1);
                mbar_arrive(bar + 8 * (GB_FREE + (tile & 1)));
                if (g < 32 || tile < LLT) PUBLISH(g < 32 ? &g_f.o[tile][g >> 2][g & 3] : &g_f.p[tile][g - 32], epoch);
                else stg_rlx(&g_f.p[tile][g - 32], epoch);
                if (g == 3 && tile == NT - 1) GT(1436);
                if (g == 3) GT(1896 + tile);
                if (g < 32 && tile == NT - 1) GT(1610 + g);
                if (g == 40 && tile == NT - 1) GT(1435);
                if (g == 40) GT(1864 + tile);
                if (g >= 32 && tile == NT - 1) GT(1650 + g - 32);
            }
        }
    }
}

struct WPtr { const bf16 *q, *k, *v, *o, *g, *u; };
__device__ __forceinline__ int startup(uint8_t* smem, const bf16* __restrict__ x, const Maps& maps, uint32_t& epoch, const WPtr& pw) {
    const int tid = threadIdx.x, lane = tid & 31, w = tid >> 5, cta = blockIdx.x;
    volatile uint32_t* sh = (volatile uint32_t*)(smem + SH_OFF);
    if (cta == 4 && tid == 0) GT(1399);
    epoch = (ldg_rlx(&g_epoch) + 1) & 0x00ffffffu;
    if (w < 4) {
        if (!(cta & 1)) {
            uint32_t* pp = (uint32_t*)(xpage() + ((XR3 ^ 0x3000u) ^ ((w == 1 || w == 2) ? 0x1000u : 0u) ^ ((w & 2) << 13))) + (cta >> 1) * 8;
            if (lane < 8) stg_rlx(pp + lane, 0u);
            __syncwarp();
            if (lane == 0) {
                uint32_t best = 0xffffffffu, a = 0;
#pragma unroll 1
                for (int r = 0; r < NPROBE; r++) {
                    uint32_t t0 = clk32();
                    asm volatile("atom.relaxed.gpu.global.add.u32 %0, [%1], %2;" : "=r"(a) : "l"(pp), "r"(a + 1) : "memory");
                    if (a == 0x7fffffffu) ABORT(15);
                    uint32_t t1 = clk32();
                    if (r > 0) best = min(best, t1 - t0);
                    else if (w == 0) {
                        asm volatile("red.relaxed.gpu.global.max.u32 [%0], %1;" :: "l"(&g_ticket[0]), "r"(epoch << 8) : "memory");
                        asm volatile("red.relaxed.gpu.global.max.u32 [%0], %1;" :: "l"(&g_ticket[32]), "r"(epoch << 8) : "memory");
                    }
                }
                sh[w] = best;
            }
        }
        if (!(cta & 1)) bar_sync(1, 128);
        if (cta == 4 && tid == 0) GT(1400);
        if (w == 0) {
            if (lane == 0) {
                uint32_t rp;
                if (!(cta & 1)) {
                    uint32_t a = sh[0], b = sh[1], c = sh[2], d = sh[3];
                    uint32_t mid = (min(min(a, b), min(c, d)) + max(max(a, b), max(c, d))) >> 1;
                    const int dd = (int)min(a, d) - (int)min(b, c);
                    uint32_t cls = abs(dd) > 60 ? dd > 0 : a > mid;
                    uint32_t t = atomicAdd(&g_ticket[cls * 32], 1u) & 255;
                    if (t >= (cls ? 34u : 32u)) { cls ^= 1; t = atomicAdd(&g_ticket[cls * 32], 1u) & 255; }
                    rp = min(cls ? 32 + t : t, 65u);
                    stg_rlx(&g_table[(cta >> 1) * 8], (epoch << 8) | rp);
                } else {
                    uint32_t v, n = 0;
#pragma unroll 1
                    while (((v = ldg_rlx(&g_table[(cta >> 1) * 8])) >> 8) != epoch) { if (++n > SPIN_LIMIT) { ABORT(14); break; } }
                    rp = v & 255;
                }
                const int role = rp * 2 + (cta & 1);
                sh[8] = role; sh[9] = epoch;
                while (sh[10] != epoch + 1 && cta < NWAITLN) {}
                if (role < 64) rec_first_loads(smem_u32(smem), role, maps);
                else if (role < 128) for (int k = 0; k < 2; k++) load_w(smem_u32(smem), (role & 1) ? &maps.wv4 : &maps.wk4, ((role - 64) >> 1) * 128, k);
                if (cta == 4) GT(1401);
            }
        }
    } else if (cta < 128) {
        uint4 u[2][2];
        const int row0 = cta * 16 + (w - 4) * 2;
#pragma unroll
        for (int r = 0; r < 2; r++)
#pragma unroll
            for (int j = 0; j < 2; j++) u[r][j] = *(const uint4*)(x + (size_t)(row0 + r) * DM + j * 256 + lane * 8);
        if (cta < 48) {
            const uint32_t b = cta >> 3, off = (b >= 4 ? 0x8000u + (b & 1) * 0x4000u : ((b & 1) ? 0x3000u : 0u) + ((b & 2) << 13)) ^ aslot(cta & 7);
            *(uint4*)(xpage() + off + (tid - 128) * 16) = make_uint4(0, 0, 0, 0);
        }
        float v[2][16];
#pragma unroll
        for (int r = 0; r < 2; r++)
#pragma unroll
            for (int j = 0; j < 2; j++) {
                uint32_t ww[4] = {u[r][j].x, u[r][j].y, u[r][j].z, u[r][j].w};
#pragma unroll
                for (int i = 0; i < 4; i++) { v[r][j * 8 + 2 * i] = bf_lo(ww[i]); v[r][j * 8 + 2 * i + 1] = bf_hi(ww[i]); }
            }
        ln_row2(v[0], v[1]);
#pragma unroll
        for (int r = 0; r < 2; r++)
#pragma unroll
            for (int j = 0; j < 2; j++)
                *(uint4*)(g_xn + (size_t)(row0 + r) * DM + j * 256 + lane * 8) =
                    make_uint4(pack2(v[r][j * 8], v[r][j * 8 + 1]), pack2(v[r][j * 8 + 2], v[r][j * 8 + 3]), pack2(v[r][j * 8 + 4], v[r][j * 8 + 5]), pack2(v[r][j * 8 + 6], v[r][j * 8 + 7]));
        bar_sync(2, 256);
        if (tid == 160 && cta < NWAITLN) { st_rel(&g_f.xn[cta], epoch); sh[10] = epoch + 1; }
        if (cta == 4 && tid == 160) GT(1403);
        __syncwarp();
    }
    if (cta == 4 && tid == 128) GT(1402);
    __syncthreads();
    if (tid == 160 && cta >= NWAITLN && cta < 128) st_rel(&g_f.xn[cta], epoch);
    __syncwarp();
    const int role = sh[8];
    return role;
}

__global__ void __cluster_dims__(2, 1, 1) __launch_bounds__(384, 1)
main_kernel(const __grid_constant__ Maps maps, const bf16* __restrict__ x, const bf16* __restrict__ mem0, const bf16* __restrict__ wr,
            const bf16* __restrict__ wd, bf16* __restrict__ out, const WPtr pw) {
    extern __shared__ __align__(1024) uint8_t smem[];
    const uint32_t sb = smem_u32(smem);
    if (threadIdx.x == 0) {
        for (int i = 0; i < MB_N; i++) mbar_init(sb + R_BAR + 8 * i, i == MB_V ? 4 : 1);
        for (int i = 0; i < GB_N; i++)
            mbar_init(sb + G_BAR + 8 * i, i >= GB_EMPTY && i < GB_KV ? 8 : (i >= GB_KVF ? 4 : (i >= GB_STG && i < GB_FREE ? 128 : 1)));
        asm volatile("fence.mbarrier_init.release.cluster;" ::: "memory");
    }
    __syncwarp();
    asm volatile("barrier.cluster.arrive.relaxed.aligned;" ::: "memory");
    if (threadIdx.x >= 352 && threadIdx.x < 352 + (int)(sizeof(Maps) / sizeof(CUtensorMap)))
        asm volatile("prefetch.tensormap [%0];" :: "l"((const CUtensorMap*)&maps + (threadIdx.x - 352)) : "memory");
    uint32_t epoch;
    asm volatile("fence.proxy.async.shared::cta;" ::: "memory");
    const int role = uni(startup(smem, x, maps, epoch, pw));
    asm volatile("barrier.cluster.wait.aligned;" ::: "memory");
    const int wg = uni(threadIdx.x >> 7);
    if (role < 64) {
#define SETREG(n) do { if ((n) < 168) asm volatile("setmaxnreg.dec.sync.aligned.u32 %0;" :: "n"(n)); if ((n) > 168) asm volatile("setmaxnreg.inc.sync.aligned.u32 %0;" :: "n"(n)); } while (0)
#define RESREG(n) do { if ((n) < 168) asm volatile("setmaxnreg.inc.sync.aligned.u32 168;"); if ((n) > 168) asm volatile("setmaxnreg.dec.sync.aligned.u32 168;"); } while (0)
        if (wg == WGA) {
            SETREG(RGA);
            rec_a(sb, role, mem0, epoch);
            RESREG(RGA);
        } else if (wg == WGB) {
            SETREG(RGB);
            rec_b(sb, role, epoch);
            RESREG(RGB);
        } else {
            SETREG(RGC);
            rec_c(sb, role, mem0, maps, epoch);
            RESREG(RGC);
        }
        ffn_phase(maps, out);
        if (threadIdx.x == 0) GT(((volatile int*)(smem + SH_OFF))[8] * 8 + 6);
    } else if (role < 128) {
        if (wg < 2) {
            asm volatile("setmaxnreg.inc.sync.aligned.u32 184;");
            g_consumer(sb, role - 64, wg, epoch);
            if (threadIdx.x == 128) GT(role * 8 + 6);
        } else {
            asm volatile("setmaxnreg.dec.sync.aligned.u32 136;");
            g_producer(sb, role - 64, maps, epoch, x, wr, out);
        }
    } else {
        const int id = (threadIdx.x >> 5) * 4 + role - 128;
        finalizer(64 + id, x, wr, out, epoch, id < 16 ? pw.g : (id < 32 ? pw.u : wd));

    }
}

typedef CUresult (*EncodeFn)(CUtensorMap*, CUtensorMapDataType, cuuint32_t, void*, const cuuint64_t*, const cuuint64_t*, const cuuint32_t*, const cuuint32_t*,
                             CUtensorMapInterleave, CUtensorMapSwizzle, CUtensorMapL2promotion, CUtensorMapFloatOOBfill);
static void make_map3(EncodeFn fn, CUtensorMap* m, const void* ptr, uint64_t cols, uint64_t rows) {
    cuuint64_t dims[3] = {64, rows, cols / 64};
    cuuint64_t strides[2] = {cols * 2, 128};
    cuuint32_t box[3] = {64, 64, 2};
    cuuint32_t es[3] = {1, 1, 1};
    fn(m, CU_TENSOR_MAP_DATA_TYPE_BFLOAT16, 3, (void*)ptr, dims, strides, box, es, CU_TENSOR_MAP_INTERLEAVE_NONE, CU_TENSOR_MAP_SWIZZLE_128B,
       CU_TENSOR_MAP_L2_PROMOTION_L2_256B, CU_TENSOR_MAP_FLOAT_OOB_FILL_NONE);
}
static void make_map(EncodeFn fn, CUtensorMap* m, const void* ptr, uint64_t cols, uint64_t rows, uint32_t bcols, uint32_t brows,
                     bool f32 = false, CUtensorMapSwizzle sw = CU_TENSOR_MAP_SWIZZLE_128B) {
    cuuint64_t dims[2] = {cols, rows};
    cuuint64_t strides[1] = {cols * (f32 ? 4 : 2)};
    cuuint32_t box[2] = {bcols, brows};
    cuuint32_t es[2] = {1, 1};
    fn(m, f32 ? CU_TENSOR_MAP_DATA_TYPE_FLOAT32 : CU_TENSOR_MAP_DATA_TYPE_BFLOAT16, 2, (void*)ptr, dims, strides, box, es, CU_TENSOR_MAP_INTERLEAVE_NONE, sw,
       CU_TENSOR_MAP_L2_PROMOTION_L2_256B, CU_TENSOR_MAP_FLOAT_OOB_FILL_NONE);
}

extern "C" void kernel_launch(void* const* d_in, const int* in_sizes, int n_in, void* d_out, int out_size) {
    const bf16* x = (const bf16*)d_in[0];
    const bf16* mem0 = (const bf16*)d_in[1];
    const bf16* Wq = (const bf16*)d_in[2];
    const bf16* Wk = (const bf16*)d_in[3];
    const bf16* Wv = (const bf16*)d_in[4];
    const bf16* Wo = (const bf16*)d_in[5];
    const bf16* wr = (const bf16*)d_in[8];
    const bf16* wg = (const bf16*)d_in[9];
    const bf16* wu = (const bf16*)d_in[10];
    const bf16* wd = (const bf16*)d_in[11];
    bf16* out = (bf16*)d_out;

    static EncodeFn enc = nullptr;
    static void *pxn, *pK, *pV, *pO, *pacc;
    if (!enc) {
        cudaDriverEntryPointQueryResult qr;
        void* fn = nullptr;
        cudaGetDriverEntryPoint("cuTensorMapEncodeTiled", &fn, cudaEnableDefault, &qr);
        enc = (EncodeFn)fn;
        cudaGetSymbolAddress(&pxn, g_xn); cudaGetSymbolAddress(&pK, g_K); cudaGetSymbolAddress(&pV, g_V);
        cudaGetSymbolAddress(&pO, g_O); cudaGetSymbolAddress(&pacc, g_P);
        cudaFuncSetAttribute(main_kernel, cudaFuncAttributeMaxDynamicSharedMemorySize, SMEM_TOTAL);
    }
    Maps m;
    make_map(enc, &m.wq, Wq, HD, DM, 64, 256);
    make_map(enc, &m.wk, Wk, HD, DM, 64, 256);
    make_map(enc, &m.wv, Wv, HD, DM, 64, 256);
    make_map(enc, &m.wq4, Wq, HD, DM, 64, 128); make_map(enc, &m.wk4, Wk, HD, DM, 64, 128); make_map(enc, &m.wv4, Wv, HD, DM, 64, 128);
    make_map(enc, &m.wo, Wo, DM, HD, 64, 128);
    {
        cuuint64_t dims[5] = {DM, 2, 4, 4, HD / 32};
        cuuint64_t strides[4] = {DM * 2, 8 * DM * 2, 2 * DM * 2, 32 * DM * 2};
        cuuint32_t box[5] = {64, 2, 4, 4, 4};
        cuuint32_t es[5] = {1, 1, 1, 1, 1};
        enc(&m.wo2, CU_TENSOR_MAP_DATA_TYPE_BFLOAT16, 5, (void*)Wo, dims, strides, box, es, CU_TENSOR_MAP_INTERLEAVE_NONE, CU_TENSOR_MAP_SWIZZLE_128B,
            CU_TENSOR_MAP_L2_PROMOTION_L2_256B, CU_TENSOR_MAP_FLOAT_OOB_FILL_NONE);
    }
    make_map(enc, &m.kx, pK, HD, SQ, 64, 64);
    make_map(enc, &m.ox2, pO, HD, SQ, 64, 64);
    make_map(enc, &m.xn2, pxn, DM, SQ, 64, 64);
    make_map3(enc, &m.kx3, pK, HD, SQ); make_map3(enc, &m.vx3, pV, HD, SQ);
    make_map(enc, &m.wg, wg, FF, DM, 32, 256, false, CU_TENSOR_MAP_SWIZZLE_64B);
    make_map(enc, &m.wu, wu, FF, DM, 32, 256, false, CU_TENSOR_MAP_SWIZZLE_64B);
    make_map(enc, &m.wd, wd, DM, FF, 64, 32);

    cudaStream_t st = cudaStreamPerThread;
    main_kernel<<<NCTA, 384, SMEM_TOTAL, st>>>(m, x, mem0, wr, wd, out, WPtr{Wq, Wk, Wv, Wo, wg, wu});
}
```

```cpp
#include <cuda_runtime.h>
#include <cuda_bf16.h>
#include <cuda.h>
#include <stdint.h>
#include <stddef.h>

typedef __nv_bfloat16 bf16;

constexpr int SQ = 2048, DM = 512, NH = 32, DH = 128, NSEG = 64, HD = 4096, FF = 1792;

constexpr int NT = 32;
#define SPEC_TILES 30
__device__ __align__(1024) bf16 g_xn[SQ * DM];
__device__ __align__(1024) bf16 g_K[SQ * HD];
__device__ __align__(1024) bf16 g_V[SQ * HD];
__device__ __align__(1024) bf16 g_O[SQ * HD];
__device__ __align__(1024) uint32_t g_KVf[NSEG][NH][1024];
__device__ __align__(1024) bf16 g_P[8 * SQ * DM];
__device__ __align__(1024) bf16 g_h[SQ * DM];
__device__ __align__(1024) bf16 g_hn[SQ * DM];
__device__ uint8_t g_xraw[12 << 20];
#define XPG 0
__device__ __forceinline__ uint64_t xpage() { return (((uint64_t)g_xraw + (2 << 20) - 1) & ~(uint64_t)((2 << 20) - 1)) + ((uint64_t)XPG << 21); }
constexpr uint32_t XR3 = (1u << 20) | (1u << 19) | (1u << 12);
__device__ __forceinline__ uint32_t aslot(uint32_t s) { return ((s & 1) << 18) | ((s & 2) << 19) | ((s & 4) * 0xc000u); }
__device__ __forceinline__ uint32_t acc_base(uint32_t W) { return ((W & 2) ? 0x3000u : 0u) + ((W & 4) << 12) + (W & 1) * 2048; }
__device__ __forceinline__ uint32_t ext_base(uint32_t W) { return 0x8000u + ((W & 4) << 12) + (W & 3) * 1024; }
#define XHS 256
#define XSS 32
__device__ __forceinline__ uint32_t zero_off(uint32_t c, uint32_t ln) {
    return ln < 8 ? acc_base(c >> 3) + (c & 7) * 256 + ln * 16 : ext_base(c >> 3) + ((c >> 2) & 1) * XHS + ((c >> 1) & 1) * XSS + (c & 1) * 16;
}
struct Flags {
    uint32_t p[NT][32];
    uint4 cand[2][128];
    uint32_t rows[2][128];
    uint4 norm[64];
    uint32_t pad0[512];
    uint32_t kv[NT][NH][2];
    uint32_t pad1[2048];
    uint32_t o[NT][8][8];
    uint32_t pad2[2048];
    uint32_t rec[NH][32];
    uint32_t xn[128];
};
static_assert(offsetof(Flags, kv) == 0x3000 && offsetof(Flags, o) == 0x7000 && offsetof(Flags, xn) == 0xc000, "flags");
#define FLX 0
#define g_f (*(Flags*)(xpage() + (1u << 19) + FLX))
__device__ __align__(1024) uint4 g_yp[2][FF / 32][DM];
__device__ __align__(1024) uint32_t g_table[66 * 8];
__device__ __align__(256) uint32_t g_ticket[64];
__device__ uint32_t g_epoch;
#define NS3 6
#define HSPLIT 26
#define PFK 0
#define NWAITLN 8
#define WGA 0
#define WGB 1
#define WGC (3 - WGA - WGB)
#define PFF 10
#define FFW 0
#define FFS 200
#define LLT 31
#define NPROBE 3
constexpr int NCTA = 132;
constexpr int NFW = 112;
__device__ uint32_t g_abort;
__device__ long long g_dbg[4096];
#define TR(slot, v)

__device__ __forceinline__ uint32_t smem_u32(const void* p) { return (uint32_t)__cvta_generic_to_shared(p); }
__device__ __forceinline__ void mbar_init(uint32_t a, uint32_t c) { asm volatile("mbarrier.init.shared::cta.b64 [%0], %1;" :: "r"(a), "r"(c) : "memory"); }
__device__ __forceinline__ void mbar_expect_tx(uint32_t a, uint32_t tx) { asm volatile("mbarrier.arrive.expect_tx.shared::cta.b64 _, [%0], %1;" :: "r"(a), "r"(tx) : "memory"); }
__device__ __forceinline__ void mbar_arrive(uint32_t a) { asm volatile("mbarrier.arrive.shared::cta.b64 _, [%0];" :: "r"(a) : "memory"); }
__device__ __forceinline__ void mbar_arrive_if(uint32_t a, uint32_t pred) {
    asm volatile("{\n.reg .pred p;\nsetp.ne.u32 p, %1, 0;\n@p mbarrier.arrive.shared::cta.b64 _, [%0];\n}" :: "r"(a), "r"(pred) : "memory");
}
__device__ __forceinline__ bool mbar_try(uint32_t a, uint32_t ph) {
    uint32_t ok;
    asm volatile("{\n.reg .pred p;\nmbarrier.try_wait.parity.shared::cta.b64 p, [%1], %2;\nselp.u32 %0, 1, 0, p;\n}" : "=r"(ok) : "r"(a), "r"(ph) : "memory");
    return ok != 0;
}
#define SPINLOG 20
constexpr uint32_t SPIN_LIMIT = 1u << SPINLOG;
#define ABORT(code_) atomicCAS(&g_abort, 0u, (code_))
__device__ __forceinline__ void mbar_wait(uint32_t a, uint32_t ph) {
    uint32_t n = 0;
#pragma unroll 1
    while (!mbar_try(a, ph)) { if (++n > SPIN_LIMIT) { ABORT(1); break; } }
}
__device__ __forceinline__ void bar_sync(int id, int n) { asm volatile("bar.sync %0, %1;" :: "r"(id), "r"(n) : "memory"); }
__device__ __forceinline__ void bar_arrive(int id, int n) { asm volatile("bar.arrive %0, %1;" :: "r"(id), "r"(n) : "memory"); }

__device__ __forceinline__ void ldsm4(uint32_t* r, uint32_t a) {
    asm volatile("ldmatrix.sync.aligned.m8n8.x4.shared.b16 {%0,%1,%2,%3}, [%4];" : "=r"(r[0]), "=r"(r[1]), "=r"(r[2]), "=r"(r[3]) : "r"(a) : "memory");
}
__device__ __forceinline__ void ldsm4t(uint32_t* r, uint32_t a) {
    asm volatile("ldmatrix.sync.aligned.m8n8.x4.trans.shared.b16 {%0,%1,%2,%3}, [%4];" : "=r"(r[0]), "=r"(r[1]), "=r"(r[2]), "=r"(r[3]) : "r"(a) : "memory");
}
__device__ __forceinline__ void stsm4t(uint32_t a, uint32_t r0, uint32_t r1, uint32_t r2, uint32_t r3) {
    asm volatile("stmatrix.sync.aligned.m8n8.x4.trans.shared.b16 [%0], {%1,%2,%3,%4};" :: "r"(a), "r"(r0), "r"(r1), "r"(r2), "r"(r3) : "memory");
}
__device__ __forceinline__ void stsm4(uint32_t a, uint32_t r0, uint32_t r1, uint32_t r2, uint32_t r3) {
    asm volatile("stmatrix.sync.aligned.m8n8.x4.shared.b16 [%0], {%1,%2,%3,%4};" :: "r"(a), "r"(r0), "r"(r1), "r"(r2), "r"(r3) : "memory");
}
__device__ __forceinline__ uint32_t movm(uint32_t a) { uint32_t d; asm volatile("movmatrix.sync.aligned.m8n8.trans.b16 %0, %1;" : "=r"(d) : "r"(a)); return d; }
__device__ __forceinline__ void mma16816(float* d, uint32_t a0, uint32_t a1, uint32_t a2, uint32_t a3, uint32_t b0, uint32_t b1) {
    asm volatile("mma.sync.aligned.m16n8k16.row.col.f32.bf16.bf16.f32 {%0,%1,%2,%3}, {%4,%5,%6,%7}, {%8,%9}, {%0,%1,%2,%3};"
        : "+f"(d[0]), "+f"(d[1]), "+f"(d[2]), "+f"(d[3]) : "r"(a0), "r"(a1), "r"(a2), "r"(a3), "r"(b0), "r"(b1));
}
__device__ __forceinline__ void mma1688(float* d, uint32_t a0, uint32_t a1, uint32_t b0) {
    asm volatile("mma.sync.aligned.m16n8k8.row.col.f32.bf16.bf16.f32 {%0,%1,%2,%3}, {%4,%5}, {%6}, {%0,%1,%2,%3};"
        : "+f"(d[0]), "+f"(d[1]), "+f"(d[2]), "+f"(d[3]) : "r"(a0), "r"(a1), "r"(b0));
}
__device__ __forceinline__ uint32_t pack2(float a, float b) { uint32_t d; asm("cvt.rn.bf16x2.f32 %0, %1, %2;" : "=r"(d) : "f"(b), "f"(a)); return d; }
__device__ __forceinline__ float bf_lo(uint32_t w) { return __uint_as_float(w << 16); }
__device__ __forceinline__ float bf_hi(uint32_t w) { return __uint_as_float(w & 0xffff0000u); }
__device__ __forceinline__ float rbf(float x) { return __bfloat162float(__float2bfloat16_rn(x)); }

__device__ __forceinline__ void sts128(uint32_t a, float x, float y, float z, float w) { asm volatile("st.shared.v4.f32 [%0], {%1,%2,%3,%4};" :: "r"(a), "f"(x), "f"(y), "f"(z), "f"(w) : "memory"); }
__device__ __forceinline__ void sts128u(uint32_t a, uint32_t x, uint32_t y, uint32_t z, uint32_t w) { asm volatile("st.shared.v4.b32 [%0], {%1,%2,%3,%4};" :: "r"(a), "r"(x), "r"(y), "r"(z), "r"(w) : "memory"); }
__device__ __forceinline__ void sts64(uint32_t a, float x, float y) { asm volatile("st.shared.v2.f32 [%0], {%1,%2};" :: "r"(a), "f"(x), "f"(y) : "memory"); }
__device__ __forceinline__ float4 lds128(uint32_t a) { float4 v; asm volatile("ld.shared.v4.f32 {%0,%1,%2,%3}, [%4];" : "=f"(v.x), "=f"(v.y), "=f"(v.z), "=f"(v.w) : "r"(a) : "memory"); return v; }
__device__ __forceinline__ float2 lds64(uint32_t a) { float2 v; asm volatile("ld.shared.v2.f32 {%0,%1}, [%2];" : "=f"(v.x), "=f"(v.y) : "r"(a) : "memory"); return v; }
__device__ __forceinline__ uint2 lds64u(uint32_t a) { uint2 v; asm volatile("ld.shared.v2.b32 {%0,%1}, [%2];" : "=r"(v.x), "=r"(v.y) : "r"(a) : "memory"); return v; }
__device__ __forceinline__ float4 lds128v(uint32_t a) { float4 v; asm volatile("ld.volatile.shared.v4.f32 {%0,%1,%2,%3}, [%4];" : "=f"(v.x), "=f"(v.y), "=f"(v.z), "=f"(v.w) : "r"(a) : "memory"); return v; }
__device__ __forceinline__ float2 lds64v(uint32_t a) { float2 v; asm volatile("ld.volatile.shared.v2.f32 {%0,%1}, [%2];" : "=f"(v.x), "=f"(v.y) : "r"(a) : "memory"); return v; }
__device__ __forceinline__ uint4 lds128uv(uint32_t a) { uint4 v; asm volatile("ld.volatile.shared.v4.b32 {%0,%1,%2,%3}, [%4];" : "=r"(v.x), "=r"(v.y), "=r"(v.z), "=r"(v.w) : "r"(a) : "memory"); return v; }
__device__ __forceinline__ void st_async4(uint32_t a, float x, float y, float z, float w, uint32_t mb) {
    asm volatile("st.async.weak.shared::cluster.mbarrier::complete_tx::bytes.v4.f32 [%0], {%1,%2,%3,%4}, [%5];" :: "r"(a), "f"(x), "f"(y), "f"(z), "f"(w), "r"(mb) : "memory");
}
__device__ __forceinline__ void st_async2(uint32_t a, uint32_t x, uint32_t y, uint32_t mb) {
    asm volatile("st.async.weak.shared::cluster.mbarrier::complete_tx::bytes.v2.b32 [%0], {%1,%2}, [%3];" :: "r"(a), "r"(x), "r"(y), "r"(mb) : "memory");
}
__device__ __forceinline__ uint32_t ldg_rlx(const uint32_t* p) { uint32_t v; asm volatile("ld.relaxed.gpu.global.b32 %0, [%1];" : "=r"(v) : "l"(p) : "memory"); return v; }
__device__ __forceinline__ uint4 ldg_rlx4(const uint32_t* p) { uint4 v; asm volatile("ld.relaxed.gpu.global.v4.b32 {%0,%1,%2,%3}, [%4];" : "=r"(v.x), "=r"(v.y), "=r"(v.z), "=r"(v.w) : "l"(p) : "memory"); return v; }
__device__ __forceinline__ uint4 ldg_rlx4_if(const uint32_t* p, bool c) {
    uint4 v;
    asm volatile("{\n.reg .pred p;\nsetp.ne.u32 p, %5, 0;\nmov.b32 %0, 0;\nmov.b32 %1, 0;\nmov.b32 %2, 0;\nmov.b32 %3, 0;\n@p ld.relaxed.gpu.global.v4.b32 {%0,%1,%2,%3}, [%4];\n}"
                 : "=r"(v.x), "=r"(v.y), "=r"(v.z), "=r"(v.w) : "l"(p), "r"((uint32_t)c) : "memory");
    return v;
}
__device__ __forceinline__ void stg_rlx(uint32_t* p, uint32_t v) { asm volatile("st.relaxed.gpu.global.b32 [%0], %1;" :: "l"(p), "r"(v) : "memory"); }
__device__ __forceinline__ void tma2d(uint32_t dst, const CUtensorMap* tm, int c0, int c1, uint32_t mb) {
    asm volatile("cp.async.bulk.tensor.2d.shared::cluster.global.mbarrier::complete_tx::bytes [%0], [%1, {%3, %4}], [%2];"
        :: "r"(dst), "l"((uint64_t)tm), "r"(mb), "r"(c0), "r"(c1) : "memory");
}

__device__ __forceinline__ void tma3d(uint32_t dst, const CUtensorMap* tm, int row, int chunk, uint32_t mb) {
    asm volatile("cp.async.bulk.tensor.3d.shared::cluster.global.mbarrier::complete_tx::bytes [%0], [%1, {%3, %4, %5}], [%2];"
        :: "r"(dst), "l"((uint64_t)tm), "r"(mb), "r"(0), "r"(row), "r"(chunk) : "memory");
}
#define EF 0xff
__device__ __forceinline__ uint64_t pol_ef(int bit) {
    uint64_t p;
    if ((EF >> bit) & 1) asm("createpolicy.fractional.L2::evict_first.b64 %0, 1.0;" : "=l"(p));
    else asm("createpolicy.fractional.L2::evict_normal.b64 %0, 1.0;" : "=l"(p));
    return p;
}
__device__ __forceinline__ void tma3d_h(uint32_t dst, const CUtensorMap* tm, int row, int chunk, uint32_t mb, uint64_t pol) {
    asm volatile("cp.async.bulk.tensor.3d.shared::cluster.global.mbarrier::complete_tx::bytes.L2::cache_hint [%0], [%1, {%3, %4, %5}], [%2], %6;"
        :: "r"(dst), "l"((uint64_t)tm), "r"(mb), "r"(0), "r"(row), "r"(chunk), "l"(pol) : "memory");
}
__device__ __forceinline__ void tma2d_h(uint32_t dst, const CUtensorMap* tm, int c0, int c1, uint32_t mb, uint64_t pol) {
    asm volatile("cp.async.bulk.tensor.2d.shared::cluster.global.mbarrier::complete_tx::bytes.L2::cache_hint [%0], [%1, {%3, %4}], [%2], %5;"
        :: "r"(dst), "l"((uint64_t)tm), "r"(mb), "r"(c0), "r"(c1), "l"(pol) : "memory");
}
__device__ __forceinline__ void tma2d_mc_h(uint32_t dst, const CUtensorMap* tm, int c0, int c1, uint32_t mb, uint64_t pol) {
    asm volatile("cp.async.bulk.tensor.2d.shared::cluster.global.mbarrier::complete_tx::bytes.multicast::cluster.L2::cache_hint [%0], [%1, {%3, %4}], [%2], %5, %6;"
        :: "r"(dst), "l"((uint64_t)tm), "r"(mb), "r"(c0), "r"(c1), "h"((uint16_t)3), "l"(pol) : "memory");
}
__device__ __forceinline__ uint4 ldg4_h(const void* p, uint64_t pol) {
    uint4 v;
    asm volatile("ld.relaxed.gpu.global.L2::cache_hint.v4.b32 {%0,%1,%2,%3}, [%4], %5;" : "=r"(v.x), "=r"(v.y), "=r"(v.z), "=r"(v.w) : "l"(p), "l"(pol) : "memory");
    return v;
}
__device__ __forceinline__ void stg4_h(void* p, uint4 v, uint64_t pol) {
    asm volatile("st.relaxed.gpu.global.L2::cache_hint.v4.b32 [%0], {%1,%2,%3,%4}, %5;" :: "l"(p), "r"(v.x), "r"(v.y), "r"(v.z), "r"(v.w), "l"(pol) : "memory");
}
__device__ __forceinline__ void tma2d_mc(uint32_t dst, const CUtensorMap* tm, int c0, int c1, uint32_t mb) {
    asm volatile("cp.async.bulk.tensor.2d.shared::cluster.global.mbarrier::complete_tx::bytes.multicast::cluster [%0], [%1, {%3, %4}], [%2], %5;"
        :: "r"(dst), "l"((uint64_t)tm), "r"(mb), "r"(c0), "r"(c1), "h"((uint16_t)3) : "memory");
}
__device__ __forceinline__ void mbar_arrive2_if(uint32_t a, uint32_t pred) {
    asm volatile("{\n.reg .pred p;\nsetp.ne.u32 p, %1, 0;\n@p mbarrier.arrive.shared::cta.b64 _, [%0];\n@p mbarrier.arrive.shared::cluster.b64 _, [%2];\n}"
                 :: "r"(a), "r"(pred), "r"(a ^ 0x01000000u) : "memory");
}
__device__ __forceinline__ void tma_pf3d(const CUtensorMap* tm, int row, int chunk) {
    asm volatile("cp.async.bulk.prefetch.tensor.3d.L2.global.tile [%0, {%1, %2, %3}];" :: "l"((uint64_t)tm), "r"(0), "r"(row), "r"(chunk) : "memory");
}
__device__ __forceinline__ void tma_pf2d(const CUtensorMap* tm, int c0, int c1) {
    asm volatile("cp.async.bulk.prefetch.tensor.2d.L2.global.tile [%0, {%1, %2}];" :: "l"((uint64_t)tm), "r"(c0), "r"(c1) : "memory");
}
__device__ __forceinline__ void tma_store3d(const CUtensorMap* tm, uint32_t src, int row, int chunk) {
    asm volatile("cp.async.bulk.tensor.3d.global.shared::cta.bulk_group [%0, {%2, %3, %4}], [%1];" :: "l"((uint64_t)tm), "r"(src), "r"(0), "r"(row), "r"(chunk) : "memory");
}
__device__ __forceinline__ void bulk_store(void* dst, uint32_t src, uint32_t bytes) {
    asm volatile("cp.async.bulk.global.shared::cta.bulk_group [%0], [%1], %2;" :: "l"(dst), "r"(src), "r"(bytes) : "memory");
}
#define GT(slot)
#define CNT(k)
#define CNT2(k, c)
#define TS(i, dep)
#define TSACC()
#define TSDECL
struct Maps { CUtensorMap wq, wk, wv, wo, wo2, kx, ox2, kx3, vx3, xn2, wg, wu, wd, wq4, wk4, wv4; };
typedef Maps RecMaps;
__device__ __forceinline__ void st_rel(uint32_t* p, uint32_t v) { asm volatile("st.release.gpu.global.u32 [%0], %1;" :: "l"(p), "r"(v) : "memory"); }
#define PUBLISH(p, v) st_rel(p, v)
__device__ __forceinline__ uint2 ldg_rlx2(const uint32_t* p) { uint2 v; asm volatile("ld.relaxed.gpu.global.v2.b32 {%0,%1}, [%2];" : "=r"(v.x), "=r"(v.y) : "l"(p) : "memory"); return v; }
__device__ __forceinline__ void wait_eq2(const uint32_t* p, uint32_t e, int code) {
    uint32_t n = 0;
#pragma unroll 1
    while (true) { uint2 v = ldg_rlx2(p); if (v.x == e && v.y == e) break; __nanosleep(64); if (++n > SPIN_LIMIT) { ABORT(code); break; } }
}
__device__ __forceinline__ void wait_eq4(const uint32_t* p, uint32_t e, int code) {
    uint32_t n = 0;
#pragma unroll 1
    while (true) { uint4 v = ldg_rlx4(p); if (v.x == e && v.y == e && v.z == e && v.w == e) break; __nanosleep(64); if (++n > SPIN_LIMIT) { ABORT(code); break; } }
}
__device__ __forceinline__ void wait_rec(const uint32_t* p, uint32_t e, uint32_t steps) {
    uint32_t n = 0;
#pragma unroll 1
    while (true) {
        uint2 v = ldg_rlx2(p);
        if (__all_sync(0xffffffffu, (v.x >> 8) == e && (v.y >> 8) == e && (v.x & 255) >= steps && (v.y & 255) >= steps)) break;
        __nanosleep(64); if (++n > SPIN_LIMIT) { ABORT(8); break; }
    }
}

constexpr int R_QK1 = 0;
constexpr int R_WO = 65536;
constexpr int R_T = 131072;
constexpr int R_SLOT1 = R_T;
constexpr int R_MEMB = R_T + 24576;
constexpr int R_QP = R_MEMB + 8192;
constexpr int R_VRED = R_QP + 4096;
constexpr int R_STG = R_VRED + 2048;
constexpr int R_AX = R_STG + 2048;
constexpr int R_SLOT0 = 196608;
constexpr int R_SLOC = R_SLOT0 + 24576;
constexpr int R_SREM = R_SLOC + 1536;
constexpr int R_VB = R_SREM + 1536;
constexpr int R_MISC = R_VB + 2048;
constexpr int R_LT = R_MISC + 128;
constexpr int R_BAR = 229888;
constexpr int R_TS = 229888 + 128;
static_assert(R_AX + 24576 <= R_SLOT0 && R_LT + 2560 <= 229376, "smem map");
enum { MB_W0 = 0, MB_W1, MB_WV, MB_WO, MB_S, MB_FULL0, MB_FULL1, MB_V, MB_N };

__device__ __forceinline__ float ex2(float x) { float y; asm("ex2.approx.ftz.f32 %0, %1;" : "=f"(y) : "f"(x)); return y; }
__device__ __forceinline__ float rcpf(float x) { float y; asm("rcp.approx.ftz.f32 %0, %1;" : "=f"(y) : "f"(x)); return y; }
__device__ __forceinline__ void mma16816z(float* d, uint32_t a0, uint32_t a1, uint32_t a2, uint32_t a3, uint32_t b0, uint32_t b1) {
    asm volatile("mma.sync.aligned.m16n8k16.row.col.f32.bf16.bf16.f32 {%0,%1,%2,%3}, {%4,%5,%6,%7}, {%8,%9}, {%10,%10,%10,%10};"
        : "=f"(d[0]), "=f"(d[1]), "=f"(d[2]), "=f"(d[3]) : "r"(a0), "r"(a1), "r"(a2), "r"(a3), "r"(b0), "r"(b1), "f"(0.f));
}
__device__ __forceinline__ void mma1688hz(float* d, uint32_t a0, uint32_t a1, uint32_t b0) {
    asm volatile("mma.sync.aligned.m16n8k8.row.col.f32.f16.f16.f32 {%0,%1,%2,%3}, {%4,%5}, {%6}, {%7,%7,%7,%7};"
        : "=f"(d[0]), "=f"(d[1]), "=f"(d[2]), "=f"(d[3]) : "r"(a0), "r"(a1), "r"(b0), "f"(0.f));
}
#define MMA(d, a, b0, b1) mma16816(d, a[0], a[1], a[2], a[3], b0, b1)
#define MMAZ(d, a, b0, b1) mma16816z(d, a[0], a[1], a[2], a[3], b0, b1)
#define MMAF(first, d, a, b0, b1) do { if (first) MMAZ(d, a, b0, b1); else MMA(d, a, b0, b1); } while (0)

__device__ __forceinline__ uint32_t uni(uint32_t x) { return __reduce_max_sync(0xffffffffu, x); }
__device__ __forceinline__ void mbar_wait_u(uint32_t a, uint32_t ph) {
    uint32_t n = 0;
#pragma unroll 1
    while (!__all_sync(0xffffffffu, mbar_try(a, ph))) { if (++n > SPIN_LIMIT) { ABORT(1); break; } }
}
__device__ __forceinline__ void mbar_wait_p(uint32_t a, uint32_t ph) {
    asm volatile("{\n.reg .pred p, q;\n.reg .u32 n;\nmov.u32 n, 0;\nWL: mbarrier.try_wait.parity.shared::cta.b64 p, [%0], %1;\nadd.u32 n, n, 1;\n"
                 "setp.lt.and.u32 q, n, %2, !p;\n@q bra.uni WL;\n}" :: "r"(a), "r"(ph), "n"(SPIN_LIMIT) : "memory");
}
__device__ __forceinline__ uint32_t mbar_test(uint32_t a, uint32_t ph) {
    uint32_t ok;
    asm volatile("{\n.reg .pred p;\nmbarrier.test_wait.parity.shared::cta.b64 p, [%1], %2;\nselp.u32 %0, 1, 0, p;\n}" : "=r"(ok) : "r"(a), "r"(ph) : "memory");
    return ok;
}
__device__ __forceinline__ uint32_t opaque(uint32_t x) { return __shfl_sync(0xffffffffu, x, threadIdx.x & 31); }
__device__ __forceinline__ const uint32_t* mkptr(uint32_t lo, uint32_t hi) { uint64_t r; asm("mov.b64 %0, {%1, %2};" : "=l"(r) : "r"(lo), "r"(hi)); return (const uint32_t*)r; }
__device__ __forceinline__ uint32_t prmt(uint32_t a, uint32_t b, uint32_t s) { uint32_t d; asm("prmt.b32 %0, %1, %2, %3;" : "=r"(d) : "r"(a), "r"(b), "r"(s)); return d; }
__device__ __forceinline__ uint32_t packh2(float a, float b) { uint32_t d; asm("cvt.rn.f16x2.f32 %0, %1, %2;" : "=r"(d) : "f"(b), "f"(a)); return d; }
__device__ __forceinline__ uint32_t hadd2b(uint32_t a, uint32_t b) { uint32_t d; asm("add.rn.bf16x2 %0, %1, %2;" : "=r"(d) : "r"(a), "r"(b)); return d; }
__device__ __forceinline__ uint32_t hmul2b(uint32_t a, uint32_t b) { uint32_t d; asm("mul.rn.bf16x2 %0, %1, %2;" : "=r"(d) : "r"(a), "r"(b)); return d; }
__device__ __forceinline__ uint32_t amax2b(uint32_t a, uint32_t b) { uint32_t d; asm("max.xorsign.abs.bf16x2 %0, %1, %2;" : "=r"(d) : "r"(a), "r"(b)); return d; }
__device__ __forceinline__ uint32_t amax2h(uint32_t a, uint32_t b) { uint32_t d; asm("max.xorsign.abs.f16x2 %0, %1, %2;" : "=r"(d) : "r"(a), "r"(b)); return d; }
__device__ __forceinline__ void sts32(uint32_t a, uint32_t x) { asm volatile("st.shared.b32 [%0], %1;" :: "r"(a), "r"(x) : "memory"); }
__device__ __forceinline__ uint32_t lds32v_(uint32_t a) { uint32_t v; asm volatile("ld.volatile.shared.b32 %0, [%1];" : "=r"(v) : "r"(a) : "memory"); return v; }
__device__ __forceinline__ void stg4(void* p, uint4 v) { asm volatile("st.relaxed.gpu.global.v4.b32 [%0], {%1,%2,%3,%4};" :: "l"(p), "r"(v.x), "r"(v.y), "r"(v.z), "r"(v.w) : "memory"); }
__device__ __forceinline__ void lds_frag(uint32_t* r, uint32_t a) {
    asm volatile("ld.shared.v4.b32 {%0,%1,%2,%3}, [%4];" : "=r"(r[0]), "=r"(r[1]), "=r"(r[2]), "=r"(r[3]) : "r"(a) : "memory");
}
__device__ __forceinline__ void lds_fragv(uint32_t* r, uint32_t a) {
    asm volatile("ld.volatile.shared.v4.b32 {%0,%1,%2,%3}, [%4];" : "=r"(r[0]), "=r"(r[1]), "=r"(r[2]), "=r"(r[3]) : "r"(a) : "memory");
}
__device__ __forceinline__ uint32_t xorv(uint32_t a, uint32_t b) { uint32_t d; asm volatile("xor.b32 %0, %1, %2;" : "=r"(d) : "r"(a), "r"(b)); return d; }
#define SCHED(k) asm volatile("{\n.reg .pred p;\nsetp.ne.u32 p, %0, %1;\n@p bra.uni SD;\nSL: nanosleep.u32 64;\nbra.uni SL;\nSD:\n}" :: "r"(sbu - s), "n"(k) : "memory")
#define PINM() asm volatile("{\n.reg .pred p;\nsetp.eq.u32 p, %0, 1;\n@p st.shared.u32 [%0], 0;\n}" :: "r"(sbu) : "memory")
__device__ __forceinline__ uint32_t or_and(uint32_t a, uint32_t b, uint32_t c) { uint32_t d; asm("lop3.b32 %0, %1, %2, %3, 0xF8;" : "=r"(d) : "r"(a), "r"(b), "r"(c)); return d; }
__device__ __forceinline__ uint32_t pack2v(float a, float b) { uint32_t d; asm volatile("cvt.rn.bf16x2.f32 %0, %1, %2;" : "=r"(d) : "f"(b), "f"(a)); return d; }
#define FU(x) __float_as_uint(x)
__device__ __forceinline__ uint32_t clk32() { uint32_t t; asm volatile("mov.u32 %0, %%clock;" : "=r"(t) :: "memory"); return t; }
__device__ __forceinline__ void spin_until(uint32_t t0, uint32_t d) {
    if (d) {
#pragma unroll 1
        while (__any_sync(0xffffffffu, clk32() - t0 < d)) {}
    }
}
constexpr int SH_OFF = 229376 + 384;
constexpr uint32_t HONE2 = 0x3c003c00u, HCNT2 = 0x50005000u;

__device__ __forceinline__ uint64_t desc_sw128(uint32_t addr, uint32_t lbo, uint32_t sbo) {
    return (uint64_t)((addr & 0x3FFFF) >> 4) | ((uint64_t)(lbo >> 4) << 16) | ((uint64_t)(sbo >> 4) << 32) | (1ull << 62);
}
#define DP 375
#define NAX 3
#define NXL 0
#define NCX 2
#define NCL 1
#define FLIP 1
#define VTA 1
#define KXB 4
#define ANB 3
#define BNB 3
#define CNB 3
#define SMA 0
#define SMB 0
#define SMC 0x01
#define IVA 0
#define RGA 160
#define RGC 160
#define RGB (504 - RGA - RGC)
#define NRW 8
#define NBR 16
#define E0 0
#define E1 6
#define E2 4
#define E3 8
#define IV 2
#define G2V 0
#define G2K 2
#define VDEP 0
#define AEARLY 0
#define VTP 2
#define LORD 1
#define TRK 1
#define T2N 14
#define NB0 0
#define NB1 9
#define DB2 80
#define DITHER 0
#define DB 40

__device__ __forceinline__ uint32_t wrow_off(int kk, int ch) {
    const int lane = threadIdx.x & 31, r = lane & 7;
    const int row = 64 * (kk >> 2) + 32 * (r & 1) + 16 * (kk & 1) + 8 * (lane >> 4) + 4 * ((kk >> 1) & 1) + (r >> 1);
    return row * 128 + ((ch ^ (row & 7)) << 4);
}
template <int K> __device__ __forceinline__ void sched(uint32_t key) {
    asm volatile("{\n.reg .pred p;\nsetp.ne.u32 p, %0, %1;\n@p bra.uni SD;\nSL: nanosleep.u32 64;\nbra.uni SL;\nSD:\n}" :: "r"(key), "n"(K) : "memory");
}
__device__ __forceinline__ void sched_i(int i, uint32_t key) {
    if (i == -1) sched<20>(key); if (i == 0) sched<21>(key); if (i == 1) sched<22>(key); if (i == 2) sched<23>(key);
    if (i == 3) sched<24>(key); if (i == 4) sched<25>(key); if (i == 5) sched<26>(key); if (i == 6) sched<27>(key);
}
template <int NB, int SM, class F>
__device__ __forceinline__ void g1(float* q0, float* k0, uint32_t (*wq)[4], uint32_t (*wk)[4], uint32_t ga, uint32_t key, F&& hook) {
    float q1[4], k1[4];
    uint32_t b[NB][4];
#pragma unroll
    for (int i = 0; i < NB; i++) ldsm4(b[i], ga + i * 512);
    hook(-1, b[0]);
    if (SM & 1) sched_i(-1, key);
#pragma unroll
    for (int i = 0; i < 8; i++) {
        uint32_t* c = b[i % NB];
        MMAF(i == 0, q0, wq[2 * i], c[0], c[1]); MMAF(i == 0, k0, wk[2 * i], c[0], c[1]);
        MMAF(i == 0, q1, wq[2 * i + 1], c[2], c[3]); MMAF(i == 0, k1, wk[2 * i + 1], c[2], c[3]);
        const uint32_t cc_[4] = {c[0], c[1], c[2], c[3]};
        if (i + NB < 8) ldsm4(b[i % NB], ga + (i + NB) * 512);
        hook(i, cc_);
        if ((SM >> (i + 1)) & 1) sched_i(i, key);
    }
#pragma unroll
    for (int i = 0; i < 4; i++) { q0[i] += q1[i]; k0[i] += k1[i]; }
}
__device__ __forceinline__ float frag_norm2(uint32_t (*w)[4]) {
    float d0[4], d1[4];
#pragma unroll
    for (int i = 0; i < 32; i++) { MMAF(i == 0, d0, w[i], w[i][0], w[i][2]); MMAF(i == 0, d1, w[i], w[i][1], w[i][3]); }
    const int lane = threadIdx.x & 31, g = lane >> 2, t = lane & 3;
    float v = g == 2 * t ? d0[0] + d1[2] : (g == 2 * t + 1 ? d0[1] + d1[3] : 0.f);
#pragma unroll
    for (int o = 16; o; o >>= 1) v += __shfl_xor_sync(0xffffffffu, v, o);
    return v;
}
__device__ __forceinline__ void load_slot(uint32_t sb, int c, int tile, const Maps& maps) {
    const uint32_t dst = sb + ((tile & 1) ? R_SLOT1 : R_SLOT0), mb = sb + R_BAR + 8 * (MB_FULL0 + (tile & 1));
    mbar_expect_tx(mb, 24576);
    if ((EF >> 8) & 1) {
        tma2d_h(dst + 16384, &maps.kx, c * 64, tile * 64, mb, pol_ef(8));
        tma3d_h(dst, &maps.vx3, tile * 64, (c >> 1) * 2, mb, pol_ef(8));
    } else {
        tma2d(dst + 16384, &maps.kx, c * 64, tile * 64, mb);
        tma3d(dst, &maps.vx3, tile * 64, (c >> 1) * 2, mb);
    }
}
__device__ __forceinline__ uint32_t put_mem0(uint32_t sb, int W, const bf16* __restrict__ mem0) {
    const int lane = threadIdx.x & 31;
    const uint4 a = *(const uint4*)(mem0 + (lane & 7) * DM + W * 64 + (lane >> 3) * 8), b = *(const uint4*)(mem0 + (lane & 7) * DM + W * 64 + 32 + (lane >> 3) * 8);
    const uint4 m0 = make_uint4(prmt(a.x, b.x, 0x5410u), prmt(a.x, b.x, 0x7632u), prmt(a.y, b.y, 0x5410u), prmt(a.y, b.y, 0x7632u));
    const uint4 m1 = make_uint4(prmt(a.z, b.z, 0x5410u), prmt(a.z, b.z, 0x7632u), prmt(a.w, b.w, 0x5410u), prmt(a.w, b.w, 0x7632u));
    bar_sync(3, 256);
    sts128u(sb + R_MEMB + W * 1024 + lane * 16, m0.x, m0.y, m0.z, m0.w);
    sts128u(sb + R_MEMB + W * 1024 + 512 + lane * 16, m1.x, m1.y, m1.z, m1.w);
    return amax2b(amax2b(amax2b(m0.x, m0.y), amax2b(m0.z, m0.w)), amax2b(amax2b(m1.x, m1.y), amax2b(m1.z, m1.w)));
}
#define PUT_MAX(rL, W) sts32(rL + R_STG + 1024 + ((W) >> 2) * 512 + ((W) & 3) * 4, amax2b(amax2b(mx, my), mz));
__device__ __forceinline__ uint32_t h2b(uint32_t w) {
    uint32_t d;
    asm("{\n.reg .f16 l, h;\n.reg .f32 a, b;\nmov.b32 {l, h}, %1;\ncvt.f32.f16 a, l;\ncvt.f32.f16 b, h;\ncvt.rn.bf16x2.f32 %0, b, a;\n}" : "=r"(d) : "r"(w));
    return d;
}
#define GATHER1(HALF)                                                                                           \
        {                                                                                                       \
            const uint4 x0 = ldg_rlx4(pm), x1 = ldg_rlx4(pm + 256); const uint2 y = ldg_rlx2(px);                 \
            cw = (sel & 0x4000u) ? prmt(x0.w, x1.w, 0x7632u) : prmt(y.x, y.y, 0x5410u);                         \
            const uint32_t p0 = h2b(x0.x), p1 = h2b(x0.y), p2 = h2b(x0.z), p3 = h2b(prmt(x0.w, y.x, sel));      \
            stsm4t(rG + R_MEMB + HALF * 4096, p0, p1, p2, p3);                                                  \
            const uint32_t p4 = h2b(x1.x), p5 = h2b(x1.y), p6 = h2b(x1.z), p7 = h2b(prmt(x1.w, y.y, sel));      \
            stsm4t(rG + R_MEMB + HALF * 4096 + 512, p4, p5, p6, p7);                                            \
            mx = amax2b(amax2b(p0, p1), amax2b(p2, p3)); my = amax2b(p4, p5); mz = amax2b(p6, p7);              \
        }
#define GATHER(HALF, PRE, SYNC, AFTER)                                                                                      \
        {                                                                                                       \
            const uint32_t so = aslot(s);                                                                       \
            const uint32_t ua = (glo + acc_base(HALF * 4 + fo)) ^ so, ux = (glo + ext_base(HALF * 4 + fo)) ^ so; \
            uint2 lt;                                                                                           \
            lt.x = lds32v_(rL + R_LT); lt.y = lds32v_(rL + R_LT + 4);                                           \
            const uint32_t sel = 0x7610u - ((lt.x ^ (lt.x >> 2)) & 16) * 0x440u;                                \
            const uint32_t* pm = mkptr(ua + lt.x, ghi);                                                         \
            const uint32_t* px = mkptr(ux + lt.y, ghi);                                                         \
            PRE                                                                                                 \
            bar_sync(5, 384);                                                                                   \
            const uint32_t t0 = clk32();                                                                        \
            TSACC();                                                                        \
            SYNC                                                                                                \
            spin_until(t0, DP + DITHER);                                                                                 \
            \
            TS(10, 0);                                                                                          \
            uint32_t cw, nr = 0;                                                                                \
            _Pragma("unroll 1") do {                                                                            \
                GATHER1(HALF)                                                                                   \
                nr++;                                                                                           \
            } while (__any_sync(0xffffffffu, cw != HCNT2 && nr < SPIN_LIMIT));                                  \
            TS(11, cw);                                                                                         \
            AFTER                                                                                               \
            CNT2(HALF * 4 + (s & 1) * 2 + (nr > 2), nr > 1);                                                    \
            \
        }
#define GOBAR (fo == 3 ? 14 : 10 + fo)

__device__ __forceinline__ void rec_a(uint32_t sb, int c, const bf16* __restrict__ mem0, uint32_t epoch) {
    const int tid = threadIdx.x - WGA * 128, lane = tid & 31, f = tid >> 5;
    uint32_t wq[16][4], wk[16][4], mx, my = 0, mz = 0;
    const int lrow = ((lane >> 4) << 3) + (lane & 7), lsel = (lane >> 3) & 1;
    {
        mbar_wait(sb + R_BAR + 8 * MB_W0, 0);
        if (c == 7 && tid == 0) GT(1421);
#pragma unroll
        for (int kk = 0; kk < 16; kk++) { const uint32_t a = sb + R_T + wrow_off(kk, 2 * f + lsel); ldsm4t(wq[kk], a); ldsm4t(wk[kk], a + 32768); }
        __syncwarp();
        mx = put_mem0(sb, f, mem0);
    }
    const uint32_t rL = opaque(sb + lane * 16), rG = opaque(sb + lane * 16 + f * 1024);
    const uint32_t sbu = uni(sb), fo = uni(f), cc = uni(c);
    const uint64_t gx = xpage();
    const uint32_t ghi = uni((uint32_t)(gx >> 32)), glo = uni((uint32_t)gx);
#pragma unroll
    for (int i = 0; i < NAX; i++) {
        sts128u(rG + R_AX + 4096 * i, wq[i][0], wq[i][1], wq[i][2], wq[i][3]);
        sts128u(rG + R_AX + 4096 * i + 512, wk[i][0], wk[i][1], wk[i][2], wk[i][3]);
    }
    sts128u(rL + R_LT + 512 + f * 512, (sb + R_SREM + (f >= 2 ? lane * 8 + f * 256 : lane * 16 + f * 1024)) ^ 0x01000000u, (sb + R_BAR + 8 * MB_S) ^ 0x01000000u,
            sb + R_QP + (lane >> 4) * 128 + lsel * 512 + (lane & 7) * 16 + (f == 3 ? 2048 : 0), sb + R_SLOT0 + lrow * 128 + ((lsel ^ (lane & 7)) << 4));
    __syncwarp();
    if (tid == 0) GT(c * 8 + 1);
    TSDECL;
    const float cexp = 0.08838834764831845f * 1.4426950408889634f;
    float cs = cexp;
    auto step = [&](int s, bool first) -> bool {
        bar_sync(1, 128);
        float q0[4], k0[4];
        uint4 ta;
        uint32_t zr, rl2;
        g1<ANB, SMA>(q0, k0, wq, wk, rL + R_MEMB, sbu - s, [&](int i, const uint32_t* c_) {
            if (i == 0) TS(0, c_[0]);
            if (i == -1) {
#pragma unroll
                for (int n = NAX - NXL; n < NAX; n++) { lds_fragv(wq[n], rG + R_AX + 4096 * n); lds_fragv(wk[n], rG + R_AX + 4096 * n + 512); }
                ta = lds128uv(rL + R_LT + 512 + fo * 512);
                zr = ta.w & 1; rl2 = rL | zr;
            }
            if (i == IVA) { PUT_MAX(rl2, fo) bar_arrive(15, 256); bar_arrive(GOBAR, 96); }
        });
        stsm4t(rG + R_QP, pack2(q0[0], q0[1]), pack2(q0[2], q0[3]), pack2(k0[0], k0[1]), pack2(k0[2], k0[3]));
        TS(1, FU(k0[3]));
        if (first) mbar_wait_p(sbu + R_BAR + 8 * MB_FULL0, 0);
        if (fo >= 2) {
            bar_sync(3, 256);
            uint32_t kb[4], kc[4], qa[4], qc[4];
            ldsm4(kb, ta.z + 256); ldsm4(qa, ta.z);
            ldsm4(kc, ta.z + 1280); ldsm4(qc, ta.z + 1024);
            const uint32_t k0_ = hadd2b(kb[0], kb[1]), k1_ = hadd2b(kb[2], kb[3]), k2_ = hadd2b(kc[0], kc[1]), k3_ = hadd2b(kc[2], kc[3]);
            float s0[4], s2[4];
            MMAZ(s0, qa, k0_, k1_); MMAZ(s2, qc, k2_, k3_);
            const float x = ((s0[0] + s0[2]) + (s2[0] + s2[2])) * cs, y = ((s0[1] + s0[3]) + (s2[1] + s2[3])) * cs;
            st_async2(ta.x, FU(x), FU(y), ta.y);
            TS(3, FU(y));
            sts64((ta.x ^ 0x01000000u) + (R_SLOC - R_SREM), x, y);
            sts128u(rl2 + R_STG + (fo & 1) * 512, k0_, k1_, k2_, k3_);
            bar_arrive(9, 192);
        } else {
            uint32_t qa[4][4], kx[4][4];
#pragma unroll
            for (int kk = 0; kk < KXB; kk++) ldsm4(kx[kk], (ta.w ^ (kk * 32)) + (16384 + fo * 2048));
            bar_sync(3, 256);
#pragma unroll
            for (int kk = 0; kk < 4; kk++) {
                if (kk >= KXB) ldsm4(kx[kk], (ta.w ^ (kk * 32)) + (16384 + fo * 2048));
                ldsm4(qa[kk], ta.z + kk * 1024);
            }
            float s0[4], s1[4], s2[4], s3[4];
            MMAZ(s0, qa[0], kx[0][0], kx[0][1]); MMAZ(s1, qa[0], kx[0][2], kx[0][3]);
            MMAZ(s2, qa[1], kx[1][0], kx[1][1]); MMAZ(s3, qa[1], kx[1][2], kx[1][3]);
            MMA(s0, qa[2], kx[2][0], kx[2][1]); MMA(s1, qa[2], kx[2][2], kx[2][3]);
            MMA(s2, qa[3], kx[3][0], kx[3][1]); MMA(s3, qa[3], kx[3][2], kx[3][3]);
            const float x = ((s0[0] + s0[2]) + (s2[0] + s2[2])) * cs, y = ((s0[1] + s0[3]) + (s2[1] + s2[3])) * cs;
            const float z = ((s1[0] + s1[2]) + (s3[0] + s3[2])) * cs, w = ((s1[1] + s1[3]) + (s3[1] + s3[3])) * cs;
            st_async4(ta.x, x, y, z, w, ta.y);
            TS(3, FU(w));
            sts128(rG + R_SLOC, x, y, z, w);
        }
        const uint32_t r8 = (rl2 + sbu) >> 1;
        uint32_t vt00[4], vt01[4], vt10[4], vt11[4];
        const uint32_t rV = ta.w ^ ((fo & 1) * 64), vo = (fo >> 1) * 8192;
        if (!VTA && VTP < 2) { ldsm4t(vt00, rV + vo); ldsm4t(vt10, (rV ^ 32) + vo); }
        if (!VTA && VTP < 1) { ldsm4t(vt01, rV + vo + 2048); ldsm4t(vt11, (rV ^ 32) + vo + 2048); }
        bar_sync(4, 128);
        const float2 l2 = lds64v(r8 + R_SLOC + 512), l3 = lds64v(r8 + R_SLOC + 768);
        const float4 l0 = lds128v(rL + R_SLOC), l1 = lds128v(rL + R_SLOC + 1024);
        if (VTA && VTP < 2) { ldsm4t(vt00, rV + vo); ldsm4t(vt10, (rV ^ 32) + vo); }
        if (VTA && VTP < 1) { ldsm4t(vt01, rV + vo + 2048); ldsm4t(vt11, (rV ^ 32) + vo + 2048); }

        if (s == NSEG - 1) { mbar_wait_u(sbu + R_BAR + 8 * MB_S, 1); mbar_wait_u(sbu + R_BAR + 8 * MB_V, 1); return true; }
        TS(2, FU(l3.y));
        mbar_wait_p(sbu + R_BAR + 8 * MB_S, s & 1);
        TS(4, 0);
        {
            const float2 r2 = lds64v(r8 + R_SREM + 512), r3 = lds64v(r8 + R_SREM + 768);
            const float4 r0 = lds128v(rL + R_SREM), r1 = lds128v(rL + R_SREM + 1024);
            if (VTP >= 1) PINM();
            if (VTP >= 2) { ldsm4t(vt00, rV + vo); ldsm4t(vt10, (rV ^ 32) + vo); }
            if (VTP >= 1) { ldsm4t(vt01, rV + vo + 2048); ldsm4t(vt11, (rV ^ 32) + vo + 2048); }
            float sv[10];
            sv[0] = l0.x + r0.x; sv[1] = l0.y + r0.y; sv[2] = l0.z + r0.z; sv[3] = l0.w + r0.w;
            sv[4] = l1.x + r1.x; sv[5] = l1.y + r1.y; sv[6] = l1.z + r1.z; sv[7] = l1.w + r1.w;
            sv[8] = ((l2.x + l3.x) + r2.x) + r3.x; sv[9] = ((l2.y + l3.y) + r2.y) + r3.y;
            float m = fmaxf(fmaxf(fmaxf(fmaxf(sv[8], sv[9]), sv[0]), fmaxf(fmaxf(sv[2], sv[3]), sv[1])), fmaxf(fmaxf(sv[4], sv[5]), fmaxf(sv[6], sv[7])));
            {
                const float m1 = __shfl_xor_sync(0xffffffffu, m, 1), m2 = __shfl_xor_sync(0xffffffffu, m, 2), m3 = __shfl_xor_sync(0xffffffffu, m, 3);
                m = fmaxf(fmaxf(m, m1), fmaxf(m2, m3));
            }
            TS(5, FU(m));
            const uint32_t ONE2 = 0x3f803f80u;
            float o0[4], o1[4], sm[4];
            const uint32_t pb0 = pack2(ex2(sv[0] - m), ex2(sv[1] - m)), pb1 = pack2(ex2(sv[2] - m), ex2(sv[3] - m));
            mma16816z(sm, ONE2, ONE2, ONE2, ONE2, pb0, pb1);
            MMAZ(o0, vt00, pb0, pb1); MMAZ(o1, vt10, pb0, pb1);
            const uint32_t z = (VDEP == 0 ? FU(m) : pb0) & zr;
            const uint32_t vok = mbar_test(sbu + R_BAR + 8 * MB_V + z, s & 1);
            const uint32_t rv = r8 + vok * 8;
            float2 va = lds64v(rv + R_VB - 8 + fo * 512);
            float2 vb = lds64v(rv + R_VB - 8 + fo * 512 + 256);
            float sig = __uint_as_float(lds32v_(sbu + R_MISC + 40));
            const uint32_t pb2 = pack2(ex2(sv[4] - m), ex2(sv[5] - m)), pb3 = pack2(ex2(sv[6] - m), ex2(sv[7] - m));
            mma16816(sm, ONE2, ONE2, ONE2, ONE2, pb2, pb3);
            const uint32_t pb4 = pack2(ex2(sv[8] - m), ex2(sv[9] - m));
            MMA(o0, vt01, pb2, pb3); MMA(o1, vt11, pb2, pb3);
            mma1688(sm, ONE2, ONE2, pb4);
            const float z0 = rcpf(sm[0]), z1 = rcpf(sm[1]);
#define PUT_O()                                                                                                   \
            {                                                                                                     \
                float a0[4] = {o0[0], o0[1], o0[2], o0[3]}, a1[4] = {o1[0], o1[1], o1[2], o1[3]};                 \
                mma1688(a0, FU(va.x), FU(va.y), pb4); mma1688(a1, FU(vb.x), FU(vb.y), pb4);                       \
                const float i0 = z0 * sig, i1 = z1 * sig;                                                         \
                stsm4t(rG + R_QP, pack2(a0[0] * i0, a0[1] * i1), pack2(a0[2] * i0, a0[3] * i1), pack2(a1[0] * i0, a1[1] * i1), pack2(a1[2] * i0, a1[3] * i1)); \
            }
            PUT_O()
            asm volatile("{\n.reg .pred p;\nsetp.ne.u32 p, %0, 0;\n@p bar.arrive 8, 256;\n}" :: "r"(vok) : "memory");
            if (__builtin_expect(__any_sync(0xffffffffu, vok == 0), 0)) {
                mbar_wait_p(sbu + R_BAR + 8 * MB_V, s & 1);
                va = lds64v(r8 + R_VB + fo * 512); vb = lds64v(r8 + R_VB + fo * 512 + 256);
                sig = __uint_as_float(lds32v_(sbu + R_MISC + 40));
                PUT_O()
                bar_arrive(8, 256);
                CNT(8);
            }
            TS(6, 0);
            const float r = __uint_as_float(0x7f000000u - FU(sig));
            cs = cexp * r * (fo >= 2 ? r : 1.f);
        }
        return false;
    };
    step(0, true);
#pragma unroll 1
    for (int s = 0;; s++) {
        if (s & 1) mbar_wait_p(sbu + R_BAR + 8 * (MB_FULL0 + (((s + 1) >> 1) & 1)), ((s + 1) >> 2) & 1);
        {
            const uint32_t a = rL + R_LT + 512 + 12 + fo * 512;
            sts32(a, lds32v_(a) + ((s & 1) ? ((s & 2) ? R_SLOT0 - R_SLOT1 - 4096 : R_SLOT1 - R_SLOT0 - 4096) : 4096));
        }
        auto early = [&]() {
            SCHED(13);
#pragma unroll
            for (int i = 0; i < NAX - NXL; i++) { lds_fragv(wq[i], rG + R_AX + 4096 * i); lds_fragv(wk[i], rG + R_AX + 4096 * i + 512); }
        };
        GATHER(0, , early();, )
        if (step(s + 1, false)) break;
    }
    CNT(9);
    if (rG == sbu) GT(cc * 8 + 4);
}

__device__ __forceinline__ void rec_b(uint32_t sb, int c, uint32_t epoch) {
    const int tid = threadIdx.x - WGB * 128, lane = tid & 31, f = tid >> 5;
    uint32_t wq[16][4], wk[16][4], wo[32][4];
    const int lrow = ((lane >> 4) << 3) + (lane & 7), lsel = (lane >> 3) & 1;
    const uint32_t rL = opaque(sb + lane * 16), rW = opaque(sb + lane * 16 + f * 16384);
    const uint32_t sbu = uni(sb), fo = uni(f), cc = uni(c), po = cc & 1, ep = uni(epoch);
    {
        mbar_wait(sb + R_BAR + 8 * MB_WO, 0);
        if (c == 7 && tid == 0) GT(1426);
        const uint32_t aO = sb + R_WO + f * 16384 + lrow * 128 + ((lsel ^ (lane & 7)) << 4);
#pragma unroll
        for (int i = 0; i < 32; i++) {
            const int tile = (i >> 4) * 2 + (i & 1), kk = (i >> 1) & 7;
            ldsm4t(wo[i], (aO ^ (32 * tile)) + kk * 2048);
        }
        const float no = frag_norm2(wo);
        if (lane == 0) sts32(sb + R_MISC + 80 + f * 4, FU(no));
        __syncwarp();
        bar_sync(0, 256);
        if (tid == 0) {
            const float4 a = lds128(sb + R_MISC + 64), b = lds128(sb + R_MISC + 80);
            stg4(&g_f.norm[c], make_uint4(FU((a.x + a.y) + (a.z + a.w)), epoch, FU((b.x + b.y) + (b.z + b.w)), epoch));
        }
        __syncwarp();
#pragma unroll
        for (int i = NRW; i < 32; i++) sts128u(rW + R_WO + i * 512, wo[i][0], wo[i][1], wo[i][2], wo[i][3]);
        mbar_wait(sb + R_BAR + 8 * MB_W1, 0);
        if (c == 7 && tid == 0) GT(1422);
        __syncwarp();
#pragma unroll
        for (int kk = 0; kk < 16; kk++) { const uint32_t a = sb + R_QK1 + wrow_off(kk, 2 * f + lsel); ldsm4t(wq[kk], a); ldsm4t(wk[kk], a + 32768); }
        bar_sync(13, 128);
#pragma unroll
        for (int i = 0; i < 16; i++) {
            sts128u(rW + R_QK1 + i * 1024, wq[i][0], wq[i][1], wq[i][2], wq[i][3]);
            sts128u(rW + R_QK1 + i * 1024 + 512, wk[i][0], wk[i][1], wk[i][2], wk[i][3]);
        }
        __syncwarp();
    }
    const uint64_t gx = xpage();
    const uint32_t ghi = uni((uint32_t)(gx >> 32)), glo = uni((uint32_t)gx);
    TSDECL;
#pragma unroll 1
    for (int s = 0;; s++) {
        bar_sync(2, 256);
        float q0[4], k0[4];
        g1<BNB, SMB>(q0, k0, wq, wk, rL + R_MEMB + 4096, sbu - s, [&](int i, const uint32_t* c_) {
            if (i == 0) TS(0, c_[0]);
            if (i >= 2 && i < 6) {
#pragma unroll
                for (int n = NRW + (i - 2) * E0 / 4; n < NRW + (i - 1) * E0 / 4; n++) lds_fragv(wo[n], rW + R_WO + n * 512);
            }
            if (i == IV) bar_arrive(GOBAR, 96);
        });
        stsm4t(rL + fo * 1024 + R_QP + 512, pack2(q0[0], q0[1]), pack2(q0[2], q0[3]), pack2(k0[0], k0[1]), pack2(k0[2], k0[3]));
        bar_arrive(3, 256);
        TS(1, FU(k0[3]));
        const uint32_t so = aslot(s);
        uint2 lt;
        { const float2 t = lds64v(rL + R_LT + 8); lt.x = FU(t.x); lt.y = FU(t.y); }
        const uint32_t sel = 0x3210u + (lt.x & 16) * 0x440u;
        uint32_t* pm = (uint32_t*)mkptr(((glo + acc_base(po * 4 + fo)) ^ so) + lt.x, ghi);
        uint32_t* px = (uint32_t*)mkptr(((glo + ext_base(po * 4 + fo)) ^ so) + lt.y, ghi);
        if (s == NSEG - 1) break;
        {
            const uint32_t z = lt.x & 1;
#pragma unroll
            for (int n = NRW; n < NRW + E0 + E1 + E2 + E3; n++) {
                const int d = n - (n < NRW + T2N ? TRK + 1 : TRK);
                lds_fragv(wo[n], (d >= NRW ? or_and(rW, wo[d][0], z) : rW) + R_WO + n * 512);
            }
        }
        TS(2, wo[NRW + E0 + E1 + E2 + E3 - 1][0]);
        SCHED(4);
        bar_sync(8, 256);
        {
            float o[4][4];
            uint32_t b[4][4];
#pragma unroll
            for (int i = 0; i < 4; i++) ldsm4(b[i], rL + R_QP + i * 1024);
            PINM();
#pragma unroll
            for (int n = NRW + E0 + E1 + E2 + E3; n < 32; n++) lds_fragv(wo[n], rW + R_WO + n * 512);
            float p[4][4];
#define G2_STEP(o, hf, kk) _Pragma("unroll") for (int i = 0; i < 2; i++) MMAF((kk) < 2, o[((kk) & 1) * 2 + i], wo[(hf) * 16 + (kk) * 2 + i], b[(kk) >> 1][((kk) & 1) * 2], b[(kk) >> 1][((kk) & 1) * 2 + 1])
#define G2_RED(o, wl, h) const uint32_t wl = packh2(o[1][2] + o[3][2], o[1][3] + o[3][3]);                            \
                asm volatile("red.relaxed.gpu.global.add.noftz.v4.f16x2 [%0], {%1,%2,%3,%4};" :: "l"(pm + (h) * 16),  \
                    "r"(packh2(o[0][0] + o[2][0], o[0][1] + o[2][1])), "r"(packh2(o[0][2] + o[2][2], o[0][3] + o[2][3])), \
                    "r"(packh2(o[1][0] + o[3][0], o[1][1] + o[3][1])), "r"(prmt(wl, HONE2, (h) ? sel : sel ^ 0x4400u)) : "memory")
            if (G2V == 1) SCHED(11);
#pragma unroll
            for (int kk = 0; kk < 8; kk++) { G2_STEP(o, 0, kk); }
            TS(7, b[0][0]);
            if (G2V == 0) SCHED(11);
            else {
#pragma unroll
                for (int i = 0; i < 4; i++) wo[16 + i][0] = or_and(wo[16 + i][0], FU(o[i][0]), lt.x & 1);
            }
#pragma unroll
            for (int kk = 0; kk < G2K; kk++) { G2_STEP(p, 1, kk); }
#pragma unroll
            for (int i = 0; i < NB0; i++) { lds_fragv(wq[i], rW + R_QK1 + i * 1024); lds_fragv(wk[i], rW + R_QK1 + i * 1024 + 512); }
            G2_RED(o, w3, 0);
            TS(8, w3);
            if (G2V == 0) SCHED(12);
#pragma unroll
            for (int kk = G2K; kk < 8; kk++) { G2_STEP(p, 1, kk); }
            G2_RED(p, w7, 1);
            asm volatile("red.relaxed.gpu.global.add.noftz.f16x2 [%0], %1;" :: "l"(px), "r"(prmt((w3 & 0xffff0000u) | 0x3c00u, w7, sel)) : "memory");
            TS(9, w7);
        }
        bar_arrive(5, 384);
        asm volatile("{\n.reg .pred p;\nsetp.eq.u32 p, %0, %1;\n@p mbarrier.arrive.expect_tx.shared::cta.b64 _, [%2], 1536;\n}"
                     :: "r"(rW), "r"(sbu), "r"(sbu + R_BAR + 8 * MB_S) : "memory");
        const uint32_t tb = clk32();
        TSACC();
        spin_until(tb, DB);
#pragma unroll
        for (int i = NB0; i < NBR; i++) {
            if (i == NB1) spin_until(tb, DP + DB2);
            lds_fragv(wq[i], rW + R_QK1 + i * 1024); lds_fragv(wk[i], rW + R_QK1 + i * 1024 + 512);
        }
    }
}

#undef lds_fragv
__device__ __forceinline__ void rec_first_loads(uint32_t sb, int c, const Maps& maps) {
    const uint32_t bar = sb + R_BAR;
    const int F0 = c * 64;
    mbar_expect_tx(bar + 8 * MB_W0, 65536); mbar_expect_tx(bar + 8 * MB_WO, 65536); mbar_expect_tx(bar + 8 * MB_WV, 65536);
    tma2d(sb + R_QK1, &maps.wv, F0, 0, bar + 8 * MB_WV); tma2d(sb + R_QK1 + 32768, &maps.wv, F0, 256, bar + 8 * MB_WV);
    tma2d(sb + R_T + 32768, &maps.wk, F0, 0, bar + 8 * MB_W0);
    if (!LORD) {
        for (int i = 0; i < 4; i++) tma2d(sb + R_WO + i * 16384, &maps.wo, (c & 1) * 256 + i * 64, (c >> 1) * 128, bar + 8 * MB_WO);
        tma2d(sb + R_T, &maps.wq, F0, 0, bar + 8 * MB_W0);
    }
    mbar_expect_tx(bar + 8 * MB_S, 1536);
}
__device__ __forceinline__ void rec_c(uint32_t sb, int c, const bf16* __restrict__ mem0, const Maps& maps, uint32_t epoch) {
    const int tid = threadIdx.x - WGC * 128, lane = tid & 31, u = tid >> 5;
    const uint32_t bar = sb + R_BAR;
    const int lrow = ((lane >> 4) << 3) + (lane & 7), lsel = (lane >> 3) & 1;
    const int kh = u >> 1, j = u & 1;
    uint32_t wv[32][4], mx, my = 0, mz = 0;
    {
        if (u == 0) {
            sts128u(sb + lane * 16 + R_LT, (lane >> 3) * 256 + (lane & 7) * 16, ((lane >> 2) & 1) * XHS + (lane >> 4) * XSS + (lane & 8) * 2 + (lane & 2) * 4,
                    (lane >> 2) * 256 + (lane & 3) * 16, (lane & 1) * XHS + ((lane >> 3) & 1) * XSS + (lane & 6) * 4 + (lane >> 4) * 4);
        }
        mbar_wait(bar + 8 * MB_WV, 0);
        if (c == 7 && tid == 0) GT(1425);
        if (LORD && tid == 32) {
            for (int i = 0; i < 4; i++) tma2d(sb + R_WO + i * 16384, &maps.wo, (c & 1) * 256 + i * 64, (c >> 1) * 128, bar + 8 * MB_WO);
            tma2d(sb + R_T, &maps.wq, c * 64, 0, bar + 8 * MB_W0);
        }
        __syncwarp();
#pragma unroll
        for (int kk = 0; kk < 16; kk++) {
            const uint32_t aa = sb + R_QK1 + kh * 32768 + wrow_off(kk, 4 * j + 2 * kh + lsel);
            ldsm4t(wv[kk], aa); ldsm4t(wv[16 + kk], aa ^ 32);
        }
        {
            uint32_t x = 0;
#pragma unroll
            for (int i = 0; i < 32; i++) x ^= wv[i][0];
            sts32(sb + R_MISC + 96 + u * 4, __reduce_xor_sync(0xffffffffu, x));
        }
        bar_sync(9, 128);
        if (c == 7 && tid == 0) GT(1423);
        if (tid == 0) {
            mbar_expect_tx(bar + 8 * MB_W1, 65536);
            tma2d(sb + R_QK1 + 32768, &maps.wk, c * 64, 256, bar + 8 * MB_W1); tma2d(sb + R_QK1, &maps.wq, c * 64, 256, bar + 8 * MB_W1);
        }
        __syncwarp();
        const float nv = frag_norm2(wv);
        if (lane == 0) sts32(sb + R_MISC + 64 + u * 4, FU(nv));
        __syncwarp();
        bar_arrive(0, 256);
        mx = put_mem0(sb, 4 + u, mem0);
    }
    const uint32_t rL = opaque(sb + lane * 16), rG = opaque(sb + lane * 16 + u * 1024);
    const uint32_t sbu = uni(sb), fo = uni(u), cc = uni(c), ep = uni(epoch);
    const uint64_t gx = xpage();
    const uint32_t ghi = uni((uint32_t)(gx >> 32)), glo = uni((uint32_t)gx);
    constexpr int CX = R_AX + NAX * 4096;
    static_assert(NAX + NCX <= 6, "AX");
#pragma unroll
    for (int i = 0; i < NCX; i++) {
        sts128u(rG + CX + 4096 * i, wv[i][0], wv[i][1], wv[i][2], wv[i][3]);
        sts128u(rG + CX + 4096 * i + 512, wv[16 + i][0], wv[16 + i][1], wv[16 + i][2], wv[16 + i][3]);
    }
    __syncwarp();
    TSDECL;
    uint32_t rpb = 0x3f800000u;
    bar_arrive(2, 256);
    uint32_t kvq = ~ep;
    auto ring = [&](int s) {
        uint32_t n = 0;
#pragma unroll 1
        while (!__all_sync(0xffffffffu, kvq == ep)) {
            kvq = ldg_rlx(&g_f.kv[(s + 2) >> 1][cc >> 1][(rL >> 4) & 1]);
            if (++n > SPIN_LIMIT) { ABORT(6); break; }
        }
        if (rL == sbu) load_slot(sbu, cc, (s + 2) >> 1, maps);
        __syncwarp();
    };
    if (fo == 3) { ring(-2); if (cc == 7 && rL == sbu) GT(1427); }
#pragma unroll 1
    for (int s = 0;; s++) {
        PUT_MAX(rL, 4 + fo)
        if (fo != 0) bar_arrive(15, 256);
        if (fo == 3 && !(s & 1) && s > 0 && s + 2 < NSEG) ring(s);
#pragma unroll
        for (int i = NCX - NCL; i < NCX; i++) { lds_fragv(wv[i], rG + CX + 4096 * i); lds_fragv(wv[16 + i], rG + CX + 4096 * i + 512); }
        if (fo == 0) {
                bar_sync(15, 256);
                if (s == 0) {
                    const uint32_t* np = (const uint32_t*)&g_f.norm[0] + ((rL ^ sbu) >> 2);
                    uint4 r, q; uint32_t n = 0;
#pragma unroll 1
                    while (true) {
                        r = ldg_rlx4(np); q = ldg_rlx4(np + 128);
                        const uint2 z = ldg_rlx2(&g_f.xn[(rL ^ sbu) >> 3]);
                        if (__all_sync(0xffffffffu, r.y == ep && r.w == ep && q.y == ep && q.w == ep && z.x == ep && z.y == ep)) break;
                        if (++n > SPIN_LIMIT) { ABORT(5); break; }
                    }
                    float nv = __uint_as_float(r.x) + __uint_as_float(q.x), no = __uint_as_float(r.z) + __uint_as_float(q.z);
#pragma unroll
                    for (int o = 16; o; o >>= 1) { nv += __shfl_xor_sync(0xffffffffu, nv, o); no += __shfl_xor_sync(0xffffffffu, no, o); }
                    const int lc = ((int)(FU(nv) >> 23) + (int)(FU(no) >> 23) - 252 + 9 + 1) >> 1;
                    sts32(sbu + R_MISC + 32, 140 - lc);
                    __syncwarp();
                }
                const uint4 ma = lds128uv(rL + R_STG + 1024), mb = lds128uv(rL + R_STG + 1536);
                const uint32_t m_ = amax2b(amax2b(amax2b(ma.x, ma.y), amax2b(ma.z, ma.w)), amax2b(amax2b(mb.x, mb.y), amax2b(mb.z, mb.w)));
                const int em = (int)(__reduce_max_sync(0xffffffffu, amax2b(m_, m_ << 16) & 0x7f800000u) >> 23) + (int)(rpb >> 23) - 127;
                const int es = min(max((int)lds32v_(sbu + R_MISC + 32) - max(em, 127), -60), 60);
                sts32(sbu + R_MISC + 40, (127 + es) << 23);
                TS(4, es);
        }
        bar_sync(GOBAR, 96);
        float v0[4], v1[4];
        g1<CNB, SMC>(v0, v1, wv, wv + 16, rL + R_MEMB + (fo >> 1) * 4096, sbu - s, [&](int i, const uint32_t* c_) { if (i == 0) TS(0, c_[0]); });
        TS(1, FU(v1[3]));
        const uint32_t l16 = (rL ^ sbu) | (lds32v_(rL + R_LT + 4) & 1);
        const uint32_t r8 = sbu + (l16 >> 1);
        {
            sts128(rL + R_VRED + fo * 512, v1[0], v1[1], v1[2], v1[3]);
            const uint32_t d = r8 + R_VB + ((cc & 1) * 4 + (fo & 1) * 2 + (fo >> 1)) * 256;
            const uint32_t dr = xorv(d, 0x01000000u), br = xorv(sbu + R_BAR + 8 * MB_V, 0x01000000u);
            bar_sync(6 + (fo & 1), 64);
            const float4 a0 = lds128(rL + R_VRED + (fo ^ 2) * 512);
            const float rp = __uint_as_float(rpb);
            const uint32_t w0 = pack2((v0[0] + a0.x) * rp, (v0[1] + a0.y) * rp), w1 = pack2((v0[2] + a0.z) * rp, (v0[3] + a0.w) * rp);
            st_async2(dr, w0, w1, br);
            TS(3, w1);
            sts64(d, __uint_as_float(w0), __uint_as_float(w1));
            if (fo != 1) bar_arrive(9, 192);
            __syncwarp();
            asm volatile("{\n.reg .pred p;\nsetp.eq.u32 p, %0, %1;\n@p mbarrier.arrive.expect_tx.shared::cta.b64 _, [%2], 256;\n}"
                         :: "r"(rL), "r"(sbu), "r"(sbu + R_BAR + 8 * MB_V) : "memory");
        }
        if (fo == 1) {
            bar_sync(9, 192);
            uint8_t* dst = (uint8_t*)&g_KVf[s][cc >> 1][(cc & 1) * 256] + l16;
            const uint32_t r2 = prmt(rpb, 0, 0x3232u);
#pragma unroll
            for (int i = 0; i < 2; i++) {
                const uint4 a = lds128uv(rL + R_STG + i * 512);
                stg4(dst + i * 512, make_uint4(~hmul2b(a.x, r2), ~hmul2b(a.y, r2), ~hmul2b(a.z, r2), ~hmul2b(a.w, r2)));
                const float2 b0 = lds64v(r8 + R_VB + (cc & 1) * 1024 + i * 512), b1 = lds64v(r8 + R_VB + (cc & 1) * 1024 + i * 512 + 256);
                stg4(dst + 2048 + i * 512, make_uint4(~FU(b0.x), ~FU(b0.y), ~FU(b1.x), ~FU(b1.y)));
            }
            __syncwarp();
            if (l16 == 0) { stg_rlx(&g_f.rec[cc >> 1][cc & 1], (ep << 8) | (s + 1)); if (s == NSEG - 1) GT(1500 + cc); }
            __syncwarp();
        } else {
            if (fo == 2) {
                if (l16 < 144) stg4((void*)mkptr((glo + zero_off(cc, l16 >> 4)) ^ aslot(s + 4), ghi), make_uint4(0, 0, 0, 0));
                __syncwarp();
            } else if (fo == 3) {
                kvq = ldg_rlx(&g_f.kv[min((s + 3) >> 1, NT - 1)][cc >> 1][(l16 >> 4) & 1]);
                if (s == 0) ring(s);
            }
        }
        if (s == NSEG - 1) break;
        auto early = [&]() {
#pragma unroll
            for (int i = 0; i < NCX - NCL; i++) { lds_fragv(wv[i], rG + CX + 4096 * i); lds_fragv(wv[16 + i], rG + CX + 4096 * i + 512); }
        };
        GATHER(1, , early(); rpb = 0x7f000000u - lds32v_(sbu + R_MISC + 40);, bar_arrive(2, 256);)
    }
}

__device__ __forceinline__ bool cand_better(float v, int i, float bv, int bi) { return v > bv || (v == bv && i < bi); }

constexpr int G_W = 0;
constexpr int G_RING = 131072;
constexpr int G_BUF = 163840;
constexpr int G_BAR = 229376;
constexpr int G_SMEM = G_BAR + 512;
enum { GB_FULL = 0, GB_EMPTY = GB_FULL + 8, GB_KV = GB_EMPTY + 8, GB_STG = GB_KV + 2, GB_FREE = GB_STG + 2, GB_XN = GB_FREE + 2, GB_T1D, GB_VV, GB_KVF = GB_VV + 2, GB_VF, GB_N };
constexpr int SMEM_TOTAL = 232448;

__device__ __forceinline__ void wgmma_n128(float* d, uint64_t da, uint64_t db, int scale_d) {
    asm volatile("{\n.reg .pred p;\nsetp.ne.b32 p, %66, 0;\n"
        "wgmma.mma_async.sync.aligned.m64n128k16.f32.bf16.bf16 "
        "{%0,%1,%2,%3,%4,%5,%6,%7,%8,%9,%10,%11,%12,%13,%14,%15,%16,%17,%18,%19,%20,%21,%22,%23,%24,%25,%26,%27,%28,%29,%30,%31,"
        "%32,%33,%34,%35,%36,%37,%38,%39,%40,%41,%42,%43,%44,%45,%46,%47,%48,%49,%50,%51,%52,%53,%54,%55,%56,%57,%58,%59,%60,%61,%62,%63}, "
        "%64, %65, p, 1, 1, 0, 1;\n}"
        : "+f"(d[0]), "+f"(d[1]), "+f"(d[2]), "+f"(d[3]), "+f"(d[4]), "+f"(d[5]), "+f"(d[6]), "+f"(d[7]), "+f"(d[8]), "+f"(d[9]), "+f"(d[10]), "+f"(d[11]),
          "+f"(d[12]), "+f"(d[13]), "+f"(d[14]), "+f"(d[15]), "+f"(d[16]), "+f"(d[17]), "+f"(d[18]), "+f"(d[19]), "+f"(d[20]), "+f"(d[21]), "+f"(d[22]), "+f"(d[23]),
          "+f"(d[24]), "+f"(d[25]), "+f"(d[26]), "+f"(d[27]), "+f"(d[28]), "+f"(d[29]), "+f"(d[30]), "+f"(d[31]), "+f"(d[32]), "+f"(d[33]), "+f"(d[34]), "+f"(d[35]),
          "+f"(d[36]), "+f"(d[37]), "+f"(d[38]), "+f"(d[39]), "+f"(d[40]), "+f"(d[41]), "+f"(d[42]), "+f"(d[43]), "+f"(d[44]), "+f"(d[45]), "+f"(d[46]), "+f"(d[47]),
          "+f"(d[48]), "+f"(d[49]), "+f"(d[50]), "+f"(d[51]), "+f"(d[52]), "+f"(d[53]), "+f"(d[54]), "+f"(d[55]), "+f"(d[56]), "+f"(d[57]), "+f"(d[58]), "+f"(d[59]),
          "+f"(d[60]), "+f"(d[61]), "+f"(d[62]), "+f"(d[63])
        : "l"(da), "l"(db), "r"(scale_d));
}

__device__ __forceinline__ constexpr uint32_t slot_off(int slot) {
    return slot < 2 ? G_RING + slot * 16384 : G_BUF + (slot & 1) * 32768 + (slot < 4 ? 16384 : 0);
}
constexpr int PO = (HSPLIT / 2) & 1;
template <int NSLOT, class F>
__device__ __forceinline__ void gemm_tile(float* acc, uint32_t sb, int tile, int it, int wg, bool pass, uint32_t l0, F&& hook) {
    const uint32_t bar = sb + G_BAR;
    bar_sync(3 + wg, 256);
    int prev = 0;
#pragma unroll
    for (int k = 0; k < 4; k++) {
        const int n = tile * 4 + k, slot = NSLOT == 4 ? k : n % NSLOT;
        const uint32_t sz = sb + (((it + k) << 4) & sb & 0x3f0);
        const uint64_t da = desc_sw128(sz + slot_off(slot), 16, 1024), db0 = desc_sw128(sz + G_W, 65536, 1024);
        mbar_wait_p(bar + 8 * (GB_FULL + slot), NSLOT == 4 ? (tile & 1) : ((n / NSLOT) & 1));
        if (k == 3 && pass) bar_arrive(3 + (wg ^ 1), 256);
        asm volatile("wgmma.fence.sync.aligned;" ::: "memory");
#pragma unroll
        for (int kk = 0; kk < 4; kk++) wgmma_n128(acc, da + kk * 2, db0 + k * 1024 + kk * 128, (k | kk) != 0);
        asm volatile("wgmma.commit_group.sync.aligned;" ::: "memory");
        if (k > 0) {
            asm volatile("wgmma.wait_group.sync.aligned 1;" ::: "memory");
            mbar_arrive2_if(bar + 8 * (GB_EMPTY + prev), l0);
        }
#pragma unroll
        for (int kk = 0; kk < 4; kk++) wgmma_n128(acc, da + 512 + kk * 2, db0 + k * 1024 + 512 + kk * 128, 1);
        asm volatile("wgmma.commit_group.sync.aligned;" ::: "memory");
        if (k == 1) hook();
        prev = slot;
    }
    asm volatile("wgmma.wait_group.sync.aligned 0;" ::: "memory");
    mbar_arrive2_if(bar + 8 * (GB_EMPTY + prev), l0);
}
__device__ __forceinline__ void stage_bf16(const float* acc, uint32_t buf, float s0, float s1) {
    const int lane = threadIdx.x & 31, wq = (threadIdx.x >> 5) & 3;
    const int row = wq * 16 + (lane & 7) + ((lane >> 3) & 1) * 8;
    const uint32_t base = buf + row * 128;
#pragma unroll
    for (int j = 0; j < 16; j += 2) {
        const int ch = (j & 7) + (lane >> 4);
        stsm4(base + (j >> 3) * 8192 + ((ch ^ (row & 7)) << 4),
              pack2(acc[4 * j] * s0, acc[4 * j + 1] * s0), pack2(acc[4 * j + 2] * s1, acc[4 * j + 3] * s1),
              pack2(acc[4 * j + 4] * s0, acc[4 * j + 5] * s0), pack2(acc[4 * j + 6] * s1, acc[4 * j + 7] * s1));
    }
}

__device__ __forceinline__ void store_perm(const float* acc, bf16* dst, int ld, float s0, float s1, uint32_t m) {
#pragma unroll
    for (int i = 0; i < 4; i++) {
        const float* a = acc + 16 * i;
        stg4(dst + i * 32, make_uint4(pack2(a[0] * s0, a[1] * s0) ^ m, pack2(a[4] * s0, a[5] * s0) ^ m, pack2(a[8] * s0, a[9] * s0) ^ m, pack2(a[12] * s0, a[13] * s0) ^ m));
        stg4(dst + 8 * ld + i * 32, make_uint4(pack2(a[2] * s1, a[3] * s1) ^ m, pack2(a[6] * s1, a[7] * s1) ^ m, pack2(a[10] * s1, a[11] * s1) ^ m, pack2(a[14] * s1, a[15] * s1) ^ m));
    }
}
template <int ACC>
__device__ __forceinline__ void wgmma_rs64(float* d, const uint32_t* a, uint64_t db) {
    asm volatile("{\n.reg .pred p;\nsetp.ne.b32 p, %37, 0;\n"
        "wgmma.mma_async.sync.aligned.m64n64k16.f32.bf16.bf16 {%0,%1,%2,%3,%4,%5,%6,%7,%8,%9,%10,%11,%12,%13,%14,%15,%16,%17,%18,%19,%20,%21,%22,%23,%24,%25,%26,%27,%28,%29,%30,%31}, {%32,%33,%34,%35}, %36, p, 1, 1, 0;\n}"
        : "+f"(d[0]), "+f"(d[1]), "+f"(d[2]), "+f"(d[3]), "+f"(d[4]), "+f"(d[5]), "+f"(d[6]), "+f"(d[7]), "+f"(d[8]), "+f"(d[9]), "+f"(d[10]), "+f"(d[11]), "+f"(d[12]), "+f"(d[13]), "+f"(d[14]), "+f"(d[15]), "+f"(d[16]), "+f"(d[17]), "+f"(d[18]), "+f"(d[19]), "+f"(d[20]), "+f"(d[21]), "+f"(d[22]), "+f"(d[23]), "+f"(d[24]), "+f"(d[25]), "+f"(d[26]), "+f"(d[27]), "+f"(d[28]), "+f"(d[29]), "+f"(d[30]), "+f"(d[31])
        : "r"(a[0]), "r"(a[1]), "r"(a[2]), "r"(a[3]), "l"(db), "n"(ACC));
}
template <int ACC>
__device__ __forceinline__ void wgmma_rs128t(float* d, const uint32_t* a, uint64_t db) {
    asm volatile("{\n.reg .pred p;\nsetp.ne.b32 p, %69, 0;\n"
        "wgmma.mma_async.sync.aligned.m64n128k16.f32.bf16.bf16 {%0,%1,%2,%3,%4,%5,%6,%7,%8,%9,%10,%11,%12,%13,%14,%15,%16,%17,%18,%19,%20,%21,%22,%23,%24,%25,%26,%27,%28,%29,%30,%31,%32,%33,%34,%35,%36,%37,%38,%39,%40,%41,%42,%43,%44,%45,%46,%47,%48,%49,%50,%51,%52,%53,%54,%55,%56,%57,%58,%59,%60,%61,%62,%63}, {%64,%65,%66,%67}, %68, p, 1, 1, 1;\n}"
        : "+f"(d[0]), "+f"(d[1]), "+f"(d[2]), "+f"(d[3]), "+f"(d[4]), "+f"(d[5]), "+f"(d[6]), "+f"(d[7]), "+f"(d[8]), "+f"(d[9]), "+f"(d[10]), "+f"(d[11]), "+f"(d[12]), "+f"(d[13]), "+f"(d[14]), "+f"(d[15]), "+f"(d[16]), "+f"(d[17]), "+f"(d[18]), "+f"(d[19]), "+f"(d[20]), "+f"(d[21]), "+f"(d[22]), "+f"(d[23]), "+f"(d[24]), "+f"(d[25]), "+f"(d[26]), "+f"(d[27]), "+f"(d[28]), "+f"(d[29]), "+f"(d[30]), "+f"(d[31]), "+f"(d[32]), "+f"(d[33]), "+f"(d[34]), "+f"(d[35]), "+f"(d[36]), "+f"(d[37]), "+f"(d[38]), "+f"(d[39]), "+f"(d[40]), "+f"(d[41]), "+f"(d[42]), "+f"(d[43]), "+f"(d[44]), "+f"(d[45]), "+f"(d[46]), "+f"(d[47]), "+f"(d[48]), "+f"(d[49]), "+f"(d[50]), "+f"(d[51]), "+f"(d[52]), "+f"(d[53]), "+f"(d[54]), "+f"(d[55]), "+f"(d[56]), "+f"(d[57]), "+f"(d[58]), "+f"(d[59]), "+f"(d[60]), "+f"(d[61]), "+f"(d[62]), "+f"(d[63])
        : "r"(a[0]), "r"(a[1]), "r"(a[2]), "r"(a[3]), "l"(db), "n"(ACC));
}
__device__ __forceinline__ void attention_tile(float* acc, uint32_t sb, int tile, int h, int wg, int wq, uint32_t l0, uint32_t epoch, uint4* km, uint4* vm) {
    const uint32_t buf = sb + G_BUF + ((tile << 4) & sb & 0x3f0);
    const int lane = threadIdx.x & 31, g = lane >> 2, t = lane & 3;
    const int sg = wq >> 1, hf = wq & 1, seg = tile * 2 + sg;
    uint32_t qf[8][4];
#pragma unroll
    for (int kk = 0; kk < 8; kk++) {
        qf[kk][0] = pack2(acc[8 * kk], acc[8 * kk + 1]); qf[kk][1] = pack2(acc[8 * kk + 2], acc[8 * kk + 3]);
        qf[kk][2] = pack2(acc[8 * kk + 4], acc[8 * kk + 5]); qf[kk][3] = pack2(acc[8 * kk + 6], acc[8 * kk + 7]);
    }
    uint32_t* kvf = &g_KVf[seg][h][lane * 4];
    auto kv_valid = [&]() {
        uint32_t mn = 0xffffffffu;
#pragma unroll
        for (int i = 0; i < 4; i++) mn = min(min(min(mn, min(km[i].x, km[i].y)), min(km[i].z, km[i].w)), min(min(vm[i].x, vm[i].y), min(vm[i].z, vm[i].w)));
        return __all_sync(0xffffffffu, mn != 0);
    };
    float sc[5][4];
    auto mem_scores = [&]() {
        float sb_[4];
#pragma unroll
        for (int i = 0; i < 4; i++) { MMAF(i == 0, sc[4], qf[2 * i], ~km[i].x, ~km[i].y); MMAF(i == 0, sb_, qf[2 * i + 1], ~km[i].z, ~km[i].w); }
#pragma unroll
        for (int i = 0; i < 4; i++) sc[4][i] += sb_[i];
    };
    mbar_wait_p(sb + G_BAR + 8 * (GB_KV + wg), (tile >> 1) & 1);
    if (h == 5 && (threadIdx.x & 127) == 0 && tile < 6) GT(1750 + tile * 8 + 2);
    bool fast;
    {
        const uint64_t dk = desc_sw128(buf, 16, 1024);
        asm volatile("wgmma.fence.sync.aligned;" ::: "memory");
#pragma unroll
        for (int kk = 0; kk < 8; kk++) {
            if (kk == 0) wgmma_rs64<0>(acc, qf[kk], dk); else wgmma_rs64<1>(acc, qf[kk], dk + (kk >> 2) * 512 + (kk & 3) * 2);
        }
        asm volatile("wgmma.commit_group.sync.aligned;" ::: "memory");
        mem_scores();
        fast = kv_valid();
        asm volatile("wgmma.wait_group.sync.aligned 0;" ::: "memory");
        mbar_arrive_if(sb + G_BAR + 8 * GB_KVF, l0);
#pragma unroll
        for (int i = 0; i < 32; i++) asm volatile("" : "+f"(acc[i]) :: "memory");
#pragma unroll
        for (int b = 0; b < 4; b++)
#pragma unroll
            for (int i = 0; i < 4; i++) sc[b][i] = sg ? acc[16 + 4 * b + i] : acc[4 * b + i];
#pragma unroll
        for (int i = 0; i < 4; i++) sc[4][i] = fast ? sc[4][i] : -INFINITY;
    }
    const float cexp = 0.08838834764831845f * 1.4426950408889634f;
    const int r0 = hf * 16 + g, r1 = r0 + 8;
#pragma unroll
    for (int b = 0; b < 4; b++) {
        const int j = b * 8 + 2 * t;
        if (j > r0) sc[b][0] = -INFINITY;
        if (j + 1 > r0) sc[b][1] = -INFINITY;
        if (j > r1) sc[b][2] = -INFINITY;
        if (j + 1 > r1) sc[b][3] = -INFINITY;
    }
    float m0 = -INFINITY, m1 = -INFINITY;
#pragma unroll
    for (int b = 0; b < 5; b++) { m0 = fmaxf(m0, fmaxf(sc[b][0], sc[b][1])); m1 = fmaxf(m1, fmaxf(sc[b][2], sc[b][3])); }
    m0 = fmaxf(m0, __shfl_xor_sync(0xffffffffu, m0, 1)); m1 = fmaxf(m1, __shfl_xor_sync(0xffffffffu, m1, 1));
    m0 = fmaxf(m0, __shfl_xor_sync(0xffffffffu, m0, 2)); m1 = fmaxf(m1, __shfl_xor_sync(0xffffffffu, m1, 2));
    float z0 = 0.f, z1 = 0.f;
    uint32_t p0, p1;
    {
        const float c0 = -m0 * cexp, c1 = -m1 * cexp;
        uint32_t pf[5][2];
#pragma unroll
        for (int b = 0; b < 5; b++) {
            pf[b][0] = pack2(ex2(fmaf(sc[b][0], cexp, c0)), ex2(fmaf(sc[b][1], cexp, c0)));
            pf[b][1] = pack2(ex2(fmaf(sc[b][2], cexp, c1)), ex2(fmaf(sc[b][3], cexp, c1)));
        }
        p0 = pf[4][0]; p1 = pf[4][1];
        uint32_t pa[4][4];
#pragma unroll
        for (int kk = 0; kk < 4; kk++)
#pragma unroll
            for (int i = 0; i < 4; i++) pa[kk][i] = (kk >> 1) == sg ? pf[(kk & 1) * 2 + (i >> 1)][i & 1] : 0u;
        const uint64_t dv = desc_sw128(buf + 32768, 8192, 1024);
        mbar_wait_p(sb + G_BAR + 8 * (GB_VV + wg), (tile >> 1) & 1);
        asm volatile("wgmma.fence.sync.aligned;" ::: "memory");
#pragma unroll
        for (int kk = 0; kk < 4; kk++) { if (kk == 0) wgmma_rs128t<0>(acc, pa[kk], dv); else wgmma_rs128t<1>(acc, pa[kk], dv + kk * 128); }
        asm volatile("wgmma.commit_group.sync.aligned;" ::: "memory");
#pragma unroll
        for (int b = 0; b < 5; b++) { z0 += bf_lo(pf[b][0]) + bf_hi(pf[b][0]); z1 += bf_lo(pf[b][1]) + bf_hi(pf[b][1]); }
        asm volatile("wgmma.wait_group.sync.aligned 0;" ::: "memory");
#pragma unroll
        for (int i = 0; i < 64; i++) asm volatile("" : "+f"(acc[i]) :: "memory");
    }
    mbar_arrive_if(sb + G_BAR + 8 * GB_VF, l0);
    if (h == 5 && (threadIdx.x & 127) == 0 && tile < 6) GT(1750 + tile * 8 + 3);
    if (!fast) {
        wait_rec(&g_f.rec[h][0], epoch, seg + 1);
        if (seg == 63 && (threadIdx.x & 63) == 0) GT(1570 + h);
        uint32_t n = 0;
#pragma unroll 1
        do {
#pragma unroll
            for (int i = 0; i < 4; i++) { km[i] = ldg_rlx4(kvf + i * 128); vm[i] = ldg_rlx4(kvf + 512 + i * 128); }
            if (++n > SPIN_LIMIT) { ABORT(4); break; }
        } while (!kv_valid());
        mem_scores();
        float n0 = fmaxf(sc[4][0], sc[4][1]), n1 = fmaxf(sc[4][2], sc[4][3]);
        n0 = fmaxf(n0, __shfl_xor_sync(0xffffffffu, n0, 1)); n1 = fmaxf(n1, __shfl_xor_sync(0xffffffffu, n1, 1));
        n0 = fmaxf(n0, __shfl_xor_sync(0xffffffffu, n0, 2)); n1 = fmaxf(n1, __shfl_xor_sync(0xffffffffu, n1, 2));
        n0 = fmaxf(n0, m0); n1 = fmaxf(n1, m1);
        const float a0 = ex2((m0 - n0) * cexp), a1 = ex2((m1 - n1) * cexp);
        const float c0 = -n0 * cexp, c1 = -n1 * cexp;
        p0 = pack2(ex2(fmaf(sc[4][0], cexp, c0)), ex2(fmaf(sc[4][1], cexp, c0)));
        p1 = pack2(ex2(fmaf(sc[4][2], cexp, c1)), ex2(fmaf(sc[4][3], cexp, c1)));
        z0 = fmaf(z0, a0, bf_lo(p0) + bf_hi(p0)); z1 = fmaf(z1, a1, bf_lo(p1) + bf_hi(p1));
#pragma unroll
        for (int j = 0; j < 16; j++) { float* o = acc + 4 * j; o[0] *= a0; o[1] *= a0; o[2] *= a1; o[3] *= a1; }
    }
    if (h == 5 && (threadIdx.x & 127) == 0 && tile < 6) GT(1750 + tile * 8 + 4);
    if (hf) bar_arrive(5 + wg * 2 + sg, 64);
#pragma unroll
    for (int i = 0; i < 4; i++) {
        mma1688(acc + 16 * i, p0, p1, ~vm[i].x); mma1688(acc + 16 * i + 4, p0, p1, ~vm[i].y);
        mma1688(acc + 16 * i + 8, p0, p1, ~vm[i].z); mma1688(acc + 16 * i + 12, p0, p1, ~vm[i].w);
    }
    z0 += __shfl_xor_sync(0xffffffffu, z0, 1); z1 += __shfl_xor_sync(0xffffffffu, z1, 1);
    z0 += __shfl_xor_sync(0xffffffffu, z0, 2); z1 += __shfl_xor_sync(0xffffffffu, z1, 2);
    if (h == 5 && (threadIdx.x & 127) == 0 && tile < 6) GT(1750 + tile * 8 + 5);
    if (tile >= 2) mbar_wait_p(sb + G_BAR + 8 * (GB_FREE + wg), ((tile >> 1) - 1 + PO) & 1);
    store_perm(acc, g_O + (size_t)(tile * 64 + wq * 16 + g) * HD + h * 128 + t * 8, HD, rcpf(z0), rcpf(z1), 0);
    mbar_arrive(sb + G_BAR + 8 * (GB_STG + wg));
    if (!hf) {
        bar_sync(5 + wg * 2 + sg, 64);
#pragma unroll
        for (int i = 0; i < 8; i++) stg4_h(kvf + i * 128, make_uint4(0, 0, 0, 0), pol_ef(3));
    }
}

constexpr int NWK = FF / 32;
constexpr int F_WG = 0, F_WU = 32768, F_WD = 65536, F_RED = 98304, F_ACT = F_RED + 8192, F_SEL = F_ACT + 256;
__device__ __noinline__ void ffn_phase(const Maps& maps, bf16* __restrict__ out) {
    extern __shared__ __align__(1024) uint8_t smem[];
    const uint32_t sb = smem_u32(smem);
    const int c = ((volatile int*)(smem + SH_OFF))[8];
    const uint32_t epoch = ((volatile uint32_t*)(smem + SH_OFF))[9];
    const int tid = threadIdx.x;
    const bool worker = c < NWK;
    bar_sync(0, 384);
    const uint32_t mb = sb + R_BAR + 8 * MB_W0;
    if (tid == 352 && worker) {
        if (FFW) __nanosleep(FFW);
        asm volatile("fence.proxy.async.shared::cta;" ::: "memory");
        mbar_expect_tx(mb, 98304);
#pragma unroll 1
        for (int j = 0; j < 6; j++) {
            if (j < 4) tma2d_h(sb + j * 16384, j < 2 ? &maps.wg : &maps.wu, c * 32, (j & 1) * 256, mb, pol_ef(5));
            else for (int i = 0; i < 4; i++) tma2d_h(sb + F_WD + ((j - 4) * 4 + i) * 4096, &maps.wd, ((j - 4) * 4 + i) * 64, c * 32, mb, pol_ef(5));
            if (FFS) __nanosleep(FFS);
        }
    }
    int p0 = -1, p1 = -1;
    float pb = 0.f;
#pragma unroll 1
    for (int pass = 0; pass < 2; pass++) {
        if (tid < 32) {
            const uint32_t tag = epoch & 0xfffffu;
            uint4 r[4]; uint32_t n = 0;
            const int t3 = tid + 96 < NFW ? tid + 96 : tid;
#pragma unroll 1
            while (true) {
                bool ok = true;
#pragma unroll
                for (int i = 0; i < 4; i++) r[i] = ldg_rlx4((const uint32_t*)&g_f.cand[pass][i < 3 ? tid + 32 * i : t3]);
#pragma unroll
                for (int i = 0; i < 4; i++) ok = ok && (r[i].y >> 12) == tag && (r[i].w >> 12) == tag;
                if (__all_sync(0xffffffffu, ok)) break;
                if (pass == 0) __nanosleep(100);
                if (++n > SPIN_LIMIT) { ABORT(7); break; }
            }
            bool chg = pass == 0;
#pragma unroll
            for (int i = 0; i < 4; i++) {
                const int j0 = r[i].y & 4095, j1 = r[i].w & 4095;
                chg = chg || (j0 != p0 && cand_better(__uint_as_float(r[i].x), j0, pb, p1)) || (j1 != p0 && cand_better(__uint_as_float(r[i].z), j1, pb, p1));
            }
            int* sel = (int*)(smem + F_SEL);
            if (__any_sync(0xffffffffu, chg)) {
                float b0 = __uint_as_float(r[0].x), b1 = __uint_as_float(r[0].z); int i0 = r[0].y & 4095, i1 = r[0].w & 4095;
#pragma unroll
                for (int i = 1; i < 9; i++) {
                    float c0, c1; int j0, j1;
                    if (i < 4) { c0 = __uint_as_float(r[i].x); c1 = __uint_as_float(r[i].z); j0 = r[i].y & 4095; j1 = r[i].w & 4095; }
                    else {
                        const int o = 1 << (i - 4);
                        c0 = __shfl_xor_sync(0xffffffffu, b0, o); c1 = __shfl_xor_sync(0xffffffffu, b1, o);
                        j0 = __shfl_xor_sync(0xffffffffu, i0, o); j1 = __shfl_xor_sync(0xffffffffu, i1, o);
                    }
                    if (i != 3 || t3 != tid) {
                        if (cand_better(c0, j0, b0, i0)) {
                            if (cand_better(c1, j1, b0, i0)) { b1 = c1; i1 = j1; } else { b1 = b0; i1 = i0; }
                            b0 = c0; i0 = j0;
                        } else if (cand_better(c0, j0, b1, i1)) { b1 = c0; i1 = j0; }
                    }
                }
                n = 0;
#pragma unroll 1
                while (!__all_sync(0xffffffffu, (ldg_rlx(&g_f.rows[pass][tid]) == epoch) & (ldg_rlx(&g_f.rows[pass][tid + 32]) == epoch) &
                                                   (ldg_rlx(&g_f.rows[pass][tid + 64]) == epoch) & (ldg_rlx(&g_f.rows[pass][t3]) == epoch))) { if (++n > SPIN_LIMIT) { ABORT(7); break; } }
                if (tid == 0) { sel[0] = min(i0, SQ - 1); sel[1] = min(i1, SQ - 1); ((float*)sel)[2] = b0; ((float*)sel)[3] = b1; }
            }
            if (pass && tid == 0 && c == 3) GT(1440);
        }
        bar_sync(0, 384);
        const int t0 = ((int*)(smem + F_SEL))[0], t1 = ((int*)(smem + F_SEL))[1];
        if (c == 3 && tid == 0 && pass == 0) GT(1430);
        if (t0 == p0 && t1 == p1) break;
        pb = ((float*)(smem + F_SEL))[3];
        const uint32_t ytag = epoch * 2 + pass + 1;
        if (worker) {
            const int lane = tid & 31, w = tid >> 5, g = lane >> 2, t = lane & 3;
            const int lrow = ((lane >> 4) << 3) + (lane & 7), lsel = (lane >> 3) & 1;
            float2* red = (float2*)(smem + F_RED);
            if (w < 8) {
                const uint32_t* xp = (const uint32_t*)(g_hn + (size_t)((g & 1) ? t1 : t0) * DM) + w * 32 + t;
                uint32_t xb[8];
#pragma unroll
                for (int i = 0; i < 8; i++) xb[i] = __ldcg(xp + i * 4);
                mbar_wait(mb, 1);
                if (c == 3 && tid == 0 && pass == 0) GT(1431);
                float d[4][4];
#pragma unroll
                for (int kk = 0; kk < 4; kk++) {
                    const int row = w * 64 + kk * 16 + lrow;
#pragma unroll
                    for (int m = 0; m < 4; m++) {
                        uint32_t a[4];
                        ldsm4t(a, sb + (m >> 1) * F_WU + row * 64 + ((((m & 1) * 2 + lsel) ^ ((row >> 1) & 3)) << 4));
                        MMAF(kk == 0, d[m], a, xb[2 * kk], xb[2 * kk + 1]);
                    }
                }
                const float e0 = t == 0 ? d[0][0] : (t == 1 ? d[1][0] : (t == 2 ? d[2][0] : d[3][0])), e1 = t == 0 ? d[0][1] : (t == 1 ? d[1][1] : (t == 2 ? d[2][1] : d[3][1]));
                const float e2 = t == 0 ? d[0][2] : (t == 1 ? d[1][2] : (t == 2 ? d[2][2] : d[3][2])), e3 = t == 0 ? d[0][3] : (t == 1 ? d[1][3] : (t == 2 ? d[2][3] : d[3][3]));
                red[w * 64 + t * 16 + g] = make_float2(e0, e1); red[w * 64 + t * 16 + g + 8] = make_float2(e2, e3);
            }
            bar_sync(0, 384);
            if (tid < 64) {
                const float* r = (const float*)red + tid;
                float gsum = 0.f, usum = 0.f;
#pragma unroll
                for (int kg = 0; kg < 8; kg++) { gsum += r[kg * 128]; usum += r[kg * 128 + 64]; }
                gsum = rbf(gsum); usum = rbf(usum);
                const float sg = rbf(gsum / (1.f + __expf(-gsum)));
                ((bf16*)(smem + F_ACT))[(tid & 1) * 32 + (tid >> 1)] = __float2bfloat16_rn(sg * usum);
            }
            bar_sync(0, 384);
            if (w < 8) {
                const uint32_t* ap = (const uint32_t*)(smem + F_ACT) + (g & 1) * 16 + t;
                float d[4][4];
#pragma unroll
                for (int kk = 0; kk < 2; kk++) {
                    const uint32_t b0 = ap[kk * 8], b1 = ap[kk * 8 + 4];
#pragma unroll
                    for (int m = 0; m < 4; m++) {
                        uint32_t a[4];
                        ldsm4t(a, sb + F_WD + w * 4096 + (kk * 16 + lrow) * 128 + (((m * 2 + lsel) ^ (lane & 7)) << 4));
                        MMAF(kk == 0, d[m], a, b0, b1);
                    }
                }
                const float e0 = t == 0 ? d[0][0] : (t == 1 ? d[1][0] : (t == 2 ? d[2][0] : d[3][0])), e1 = t == 0 ? d[0][1] : (t == 1 ? d[1][1] : (t == 2 ? d[2][1] : d[3][1]));
                const float e2 = t == 0 ? d[0][2] : (t == 1 ? d[1][2] : (t == 2 ? d[2][2] : d[3][2])), e3 = t == 0 ? d[0][3] : (t == 1 ? d[1][3] : (t == 2 ? d[2][3] : d[3][3]));
                uint4* yp = &g_yp[pass][c][w * 64 + t * 16 + g];
                stg4(yp, make_uint4(FU(e0), ytag, FU(e1), ytag)); stg4(yp + 8, make_uint4(FU(e2), ytag, FU(e3), ytag));
            }
            if (c == 3 && tid == 0 && pass == 0) GT(1432);
        } else {
            const int j = tid & 63, part = tid >> 6, col = (c - NWK) * 64 + j;
            const int tok = part ? t1 : t0, old = part ? p1 : p0;
            float hv = 0.f, nv = 0.f;
            if (part < 2) {
                hv = __bfloat162float(__ldcg(g_h + (size_t)tok * DM + col)); nv = __bfloat162float(__ldcg(g_hn + (size_t)tok * DM + col));
                if (old >= 0 && old != t0 && old != t1)
                    out[(size_t)old * DM + col] = __float2bfloat16_rn(__bfloat162float(__ldcg(g_h + (size_t)old * DM + col)) + __bfloat162float(__ldcg(g_hn + (size_t)old * DM + col)));
            }
            float s0 = 0.f, s1 = 0.f;
            uint4 v[10]; uint32_t n = 0;
            bool ok;
#pragma unroll 1
            do {
                ok = true;
#pragma unroll
                for (int i = 0; i < 10; i++) {
                    const int src = part + 6 * i;
                    v[i] = src < NWK ? ldg_rlx4((const uint32_t*)&g_yp[pass][src][col]) : make_uint4(0, ytag, 0, ytag);
                }
#pragma unroll
                for (int i = 0; i < 10; i++) ok = ok && v[i].y == ytag && v[i].w == ytag;
                if (!ok) __nanosleep(100);
                if (++n > SPIN_LIMIT) { ABORT(7); break; }
            } while (!ok);
#pragma unroll
            for (int i = 0; i < 10; i++) { s0 += __uint_as_float(v[i].x); s1 += __uint_as_float(v[i].z); }
            float2* red = (float2*)(smem + F_RED);
            red[part * 64 + j] = make_float2(s0, s1);
            bar_sync(0, 384);
            if (part < 2) {
                float y = 0.f;
#pragma unroll
                for (int i = 0; i < 6; i++) y += ((const float*)red)[(i * 64 + j) * 2 + part];
                const float rs = rbf(1.f / (1.f + __expf(-((float*)(smem + F_SEL))[2 + part])));
                out[(size_t)tok * DM + col] = __float2bfloat16_rn(hv + rbf(nv + rbf(rbf(y) * rs)));
            }
            if (tid == 0 && pass == 0 && c == NWK) GT(1434);
        }
        p0 = t0; p1 = t1;
        if (c == 3 && tid == 0 && pass == 0) GT(1433);
        bar_sync(0, 384);
    }
}

__device__ __forceinline__ void g_consumer(uint32_t sb_, int g_, int wg_, uint32_t epoch) {
    const uint32_t sb = uni(sb_);
    const int g = uni(g_), wg = uni(wg_), wq = uni((threadIdx.x >> 5) & 3);
    const uint32_t l0 = opaque((threadIdx.x & 31) == 0);
    const uint32_t bar = sb + G_BAR, buf = sb + G_BUF + wg * 32768;
    const int lane = threadIdx.x & 31;
    float acc[64];
    if (wg == 1) bar_arrive(3, 256);
    const int n1 = g < 32 ? HSPLIT / 2 : NT - HSPLIT / 2;
#pragma unroll 1
    for (int i = 0; i < n1; i++) {
        gemm_tile<4>(acc, sb, wg, i, wg, true, l0, []() {});
        if (threadIdx.x == 0 && i == 0) GT((64 + g) * 8 + 1);
        if (threadIdx.x == 128 && i == 3) GT((64 + g) * 8 + 2);
        if (i > 0) mbar_wait_p(bar + 8 * (GB_FREE + wg), (i - 1) & 1);
        stage_bf16(acc, buf, 1.f, 1.f);
        asm volatile("fence.proxy.async.shared::cta;" ::: "memory");
        mbar_arrive(bar + 8 * (GB_STG + wg));
    }
    if (threadIdx.x == 128) GT((64 + g) * 8 + 3);
    if (g < 32) {
#pragma unroll 1
        for (int i = 0; i < NT / 2; i++) {
            const int tile = 2 * i + wg;
            const uint2 rec = ldg_rlx2(&g_f.rec[g][0]);
            uint4 km[4], vm[4];
            gemm_tile<4>(acc, sb, tile, i, wg, tile != NT - 1, l0, [&]() {
                const uint32_t seg = tile * 2 + (wq >> 1);
                const uint32_t* kvf = &g_KVf[seg][g][lane * 4];
                const bool early = (rec.x >> 8) == epoch && (rec.y >> 8) == epoch && (rec.x & 255) > seg && (rec.y & 255) > seg;
#pragma unroll
                for (int j = 0; j < 4; j++) { km[j] = ldg_rlx4_if(kvf + j * 128, early); vm[j] = ldg_rlx4_if(kvf + 512 + j * 128, early); }
            });
            if (threadIdx.x == 0 && i == 0) GT((64 + g) * 8 + 4);
            if (threadIdx.x == 128 && i == 3) GT((64 + g) * 8 + 5);
            if (g == 5 && (threadIdx.x & 127) == 0 && tile < 6) GT(1750 + tile * 8 + 1);
            attention_tile(acc, sb, tile, g, wg, wq, l0, epoch, km, vm);
            if (g == 5 && (threadIdx.x & 127) == 0 && tile < 6) GT(1750 + tile * 8 + 6);
        }
    } else {
#pragma unroll 1
        for (int i = 0; i < NT / 2; i++) {
            const int tile = 2 * i + wg;
            gemm_tile<NS3>(acc, sb, tile, i, wg, tile != NT - 1, l0, []() {});
            if (threadIdx.x == 0 && i == 0) GT((64 + g) * 8 + 4);
            if (threadIdx.x == 128 && i == 3) GT((64 + g) * 8 + 5);
            mbar_wait_p(bar + 8 * (GB_FREE + wg), (i - 1 + PO) & 1);
            store_perm(acc, g_P + (size_t)(((g - 32) >> 2) * SQ + tile * 64 + wq * 16 + (lane >> 2)) * DM + ((g - 32) & 3) * 128 + (lane & 3) * 8, DM, 1.f, 1.f, 0xffffffffu);
            mbar_arrive(bar + 8 * (GB_STG + wg));
        }
    }
}

__device__ __forceinline__ void load_w(uint32_t sb, const CUtensorMap* tm, int col, int k) {
    tma2d_h(sb + G_W + k * 16384, tm, col, k * 128, sb + G_BAR + 8 * (GB_FULL + k), pol_ef(5));
    tma2d_h(sb + G_W + 65536 + k * 16384, tm, col + 64, k * 128, sb + G_BAR + 8 * (GB_FULL + k), pol_ef(5));
}

__device__ __forceinline__ void rbf2(float& a, float& b) { uint32_t w = pack2(a, b); a = bf_lo(w); b = bf_hi(w); }
__device__ __forceinline__ void warp_sum2(float& a, float& b) {
#pragma unroll
    for (int o = 16; o; o >>= 1) { float c = __shfl_xor_sync(0xffffffffu, a, o), d = __shfl_xor_sync(0xffffffffu, b, o); a += c; b += d; }
}
__device__ __forceinline__ float sum16(const float* v) {
    return (((v[0] + v[1]) + (v[2] + v[3])) + ((v[4] + v[5]) + (v[6] + v[7]))) + (((v[8] + v[9]) + (v[10] + v[11])) + ((v[12] + v[13]) + (v[14] + v[15])));
}
__device__ __forceinline__ void ln_row2(float* v, float* u) {
    float sv = sum16(v), su = sum16(u);
    warp_sum2(sv, su);
    const float mv = sv * (1.f / DM), mu = su * (1.f / DM);
    float qv = 0.f, qu = 0.f, qv2 = 0.f, qu2 = 0.f;
#pragma unroll
    for (int i = 0; i < 16; i += 2) {
        float d0 = v[i] - mv, d1 = v[i + 1] - mv, e0 = u[i] - mu, e1 = u[i + 1] - mu;
        qv = fmaf(d0, d0, qv); qv2 = fmaf(d1, d1, qv2); qu = fmaf(e0, e0, qu); qu2 = fmaf(e1, e1, qu2);
    }
    qv += qv2; qu += qu2;
    warp_sum2(qv, qu);
    const float rv = rbf(mv), ru = rbf(mu);
    const float iv = __frcp_rn(rbf(sqrtf(rbf(rbf(qv * (1.f / DM)) + 1e-5f)))), iu = __frcp_rn(rbf(sqrtf(rbf(rbf(qu * (1.f / DM)) + 1e-5f))));
#pragma unroll
    for (int i = 0; i < 16; i += 2) {
        float a = v[i] - rv, b = v[i + 1] - rv, c = u[i] - ru, d = u[i + 1] - ru;
        rbf2(a, b); rbf2(c, d);
        a *= iv; b *= iv; c *= iu; d *= iu;
        rbf2(a, b); rbf2(c, d);
        v[i] = a; v[i + 1] = b; u[i] = c; u[i + 1] = d;
    }
}

__device__ __forceinline__ void ln_row1(float* v) {
    const float pv = __shfl_sync(0xffffffffu, v[0], 0);
    float sv = 0.f, sv2 = 0.f, qv = 0.f, qv2 = 0.f;
#pragma unroll
    for (int i = 0; i < 16; i += 2) { const float d0 = v[i] - pv, d1 = v[i + 1] - pv; sv += d0; sv2 += d1; qv = fmaf(d0, d0, qv); qv2 = fmaf(d1, d1, qv2); }
    sv += sv2; qv += qv2;
    warp_sum2(sv, qv);
    const float dm = sv * (1.f / DM), mv = pv + dm;
    qv = fmaxf(fmaf(-dm, sv, qv), 0.f);
    const float rv = rbf(mv);
    float sq, iv;
    asm("sqrt.approx.f32 %0, %1;" : "=f"(sq) : "f"(rbf(rbf(qv * (1.f / DM)) + 1e-5f)));
    asm("rcp.approx.f32 %0, %1;" : "=f"(iv) : "f"(rbf(sq)));
#pragma unroll
    for (int i = 0; i < 16; i += 2) {
        float a = v[i] - rv, b = v[i + 1] - rv;
        rbf2(a, b);
        a *= iv; b *= iv;
        rbf2(a, b);
        v[i] = a; v[i + 1] = b;
    }
}
constexpr int FSPLIT = 28;
__device__ __forceinline__ int fin_row(int id, int i) {
    if (id < 64) { const int tile = i < FSPLIT / 2 ? 2 * i : i + FSPLIT / 2; return tile < NT ? tile * 64 + id : -1; }
    const int j = id - 64 + i * 48;
    return j < FSPLIT * 32 ? (j >> 6) * 128 + 64 + (j & 63) : -1;
}
__device__ __forceinline__ void finalizer(int id, const bf16* __restrict__ x, const bf16* __restrict__ wr, bf16* __restrict__ out, uint32_t epoch, const bf16* pf) {
    const int lane = threadIdx.x & 31;
    float b0 = -INFINITY, b1 = -INFINITY; int i0 = 0x7fffffff, i1 = 0x7fffffff;
    const uint32_t tag = (epoch & 0xfffffu) << 12;
    uint32_t fl = ~epoch;
    int row = fin_row(id, 0);
    const uint4 ra = *(const uint4*)(wr + lane * 8), rb = *(const uint4*)(wr + 256 + lane * 8);
    uint4 xa = *(const uint4*)(x + (size_t)row * DM + lane * 8), xb = *(const uint4*)(x + (size_t)row * DM + lane * 8 + 256);
#pragma unroll 1
    for (int it = 0; row >= 0; it++) {
        const int tile = row >> 6, nxt = fin_row(id, it + 1);
        const size_t o0 = (size_t)row * DM + lane * 8;
        uint32_t n = 0;
#pragma unroll 1
        while (!__all_sync(0xffffffffu, fl == epoch)) {
            if (n && tile < NT - 1) __nanosleep(it ? 64 : 1000);
            fl = ldg_rlx(&g_f.p[tile][lane]);
            if (++n > SPIN_LIMIT) { ABORT(12); break; }
        }
        if (tile == NT - 1 && id == 63 && lane == 0) GT(1438);
        if ((id == 63 || id == 3 || id == 70) && lane == 0) GT(1800 + (id == 3) * 32 + tile);
        if (PFF && pf && lane == 0 && (unsigned)(it - PFF) < 7u)
            asm volatile("cp.async.bulk.prefetch.L2.global [%0], %1;" :: "l"(pf + (size_t)((id & 15) * 7 + it - PFF) * 8192), "r"(16384) : "memory");
        float v[16];
        {
            uint4 pa[8][2];
            n = 0;
#pragma unroll 1
            while (true) {
#pragma unroll
                for (int k = 0; k < 8; k++) {
                    pa[k][0] = ldg4_h(g_P + (size_t)k * SQ * DM + o0, pol_ef(2));
                    pa[k][1] = ldg4_h(g_P + (size_t)k * SQ * DM + o0 + 256, pol_ef(2));
                }
                fl = ldg_rlx(&g_f.p[max(nxt, 0) >> 6][lane]);
                uint32_t mn = 0xffffffffu;
#pragma unroll
                for (int k = 0; k < 8; k++) mn = min(min(min(mn, min(pa[k][0].x, pa[k][0].y)), min(pa[k][0].z, pa[k][0].w)), min(min(pa[k][1].x, pa[k][1].y), min(pa[k][1].z, pa[k][1].w)));
                if (__all_sync(0xffffffffu, mn != 0)) break;
                if (++n > SPIN_LIMIT) { ABORT(11); break; }
            }
            if (tile == NT - 1 && id == 63 && lane == 0) GT(1443);
#pragma unroll
            for (int j = 0; j < 2; j++) {
#pragma unroll
                for (int i = 0; i < 4; i++) {
                    uint32_t w[8];
#pragma unroll
                    for (int k = 0; k < 8; k++) w[k] = ~(i == 0 ? pa[k][j].x : (i == 1 ? pa[k][j].y : (i == 2 ? pa[k][j].z : pa[k][j].w)));
                    v[j * 8 + 2 * i] = ((bf_lo(w[0]) + bf_lo(w[1])) + (bf_lo(w[2]) + bf_lo(w[3]))) + ((bf_lo(w[4]) + bf_lo(w[5])) + (bf_lo(w[6]) + bf_lo(w[7])));
                    v[j * 8 + 2 * i + 1] = ((bf_hi(w[0]) + bf_hi(w[1])) + (bf_hi(w[2]) + bf_hi(w[3]))) + ((bf_hi(w[4]) + bf_hi(w[5])) + (bf_hi(w[6]) + bf_hi(w[7])));
                }
            }
        }
        uint32_t hw[8];
        {
            const uint32_t xw[8] = {xa.x, xa.y, xa.z, xa.w, xb.x, xb.y, xb.z, xb.w};
            uint32_t aw[8];
#pragma unroll
            for (int i = 0; i < 8; i++) aw[i] = pack2(v[2 * i], v[2 * i + 1]);
#pragma unroll
            for (int d = 1; d <= 2; d++) {
                const bool up = lane & d;
#pragma unroll
                for (int i = 0; i < 8; i++) {
                    if (!(i & d)) {
                        const uint32_t r = __shfl_xor_sync(0xffffffffu, up ? aw[i] : aw[i | d], d);
                        if (up) aw[i] = r; else aw[i | d] = r;
                    }
                }
            }
#pragma unroll
            for (int i = 0; i < 8; i++) {
                hw[i] = pack2(bf_lo(aw[i]) + bf_lo(xw[i]), bf_hi(aw[i]) + bf_hi(xw[i]));
                v[2 * i] = bf_lo(hw[i]); v[2 * i + 1] = bf_hi(hw[i]);
            }
        }
        xa = *(const uint4*)(x + (size_t)max(nxt, 0) * DM + lane * 8); xb = *(const uint4*)(x + (size_t)max(nxt, 0) * DM + lane * 8 + 256);
        ln_row1(v);
        float r0 = 0.f, r1 = 0.f;
        {
            const uint32_t ww[8] = {ra.x, ra.y, ra.z, ra.w, rb.x, rb.y, rb.z, rb.w};
#pragma unroll
            for (int i = 0; i < 8; i++) { r0 = fmaf(v[2 * i], bf_lo(ww[i]), r0); r1 = fmaf(v[2 * i + 1], bf_hi(ww[i]), r1); }
        }
        r0 += r1;
#pragma unroll
        for (int o = 16; o; o >>= 1) r0 += __shfl_xor_sync(0xffffffffu, r0, o);
        r0 = rbf(r0);
        if (cand_better(r0, row, b0, i0)) { b1 = b0; i1 = i0; b0 = r0; i0 = row; }
        else if (cand_better(r0, row, b1, i1)) { b1 = r0; i1 = row; }
        if (tile == NT - 1 && id == 63 && lane == 0) GT(1439);
        const bool keep = i0 == row || i1 == row || i1 >= SQ || row == SQ - 1;
        const bool last = nxt < 0, spec = tile < SPEC_TILES && (last || (nxt >> 6) >= SPEC_TILES);
        const bool pub = (lane == 0 && spec) || (lane == 1 && last);
        if (pub)
            asm volatile("st.relaxed.gpu.global.v4.b32 [%0], {%1,%2,%3,%4};" :: "l"(&g_f.cand[lane][id]),
                         "r"(FU(b0)), "r"(tag | (uint32_t)min(i0, 4095)), "r"(FU(b1)), "r"(tag | (uint32_t)min(i1, 4095)) : "memory");
#pragma unroll
        for (int j = 0; j < 2; j++) {
            const uint32_t* hh = hw + j * 4; const float* nn = v + j * 8;
            stg4_h(out + o0 + j * 256, make_uint4(pack2(bf_lo(hh[0]) + nn[0], bf_hi(hh[0]) + nn[1]), pack2(bf_lo(hh[1]) + nn[2], bf_hi(hh[1]) + nn[3]),
                                                  pack2(bf_lo(hh[2]) + nn[4], bf_hi(hh[2]) + nn[5]), pack2(bf_lo(hh[3]) + nn[6], bf_hi(hh[3]) + nn[7])), pol_ef(4));
            if (keep) {
                *(uint4*)(g_h + o0 + j * 256) = make_uint4(hh[0], hh[1], hh[2], hh[3]);
                *(uint4*)(g_hn + o0 + j * 256) = make_uint4(pack2(nn[0], nn[1]), pack2(nn[2], nn[3]), pack2(nn[4], nn[5]), pack2(nn[6], nn[7]));
            }
        }
        if (keep) { __threadfence(); __syncwarp(); }
        if (pub) stg_rlx(&g_f.rows[lane][id], epoch);
        if (tile >= LLT) {
#pragma unroll
            for (int k = 0; k < 8; k++) { stg4(g_P + (size_t)k * SQ * DM + o0, make_uint4(0, 0, 0, 0)); stg4(g_P + (size_t)k * SQ * DM + o0 + 256, make_uint4(0, 0, 0, 0)); }
        }
        row = nxt;
    }
    if (id == 0 && lane == 0) { g_epoch = epoch; if (epoch == 0xffffffu) { g_ticket[0] = 0; g_ticket[32] = 0; } }
}

__device__ __forceinline__ void g_producer(uint32_t sb, int g, const Maps& maps, uint32_t epoch, const bf16* __restrict__ x, const bf16* __restrict__ wr, bf16* __restrict__ out) {
    const uint32_t bar = sb + G_BAR;
    const int warp = (threadIdx.x >> 5) - 8;
    if (threadIdx.x == 256 && g == 5) GT(1410);
    if (threadIdx.x == 256 && g == 5) GT(1411);
    if (warp == 3) {
        wait_eq4(&g_f.xn[(threadIdx.x & 31) * 4], epoch, 13);
        __syncwarp();
        if ((threadIdx.x & 31) == 0) mbar_arrive(bar + 8 * GB_XN);
        finalizer(g, x, wr, out, epoch, nullptr);
        if (g == 63 && (threadIdx.x & 31) == 0) GT(128 * 8 + 6);
    }
    if ((threadIdx.x & 31) != 0) return;
    if (threadIdx.x == 256 && g == 5) GT(1412);
    if (warp == 0) {
        wait_eq4(&g_f.xn[0], epoch, 13);
        const int rk = g & 1;
        const int m1 = g < 32 ? HSPLIT : 2 * NT - HSPLIT;
        const int mx = g < 32 ? m1 + NT : m1;
#pragma unroll 1
        for (int it = 0; it < mx; it++) {
            const int tile = g < 32 ? (it < m1 ? it : it - m1) : (it < NT ? it : it - NT + HSPLIT);
            if (it == 1) wait_eq4(&g_f.xn[4], epoch, 13);
            if (it == 2) mbar_wait(bar + 8 * GB_XN, 0);
            const bool nw = it == 0 || it == (g < 32 ? m1 : NT);
#pragma unroll
            for (int k = 0; k < 4; k++) {
                mbar_wait(bar + 8 * (GB_EMPTY + k), (it & 1) ^ 1);
                mbar_expect_tx(bar + 8 * (GB_FULL + k), nw ? 49152 : 16384);
                tma2d_mc(sb + slot_off(k) + rk * 8192, &maps.xn2, (k * 2 + rk) * 64, tile * 64, bar + 8 * (GB_FULL + k));
                if (nw && (it > 0 || k >= 2))
                    load_w(sb, it > 0 && g < 32 ? &maps.wq4 : ((g & 1) ? &maps.wv4 : &maps.wk4), it == 0 ? (g >> 1) * 128 : (g < 32 ? g * 128 : ((g - 32) >> 1) * 128), k);
            }
        }
        if (g >= 32) {
            const int u = g - 32, ks = u >> 2, ns = u & 3;
            int slot = 0, ph = 1;
#pragma unroll 1
            for (int tile = 0; tile < NT; tile++) {
                if (tile > 0) wait_eq4(&g_f.o[tile][ks][0], epoch, 9);
                if (g == 40 && tile == NT - 1) GT(1437);
                if (tile == NT - 1) GT(1690 + g - 32);
#pragma unroll 1
                for (int k = 0; k < 4; k++) {
                    mbar_wait(bar + 8 * (GB_EMPTY + slot), slot < 4 ? ph : ph ^ 1);
                    mbar_expect_tx(bar + 8 * (GB_FULL + slot), tile == 0 ? 49152 : 16384);
                    if (tile == 0) {
#pragma unroll
                        for (int nh = 0; nh < 2; nh++)
                            asm volatile("cp.async.bulk.tensor.5d.shared::cluster.global.mbarrier::complete_tx::bytes [%0], [%1, {%3, %4, %4, %4, %5}], [%2];"
                                :: "r"(sb + G_W + nh * 65536 + k * 16384), "l"((uint64_t)&maps.wo2), "r"(bar + 8 * (GB_FULL + k)), "r"(ns * 128 + nh * 64), "r"(0), "r"(ks * 16 + k * 4) : "memory");
                        if (k == 0) wait_eq4(&g_f.o[0][ks][0], epoch, 9);
                    }
                    tma2d_mc_h(sb + slot_off(slot) + rk * 8192, &maps.ox2, (ks * 8 + k * 2 + rk) * 64, tile * 64, bar + 8 * (GB_FULL + slot), pol_ef(1));
                    if (++slot == NS3) { slot = 0; ph ^= 1; }
                }
            }
        }
    } else if (warp < 3) {
        const int wg = warp - 1;
        const uint32_t buf = sb + G_BUF + wg * 32768;
        const CUtensorMap* tkv = (g & 1) ? &maps.vx3 : &maps.kx3;
        const int n1 = g < 32 ? HSPLIT / 2 : NT - HSPLIT / 2;
#pragma unroll 1
        for (int i = 0; i < n1; i++) {
            const int tile = (i < NT / 2 ? 2 * i : 2 * i - NT + HSPLIT) + wg, hd = (i < NT / 2 ? g : g - 32) >> 1;
            mbar_wait(bar + 8 * (GB_STG + wg), i & 1);
            tma_store3d(tkv, buf, tile * 64, hd * 2);
            asm volatile("cp.async.bulk.commit_group;" ::: "memory");
            asm volatile("cp.async.bulk.wait_group.read 0;" ::: "memory");
            mbar_arrive(bar + 8 * (GB_FREE + wg));
            asm volatile("cp.async.bulk.wait_group 0;" ::: "memory");
            PUBLISH(&g_f.kv[tile][hd][g & 1], epoch);
        }
        if (wg == 0) mbar_arrive(bar + 8 * GB_T1D);
        if (g >= 32) for (int i = 0; i < 4; i++) mbar_arrive2_if(bar + 8 * (GB_EMPTY + 4 + wg), 1);
        if (g < 32 && wg == 1) {
            mbar_wait(bar + 8 * GB_T1D, 0);
#pragma unroll 1
            for (int tile = 0; tile < NT; tile++) {
                wait_eq2(&g_f.kv[tile][g][0], epoch, 10);
                if (tile > 0) mbar_wait(bar + 8 * GB_KVF, (tile - 1) & 1);
                mbar_expect_tx(bar + 8 * (GB_KV + (tile & 1)), 16384);
                tma3d_h(sb + G_BUF, &maps.kx3, tile * 64, g * 2, bar + 8 * (GB_KV + (tile & 1)), pol_ef(0));
                if (tile > 0) mbar_wait(bar + 8 * GB_VF, (tile - 1) & 1);
                mbar_expect_tx(bar + 8 * (GB_VV + (tile & 1)), 16384);
                tma3d_h(sb + G_BUF + 32768, &maps.vx3, tile * 64, g * 2, bar + 8 * (GB_VV + (tile & 1)), pol_ef(0));
                if (PFK && tile + PFK < NT) {
                    const uint2 v = ldg_rlx2(&g_f.kv[tile + PFK][g][0]);
                    if (v.x == epoch && v.y == epoch) { tma_pf3d(&maps.kx3, (tile + PFK) * 64, g * 2); tma_pf3d(&maps.vx3, (tile + PFK) * 64, g * 2); }
                }
            }
        } else {
#pragma unroll 1
            for (int tile = g < 32 ? 0 : wg; tile < NT; tile += g < 32 ? 1 : 2) {
                mbar_wait(bar + 8 * (GB_STG + (tile & 1)), ((tile >> 1) + PO) & 1);
                mbar_arrive(bar + 8 * (GB_FREE + (tile & 1)));
                if (g < 32 || tile < LLT) PUBLISH(g < 32 ? &g_f.o[tile][g >> 2][g & 3] : &g_f.p[tile][g - 32], epoch);
                else stg_rlx(&g_f.p[tile][g - 32], epoch);
                if (g == 3 && tile == NT - 1) GT(1436);
                if (g == 3) GT(1896 + tile);
                if (g < 32 && tile == NT - 1) GT(1610 + g);
                if (g == 40 && tile == NT - 1) GT(1435);
                if (g == 40) GT(1864 + tile);
                if (g >= 32 && tile == NT - 1) GT(1650 + g - 32);
            }
        }
    }
}

struct WPtr { const bf16 *q, *k, *v, *o, *g, *u; };
__device__ __forceinline__ int startup(uint8_t* smem, const bf16* __restrict__ x, const Maps& maps, uint32_t& epoch, const WPtr& pw) {
    const int tid = threadIdx.x, lane = tid & 31, w = tid >> 5, cta = blockIdx.x;
    volatile uint32_t* sh = (volatile uint32_t*)(smem + SH_OFF);
    if (cta == 4 && tid == 0) GT(1399);
    epoch = (ldg_rlx(&g_epoch) + 1) & 0x00ffffffu;
    if (w < 4) {
        if (!(cta & 1)) {
            uint32_t* pp = (uint32_t*)(xpage() + ((XR3 ^ 0x3000u) ^ ((w == 1 || w == 2) ? 0x1000u : 0u) ^ ((w & 2) << 13))) + (cta >> 1) * 8;
            if (lane < 8) stg_rlx(pp + lane, 0u);
            __syncwarp();
            if (lane == 0) {
                uint32_t best = 0xffffffffu, a = 0;
#pragma unroll 1
                for (int r = 0; r < NPROBE; r++) {
                    uint32_t t0 = clk32();
                    asm volatile("atom.relaxed.gpu.global.add.u32 %0, [%1], %2;" : "=r"(a) : "l"(pp), "r"(a + 1) : "memory");
                    if (a == 0x7fffffffu) ABORT(15);
                    uint32_t t1 = clk32();
                    if (r > 0) best = min(best, t1 - t0);
                    else if (w == 0) {
                        asm volatile("red.relaxed.gpu.global.max.u32 [%0], %1;" :: "l"(&g_ticket[0]), "r"(epoch << 8) : "memory");
                        asm volatile("red.relaxed.gpu.global.max.u32 [%0], %1;" :: "l"(&g_ticket[32]), "r"(epoch << 8) : "memory");
                    }
                }
                sh[w] = best;
            }
        }
        if (!(cta & 1)) bar_sync(1, 128);
        if (cta == 4 && tid == 0) GT(1400);
        if (w == 0) {
            if (lane == 0) {
                uint32_t rp;
                if (!(cta & 1)) {
                    uint32_t a = sh[0], b = sh[1], c = sh[2], d = sh[3];
                    uint32_t mid = (min(min(a, b), min(c, d)) + max(max(a, b), max(c, d))) >> 1;
                    const int dd = (int)min(a, d) - (int)min(b, c);
                    uint32_t cls = abs(dd) > 60 ? dd > 0 : a > mid;
                    uint32_t t = atomicAdd(&g_ticket[cls * 32], 1u) & 255;
                    if (t >= (cls ? 34u : 32u)) { cls ^= 1; t = atomicAdd(&g_ticket[cls * 32], 1u) & 255; }
                    rp = min(cls ? 32 + t : t, 65u);
                    stg_rlx(&g_table[(cta >> 1) * 8], (epoch << 8) | rp);
                } else {
                    uint32_t v, n = 0;
#pragma unroll 1
                    while (((v = ldg_rlx(&g_table[(cta >> 1) * 8])) >> 8) != epoch) { if (++n > SPIN_LIMIT) { ABORT(14); break; } }
                    rp = v & 255;
                }
                const int role = rp * 2 + (cta & 1);
                sh[8] = role; sh[9] = epoch;
                while (sh[10] != epoch + 1 && cta < NWAITLN) {}
                if (role < 64) rec_first_loads(smem_u32(smem), role, maps);
                else if (role < 128) for (int k = 0; k < 2; k++) load_w(smem_u32(smem), (role & 1) ? &maps.wv4 : &maps.wk4, ((role - 64) >> 1) * 128, k);
                if (cta == 4) GT(1401);
            }
        }
    } else if (cta < 128) {
        uint4 u[2][2];
        const int row0 = cta * 16 + (w - 4) * 2;
#pragma unroll
        for (int r = 0; r < 2; r++)
#pragma unroll
            for (int j = 0; j < 2; j++) u[r][j] = *(const uint4*)(x + (size_t)(row0 + r) * DM + j * 256 + lane * 8);
        if (cta < 48) {
            const uint32_t b = cta >> 3, off = (b >= 4 ? 0x8000u + (b & 1) * 0x4000u : ((b & 1) ? 0x3000u : 0u) + ((b & 2) << 13)) ^ aslot(cta & 7);
            *(uint4*)(xpage() + off + (tid - 128) * 16) = make_uint4(0, 0, 0, 0);
        }
        float v[2][16];
#pragma unroll
        for (int r = 0; r < 2; r++)
#pragma unroll
            for (int j = 0; j < 2; j++) {
                uint32_t ww[4] = {u[r][j].x, u[r][j].y, u[r][j].z, u[r][j].w};
#pragma unroll
                for (int i = 0; i < 4; i++) { v[r][j * 8 + 2 * i] = bf_lo(ww[i]); v[r][j * 8 + 2 * i + 1] = bf_hi(ww[i]); }
            }
        ln_row2(v[0], v[1]);
#pragma unroll
        for (int r = 0; r < 2; r++)
#pragma unroll
            for (int j = 0; j < 2; j++)
                *(uint4*)(g_xn + (size_t)(row0 + r) * DM + j * 256 + lane * 8) =
                    make_uint4(pack2(v[r][j * 8], v[r][j * 8 + 1]), pack2(v[r][j * 8 + 2], v[r][j * 8 + 3]), pack2(v[r][j * 8 + 4], v[r][j * 8 + 5]), pack2(v[r][j * 8 + 6], v[r][j * 8 + 7]));
        bar_sync(2, 256);
        if (tid == 160 && cta < NWAITLN) { st_rel(&g_f.xn[cta], epoch); sh[10] = epoch + 1; }
        if (cta == 4 && tid == 160) GT(1403);
        __syncwarp();
    }
    if (cta == 4 && tid == 128) GT(1402);
    __syncthreads();
    if (tid == 160 && cta >= NWAITLN && cta < 128) st_rel(&g_f.xn[cta], epoch);
    __syncwarp();
    const int role = sh[8];
    return role;
}

__global__ void __cluster_dims__(2, 1, 1) __launch_bounds__(384, 1)
main_kernel(const __grid_constant__ Maps maps, const bf16* __restrict__ x, const bf16* __restrict__ mem0, const bf16* __restrict__ wr,
            const bf16* __restrict__ wd, bf16* __restrict__ out, const WPtr pw) {
    extern __shared__ __align__(1024) uint8_t smem[];
    const uint32_t sb = smem_u32(smem);
    if (threadIdx.x == 0) {
        for (int i = 0; i < MB_N; i++) mbar_init(sb + R_BAR + 8 * i, i == MB_V ? 4 : 1);
        for (int i = 0; i < GB_N; i++)
            mbar_init(sb + G_BAR + 8 * i, i >= GB_EMPTY && i < GB_KV ? 8 : (i >= GB_KVF ? 4 : (i >= GB_STG && i < GB_FREE ? 128 : 1)));
        asm volatile("fence.mbarrier_init.release.cluster;" ::: "memory");
    }
    __syncwarp();
    asm volatile("barrier.cluster.arrive.relaxed.aligned;" ::: "memory");
    if (threadIdx.x >= 352 && threadIdx.x < 352 + (int)(sizeof(Maps) / sizeof(CUtensorMap)))
        asm volatile("prefetch.tensormap [%0];" :: "l"((const CUtensorMap*)&maps + (threadIdx.x - 352)) : "memory");
    uint32_t epoch;
    asm volatile("fence.proxy.async.shared::cta;" ::: "memory");
    const int role = uni(startup(smem, x, maps, epoch, pw));
    asm volatile("barrier.cluster.wait.aligned;" ::: "memory");
    const int wg = uni(threadIdx.x >> 7);
    if (role < 64) {
#define SETREG(n) do { if ((n) < 168) asm volatile("setmaxnreg.dec.sync.aligned.u32 %0;" :: "n"(n)); if ((n) > 168) asm volatile("setmaxnreg.inc.sync.aligned.u32 %0;" :: "n"(n)); } while (0)
#define RESREG(n) do { if ((n) < 168) asm volatile("setmaxnreg.inc.sync.aligned.u32 168;"); if ((n) > 168) asm volatile("setmaxnreg.dec.sync.aligned.u32 168;"); } while (0)
        if (wg == WGA) {
            SETREG(RGA);
            rec_a(sb, role, mem0, epoch);
            RESREG(RGA);
        } else if (wg == WGB) {
            SETREG(RGB);
            rec_b(sb, role, epoch);
            RESREG(RGB);
        } else {
            SETREG(RGC);
            rec_c(sb, role, mem0, maps, epoch);
            RESREG(RGC);
        }
        ffn_phase(maps, out);
        if (threadIdx.x == 0) GT(((volatile int*)(smem + SH_OFF))[8] * 8 + 6);
    } else if (role < 128) {
        if (wg < 2) {
            asm volatile("setmaxnreg.inc.sync.aligned.u32 184;");
            g_consumer(sb, role - 64, wg, epoch);
            if (threadIdx.x == 128) GT(role * 8 + 6);
        } else {
            asm volatile("setmaxnreg.dec.sync.aligned.u32 136;");
            g_producer(sb, role - 64, maps, epoch, x, wr, out);
        }
    } else {
        const int id = (threadIdx.x >> 5) * 4 + role - 128;
        finalizer(64 + id, x, wr, out, epoch, id < 16 ? pw.g : (id < 32 ? pw.u : wd));

    }
}

typedef CUresult (*EncodeFn)(CUtensorMap*, CUtensorMapDataType, cuuint32_t, void*, const cuuint64_t*, const cuuint64_t*, const cuuint32_t*, const cuuint32_t*,
                             CUtensorMapInterleave, CUtensorMapSwizzle, CUtensorMapL2promotion, CUtensorMapFloatOOBfill);
static void make_map3(EncodeFn fn, CUtensorMap* m, const void* ptr, uint64_t cols, uint64_t rows) {
    cuuint64_t dims[3] = {64, rows, cols / 64};
    cuuint64_t strides[2] = {cols * 2, 128};
    cuuint32_t box[3] = {64, 64, 2};
    cuuint32_t es[3] = {1, 1, 1};
    fn(m, CU_TENSOR_MAP_DATA_TYPE_BFLOAT16, 3, (void*)ptr, dims, strides, box, es, CU_TENSOR_MAP_INTERLEAVE_NONE, CU_TENSOR_MAP_SWIZZLE_128B,
       CU_TENSOR_MAP_L2_PROMOTION_L2_256B, CU_TENSOR_MAP_FLOAT_OOB_FILL_NONE);
}
static void make_map(EncodeFn fn, CUtensorMap* m, const void* ptr, uint64_t cols, uint64_t rows, uint32_t bcols, uint32_t brows,
                     bool f32 = false, CUtensorMapSwizzle sw = CU_TENSOR_MAP_SWIZZLE_128B) {
    cuuint64_t dims[2] = {cols, rows};
    cuuint64_t strides[1] = {cols * (f32 ? 4 : 2)};
    cuuint32_t box[2] = {bcols, brows};
    cuuint32_t es[2] = {1, 1};
    fn(m, f32 ? CU_TENSOR_MAP_DATA_TYPE_FLOAT32 : CU_TENSOR_MAP_DATA_TYPE_BFLOAT16, 2, (void*)ptr, dims, strides, box, es, CU_TENSOR_MAP_INTERLEAVE_NONE, sw,
       CU_TENSOR_MAP_L2_PROMOTION_L2_256B, CU_TENSOR_MAP_FLOAT_OOB_FILL_NONE);
}

extern "C" void kernel_launch(void* const* d_in, const int* in_sizes, int n_in, void* d_out, int out_size) {
    const bf16* x = (const bf16*)d_in[0];
    const bf16* mem0 = (const bf16*)d_in[1];
    const bf16* Wq = (const bf16*)d_in[2];
    const bf16* Wk = (const bf16*)d_in[3];
    const bf16* Wv = (const bf16*)d_in[4];
    const bf16* Wo = (const bf16*)d_in[5];
    const bf16* wr = (const bf16*)d_in[8];
    const bf16* wg = (const bf16*)d_in[9];
    const bf16* wu = (const bf16*)d_in[10];
    const bf16* wd = (const bf16*)d_in[11];
    bf16* out = (bf16*)d_out;

    static EncodeFn enc = nullptr;
    static void *pxn, *pK, *pV, *pO, *pacc;
    if (!enc) {
        cudaDriverEntryPointQueryResult qr;
        void* fn = nullptr;
        cudaGetDriverEntryPoint("cuTensorMapEncodeTiled", &fn, cudaEnableDefault, &qr);
        enc = (EncodeFn)fn;
        cudaGetSymbolAddress(&pxn, g_xn); cudaGetSymbolAddress(&pK, g_K); cudaGetSymbolAddress(&pV, g_V);
        cudaGetSymbolAddress(&pO, g_O); cudaGetSymbolAddress(&pacc, g_P);
        cudaFuncSetAttribute(main_kernel, cudaFuncAttributeMaxDynamicSharedMemorySize, SMEM_TOTAL);
    }
    Maps m;
    make_map(enc, &m.wq, Wq, HD, DM, 64, 256);
    make_map(enc, &m.wk, Wk, HD, DM, 64, 256);
    make_map(enc, &m.wv, Wv, HD, DM, 64, 256);
    make_map(enc, &m.wq4, Wq, HD, DM, 64, 128); make_map(enc, &m.wk4, Wk, HD, DM, 64, 128); make_map(enc, &m.wv4, Wv, HD, DM, 64, 128);
    make_map(enc, &m.wo, Wo, DM, HD, 64, 128);
    {
        cuuint64_t dims[5] = {DM, 2, 4, 4, HD / 32};
        cuuint64_t strides[4] = {DM * 2, 8 * DM * 2, 2 * DM * 2, 32 * DM * 2};
        cuuint32_t box[5] = {64, 2, 4, 4, 4};
        cuuint32_t es[5] = {1, 1, 1, 1, 1};
        enc(&m.wo2, CU_TENSOR_MAP_DATA_TYPE_BFLOAT16, 5, (void*)Wo, dims, strides, box, es, CU_TENSOR_MAP_INTERLEAVE_NONE, CU_TENSOR_MAP_SWIZZLE_128B,
            CU_TENSOR_MAP_L2_PROMOTION_L2_256B, CU_TENSOR_MAP_FLOAT_OOB_FILL_NONE);
    }
    make_map(enc, &m.kx, pK, HD, SQ, 64, 64);
    make_map(enc, &m.ox2, pO, HD, SQ, 64, 64);
    make_map(enc, &m.xn2, pxn, DM, SQ, 64, 64);
    make_map3(enc, &m.kx3, pK, HD, SQ); make_map3(enc, &m.vx3, pV, HD, SQ);
    make_map(enc, &m.wg, wg, FF, DM, 32, 256, false, CU_TENSOR_MAP_SWIZZLE_64B);
    make_map(enc, &m.wu, wu, FF, DM, 32, 256, false, CU_TENSOR_MAP_SWIZZLE_64B);
    make_map(enc, &m.wd, wd, DM, FF, 64, 32);

    cudaStream_t st = cudaStreamPerThread;
    main_kernel<<<NCTA, 384, SMEM_TOTAL, st>>>(m, x, mem0, wr, wd, out, WPtr{Wq, Wk, Wv, Wo, wg, wu});
}
```

```cpp
#include <cuda_runtime.h>
#include <cuda_bf16.h>
#include <cuda.h>
#include <stdint.h>
#include <stddef.h>

typedef __nv_bfloat16 bf16;

constexpr int SQ = 2048, DM = 512, NH = 32, DH = 128, NSEG = 64, HD = 4096, FF = 1792;

constexpr int NT = 32;
#define SPEC_TILES 30
__device__ __align__(1024) bf16 g_xn[SQ * DM];
__device__ __align__(1024) bf16 g_K[SQ * HD];
__device__ __align__(1024) bf16 g_V[SQ * HD];
__device__ __align__(1024) bf16 g_O[SQ * HD];
__device__ __align__(1024) uint32_t g_KVf[NSEG][NH][1024];
__device__ __align__(1024) bf16 g_P[8 * SQ * DM];
__device__ __align__(1024) bf16 g_h[SQ * DM];
__device__ __align__(1024) bf16 g_hn[SQ * DM];
__device__ uint8_t g_xraw[12 << 20];
#define XPG 0
__device__ __forceinline__ uint64_t xpage() { return (((uint64_t)g_xraw + (2 << 20) - 1) & ~(uint64_t)((2 << 20) - 1)) + ((uint64_t)XPG << 21); }
constexpr uint32_t XR3 = (1u << 20) | (1u << 19) | (1u << 12);
__device__ __forceinline__ uint32_t aslot(uint32_t s) { return ((s & 1) << 18) | ((s & 2) << 19) | ((s & 4) * 0xc000u); }
__device__ __forceinline__ uint32_t acc_base(uint32_t W) { return ((W & 2) ? 0x3000u : 0u) + ((W & 4) << 12) + (W & 1) * 2048; }
__device__ __forceinline__ uint32_t ext_base(uint32_t W) { return 0x8000u + ((W & 4) << 12) + (W & 3) * 1024; }
#define XHS 256
#define XSS 32
__device__ __forceinline__ uint32_t zero_off(uint32_t c, uint32_t ln) {
    return ln < 8 ? acc_base(c >> 3) + (c & 7) * 256 + ln * 16 : ext_base(c >> 3) + ((c >> 2) & 1) * XHS + ((c >> 1) & 1) * XSS + (c & 1) * 16;
}
struct Flags {
    uint32_t p[NT][32];
    uint4 cand[2][128];
    uint32_t rows[2][128];
    uint4 norm[64];
    uint32_t pad0[512];
    uint32_t kv[NT][NH][2];
    uint32_t pad1[2048];
    uint32_t o[NT][8][8];
    uint32_t pad2[2048];
    uint32_t rec[NH][32];
    uint32_t xn[128];
};
static_assert(offsetof(Flags, kv) == 0x3000 && offsetof(Flags, o) == 0x7000 && offsetof(Flags, xn) == 0xc000, "flags");
#define FLX 0
#define g_f (*(Flags*)(xpage() + (1u << 19) + FLX))
__device__ __align__(1024) uint4 g_yp[2][FF / 32][DM];
__device__ __align__(256) uint32_t g_ticket[64];
__device__ uint32_t g_epoch;
#define NS3 6
#define HSPLIT 26
#define PFK 0
#define NWAITLN 4
#define WGA 0
#define WGB 1
#define WGC (3 - WGA - WGB)
#define PFF 10
#define FFW 0
#define FFS 200
#define LLT 31
#define HP 3
#define WK0 1
#define RDEL 0
#define NPROBE 3
constexpr int NCTA = 132;
constexpr int NFW = 112;
__device__ uint32_t g_abort;
__device__ long long g_dbg[4096];
#define TR(slot, v)

__device__ __forceinline__ uint32_t smem_u32(const void* p) { return (uint32_t)__cvta_generic_to_shared(p); }
__device__ __forceinline__ void mbar_init(uint32_t a, uint32_t c) { asm volatile("mbarrier.init.shared::cta.b64 [%0], %1;" :: "r"(a), "r"(c) : "memory"); }
__device__ __forceinline__ void mbar_expect_tx(uint32_t a, uint32_t tx) { asm volatile("mbarrier.arrive.expect_tx.shared::cta.b64 _, [%0], %1;" :: "r"(a), "r"(tx) : "memory"); }
__device__ __forceinline__ void mbar_arrive(uint32_t a) { asm volatile("mbarrier.arrive.shared::cta.b64 _, [%0];" :: "r"(a) : "memory"); }
__device__ __forceinline__ void mbar_arrive_if(uint32_t a, uint32_t pred) {
    asm volatile("{\n.reg .pred p;\nsetp.ne.u32 p, %1, 0;\n@p mbarrier.arrive.shared::cta.b64 _, [%0];\n}" :: "r"(a), "r"(pred) : "memory");
}
__device__ __forceinline__ bool mbar_try(uint32_t a, uint32_t ph) {
    uint32_t ok;
    asm volatile("{\n.reg .pred p;\nmbarrier.try_wait.parity.shared::cta.b64 p, [%1], %2;\nselp.u32 %0, 1, 0, p;\n}" : "=r"(ok) : "r"(a), "r"(ph) : "memory");
    return ok != 0;
}
#define SPINLOG 20
constexpr uint32_t SPIN_LIMIT = 1u << SPINLOG;
#define ABORT(code_) atomicCAS(&g_abort, 0u, (code_))
__device__ __forceinline__ void mbar_wait(uint32_t a, uint32_t ph) {
    uint32_t n = 0;
#pragma unroll 1
    while (!mbar_try(a, ph)) { if (++n > SPIN_LIMIT) { ABORT(1); break; } }
}
__device__ __forceinline__ void bar_sync(int id, int n) { asm volatile("bar.sync %0, %1;" :: "r"(id), "r"(n) : "memory"); }
__device__ __forceinline__ void bar_arrive(int id, int n) { asm volatile("bar.arrive %0, %1;" :: "r"(id), "r"(n) : "memory"); }

__device__ __forceinline__ void ldsm4(uint32_t* r, uint32_t a) {
    asm volatile("ldmatrix.sync.aligned.m8n8.x4.shared.b16 {%0,%1,%2,%3}, [%4];" : "=r"(r[0]), "=r"(r[1]), "=r"(r[2]), "=r"(r[3]) : "r"(a) : "memory");
}
__device__ __forceinline__ void ldsm4t(uint32_t* r, uint32_t a) {
    asm volatile("ldmatrix.sync.aligned.m8n8.x4.trans.shared.b16 {%0,%1,%2,%3}, [%4];" : "=r"(r[0]), "=r"(r[1]), "=r"(r[2]), "=r"(r[3]) : "r"(a) : "memory");
}
__device__ __forceinline__ void stsm4t(uint32_t a, uint32_t r0, uint32_t r1, uint32_t r2, uint32_t r3) {
    asm volatile("stmatrix.sync.aligned.m8n8.x4.trans.shared.b16 [%0], {%1,%2,%3,%4};" :: "r"(a), "r"(r0), "r"(r1), "r"(r2), "r"(r3) : "memory");
}
__device__ __forceinline__ void stsm4(uint32_t a, uint32_t r0, uint32_t r1, uint32_t r2, uint32_t r3) {
    asm volatile("stmatrix.sync.aligned.m8n8.x4.shared.b16 [%0], {%1,%2,%3,%4};" :: "r"(a), "r"(r0), "r"(r1), "r"(r2), "r"(r3) : "memory");
}
__device__ __forceinline__ uint32_t movm(uint32_t a) { uint32_t d; asm volatile("movmatrix.sync.aligned.m8n8.trans.b16 %0, %1;" : "=r"(d) : "r"(a)); return d; }
__device__ __forceinline__ void mma16816(float* d, uint32_t a0, uint32_t a1, uint32_t a2, uint32_t a3, uint32_t b0, uint32_t b1) {
    asm volatile("mma.sync.aligned.m16n8k16.row.col.f32.bf16.bf16.f32 {%0,%1,%2,%3}, {%4,%5,%6,%7}, {%8,%9}, {%0,%1,%2,%3};"
        : "+f"(d[0]), "+f"(d[1]), "+f"(d[2]), "+f"(d[3]) : "r"(a0), "r"(a1), "r"(a2), "r"(a3), "r"(b0), "r"(b1));
}
__device__ __forceinline__ void mma1688(float* d, uint32_t a0, uint32_t a1, uint32_t b0) {
    asm volatile("mma.sync.aligned.m16n8k8.row.col.f32.bf16.bf16.f32 {%0,%1,%2,%3}, {%4,%5}, {%6}, {%0,%1,%2,%3};"
        : "+f"(d[0]), "+f"(d[1]), "+f"(d[2]), "+f"(d[3]) : "r"(a0), "r"(a1), "r"(b0));
}
__device__ __forceinline__ uint32_t pack2(float a, float b) { uint32_t d; asm("cvt.rn.bf16x2.f32 %0, %1, %2;" : "=r"(d) : "f"(b), "f"(a)); return d; }
__device__ __forceinline__ float bf_lo(uint32_t w) { return __uint_as_float(w << 16); }
__device__ __forceinline__ float bf_hi(uint32_t w) { return __uint_as_float(w & 0xffff0000u); }
__device__ __forceinline__ float rbf(float x) { return __bfloat162float(__float2bfloat16_rn(x)); }

__device__ __forceinline__ void sts128(uint32_t a, float x, float y, float z, float w) { asm volatile("st.shared.v4.f32 [%0], {%1,%2,%3,%4};" :: "r"(a), "f"(x), "f"(y), "f"(z), "f"(w) : "memory"); }
__device__ __forceinline__ void sts128u(uint32_t a, uint32_t x, uint32_t y, uint32_t z, uint32_t w) { asm volatile("st.shared.v4.b32 [%0], {%1,%2,%3,%4};" :: "r"(a), "r"(x), "r"(y), "r"(z), "r"(w) : "memory"); }
__device__ __forceinline__ void sts64(uint32_t a, float x, float y) { asm volatile("st.shared.v2.f32 [%0], {%1,%2};" :: "r"(a), "f"(x), "f"(y) : "memory"); }
__device__ __forceinline__ float4 lds128(uint32_t a) { float4 v; asm volatile("ld.shared.v4.f32 {%0,%1,%2,%3}, [%4];" : "=f"(v.x), "=f"(v.y), "=f"(v.z), "=f"(v.w) : "r"(a) : "memory"); return v; }
__device__ __forceinline__ float2 lds64(uint32_t a) { float2 v; asm volatile("ld.shared.v2.f32 {%0,%1}, [%2];" : "=f"(v.x), "=f"(v.y) : "r"(a) : "memory"); return v; }
__device__ __forceinline__ uint2 lds64u(uint32_t a) { uint2 v; asm volatile("ld.shared.v2.b32 {%0,%1}, [%2];" : "=r"(v.x), "=r"(v.y) : "r"(a) : "memory"); return v; }
__device__ __forceinline__ float4 lds128v(uint32_t a) { float4 v; asm volatile("ld.volatile.shared.v4.f32 {%0,%1,%2,%3}, [%4];" : "=f"(v.x), "=f"(v.y), "=f"(v.z), "=f"(v.w) : "r"(a) : "memory"); return v; }
__device__ __forceinline__ float2 lds64v(uint32_t a) { float2 v; asm volatile("ld.volatile.shared.v2.f32 {%0,%1}, [%2];" : "=f"(v.x), "=f"(v.y) : "r"(a) : "memory"); return v; }
__device__ __forceinline__ uint4 lds128uv(uint32_t a) { uint4 v; asm volatile("ld.volatile.shared.v4.b32 {%0,%1,%2,%3}, [%4];" : "=r"(v.x), "=r"(v.y), "=r"(v.z), "=r"(v.w) : "r"(a) : "memory"); return v; }
__device__ __forceinline__ void st_async4(uint32_t a, float x, float y, float z, float w, uint32_t mb) {
    asm volatile("st.async.weak.shared::cluster.mbarrier::complete_tx::bytes.v4.f32 [%0], {%1,%2,%3,%4}, [%5];" :: "r"(a), "f"(x), "f"(y), "f"(z), "f"(w), "r"(mb) : "memory");
}
__device__ __forceinline__ void st_async2(uint32_t a, uint32_t x, uint32_t y, uint32_t mb) {
    asm volatile("st.async.weak.shared::cluster.mbarrier::complete_tx::bytes.v2.b32 [%0], {%1,%2}, [%3];" :: "r"(a), "r"(x), "r"(y), "r"(mb) : "memory");
}
__device__ __forceinline__ uint32_t ldg_rlx(const uint32_t* p) { uint32_t v; asm volatile("ld.relaxed.gpu.global.b32 %0, [%1];" : "=r"(v) : "l"(p) : "memory"); return v; }
__device__ __forceinline__ uint4 ldg_rlx4(const uint32_t* p) { uint4 v; asm volatile("ld.relaxed.gpu.global.v4.b32 {%0,%1,%2,%3}, [%4];" : "=r"(v.x), "=r"(v.y), "=r"(v.z), "=r"(v.w) : "l"(p) : "memory"); return v; }
__device__ __forceinline__ uint4 ldg_rlx4_if(const uint32_t* p, bool c) {
    uint4 v;
    asm volatile("{\n.reg .pred p;\nsetp.ne.u32 p, %5, 0;\nmov.b32 %0, 0;\nmov.b32 %1, 0;\nmov.b32 %2, 0;\nmov.b32 %3, 0;\n@p ld.relaxed.gpu.global.v4.b32 {%0,%1,%2,%3}, [%4];\n}"
                 : "=r"(v.x), "=r"(v.y), "=r"(v.z), "=r"(v.w) : "l"(p), "r"((uint32_t)c) : "memory");
    return v;
}
__device__ __forceinline__ void stg_rlx(uint32_t* p, uint32_t v) { asm volatile("st.relaxed.gpu.global.b32 [%0], %1;" :: "l"(p), "r"(v) : "memory"); }
__device__ __forceinline__ void tma2d(uint32_t dst, const CUtensorMap* tm, int c0, int c1, uint32_t mb) {
    asm volatile("cp.async.bulk.tensor.2d.shared::cluster.global.mbarrier::complete_tx::bytes [%0], [%1, {%3, %4}], [%2];"
        :: "r"(dst), "l"((uint64_t)tm), "r"(mb), "r"(c0), "r"(c1) : "memory");
}

__device__ __forceinline__ void tma3d(uint32_t dst, const CUtensorMap* tm, int row, int chunk, uint32_t mb) {
    asm volatile("cp.async.bulk.tensor.3d.shared::cluster.global.mbarrier::complete_tx::bytes [%0], [%1, {%3, %4, %5}], [%2];"
        :: "r"(dst), "l"((uint64_t)tm), "r"(mb), "r"(0), "r"(row), "r"(chunk) : "memory");
}
#define EF 0xff
__device__ __forceinline__ uint64_t pol_ef(int bit) {
    uint64_t p;
    if ((EF >> bit) & 1) asm("createpolicy.fractional.L2::evict_first.b64 %0, 1.0;" : "=l"(p));
    else asm("createpolicy.fractional.L2::evict_normal.b64 %0, 1.0;" : "=l"(p));
    return p;
}
__device__ __forceinline__ void tma3d_h(uint32_t dst, const CUtensorMap* tm, int row, int chunk, uint32_t mb, uint64_t pol) {
    asm volatile("cp.async.bulk.tensor.3d.shared::cluster.global.mbarrier::complete_tx::bytes.L2::cache_hint [%0], [%1, {%3, %4, %5}], [%2], %6;"
        :: "r"(dst), "l"((uint64_t)tm), "r"(mb), "r"(0), "r"(row), "r"(chunk), "l"(pol) : "memory");
}
__device__ __forceinline__ void tma2d_h(uint32_t dst, const CUtensorMap* tm, int c0, int c1, uint32_t mb, uint64_t pol) {
    asm volatile("cp.async.bulk.tensor.2d.shared::cluster.global.mbarrier::complete_tx::bytes.L2::cache_hint [%0], [%1, {%3, %4}], [%2], %5;"
        :: "r"(dst), "l"((uint64_t)tm), "r"(mb), "r"(c0), "r"(c1), "l"(pol) : "memory");
}
__device__ __forceinline__ void tma2d_mc_h(uint32_t dst, const CUtensorMap* tm, int c0, int c1, uint32_t mb, uint64_t pol) {
    asm volatile("cp.async.bulk.tensor.2d.shared::cluster.global.mbarrier::complete_tx::bytes.multicast::cluster.L2::cache_hint [%0], [%1, {%3, %4}], [%2], %5, %6;"
        :: "r"(dst), "l"((uint64_t)tm), "r"(mb), "r"(c0), "r"(c1), "h"((uint16_t)3), "l"(pol) : "memory");
}
__device__ __forceinline__ uint4 ldg4_h(const void* p, uint64_t pol) {
    uint4 v;
    asm volatile("ld.relaxed.gpu.global.L2::cache_hint.v4.b32 {%0,%1,%2,%3}, [%4], %5;" : "=r"(v.x), "=r"(v.y), "=r"(v.z), "=r"(v.w) : "l"(p), "l"(pol) : "memory");
    return v;
}
__device__ __forceinline__ void stg4_h(void* p, uint4 v, uint64_t pol) {
    asm volatile("st.relaxed.gpu.global.L2::cache_hint.v4.b32 [%0], {%1,%2,%3,%4}, %5;" :: "l"(p), "r"(v.x), "r"(v.y), "r"(v.z), "r"(v.w), "l"(pol) : "memory");
}
__device__ __forceinline__ void tma2d_mc(uint32_t dst, const CUtensorMap* tm, int c0, int c1, uint32_t mb) {
    asm volatile("cp.async.bulk.tensor.2d.shared::cluster.global.mbarrier::complete_tx::bytes.multicast::cluster [%0], [%1, {%3, %4}], [%2], %5;"
        :: "r"(dst), "l"((uint64_t)tm), "r"(mb), "r"(c0), "r"(c1), "h"((uint16_t)3) : "memory");
}
__device__ __forceinline__ void mbar_arrive2_if(uint32_t a, uint32_t pred) {
    asm volatile("{\n.reg .pred p;\nsetp.ne.u32 p, %1, 0;\n@p mbarrier.arrive.shared::cta.b64 _, [%0];\n@p mbarrier.arrive.shared::cluster.b64 _, [%2];\n}"
                 :: "r"(a), "r"(pred), "r"(a ^ 0x01000000u) : "memory");
}
__device__ __forceinline__ void tma_pf3d(const CUtensorMap* tm, int row, int chunk) {
    asm volatile("cp.async.bulk.prefetch.tensor.3d.L2.global.tile [%0, {%1, %2, %3}];" :: "l"((uint64_t)tm), "r"(0), "r"(row), "r"(chunk) : "memory");
}
__device__ __forceinline__ void tma_pf2d(const CUtensorMap* tm, int c0, int c1) {
    asm volatile("cp.async.bulk.prefetch.tensor.2d.L2.global.tile [%0, {%1, %2}];" :: "l"((uint64_t)tm), "r"(c0), "r"(c1) : "memory");
}
__device__ __forceinline__ void tma_store3d(const CUtensorMap* tm, uint32_t src, int row, int chunk) {
    asm volatile("cp.async.bulk.tensor.3d.global.shared::cta.bulk_group [%0, {%2, %3, %4}], [%1];" :: "l"((uint64_t)tm), "r"(src), "r"(0), "r"(row), "r"(chunk) : "memory");
}
__device__ __forceinline__ void bulk_store(void* dst, uint32_t src, uint32_t bytes) {
    asm volatile("cp.async.bulk.global.shared::cta.bulk_group [%0], [%1], %2;" :: "l"(dst), "r"(src), "r"(bytes) : "memory");
}
#define GT(slot)
#define CNT(k)
#define CNT2(k, c)
#define TS(i, dep)
#define TSACC()
#define TSDECL
struct Maps { CUtensorMap wq, wk, wv, wo, wo2, kx, ox2, kx3, vx3, xn2, wg, wu, wd, wq4, wk4, wv4; };
typedef Maps RecMaps;
__device__ __forceinline__ void st_rel(uint32_t* p, uint32_t v) { asm volatile("st.release.gpu.global.u32 [%0], %1;" :: "l"(p), "r"(v) : "memory"); }
#define PUBLISH(p, v) st_rel(p, v)
__device__ __forceinline__ uint2 ldg_rlx2(const uint32_t* p) { uint2 v; asm volatile("ld.relaxed.gpu.global.v2.b32 {%0,%1}, [%2];" : "=r"(v.x), "=r"(v.y) : "l"(p) : "memory"); return v; }
__device__ __forceinline__ void wait_eq2(const uint32_t* p, uint32_t e, int code) {
    uint32_t n = 0;
#pragma unroll 1
    while (true) { uint2 v = ldg_rlx2(p); if (v.x == e && v.y == e) break; __nanosleep(64); if (++n > SPIN_LIMIT) { ABORT(code); break; } }
}
__device__ __forceinline__ void wait_eq4(const uint32_t* p, uint32_t e, int code) {
    uint32_t n = 0;
#pragma unroll 1
    while (true) { uint4 v = ldg_rlx4(p); if (v.x == e && v.y == e && v.z == e && v.w == e) break; __nanosleep(64); if (++n > SPIN_LIMIT) { ABORT(code); break; } }
}
__device__ __forceinline__ void wait_rec(const uint32_t* p, uint32_t e, uint32_t steps) {
    uint32_t n = 0;
#pragma unroll 1
    while (true) {
        uint2 v = ldg_rlx2(p);
        if (__all_sync(0xffffffffu, (v.x >> 8) == e && (v.y >> 8) == e && (v.x & 255) >= steps && (v.y & 255) >= steps)) break;
        __nanosleep(64); if (++n > SPIN_LIMIT) { ABORT(8); break; }
    }
}

constexpr int R_QK1 = 0;
constexpr int R_WO = 65536;
constexpr int R_T = 131072;
constexpr int R_SLOT1 = R_T;
constexpr int R_MEMB = R_T + 24576;
constexpr int R_QP = R_MEMB + 8192;
constexpr int R_VRED = R_QP + 4096;
constexpr int R_STG = R_VRED + 2048;
constexpr int R_AX = R_STG + 2048;
constexpr int R_SLOT0 = 196608;
constexpr int R_SLOC = R_SLOT0 + 24576;
constexpr int R_SREM = R_SLOC + 1536;
constexpr int R_VB = R_SREM + 1536;
constexpr int R_MISC = R_VB + 2048;
constexpr int R_LT = R_MISC + 128;
constexpr int R_BAR = 229888;
constexpr int R_TS = 229888 + 128;
static_assert(R_AX + 24576 <= R_SLOT0 && R_LT + 2560 <= 229376, "smem map");
enum { MB_W0 = 0, MB_W1, MB_WV, MB_WO, MB_S, MB_FULL0, MB_FULL1, MB_V, MB_N };

__device__ __forceinline__ float ex2(float x) { float y; asm("ex2.approx.ftz.f32 %0, %1;" : "=f"(y) : "f"(x)); return y; }
__device__ __forceinline__ float rcpf(float x) { float y; asm("rcp.approx.ftz.f32 %0, %1;" : "=f"(y) : "f"(x)); return y; }
__device__ __forceinline__ void mma16816z(float* d, uint32_t a0, uint32_t a1, uint32_t a2, uint32_t a3, uint32_t b0, uint32_t b1) {
    asm volatile("mma.sync.aligned.m16n8k16.row.col.f32.bf16.bf16.f32 {%0,%1,%2,%3}, {%4,%5,%6,%7}, {%8,%9}, {%10,%10,%10,%10};"
        : "=f"(d[0]), "=f"(d[1]), "=f"(d[2]), "=f"(d[3]) : "r"(a0), "r"(a1), "r"(a2), "r"(a3), "r"(b0), "r"(b1), "f"(0.f));
}
__device__ __forceinline__ void mma1688hz(float* d, uint32_t a0, uint32_t a1, uint32_t b0) {
    asm volatile("mma.sync.aligned.m16n8k8.row.col.f32.f16.f16.f32 {%0,%1,%2,%3}, {%4,%5}, {%6}, {%7,%7,%7,%7};"
        : "=f"(d[0]), "=f"(d[1]), "=f"(d[2]), "=f"(d[3]) : "r"(a0), "r"(a1), "r"(b0), "f"(0.f));
}
#define MMA(d, a, b0, b1) mma16816(d, a[0], a[1], a[2], a[3], b0, b1)
#define MMAZ(d, a, b0, b1) mma16816z(d, a[0], a[1], a[2], a[3], b0, b1)
#define MMAF(first, d, a, b0, b1) do { if (first) MMAZ(d, a, b0, b1); else MMA(d, a, b0, b1); } while (0)

__device__ __forceinline__ uint32_t uni(uint32_t x) { return __reduce_max_sync(0xffffffffu, x); }
__device__ __forceinline__ void mbar_wait_u(uint32_t a, uint32_t ph) {
    uint32_t n = 0;
#pragma unroll 1
    while (!__all_sync(0xffffffffu, mbar_try(a, ph))) { if (++n > SPIN_LIMIT) { ABORT(1); break; } }
}
__device__ __forceinline__ void mbar_wait_p(uint32_t a, uint32_t ph) {
    asm volatile("{\n.reg .pred p, q;\n.reg .u32 n;\nmov.u32 n, 0;\nWL: mbarrier.try_wait.parity.shared::cta.b64 p, [%0], %1;\nadd.u32 n, n, 1;\n"
                 "setp.lt.and.u32 q, n, %2, !p;\n@q bra.uni WL;\n}" :: "r"(a), "r"(ph), "n"(SPIN_LIMIT) : "memory");
}
__device__ __forceinline__ uint32_t mbar_test(uint32_t a, uint32_t ph) {
    uint32_t ok;
    asm volatile("{\n.reg .pred p;\nmbarrier.test_wait.parity.shared::cta.b64 p, [%1], %2;\nselp.u32 %0, 1, 0, p;\n}" : "=r"(ok) : "r"(a), "r"(ph) : "memory");
    return ok;
}
__device__ __forceinline__ uint32_t opaque(uint32_t x) { return __shfl_sync(0xffffffffu, x, threadIdx.x & 31); }
__device__ __forceinline__ const uint32_t* mkptr(uint32_t lo, uint32_t hi) { uint64_t r; asm("mov.b64 %0, {%1, %2};" : "=l"(r) : "r"(lo), "r"(hi)); return (const uint32_t*)r; }
__device__ __forceinline__ uint32_t prmt(uint32_t a, uint32_t b, uint32_t s) { uint32_t d; asm("prmt.b32 %0, %1, %2, %3;" : "=r"(d) : "r"(a), "r"(b), "r"(s)); return d; }
__device__ __forceinline__ uint32_t packh2(float a, float b) { uint32_t d; asm("cvt.rn.f16x2.f32 %0, %1, %2;" : "=r"(d) : "f"(b), "f"(a)); return d; }
__device__ __forceinline__ uint32_t hadd2b(uint32_t a, uint32_t b) { uint32_t d; asm("add.rn.bf16x2 %0, %1, %2;" : "=r"(d) : "r"(a), "r"(b)); return d; }
__device__ __forceinline__ uint32_t hmul2b(uint32_t a, uint32_t b) { uint32_t d; asm("mul.rn.bf16x2 %0, %1, %2;" : "=r"(d) : "r"(a), "r"(b)); return d; }
__device__ __forceinline__ uint32_t amax2b(uint32_t a, uint32_t b) { uint32_t d; asm("max.xorsign.abs.bf16x2 %0, %1, %2;" : "=r"(d) : "r"(a), "r"(b)); return d; }
__device__ __forceinline__ uint32_t amax2h(uint32_t a, uint32_t b) { uint32_t d; asm("max.xorsign.abs.f16x2 %0, %1, %2;" : "=r"(d) : "r"(a), "r"(b)); return d; }
__device__ __forceinline__ void sts32(uint32_t a, uint32_t x) { asm volatile("st.shared.b32 [%0], %1;" :: "r"(a), "r"(x) : "memory"); }
__device__ __forceinline__ uint32_t lds32v_(uint32_t a) { uint32_t v; asm volatile("ld.volatile.shared.b32 %0, [%1];" : "=r"(v) : "r"(a) : "memory"); return v; }
__device__ __forceinline__ void stg4(void* p, uint4 v) { asm volatile("st.relaxed.gpu.global.v4.b32 [%0], {%1,%2,%3,%4};" :: "l"(p), "r"(v.x), "r"(v.y), "r"(v.z), "r"(v.w) : "memory"); }
__device__ __forceinline__ void lds_frag(uint32_t* r, uint32_t a) {
    asm volatile("ld.shared.v4.b32 {%0,%1,%2,%3}, [%4];" : "=r"(r[0]), "=r"(r[1]), "=r"(r[2]), "=r"(r[3]) : "r"(a) : "memory");
}
__device__ __forceinline__ void lds_fragv(uint32_t* r, uint32_t a) {
    asm volatile("ld.volatile.shared.v4.b32 {%0,%1,%2,%3}, [%4];" : "=r"(r[0]), "=r"(r[1]), "=r"(r[2]), "=r"(r[3]) : "r"(a) : "memory");
}
__device__ __forceinline__ uint32_t xorv(uint32_t a, uint32_t b) { uint32_t d; asm volatile("xor.b32 %0, %1, %2;" : "=r"(d) : "r"(a), "r"(b)); return d; }
#define SCHED(k) asm volatile("{\n.reg .pred p;\nsetp.eq.u32 p, %0, %1;\n@p exit;\n}" :: "r"(sbu - s), "n"(k) : "memory")
#define PINM() asm volatile("{\n.reg .pred p;\nsetp.eq.u32 p, %0, 1;\n@p st.shared.u32 [%0], 0;\n}" :: "r"(sbu) : "memory")
__device__ __forceinline__ uint32_t or_and(uint32_t a, uint32_t b, uint32_t c) { uint32_t d; asm("lop3.b32 %0, %1, %2, %3, 0xF8;" : "=r"(d) : "r"(a), "r"(b), "r"(c)); return d; }
__device__ __forceinline__ uint32_t pack2v(float a, float b) { uint32_t d; asm volatile("cvt.rn.bf16x2.f32 %0, %1, %2;" : "=r"(d) : "f"(b), "f"(a)); return d; }
#define FU(x) __float_as_uint(x)
__device__ __forceinline__ uint32_t clk32() { uint32_t t; asm volatile("mov.u32 %0, %%clock;" : "=r"(t) :: "memory"); return t; }
__device__ __forceinline__ void spin_until(uint32_t t0, uint32_t d) {
    if (d) {
#pragma unroll 1
        while (__any_sync(0xffffffffu, clk32() - t0 < d)) {}
    }
}
constexpr int SH_OFF = 229376 + 384;
constexpr uint32_t HONE2 = 0x3c003c00u, HCNT2 = 0x50005000u;

__device__ __forceinline__ uint64_t desc_sw128(uint32_t addr, uint32_t lbo, uint32_t sbo) {
    return (uint64_t)((addr & 0x3FFFF) >> 4) | ((uint64_t)(lbo >> 4) << 16) | ((uint64_t)(sbo >> 4) << 32) | (1ull << 62);
}
#define DP 375
#define NAX 3
#define NXL 0
#define NCX 2
#define NCL 1
#define FLIP 1
#define VTA 1
#define KXB 4
#define ANB 3
#define BNB 3
#define CNB 3
#define SMA 0
#define SMB 0
#define SMC 0x01
#define IVA 0
#define RGA 160
#define RGC 160
#define RGB (504 - RGA - RGC)
#define NRW 8
#define NBR 16
#define E0 0
#define E1 6
#define E2 4
#define E3 8
#define IV 2
#define G2V 0
#define G2K 2
#define VDEP 0
#define AEARLY 0
#define VTP 2
#define LORD 1
#define TRK 1
#define T2N 14
#define NB0 0
#define NB1 9
#define DB2 80
#define DITHER 0
#define DB 40

__device__ __forceinline__ uint32_t wrow_off(int kk, int ch) {
    const int lane = threadIdx.x & 31, r = lane & 7;
    const int row = 64 * (kk >> 2) + 32 * (r & 1) + 16 * (kk & 1) + 8 * (lane >> 4) + 4 * ((kk >> 1) & 1) + (r >> 1);
    return row * 128 + ((ch ^ (row & 7)) << 4);
}
template <int K> __device__ __forceinline__ void sched(uint32_t key) {
    asm volatile("{\n.reg .pred p;\nsetp.eq.u32 p, %0, %1;\n@p exit;\n}" :: "r"(key), "n"(K) : "memory");
}
__device__ __forceinline__ void sched_i(int i, uint32_t key) {
    if (i == -1) sched<20>(key); if (i == 0) sched<21>(key); if (i == 1) sched<22>(key); if (i == 2) sched<23>(key);
    if (i == 3) sched<24>(key); if (i == 4) sched<25>(key); if (i == 5) sched<26>(key); if (i == 6) sched<27>(key);
}
template <int NB, int SM, class F>
__device__ __forceinline__ void g1(float* q0, float* k0, uint32_t (*wq)[4], uint32_t (*wk)[4], uint32_t ga, uint32_t key, F&& hook) {
    float q1[4], k1[4];
    uint32_t b[NB][4];
#pragma unroll
    for (int i = 0; i < NB; i++) ldsm4(b[i], ga + i * 512);
    hook(-1, b[0]);
    if (SM & 1) sched_i(-1, key);
#pragma unroll
    for (int i = 0; i < 8; i++) {
        uint32_t* c = b[i % NB];
        MMAF(i == 0, q0, wq[2 * i], c[0], c[1]); MMAF(i == 0, k0, wk[2 * i], c[0], c[1]);
        MMAF(i == 0, q1, wq[2 * i + 1], c[2], c[3]); MMAF(i == 0, k1, wk[2 * i + 1], c[2], c[3]);
        const uint32_t cc_[4] = {c[0], c[1], c[2], c[3]};
        if (i + NB < 8) ldsm4(b[i % NB], ga + (i + NB) * 512);
        hook(i, cc_);
        if ((SM >> (i + 1)) & 1) sched_i(i, key);
    }
#pragma unroll
    for (int i = 0; i < 4; i++) { q0[i] += q1[i]; k0[i] += k1[i]; }
}
__device__ __forceinline__ float frag_norm2(uint32_t (*w)[4]) {
    float d0[4], d1[4];
#pragma unroll
    for (int i = 0; i < 32; i++) { MMAF(i == 0, d0, w[i], w[i][0], w[i][2]); MMAF(i == 0, d1, w[i], w[i][1], w[i][3]); }
    const int lane = threadIdx.x & 31, g = lane >> 2, t = lane & 3;
    float v = g == 2 * t ? d0[0] + d1[2] : (g == 2 * t + 1 ? d0[1] + d1[3] : 0.f);
#pragma unroll
    for (int o = 16; o; o >>= 1) v += __shfl_xor_sync(0xffffffffu, v, o);
    return v;
}
__device__ __forceinline__ void load_slot(uint32_t sb, int c, int tile, const Maps& maps) {
    const uint32_t dst = sb + ((tile & 1) ? R_SLOT1 : R_SLOT0), mb = sb + R_BAR + 8 * (MB_FULL0 + (tile & 1));
    mbar_expect_tx(mb, 24576);
    if ((EF >> 8) & 1) {
        tma2d_h(dst + 16384, &maps.kx, c * 64, tile * 64, mb, pol_ef(8));
        tma3d_h(dst, &maps.vx3, tile * 64, (c >> 1) * 2, mb, pol_ef(8));
    } else {
        tma2d(dst + 16384, &maps.kx, c * 64, tile * 64, mb);
        tma3d(dst, &maps.vx3, tile * 64, (c >> 1) * 2, mb);
    }
}
__device__ __forceinline__ uint32_t put_mem0(uint32_t sb, int W, const bf16* __restrict__ mem0) {
    const int lane = threadIdx.x & 31;
    const uint4 a = *(const uint4*)(mem0 + (lane & 7) * DM + W * 64 + (lane >> 3) * 8), b = *(const uint4*)(mem0 + (lane & 7) * DM + W * 64 + 32 + (lane >> 3) * 8);
    const uint4 m0 = make_uint4(prmt(a.x, b.x, 0x5410u), prmt(a.x, b.x, 0x7632u), prmt(a.y, b.y, 0x5410u), prmt(a.y, b.y, 0x7632u));
    const uint4 m1 = make_uint4(prmt(a.z, b.z, 0x5410u), prmt(a.z, b.z, 0x7632u), prmt(a.w, b.w, 0x5410u), prmt(a.w, b.w, 0x7632u));
    bar_sync(3, 256);
    sts128u(sb + R_MEMB + W * 1024 + lane * 16, m0.x, m0.y, m0.z, m0.w);
    sts128u(sb + R_MEMB + W * 1024 + 512 + lane * 16, m1.x, m1.y, m1.z, m1.w);
    return amax2b(amax2b(amax2b(m0.x, m0.y), amax2b(m0.z, m0.w)), amax2b(amax2b(m1.x, m1.y), amax2b(m1.z, m1.w)));
}
#define PUT_MAX(rL, W) sts32(rL + R_STG + 1024 + ((W) >> 2) * 512 + ((W) & 3) * 4, amax2b(amax2b(mx, my), mz));
__device__ __forceinline__ uint32_t h2b(uint32_t w) {
    uint32_t d;
    asm("{\n.reg .f16 l, h;\n.reg .f32 a, b;\nmov.b32 {l, h}, %1;\ncvt.f32.f16 a, l;\ncvt.f32.f16 b, h;\ncvt.rn.bf16x2.f32 %0, b, a;\n}" : "=r"(d) : "r"(w));
    return d;
}
#define GATHER1(HALF)                                                                                           \
        {                                                                                                       \
            const uint4 x0 = ldg_rlx4(pm), x1 = ldg_rlx4(pm + 256); const uint2 y = ldg_rlx2(px);                 \
            cw = (sel & 0x4000u) ? prmt(x0.w, x1.w, 0x7632u) : prmt(y.x, y.y, 0x5410u);                         \
            const uint32_t p0 = h2b(x0.x), p1 = h2b(x0.y), p2 = h2b(x0.z), p3 = h2b(prmt(x0.w, y.x, sel));      \
            stsm4t(rG + R_MEMB + HALF * 4096, p0, p1, p2, p3);                                                  \
            const uint32_t p4 = h2b(x1.x), p5 = h2b(x1.y), p6 = h2b(x1.z), p7 = h2b(prmt(x1.w, y.y, sel));      \
            stsm4t(rG + R_MEMB + HALF * 4096 + 512, p4, p5, p6, p7);                                            \
            mx = amax2b(amax2b(p0, p1), amax2b(p2, p3)); my = amax2b(p4, p5); mz = amax2b(p6, p7);              \
        }
#define GATHER(HALF, PRE, SYNC, AFTER)                                                                                      \
        {                                                                                                       \
            const uint32_t so = aslot(s);                                                                       \
            const uint32_t ua = (glo + acc_base(HALF * 4 + fo)) ^ so, ux = (glo + ext_base(HALF * 4 + fo)) ^ so; \
            uint2 lt;                                                                                           \
            lt.x = lds32v_(rL + R_LT); lt.y = lds32v_(rL + R_LT + 4);                                           \
            const uint32_t sel = 0x7610u - ((lt.x ^ (lt.x >> 2)) & 16) * 0x440u;                                \
            const uint32_t* pm = mkptr(ua + lt.x, ghi);                                                         \
            const uint32_t* px = mkptr(ux + lt.y, ghi);                                                         \
            PRE                                                                                                 \
            bar_sync(5, 384);                                                                                   \
            const uint32_t t0 = clk32();                                                                        \
            TSACC();                                                                        \
            SYNC                                                                                                \
            spin_until(t0, DP + DITHER);                                                                                 \
            \
            TS(10, 0);                                                                                          \
            uint32_t cw, nr = 0;                                                                                \
            _Pragma("unroll 1") do {                                                                            \
                GATHER1(HALF)                                                                                   \
                nr++;                                                                                           \
            } while (__any_sync(0xffffffffu, cw != HCNT2 && nr < SPIN_LIMIT));                                  \
            TS(11, cw);                                                                                         \
            AFTER                                                                                               \
            CNT2(HALF * 4 + (s & 1) * 2 + (nr > 2), nr > 1);                                                    \
            \
        }
#define GOBAR (fo == 3 ? 14 : 10 + fo)

__device__ __forceinline__ void rec_a(uint32_t sb, int c, const bf16* __restrict__ mem0, uint32_t epoch) {
    const int tid = threadIdx.x - WGA * 128, lane = tid & 31, f = tid >> 5;
    uint32_t wq[16][4], wk[16][4], mx, my = 0, mz = 0;
    const int lrow = ((lane >> 4) << 3) + (lane & 7), lsel = (lane >> 3) & 1;
    {
        mbar_wait(sb + R_BAR + 8 * MB_W0, 0);
        if (c == 7 && tid == 0) GT(1421);
#pragma unroll
        for (int kk = 0; kk < 16; kk++) { const uint32_t a = sb + R_T + wrow_off(kk, 2 * f + lsel); ldsm4t(wq[kk], a); ldsm4t(wk[kk], a + 32768); }
        __syncwarp();
        mx = put_mem0(sb, f, mem0);
    }
    const uint32_t rL = opaque(sb + lane * 16), rG = opaque(sb + lane * 16 + f * 1024);
    const uint32_t sbu = uni(sb), fo = uni(f), cc = uni(c);
    const uint64_t gx = xpage();
    const uint32_t ghi = uni((uint32_t)(gx >> 32)), glo = uni((uint32_t)gx);
#pragma unroll
    for (int i = 0; i < NAX; i++) {
        sts128u(rG + R_AX + 4096 * i, wq[i][0], wq[i][1], wq[i][2], wq[i][3]);
        sts128u(rG + R_AX + 4096 * i + 512, wk[i][0], wk[i][1], wk[i][2], wk[i][3]);
    }
    sts128u(rL + R_LT + 512 + f * 512, (sb + R_SREM + (f >= 2 ? lane * 8 + f * 256 : lane * 16 + f * 1024)) ^ 0x01000000u, (sb + R_BAR + 8 * MB_S) ^ 0x01000000u,
            sb + R_QP + (lane >> 4) * 128 + lsel * 512 + (lane & 7) * 16 + (f == 3 ? 2048 : 0), sb + R_SLOT0 + lrow * 128 + ((lsel ^ (lane & 7)) << 4));
    __syncwarp();
    if (tid == 0) GT(c * 8 + 1);
    TSDECL;
    const float cexp = 0.08838834764831845f * 1.4426950408889634f;
    float cs = cexp;
    auto step = [&](int s, bool first) -> bool {
        bar_sync(1, 128);
        float q0[4], k0[4];
        uint4 ta;
        uint32_t zr, rl2;
        g1<ANB, SMA>(q0, k0, wq, wk, rL + R_MEMB, sbu - s, [&](int i, const uint32_t* c_) {
            if (i == 0) TS(0, c_[0]);
            if (i == -1) {
#pragma unroll
                for (int n = NAX - NXL; n < NAX; n++) { lds_fragv(wq[n], rG + R_AX + 4096 * n); lds_fragv(wk[n], rG + R_AX + 4096 * n + 512); }
                ta = lds128uv(rL + R_LT + 512 + fo * 512);
                zr = ta.w & 1; rl2 = rL | zr;
            }
            if (i == IVA) { PUT_MAX(rl2, fo) bar_arrive(15, 256); bar_arrive(GOBAR, 96); }
        });
        stsm4t(rG + R_QP, pack2(q0[0], q0[1]), pack2(q0[2], q0[3]), pack2(k0[0], k0[1]), pack2(k0[2], k0[3]));
        TS(1, FU(k0[3]));
        if (first) mbar_wait_p(sbu + R_BAR + 8 * MB_FULL0, 0);
        if (fo >= 2) {
            bar_sync(3, 256);
            uint32_t kb[4], kc[4], qa[4], qc[4];
            ldsm4(kb, ta.z + 256); ldsm4(qa, ta.z);
            ldsm4(kc, ta.z + 1280); ldsm4(qc, ta.z + 1024);
            const uint32_t k0_ = hadd2b(kb[0], kb[1]), k1_ = hadd2b(kb[2], kb[3]), k2_ = hadd2b(kc[0], kc[1]), k3_ = hadd2b(kc[2], kc[3]);
            float s0[4], s2[4];
            MMAZ(s0, qa, k0_, k1_); MMAZ(s2, qc, k2_, k3_);
            const float x = ((s0[0] + s0[2]) + (s2[0] + s2[2])) * cs, y = ((s0[1] + s0[3]) + (s2[1] + s2[3])) * cs;
            st_async2(ta.x, FU(x), FU(y), ta.y);
            TS(3, FU(y));
            sts64((ta.x ^ 0x01000000u) + (R_SLOC - R_SREM), x, y);
            sts128u(rl2 + R_STG + (fo & 1) * 512, k0_, k1_, k2_, k3_);
            bar_arrive(9, 192);
        } else {
            uint32_t qa[4][4], kx[4][4];
#pragma unroll
            for (int kk = 0; kk < KXB; kk++) ldsm4(kx[kk], (ta.w ^ (kk * 32)) + (16384 + fo * 2048));
            bar_sync(3, 256);
#pragma unroll
            for (int kk = 0; kk < 4; kk++) {
                if (kk >= KXB) ldsm4(kx[kk], (ta.w ^ (kk * 32)) + (16384 + fo * 2048));
                ldsm4(qa[kk], ta.z + kk * 1024);
            }
            float s0[4], s1[4], s2[4], s3[4];
            MMAZ(s0, qa[0], kx[0][0], kx[0][1]); MMAZ(s1, qa[0], kx[0][2], kx[0][3]);
            MMAZ(s2, qa[1], kx[1][0], kx[1][1]); MMAZ(s3, qa[1], kx[1][2], kx[1][3]);
            MMA(s0, qa[2], kx[2][0], kx[2][1]); MMA(s1, qa[2], kx[2][2], kx[2][3]);
            MMA(s2, qa[3], kx[3][0], kx[3][1]); MMA(s3, qa[3], kx[3][2], kx[3][3]);
            const float x = ((s0[0] + s0[2]) + (s2[0] + s2[2])) * cs, y = ((s0[1] + s0[3]) + (s2[1] + s2[3])) * cs;
            const float z = ((s1[0] + s1[2]) + (s3[0] + s3[2])) * cs, w = ((s1[1] + s1[3]) + (s3[1] + s3[3])) * cs;
            st_async4(ta.x, x, y, z, w, ta.y);
            TS(3, FU(w));
            sts128(rG + R_SLOC, x, y, z, w);
        }
        const uint32_t r8 = (rl2 + sbu) >> 1;
        uint32_t vt00[4], vt01[4], vt10[4], vt11[4];
        const uint32_t rV = ta.w ^ ((fo & 1) * 64), vo = (fo >> 1) * 8192;
        if (!VTA && VTP < 2) { ldsm4t(vt00, rV + vo); ldsm4t(vt10, (rV ^ 32) + vo); }
        if (!VTA && VTP < 1) { ldsm4t(vt01, rV + vo + 2048); ldsm4t(vt11, (rV ^ 32) + vo + 2048); }
        bar_sync(4, 128);
        const float2 l2 = lds64v(r8 + R_SLOC + 512), l3 = lds64v(r8 + R_SLOC + 768);
        const float4 l0 = lds128v(rL + R_SLOC), l1 = lds128v(rL + R_SLOC + 1024);
        if (VTA && VTP < 2) { ldsm4t(vt00, rV + vo); ldsm4t(vt10, (rV ^ 32) + vo); }
        if (VTA && VTP < 1) { ldsm4t(vt01, rV + vo + 2048); ldsm4t(vt11, (rV ^ 32) + vo + 2048); }

        if (s == NSEG - 1) { mbar_wait_u(sbu + R_BAR + 8 * MB_S, 1); mbar_wait_u(sbu + R_BAR + 8 * MB_V, 1); return true; }
        TS(2, FU(l3.y));
        mbar_wait_p(sbu + R_BAR + 8 * MB_S, s & 1);
        TS(4, 0);
        {
            const float2 r2 = lds64v(r8 + R_SREM + 512), r3 = lds64v(r8 + R_SREM + 768);
            const float4 r0 = lds128v(rL + R_SREM), r1 = lds128v(rL + R_SREM + 1024);
            if (VTP >= 1) PINM();
            if (VTP >= 2) { ldsm4t(vt00, rV + vo); ldsm4t(vt10, (rV ^ 32) + vo); }
            if (VTP >= 1) { ldsm4t(vt01, rV + vo + 2048); ldsm4t(vt11, (rV ^ 32) + vo + 2048); }
            float sv[10];
            sv[0] = l0.x + r0.x; sv[1] = l0.y + r0.y; sv[2] = l0.z + r0.z; sv[3] = l0.w + r0.w;
            sv[4] = l1.x + r1.x; sv[5] = l1.y + r1.y; sv[6] = l1.z + r1.z; sv[7] = l1.w + r1.w;
            sv[8] = ((l2.x + l3.x) + r2.x) + r3.x; sv[9] = ((l2.y + l3.y) + r2.y) + r3.y;
            float m = fmaxf(fmaxf(fmaxf(fmaxf(sv[8], sv[9]), sv[0]), fmaxf(fmaxf(sv[2], sv[3]), sv[1])), fmaxf(fmaxf(sv[4], sv[5]), fmaxf(sv[6], sv[7])));
            {
                const float m1 = __shfl_xor_sync(0xffffffffu, m, 1), m2 = __shfl_xor_sync(0xffffffffu, m, 2), m3 = __shfl_xor_sync(0xffffffffu, m, 3);
                m = fmaxf(fmaxf(m, m1), fmaxf(m2, m3));
            }
            TS(5, FU(m));
            const uint32_t ONE2 = 0x3f803f80u;
            float o0[4], o1[4], sm[4];
            const uint32_t pb0 = pack2(ex2(sv[0] - m), ex2(sv[1] - m)), pb1 = pack2(ex2(sv[2] - m), ex2(sv[3] - m));
            mma16816z(sm, ONE2, ONE2, ONE2, ONE2, pb0, pb1);
            MMAZ(o0, vt00, pb0, pb1); MMAZ(o1, vt10, pb0, pb1);
            const uint32_t z = (VDEP == 0 ? FU(m) : pb0) & zr;
            const uint32_t vok = mbar_test(sbu + R_BAR + 8 * MB_V + z, s & 1);
            const uint32_t rv = r8 + vok * 8;
            float2 va = lds64v(rv + R_VB - 8 + fo * 512);
            float2 vb = lds64v(rv + R_VB - 8 + fo * 512 + 256);
            float sig = __uint_as_float(lds32v_(sbu + R_MISC + 40));
            const uint32_t pb2 = pack2(ex2(sv[4] - m), ex2(sv[5] - m)), pb3 = pack2(ex2(sv[6] - m), ex2(sv[7] - m));
            mma16816(sm, ONE2, ONE2, ONE2, ONE2, pb2, pb3);
            const uint32_t pb4 = pack2(ex2(sv[8] - m), ex2(sv[9] - m));
            MMA(o0, vt01, pb2, pb3); MMA(o1, vt11, pb2, pb3);
            mma1688(sm, ONE2, ONE2, pb4);
            const float z0 = rcpf(sm[0]), z1 = rcpf(sm[1]);
#define PUT_O()                                                                                                   \
            {                                                                                                     \
                float a0[4] = {o0[0], o0[1], o0[2], o0[3]}, a1[4] = {o1[0], o1[1], o1[2], o1[3]};                 \
                mma1688(a0, FU(va.x), FU(va.y), pb4); mma1688(a1, FU(vb.x), FU(vb.y), pb4);                       \
                const float i0 = z0 * sig, i1 = z1 * sig;                                                         \
                stsm4t(rG + R_QP, pack2(a0[0] * i0, a0[1] * i1), pack2(a0[2] * i0, a0[3] * i1), pack2(a1[0] * i0, a1[1] * i1), pack2(a1[2] * i0, a1[3] * i1)); \
            }
            PUT_O()
            asm volatile("{\n.reg .pred p;\nsetp.ne.u32 p, %0, 0;\n@p bar.arrive 8, 256;\n}" :: "r"(vok) : "memory");
            if (__builtin_expect(__any_sync(0xffffffffu, vok == 0), 0)) {
                mbar_wait_p(sbu + R_BAR + 8 * MB_V, s & 1);
                va = lds64v(r8 + R_VB + fo * 512); vb = lds64v(r8 + R_VB + fo * 512 + 256);
                sig = __uint_as_float(lds32v_(sbu + R_MISC + 40));
                PUT_O()
                bar_arrive(8, 256);
                CNT(8);
            }
            TS(6, 0);
            const float r = __uint_as_float(0x7f000000u - FU(sig));
            cs = cexp * r * (fo >= 2 ? r : 1.f);
        }
        return false;
    };
    step(0, true);
#pragma unroll 1
    for (int s = 0;; s++) {
        if (s & 1) mbar_wait_p(sbu + R_BAR + 8 * (MB_FULL0 + (((s + 1) >> 1) & 1)), ((s + 1) >> 2) & 1);
        {
            const uint32_t a = rL + R_LT + 512 + 12 + fo * 512;
            sts32(a, lds32v_(a) + ((s & 1) ? ((s & 2) ? R_SLOT0 - R_SLOT1 - 4096 : R_SLOT1 - R_SLOT0 - 4096) : 4096));
        }
        auto early = [&]() {
            SCHED(13);
#pragma unroll
            for (int i = 0; i < NAX - NXL; i++) { lds_fragv(wq[i], rG + R_AX + 4096 * i); lds_fragv(wk[i], rG + R_AX + 4096 * i + 512); }
        };
        GATHER(0, , early();, )
        if (step(s + 1, false)) break;
    }
    CNT(9);
    if (rG == sbu) GT(cc * 8 + 4);
}

__device__ __forceinline__ void rec_b(uint32_t sb, int c, uint32_t epoch) {
    const int tid = threadIdx.x - WGB * 128, lane = tid & 31, f = tid >> 5;
    uint32_t wq[16][4], wk[16][4], wo[32][4];
    const int lrow = ((lane >> 4) << 3) + (lane & 7), lsel = (lane >> 3) & 1;
    const uint32_t rL = opaque(sb + lane * 16), rW = opaque(sb + lane * 16 + f * 16384);
    const uint32_t sbu = uni(sb), fo = uni(f), cc = uni(c), po = cc & 1, ep = uni(epoch);
    {
        mbar_wait(sb + R_BAR + 8 * MB_WO, 0);
        if (c == 7 && tid == 0) GT(1426);
        const uint32_t aO = sb + R_WO + f * 16384 + lrow * 128 + ((lsel ^ (lane & 7)) << 4);
#pragma unroll
        for (int i = 0; i < 32; i++) {
            const int tile = (i >> 4) * 2 + (i & 1), kk = (i >> 1) & 7;
            ldsm4t(wo[i], (aO ^ (32 * tile)) + kk * 2048);
        }
        const float no = frag_norm2(wo);
        if (lane == 0) sts32(sb + R_MISC + 80 + f * 4, FU(no));
        __syncwarp();
        bar_sync(0, 256);
        if (tid == 0) {
            const float4 a = lds128(sb + R_MISC + 64), b = lds128(sb + R_MISC + 80);
            stg4(&g_f.norm[c], make_uint4(FU((a.x + a.y) + (a.z + a.w)), epoch, FU((b.x + b.y) + (b.z + b.w)), epoch));
        }
        __syncwarp();
#pragma unroll
        for (int i = NRW; i < 32; i++) sts128u(rW + R_WO + i * 512, wo[i][0], wo[i][1], wo[i][2], wo[i][3]);
        mbar_wait(sb + R_BAR + 8 * MB_W1, 0);
        if (c == 7 && tid == 0) GT(1422);
        __syncwarp();
#pragma unroll
        for (int kk = 0; kk < 16; kk++) { const uint32_t a = sb + R_QK1 + wrow_off(kk, 2 * f + lsel); ldsm4t(wq[kk], a); ldsm4t(wk[kk], a + 32768); }
        bar_sync(13, 128);
#pragma unroll
        for (int i = 0; i < 16; i++) {
            sts128u(rW + R_QK1 + i * 1024, wq[i][0], wq[i][1], wq[i][2], wq[i][3]);
            sts128u(rW + R_QK1 + i * 1024 + 512, wk[i][0], wk[i][1], wk[i][2], wk[i][3]);
        }
        __syncwarp();
    }
    const uint64_t gx = xpage();
    const uint32_t ghi = uni((uint32_t)(gx >> 32)), glo = uni((uint32_t)gx);
    TSDECL;
#pragma unroll 1
    for (int s = 0;; s++) {
        bar_sync(2, 256);
        float q0[4], k0[4];
        g1<BNB, SMB>(q0, k0, wq, wk, rL + R_MEMB + 4096, sbu - s, [&](int i, const uint32_t* c_) {
            if (i == 0) TS(0, c_[0]);
            if (i >= 2 && i < 6) {
#pragma unroll
                for (int n = NRW + (i - 2) * E0 / 4; n < NRW + (i - 1) * E0 / 4; n++) lds_fragv(wo[n], rW + R_WO + n * 512);
            }
            if (i == IV) bar_arrive(GOBAR, 96);
        });
        stsm4t(rL + fo * 1024 + R_QP + 512, pack2(q0[0], q0[1]), pack2(q0[2], q0[3]), pack2(k0[0], k0[1]), pack2(k0[2], k0[3]));
        bar_arrive(3, 256);
        TS(1, FU(k0[3]));
        const uint32_t so = aslot(s);
        uint2 lt;
        { const float2 t = lds64v(rL + R_LT + 8); lt.x = FU(t.x); lt.y = FU(t.y); }
        const uint32_t sel = 0x3210u + (lt.x & 16) * 0x440u;
        uint32_t* pm = (uint32_t*)mkptr(((glo + acc_base(po * 4 + fo)) ^ so) + lt.x, ghi);
        uint32_t* px = (uint32_t*)mkptr(((glo + ext_base(po * 4 + fo)) ^ so) + lt.y, ghi);
        if (s == NSEG - 1) break;
        {
            const uint32_t z = lt.x & 1;
#pragma unroll
            for (int n = NRW; n < NRW + E0 + E1 + E2 + E3; n++) {
                const int d = n - (n < NRW + T2N ? TRK + 1 : TRK);
                lds_fragv(wo[n], (d >= NRW ? or_and(rW, wo[d][0], z) : rW) + R_WO + n * 512);
            }
        }
        TS(2, wo[NRW + E0 + E1 + E2 + E3 - 1][0]);
        SCHED(4);
        bar_sync(8, 256);
        {
            float o[4][4];
            uint32_t b[4][4];
#pragma unroll
            for (int i = 0; i < 4; i++) ldsm4(b[i], rL + R_QP + i * 1024);
            PINM();
#pragma unroll
            for (int n = NRW + E0 + E1 + E2 + E3; n < 32; n++) lds_fragv(wo[n], rW + R_WO + n * 512);
            float p[4][4];
#define G2_STEP(o, hf, kk) _Pragma("unroll") for (int i = 0; i < 2; i++) MMAF((kk) < 2, o[((kk) & 1) * 2 + i], wo[(hf) * 16 + (kk) * 2 + i], b[(kk) >> 1][((kk) & 1) * 2], b[(kk) >> 1][((kk) & 1) * 2 + 1])
#define G2_RED(o, wl, h) const uint32_t wl = packh2(o[1][2] + o[3][2], o[1][3] + o[3][3]);                            \
                asm volatile("red.relaxed.gpu.global.add.noftz.v4.f16x2 [%0], {%1,%2,%3,%4};" :: "l"(pm + (h) * 16),  \
                    "r"(packh2(o[0][0] + o[2][0], o[0][1] + o[2][1])), "r"(packh2(o[0][2] + o[2][2], o[0][3] + o[2][3])), \
                    "r"(packh2(o[1][0] + o[3][0], o[1][1] + o[3][1])), "r"(prmt(wl, HONE2, (h) ? sel : sel ^ 0x4400u)) : "memory")
            if (G2V == 1) SCHED(11);
#pragma unroll
            for (int kk = 0; kk < 8; kk++) { G2_STEP(o, 0, kk); }
            TS(7, b[0][0]);
            if (G2V == 0) SCHED(11);
            else {
#pragma unroll
                for (int i = 0; i < 4; i++) wo[16 + i][0] = or_and(wo[16 + i][0], FU(o[i][0]), lt.x & 1);
            }
#pragma unroll
            for (int kk = 0; kk < G2K; kk++) { G2_STEP(p, 1, kk); }
#pragma unroll
            for (int i = 0; i < NB0; i++) { lds_fragv(wq[i], rW + R_QK1 + i * 1024); lds_fragv(wk[i], rW + R_QK1 + i * 1024 + 512); }
            G2_RED(o, w3, 0);
            TS(8, w3);
            if (G2V == 0) SCHED(12);
#pragma unroll
            for (int kk = G2K; kk < 8; kk++) { G2_STEP(p, 1, kk); }
            G2_RED(p, w7, 1);
            asm volatile("red.relaxed.gpu.global.add.noftz.f16x2 [%0], %1;" :: "l"(px), "r"(prmt((w3 & 0xffff0000u) | 0x3c00u, w7, sel)) : "memory");
            TS(9, w7);
        }
        bar_arrive(5, 384);
        asm volatile("{\n.reg .pred p;\nsetp.eq.u32 p, %0, %1;\n@p mbarrier.arrive.expect_tx.shared::cta.b64 _, [%2], 1536;\n}"
                     :: "r"(rW), "r"(sbu), "r"(sbu + R_BAR + 8 * MB_S) : "memory");
        const uint32_t tb = clk32();
        TSACC();
        spin_until(tb, DB);
#pragma unroll
        for (int i = NB0; i < NBR; i++) {
            if (i == NB1) spin_until(tb, DP + DB2);
            lds_fragv(wq[i], rW + R_QK1 + i * 1024); lds_fragv(wk[i], rW + R_QK1 + i * 1024 + 512);
        }
    }
}

#undef lds_fragv
__device__ __forceinline__ void rec_first_loads(uint32_t sb, int c, const Maps& maps) {
    const uint32_t bar = sb + R_BAR;
    const int F0 = c * 64;
    mbar_expect_tx(bar + 8 * MB_W0, 65536); mbar_expect_tx(bar + 8 * MB_WO, 65536); mbar_expect_tx(bar + 8 * MB_WV, 65536);
    tma2d(sb + R_QK1, &maps.wv, F0, 0, bar + 8 * MB_WV); tma2d(sb + R_QK1 + 32768, &maps.wv, F0, 256, bar + 8 * MB_WV);
    tma2d(sb + R_T + 32768, &maps.wk, F0, 0, bar + 8 * MB_W0);
    if (!LORD) {
        for (int i = 0; i < 4; i++) tma2d(sb + R_WO + i * 16384, &maps.wo, (c & 1) * 256 + i * 64, (c >> 1) * 128, bar + 8 * MB_WO);
        tma2d(sb + R_T, &maps.wq, F0, 0, bar + 8 * MB_W0);
    }
    mbar_expect_tx(bar + 8 * MB_S, 1536);
}
__device__ __forceinline__ void rec_c(uint32_t sb, int c, const bf16* __restrict__ mem0, const Maps& maps, uint32_t epoch) {
    const int tid = threadIdx.x - WGC * 128, lane = tid & 31, u = tid >> 5;
    const uint32_t bar = sb + R_BAR;
    const int lrow = ((lane >> 4) << 3) + (lane & 7), lsel = (lane >> 3) & 1;
    const int kh = u >> 1, j = u & 1;
    uint32_t wv[32][4], mx, my = 0, mz = 0;
    {
        if (u == 0) {
            sts128u(sb + lane * 16 + R_LT, (lane >> 3) * 256 + (lane & 7) * 16, ((lane >> 2) & 1) * XHS + (lane >> 4) * XSS + (lane & 8) * 2 + (lane & 2) * 4,
                    (lane >> 2) * 256 + (lane & 3) * 16, (lane & 1) * XHS + ((lane >> 3) & 1) * XSS + (lane & 6) * 4 + (lane >> 4) * 4);
        }
        mbar_wait(bar + 8 * MB_WV, 0);
        if (c == 7 && tid == 0) GT(1425);
        if (LORD && tid == 32) {
            for (int i = 0; i < 4; i++) tma2d(sb + R_WO + i * 16384, &maps.wo, (c & 1) * 256 + i * 64, (c >> 1) * 128, bar + 8 * MB_WO);
            tma2d(sb + R_T, &maps.wq, c * 64, 0, bar + 8 * MB_W0);
        }
        __syncwarp();
#pragma unroll
        for (int kk = 0; kk < 16; kk++) {
            const uint32_t aa = sb + R_QK1 + kh * 32768 + wrow_off(kk, 4 * j + 2 * kh + lsel);
            ldsm4t(wv[kk], aa); ldsm4t(wv[16 + kk], aa ^ 32);
        }
        {
            uint32_t x = 0;
#pragma unroll
            for (int i = 0; i < 32; i++) x ^= wv[i][0];
            sts32(sb + R_MISC + 96 + u * 4, __reduce_xor_sync(0xffffffffu, x));
        }
        bar_sync(9, 128);
        if (c == 7 && tid == 0) GT(1423);
        if (tid == 0) {
            mbar_expect_tx(bar + 8 * MB_W1, 65536);
            tma2d(sb + R_QK1 + 32768, &maps.wk, c * 64, 256, bar + 8 * MB_W1); tma2d(sb + R_QK1, &maps.wq, c * 64, 256, bar + 8 * MB_W1);
        }
        __syncwarp();
        const float nv = frag_norm2(wv);
        if (lane == 0) sts32(sb + R_MISC + 64 + u * 4, FU(nv));
        __syncwarp();
        bar_arrive(0, 256);
        mx = put_mem0(sb, 4 + u, mem0);
    }
    const uint32_t rL = opaque(sb + lane * 16), rG = opaque(sb + lane * 16 + u * 1024);
    const uint32_t sbu = uni(sb), fo = uni(u), cc = uni(c), ep = uni(epoch);
    const uint64_t gx = xpage();
    const uint32_t ghi = uni((uint32_t)(gx >> 32)), glo = uni((uint32_t)gx);
    constexpr int CX = R_AX + NAX * 4096;
    static_assert(NAX + NCX <= 6, "AX");
#pragma unroll
    for (int i = 0; i < NCX; i++) {
        sts128u(rG + CX + 4096 * i, wv[i][0], wv[i][1], wv[i][2], wv[i][3]);
        sts128u(rG + CX + 4096 * i + 512, wv[16 + i][0], wv[16 + i][1], wv[16 + i][2], wv[16 + i][3]);
    }
    __syncwarp();
    TSDECL;
    uint32_t rpb = 0x3f800000u;
    bar_arrive(2, 256);
    uint32_t kvq = ~ep;
    auto ring = [&](int s) {
        uint32_t n = 0;
#pragma unroll 1
        while (!__all_sync(0xffffffffu, kvq == ep)) {
            kvq = ldg_rlx(&g_f.kv[(s + 2) >> 1][cc >> 1][(rL >> 4) & 1]);
            if (++n > SPIN_LIMIT) { ABORT(6); break; }
        }
        if (rL == sbu) load_slot(sbu, cc, (s + 2) >> 1, maps);
        __syncwarp();
    };
    if (fo == 3) { ring(-2); if (cc == 7 && rL == sbu) GT(1427); }
#pragma unroll 1
    for (int s = 0;; s++) {
        PUT_MAX(rL, 4 + fo)
        if (fo != 0) bar_arrive(15, 256);
        if (fo == 3 && !(s & 1) && s > 0 && s + 2 < NSEG) ring(s);
#pragma unroll
        for (int i = NCX - NCL; i < NCX; i++) { lds_fragv(wv[i], rG + CX + 4096 * i); lds_fragv(wv[16 + i], rG + CX + 4096 * i + 512); }
        if (fo == 0) {
                bar_sync(15, 256);
                if (s == 0) {
                    const uint32_t* np = (const uint32_t*)&g_f.norm[0] + ((rL ^ sbu) >> 2);
                    uint4 r, q; uint32_t n = 0;
#pragma unroll 1
                    while (true) {
                        r = ldg_rlx4(np); q = ldg_rlx4(np + 128);
                        const uint2 z = ldg_rlx2(&g_f.xn[(rL ^ sbu) >> 3]);
                        if (__all_sync(0xffffffffu, r.y == ep && r.w == ep && q.y == ep && q.w == ep && z.x == ep && z.y == ep)) break;
                        if (++n > SPIN_LIMIT) { ABORT(5); break; }
                    }
                    float nv = __uint_as_float(r.x) + __uint_as_float(q.x), no = __uint_as_float(r.z) + __uint_as_float(q.z);
#pragma unroll
                    for (int o = 16; o; o >>= 1) { nv += __shfl_xor_sync(0xffffffffu, nv, o); no += __shfl_xor_sync(0xffffffffu, no, o); }
                    const int lc = ((int)(FU(nv) >> 23) + (int)(FU(no) >> 23) - 252 + 9 + 1) >> 1;
                    sts32(sbu + R_MISC + 32, 140 - lc);
                    __syncwarp();
                }
                const uint4 ma = lds128uv(rL + R_STG + 1024), mb = lds128uv(rL + R_STG + 1536);
                const uint32_t m_ = amax2b(amax2b(amax2b(ma.x, ma.y), amax2b(ma.z, ma.w)), amax2b(amax2b(mb.x, mb.y), amax2b(mb.z, mb.w)));
                const int em = (int)(__reduce_max_sync(0xffffffffu, amax2b(m_, m_ << 16) & 0x7f800000u) >> 23) + (int)(rpb >> 23) - 127;
                const int es = min(max((int)lds32v_(sbu + R_MISC + 32) - max(em, 127), -60), 60);
                sts32(sbu + R_MISC + 40, (127 + es) << 23);
                TS(4, es);
        }
        bar_sync(GOBAR, 96);
        float v0[4], v1[4];
        g1<CNB, SMC>(v0, v1, wv, wv + 16, rL + R_MEMB + (fo >> 1) * 4096, sbu - s, [&](int i, const uint32_t* c_) { if (i == 0) TS(0, c_[0]); });
        TS(1, FU(v1[3]));
        const uint32_t l16 = (rL ^ sbu) | (lds32v_(rL + R_LT + 4) & 1);
        const uint32_t r8 = sbu + (l16 >> 1);
        {
            sts128(rL + R_VRED + fo * 512, v1[0], v1[1], v1[2], v1[3]);
            const uint32_t d = r8 + R_VB + ((cc & 1) * 4 + (fo & 1) * 2 + (fo >> 1)) * 256;
            const uint32_t dr = xorv(d, 0x01000000u), br = xorv(sbu + R_BAR + 8 * MB_V, 0x01000000u);
            bar_sync(6 + (fo & 1), 64);
            const float4 a0 = lds128(rL + R_VRED + (fo ^ 2) * 512);
            const float rp = __uint_as_float(rpb);
            const uint32_t w0 = pack2((v0[0] + a0.x) * rp, (v0[1] + a0.y) * rp), w1 = pack2((v0[2] + a0.z) * rp, (v0[3] + a0.w) * rp);
            st_async2(dr, w0, w1, br);
            TS(3, w1);
            sts64(d, __uint_as_float(w0), __uint_as_float(w1));
            if (fo != 1) bar_arrive(9, 192);
            __syncwarp();
            asm volatile("{\n.reg .pred p;\nsetp.eq.u32 p, %0, %1;\n@p mbarrier.arrive.expect_tx.shared::cta.b64 _, [%2], 256;\n}"
                         :: "r"(rL), "r"(sbu), "r"(sbu + R_BAR + 8 * MB_V) : "memory");
        }
        if (fo == 1) {
            bar_sync(9, 192);
            uint8_t* dst = (uint8_t*)&g_KVf[s][cc >> 1][(cc & 1) * 256] + l16;
            const uint32_t r2 = prmt(rpb, 0, 0x3232u);
#pragma unroll
            for (int i = 0; i < 2; i++) {
                const uint4 a = lds128uv(rL + R_STG + i * 512);
                stg4(dst + i * 512, make_uint4(~hmul2b(a.x, r2), ~hmul2b(a.y, r2), ~hmul2b(a.z, r2), ~hmul2b(a.w, r2)));
                const float2 b0 = lds64v(r8 + R_VB + (cc & 1) * 1024 + i * 512), b1 = lds64v(r8 + R_VB + (cc & 1) * 1024 + i * 512 + 256);
                stg4(dst + 2048 + i * 512, make_uint4(~FU(b0.x), ~FU(b0.y), ~FU(b1.x), ~FU(b1.y)));
            }
            __syncwarp();
            if (l16 == 0) { stg_rlx(&g_f.rec[cc >> 1][cc & 1], (ep << 8) | (s + 1)); if (s == NSEG - 1) GT(1500 + cc); }
            __syncwarp();
        } else {
            if (fo == 2) {
                if (l16 < 144) stg4((void*)mkptr((glo + zero_off(cc, l16 >> 4)) ^ aslot(s + 4), ghi), make_uint4(0, 0, 0, 0));
                __syncwarp();
            } else if (fo == 3) {
                kvq = ldg_rlx(&g_f.kv[min((s + 3) >> 1, NT - 1)][cc >> 1][(l16 >> 4) & 1]);
                if (s == 0) ring(s);
            }
        }
        if (s == NSEG - 1) break;
        auto early = [&]() {
#pragma unroll
            for (int i = 0; i < NCX - NCL; i++) { lds_fragv(wv[i], rG + CX + 4096 * i); lds_fragv(wv[16 + i], rG + CX + 4096 * i + 512); }
        };
        GATHER(1, , early(); rpb = 0x7f000000u - lds32v_(sbu + R_MISC + 40);, bar_arrive(2, 256);)
    }
}

__device__ __forceinline__ bool cand_better(float v, int i, float bv, int bi) { return v > bv || (v == bv && i < bi); }

constexpr int G_W = 0;
constexpr int G_RING = 131072;
constexpr int G_BUF = 163840;
constexpr int G_BAR = 229376;
constexpr int G_SMEM = G_BAR + 512;
enum { GB_FULL = 0, GB_EMPTY = GB_FULL + 8, GB_KV = GB_EMPTY + 8, GB_STG = GB_KV + 2, GB_FREE = GB_STG + 2, GB_XN = GB_FREE + 2, GB_T1D, GB_P0, GB_VV, GB_KVF = GB_VV + 2, GB_VF, GB_N };
constexpr int SMEM_TOTAL = 232448;

__device__ __forceinline__ void wgmma_n128(float* d, uint64_t da, uint64_t db, int scale_d) {
    asm volatile("{\n.reg .pred p;\nsetp.ne.b32 p, %66, 0;\n"
        "wgmma.mma_async.sync.aligned.m64n128k16.f32.bf16.bf16 "
        "{%0,%1,%2,%3,%4,%5,%6,%7,%8,%9,%10,%11,%12,%13,%14,%15,%16,%17,%18,%19,%20,%21,%22,%23,%24,%25,%26,%27,%28,%29,%30,%31,"
        "%32,%33,%34,%35,%36,%37,%38,%39,%40,%41,%42,%43,%44,%45,%46,%47,%48,%49,%50,%51,%52,%53,%54,%55,%56,%57,%58,%59,%60,%61,%62,%63}, "
        "%64, %65, p, 1, 1, 0, 1;\n}"
        : "+f"(d[0]), "+f"(d[1]), "+f"(d[2]), "+f"(d[3]), "+f"(d[4]), "+f"(d[5]), "+f"(d[6]), "+f"(d[7]), "+f"(d[8]), "+f"(d[9]), "+f"(d[10]), "+f"(d[11]),
          "+f"(d[12]), "+f"(d[13]), "+f"(d[14]), "+f"(d[15]), "+f"(d[16]), "+f"(d[17]), "+f"(d[18]), "+f"(d[19]), "+f"(d[20]), "+f"(d[21]), "+f"(d[22]), "+f"(d[23]),
          "+f"(d[24]), "+f"(d[25]), "+f"(d[26]), "+f"(d[27]), "+f"(d[28]), "+f"(d[29]), "+f"(d[30]), "+f"(d[31]), "+f"(d[32]), "+f"(d[33]), "+f"(d[34]), "+f"(d[35]),
          "+f"(d[36]), "+f"(d[37]), "+f"(d[38]), "+f"(d[39]), "+f"(d[40]), "+f"(d[41]), "+f"(d[42]), "+f"(d[43]), "+f"(d[44]), "+f"(d[45]), "+f"(d[46]), "+f"(d[47]),
          "+f"(d[48]), "+f"(d[49]), "+f"(d[50]), "+f"(d[51]), "+f"(d[52]), "+f"(d[53]), "+f"(d[54]), "+f"(d[55]), "+f"(d[56]), "+f"(d[57]), "+f"(d[58]), "+f"(d[59]),
          "+f"(d[60]), "+f"(d[61]), "+f"(d[62]), "+f"(d[63])
        : "l"(da), "l"(db), "r"(scale_d));
}

__device__ __forceinline__ constexpr uint32_t slot_off(int slot) {
    return slot < 2 ? G_RING + slot * 16384 : G_BUF + (slot & 1) * 32768 + (slot < 4 ? 16384 : 0);
}
constexpr int PO = (HSPLIT / 2) & 1;
template <int NSLOT, class F>
__device__ __forceinline__ void gemm_tile(float* acc, uint32_t sb, int tile, int it, int wg, bool pass, uint32_t l0, F&& hook) {
    const uint32_t bar = sb + G_BAR;
    bar_sync(3 + wg, 256);
    int prev = 0;
#pragma unroll
    for (int k = 0; k < 4; k++) {
        const int n = tile * 4 + k, slot = NSLOT == 4 ? k : n % NSLOT;
        const uint32_t sz = sb + (((it + k) << 4) & sb & 0x3f0);
        const uint64_t da = desc_sw128(sz + slot_off(slot), 16, 1024), db0 = desc_sw128(sz + G_W, 65536, 1024);
        mbar_wait_p(bar + 8 * (GB_FULL + slot), NSLOT == 4 ? (tile & 1) : ((n / NSLOT) & 1));
        if (k == 3 && pass) bar_arrive(3 + (wg ^ 1), 256);
        asm volatile("wgmma.fence.sync.aligned;" ::: "memory");
#pragma unroll
        for (int kk = 0; kk < 4; kk++) wgmma_n128(acc, da + kk * 2, db0 + k * 1024 + kk * 128, (k | kk) != 0);
        asm volatile("wgmma.commit_group.sync.aligned;" ::: "memory");
        if (k > 0) {
            asm volatile("wgmma.wait_group.sync.aligned 1;" ::: "memory");
            mbar_arrive2_if(bar + 8 * (GB_EMPTY + prev), l0);
        }
#pragma unroll
        for (int kk = 0; kk < 4; kk++) wgmma_n128(acc, da + 512 + kk * 2, db0 + k * 1024 + 512 + kk * 128, 1);
        asm volatile("wgmma.commit_group.sync.aligned;" ::: "memory");
        if (k == 1) hook();
        prev = slot;
    }
    asm volatile("wgmma.wait_group.sync.aligned 0;" ::: "memory");
    mbar_arrive2_if(bar + 8 * (GB_EMPTY + prev), l0);
}
__device__ __forceinline__ void stage_bf16(const float* acc, uint32_t buf, float s0, float s1) {
    const int lane = threadIdx.x & 31, wq = (threadIdx.x >> 5) & 3;
    const int row = wq * 16 + (lane & 7) + ((lane >> 3) & 1) * 8;
    const uint32_t base = buf + row * 128;
#pragma unroll
    for (int j = 0; j < 16; j += 2) {
        const int ch = (j & 7) + (lane >> 4);
        stsm4(base + (j >> 3) * 8192 + ((ch ^ (row & 7)) << 4),
              pack2(acc[4 * j] * s0, acc[4 * j + 1] * s0), pack2(acc[4 * j + 2] * s1, acc[4 * j + 3] * s1),
              pack2(acc[4 * j + 4] * s0, acc[4 * j + 5] * s0), pack2(acc[4 * j + 6] * s1, acc[4 * j + 7] * s1));
    }
}

__device__ __forceinline__ void store_perm(const float* acc, bf16* dst, int ld, float s0, float s1, uint32_t m) {
#pragma unroll
    for (int i = 0; i < 4; i++) {
        const float* a = acc + 16 * i;
        stg4(dst + i * 32, make_uint4(pack2(a[0] * s0, a[1] * s0) ^ m, pack2(a[4] * s0, a[5] * s0) ^ m, pack2(a[8] * s0, a[9] * s0) ^ m, pack2(a[12] * s0, a[13] * s0) ^ m));
        stg4(dst + 8 * ld + i * 32, make_uint4(pack2(a[2] * s1, a[3] * s1) ^ m, pack2(a[6] * s1, a[7] * s1) ^ m, pack2(a[10] * s1, a[11] * s1) ^ m, pack2(a[14] * s1, a[15] * s1) ^ m));
    }
}
template <int ACC>
__device__ __forceinline__ void wgmma_rs64(float* d, const uint32_t* a, uint64_t db) {
    asm volatile("{\n.reg .pred p;\nsetp.ne.b32 p, %37, 0;\n"
        "wgmma.mma_async.sync.aligned.m64n64k16.f32.bf16.bf16 {%0,%1,%2,%3,%4,%5,%6,%7,%8,%9,%10,%11,%12,%13,%14,%15,%16,%17,%18,%19,%20,%21,%22,%23,%24,%25,%26,%27,%28,%29,%30,%31}, {%32,%33,%34,%35}, %36, p, 1, 1, 0;\n}"
        : "+f"(d[0]), "+f"(d[1]), "+f"(d[2]), "+f"(d[3]), "+f"(d[4]), "+f"(d[5]), "+f"(d[6]), "+f"(d[7]), "+f"(d[8]), "+f"(d[9]), "+f"(d[10]), "+f"(d[11]), "+f"(d[12]), "+f"(d[13]), "+f"(d[14]), "+f"(d[15]), "+f"(d[16]), "+f"(d[17]), "+f"(d[18]), "+f"(d[19]), "+f"(d[20]), "+f"(d[21]), "+f"(d[22]), "+f"(d[23]), "+f"(d[24]), "+f"(d[25]), "+f"(d[26]), "+f"(d[27]), "+f"(d[28]), "+f"(d[29]), "+f"(d[30]), "+f"(d[31])
        : "r"(a[0]), "r"(a[1]), "r"(a[2]), "r"(a[3]), "l"(db), "n"(ACC));
}
template <int ACC>
__device__ __forceinline__ void wgmma_rs128t(float* d, const uint32_t* a, uint64_t db) {
    asm volatile("{\n.reg .pred p;\nsetp.ne.b32 p, %69, 0;\n"
        "wgmma.mma_async.sync.aligned.m64n128k16.f32.bf16.bf16 {%0,%1,%2,%3,%4,%5,%6,%7,%8,%9,%10,%11,%12,%13,%14,%15,%16,%17,%18,%19,%20,%21,%22,%23,%24,%25,%26,%27,%28,%29,%30,%31,%32,%33,%34,%35,%36,%37,%38,%39,%40,%41,%42,%43,%44,%45,%46,%47,%48,%49,%50,%51,%52,%53,%54,%55,%56,%57,%58,%59,%60,%61,%62,%63}, {%64,%65,%66,%67}, %68, p, 1, 1, 1;\n}"
        : "+f"(d[0]), "+f"(d[1]), "+f"(d[2]), "+f"(d[3]), "+f"(d[4]), "+f"(d[5]), "+f"(d[6]), "+f"(d[7]), "+f"(d[8]), "+f"(d[9]), "+f"(d[10]), "+f"(d[11]), "+f"(d[12]), "+f"(d[13]), "+f"(d[14]), "+f"(d[15]), "+f"(d[16]), "+f"(d[17]), "+f"(d[18]), "+f"(d[19]), "+f"(d[20]), "+f"(d[21]), "+f"(d[22]), "+f"(d[23]), "+f"(d[24]), "+f"(d[25]), "+f"(d[26]), "+f"(d[27]), "+f"(d[28]), "+f"(d[29]), "+f"(d[30]), "+f"(d[31]), "+f"(d[32]), "+f"(d[33]), "+f"(d[34]), "+f"(d[35]), "+f"(d[36]), "+f"(d[37]), "+f"(d[38]), "+f"(d[39]), "+f"(d[40]), "+f"(d[41]), "+f"(d[42]), "+f"(d[43]), "+f"(d[44]), "+f"(d[45]), "+f"(d[46]), "+f"(d[47]), "+f"(d[48]), "+f"(d[49]), "+f"(d[50]), "+f"(d[51]), "+f"(d[52]), "+f"(d[53]), "+f"(d[54]), "+f"(d[55]), "+f"(d[56]), "+f"(d[57]), "+f"(d[58]), "+f"(d[59]), "+f"(d[60]), "+f"(d[61]), "+f"(d[62]), "+f"(d[63])
        : "r"(a[0]), "r"(a[1]), "r"(a[2]), "r"(a[3]), "l"(db), "n"(ACC));
}
__device__ __forceinline__ void attention_tile(float* acc, uint32_t sb, int tile, int h, int wg, int wq, uint32_t l0, uint32_t epoch, uint4* km, uint4* vm) {
    const uint32_t buf = sb + G_BUF + ((tile << 4) & sb & 0x3f0);
    const int lane = threadIdx.x & 31, g = lane >> 2, t = lane & 3;
    const int sg = wq >> 1, hf = wq & 1, seg = tile * 2 + sg;
    uint32_t qf[8][4];
#pragma unroll
    for (int kk = 0; kk < 8; kk++) {
        qf[kk][0] = pack2(acc[8 * kk], acc[8 * kk + 1]); qf[kk][1] = pack2(acc[8 * kk + 2], acc[8 * kk + 3]);
        qf[kk][2] = pack2(acc[8 * kk + 4], acc[8 * kk + 5]); qf[kk][3] = pack2(acc[8 * kk + 6], acc[8 * kk + 7]);
    }
    uint32_t* kvf = &g_KVf[seg][h][lane * 4];
    auto kv_valid = [&]() {
        uint32_t mn = 0xffffffffu;
#pragma unroll
        for (int i = 0; i < 4; i++) mn = min(min(min(mn, min(km[i].x, km[i].y)), min(km[i].z, km[i].w)), min(min(vm[i].x, vm[i].y), min(vm[i].z, vm[i].w)));
        return __all_sync(0xffffffffu, mn != 0);
    };
    float sc[5][4];
    auto mem_scores = [&]() {
        float sb_[4];
#pragma unroll
        for (int i = 0; i < 4; i++) { MMAF(i == 0, sc[4], qf[2 * i], ~km[i].x, ~km[i].y); MMAF(i == 0, sb_, qf[2 * i + 1], ~km[i].z, ~km[i].w); }
#pragma unroll
        for (int i = 0; i < 4; i++) sc[4][i] += sb_[i];
    };
    mbar_wait_p(sb + G_BAR + 8 * (GB_KV + wg), (tile >> 1) & 1);
    if (h == 5 && (threadIdx.x & 127) == 0 && tile < 6) GT(1750 + tile * 8 + 2);
    bool fast;
    {
        const uint64_t dk = desc_sw128(buf, 16, 1024);
        asm volatile("wgmma.fence.sync.aligned;" ::: "memory");
#pragma unroll
        for (int kk = 0; kk < 8; kk++) {
            if (kk == 0) wgmma_rs64<0>(acc, qf[kk], dk); else wgmma_rs64<1>(acc, qf[kk], dk + (kk >> 2) * 512 + (kk & 3) * 2);
        }
        asm volatile("wgmma.commit_group.sync.aligned;" ::: "memory");
        mem_scores();
        fast = kv_valid();
        asm volatile("wgmma.wait_group.sync.aligned 0;" ::: "memory");
        mbar_arrive_if(sb + G_BAR + 8 * GB_KVF, l0);
#pragma unroll
        for (int i = 0; i < 32; i++) asm volatile("" : "+f"(acc[i]) :: "memory");
#pragma unroll
        for (int b = 0; b < 4; b++)
#pragma unroll
            for (int i = 0; i < 4; i++) sc[b][i] = sg ? acc[16 + 4 * b + i] : acc[4 * b + i];
#pragma unroll
        for (int i = 0; i < 4; i++) sc[4][i] = fast ? sc[4][i] : -INFINITY;
    }
    const float cexp = 0.08838834764831845f * 1.4426950408889634f;
    const int r0 = hf * 16 + g, r1 = r0 + 8;
#pragma unroll
    for (int b = 0; b < 4; b++) {
        const int j = b * 8 + 2 * t;
        if (j > r0) sc[b][0] = -INFINITY;
        if (j + 1 > r0) sc[b][1] = -INFINITY;
        if (j > r1) sc[b][2] = -INFINITY;
        if (j + 1 > r1) sc[b][3] = -INFINITY;
    }
    float m0 = -INFINITY, m1 = -INFINITY;
#pragma unroll
    for (int b = 0; b < 5; b++) { m0 = fmaxf(m0, fmaxf(sc[b][0], sc[b][1])); m1 = fmaxf(m1, fmaxf(sc[b][2], sc[b][3])); }
    m0 = fmaxf(m0, __shfl_xor_sync(0xffffffffu, m0, 1)); m1 = fmaxf(m1, __shfl_xor_sync(0xffffffffu, m1, 1));
    m0 = fmaxf(m0, __shfl_xor_sync(0xffffffffu, m0, 2)); m1 = fmaxf(m1, __shfl_xor_sync(0xffffffffu, m1, 2));
    float z0 = 0.f, z1 = 0.f;
    uint32_t p0, p1;
    {
        const float c0 = -m0 * cexp, c1 = -m1 * cexp;
        uint32_t pf[5][2];
#pragma unroll
        for (int b = 0; b < 5; b++) {
            pf[b][0] = pack2(ex2(fmaf(sc[b][0], cexp, c0)), ex2(fmaf(sc[b][1], cexp, c0)));
            pf[b][1] = pack2(ex2(fmaf(sc[b][2], cexp, c1)), ex2(fmaf(sc[b][3], cexp, c1)));
        }
        p0 = pf[4][0]; p1 = pf[4][1];
        uint32_t pa[4][4];
#pragma unroll
        for (int kk = 0; kk < 4; kk++)
#pragma unroll
            for (int i = 0; i < 4; i++) pa[kk][i] = (kk >> 1) == sg ? pf[(kk & 1) * 2 + (i >> 1)][i & 1] : 0u;
        const uint64_t dv = desc_sw128(buf + 32768, 8192, 1024);
        mbar_wait_p(sb + G_BAR + 8 * (GB_VV + wg), (tile >> 1) & 1);
        asm volatile("wgmma.fence.sync.aligned;" ::: "memory");
#pragma unroll
        for (int kk = 0; kk < 4; kk++) { if (kk == 0) wgmma_rs128t<0>(acc, pa[kk], dv); else wgmma_rs128t<1>(acc, pa[kk], dv + kk * 128); }
        asm volatile("wgmma.commit_group.sync.aligned;" ::: "memory");
#pragma unroll
        for (int b = 0; b < 5; b++) { z0 += bf_lo(pf[b][0]) + bf_hi(pf[b][0]); z1 += bf_lo(pf[b][1]) + bf_hi(pf[b][1]); }
        asm volatile("wgmma.wait_group.sync.aligned 0;" ::: "memory");
#pragma unroll
        for (int i = 0; i < 64; i++) asm volatile("" : "+f"(acc[i]) :: "memory");
    }
    mbar_arrive_if(sb + G_BAR + 8 * GB_VF, l0);
    if (h == 5 && (threadIdx.x & 127) == 0 && tile < 6) GT(1750 + tile * 8 + 3);
    if (!fast) {
        wait_rec(&g_f.rec[h][0], epoch, seg + 1);
        if (seg == 63 && (threadIdx.x & 63) == 0) GT(1570 + h);
        uint32_t n = 0;
#pragma unroll 1
        do {
#pragma unroll
            for (int i = 0; i < 4; i++) { km[i] = ldg_rlx4(kvf + i * 128); vm[i] = ldg_rlx4(kvf + 512 + i * 128); }
            if (++n > SPIN_LIMIT) { ABORT(4); break; }
        } while (!kv_valid());
        mem_scores();
        float n0 = fmaxf(sc[4][0], sc[4][1]), n1 = fmaxf(sc[4][2], sc[4][3]);
        n0 = fmaxf(n0, __shfl_xor_sync(0xffffffffu, n0, 1)); n1 = fmaxf(n1, __shfl_xor_sync(0xffffffffu, n1, 1));
        n0 = fmaxf(n0, __shfl_xor_sync(0xffffffffu, n0, 2)); n1 = fmaxf(n1, __shfl_xor_sync(0xffffffffu, n1, 2));
        n0 = fmaxf(n0, m0); n1 = fmaxf(n1, m1);
        const float a0 = ex2((m0 - n0) * cexp), a1 = ex2((m1 - n1) * cexp);
        const float c0 = -n0 * cexp, c1 = -n1 * cexp;
        p0 = pack2(ex2(fmaf(sc[4][0], cexp, c0)), ex2(fmaf(sc[4][1], cexp, c0)));
        p1 = pack2(ex2(fmaf(sc[4][2], cexp, c1)), ex2(fmaf(sc[4][3], cexp, c1)));
        z0 = fmaf(z0, a0, bf_lo(p0) + bf_hi(p0)); z1 = fmaf(z1, a1, bf_lo(p1) + bf_hi(p1));
#pragma unroll
        for (int j = 0; j < 16; j++) { float* o = acc + 4 * j; o[0] *= a0; o[1] *= a0; o[2] *= a1; o[3] *= a1; }
    }
    if (h == 5 && (threadIdx.x & 127) == 0 && tile < 6) GT(1750 + tile * 8 + 4);
    if (hf) bar_arrive(5 + wg * 2 + sg, 64);
#pragma unroll
    for (int i = 0; i < 4; i++) {
        mma1688(acc + 16 * i, p0, p1, ~vm[i].x); mma1688(acc + 16 * i + 4, p0, p1, ~vm[i].y);
        mma1688(acc + 16 * i + 8, p0, p1, ~vm[i].z); mma1688(acc + 16 * i + 12, p0, p1, ~vm[i].w);
    }
    z0 += __shfl_xor_sync(0xffffffffu, z0, 1); z1 += __shfl_xor_sync(0xffffffffu, z1, 1);
    z0 += __shfl_xor_sync(0xffffffffu, z0, 2); z1 += __shfl_xor_sync(0xffffffffu, z1, 2);
    if (h == 5 && (threadIdx.x & 127) == 0 && tile < 6) GT(1750 + tile * 8 + 5);
    if (tile >= 2) mbar_wait_p(sb + G_BAR + 8 * (GB_FREE + wg), ((tile >> 1) - 1 + PO) & 1);
    store_perm(acc, g_O + (size_t)(tile * 64 + wq * 16 + g) * HD + h * 128 + t * 8, HD, rcpf(z0), rcpf(z1), 0);
    mbar_arrive(sb + G_BAR + 8 * (GB_STG + wg));
    if (!hf) {
        bar_sync(5 + wg * 2 + sg, 64);
#pragma unroll
        for (int i = 0; i < 8; i++) stg4_h(kvf + i * 128, make_uint4(0, 0, 0, 0), pol_ef(3));
    }
}

constexpr int NWK = FF / 32;
constexpr int F_WG = 0, F_WU = 32768, F_WD = 65536, F_RED = 98304, F_ACT = F_RED + 8192, F_SEL = F_ACT + 256;
__device__ __noinline__ void ffn_phase(const Maps& maps, bf16* __restrict__ out) {
    extern __shared__ __align__(1024) uint8_t smem[];
    const uint32_t sb = smem_u32(smem);
    const int c = ((volatile int*)(smem + SH_OFF))[8];
    const uint32_t epoch = ((volatile uint32_t*)(smem + SH_OFF))[9];
    const int tid = threadIdx.x;
    const bool worker = c < NWK;
    bar_sync(0, 384);
    const uint32_t mb = sb + R_BAR + 8 * MB_W0;
    if (tid == 352 && worker) {
        if (FFW) __nanosleep(FFW);
        asm volatile("fence.proxy.async.shared::cta;" ::: "memory");
        mbar_expect_tx(mb, 98304);
#pragma unroll 1
        for (int j = 0; j < 6; j++) {
            if (j < 4) tma2d_h(sb + j * 16384, j < 2 ? &maps.wg : &maps.wu, c * 32, (j & 1) * 256, mb, pol_ef(5));
            else for (int i = 0; i < 4; i++) tma2d_h(sb + F_WD + ((j - 4) * 4 + i) * 4096, &maps.wd, ((j - 4) * 4 + i) * 64, c * 32, mb, pol_ef(5));
            if (FFS) __nanosleep(FFS);
        }
    }
    int p0 = -1, p1 = -1;
    float pb = 0.f;
#pragma unroll 1
    for (int pass = 0; pass < 2; pass++) {
        if (tid < 32) {
            const uint32_t tag = epoch & 0xfffffu;
            uint4 r[4]; uint32_t n = 0;
            const int t3 = tid + 96 < NFW ? tid + 96 : tid;
#pragma unroll 1
            while (true) {
                bool ok = true;
#pragma unroll
                for (int i = 0; i < 4; i++) r[i] = ldg_rlx4((const uint32_t*)&g_f.cand[pass][i < 3 ? tid + 32 * i : t3]);
#pragma unroll
                for (int i = 0; i < 4; i++) ok = ok && (r[i].y >> 12) == tag && (r[i].w >> 12) == tag;
                if (__all_sync(0xffffffffu, ok)) break;
                if (pass == 0) __nanosleep(100);
                if (++n > SPIN_LIMIT) { ABORT(7); break; }
            }
            bool chg = pass == 0;
#pragma unroll
            for (int i = 0; i < 4; i++) {
                const int j0 = r[i].y & 4095, j1 = r[i].w & 4095;
                chg = chg || (j0 != p0 && cand_better(__uint_as_float(r[i].x), j0, pb, p1)) || (j1 != p0 && cand_better(__uint_as_float(r[i].z), j1, pb, p1));
            }
            int* sel = (int*)(smem + F_SEL);
            if (__any_sync(0xffffffffu, chg)) {
                float b0 = __uint_as_float(r[0].x), b1 = __uint_as_float(r[0].z); int i0 = r[0].y & 4095, i1 = r[0].w & 4095;
#pragma unroll
                for (int i = 1; i < 9; i++) {
                    float c0, c1; int j0, j1;
                    if (i < 4) { c0 = __uint_as_float(r[i].x); c1 = __uint_as_float(r[i].z); j0 = r[i].y & 4095; j1 = r[i].w & 4095; }
                    else {
                        const int o = 1 << (i - 4);
                        c0 = __shfl_xor_sync(0xffffffffu, b0, o); c1 = __shfl_xor_sync(0xffffffffu, b1, o);
                        j0 = __shfl_xor_sync(0xffffffffu, i0, o); j1 = __shfl_xor_sync(0xffffffffu, i1, o);
                    }
                    if (i != 3 || t3 != tid) {
                        if (cand_better(c0, j0, b0, i0)) {
                            if (cand_better(c1, j1, b0, i0)) { b1 = c1; i1 = j1; } else { b1 = b0; i1 = i0; }
                            b0 = c0; i0 = j0;
                        } else if (cand_better(c0, j0, b1, i1)) { b1 = c0; i1 = j0; }
                    }
                }
                n = 0;
#pragma unroll 1
                while (!__all_sync(0xffffffffu, (ldg_rlx(&g_f.rows[pass][tid]) == epoch) & (ldg_rlx(&g_f.rows[pass][tid + 32]) == epoch) &
                                                   (ldg_rlx(&g_f.rows[pass][tid + 64]) == epoch) & (ldg_rlx(&g_f.rows[pass][t3]) == epoch))) { if (++n > SPIN_LIMIT) { ABORT(7); break; } }
                if (tid == 0) { sel[0] = min(i0, SQ - 1); sel[1] = min(i1, SQ - 1); ((float*)sel)[2] = b0; ((float*)sel)[3] = b1; }
            }
            if (pass && tid == 0 && c == 3) GT(1440);
        }
        bar_sync(0, 384);
        const int t0 = ((int*)(smem + F_SEL))[0], t1 = ((int*)(smem + F_SEL))[1];
        if (c == 3 && tid == 0 && pass == 0) GT(1430);
        if (t0 == p0 && t1 == p1) break;
        pb = ((float*)(smem + F_SEL))[3];
        const uint32_t ytag = epoch * 2 + pass + 1;
        if (worker) {
            const int lane = tid & 31, w = tid >> 5, g = lane >> 2, t = lane & 3;
            const int lrow = ((lane >> 4) << 3) + (lane & 7), lsel = (lane >> 3) & 1;
            float2* red = (float2*)(smem + F_RED);
            if (w < 8) {
                const uint32_t* xp = (const uint32_t*)(g_hn + (size_t)((g & 1) ? t1 : t0) * DM) + w * 32 + t;
                uint32_t xb[8];
#pragma unroll
                for (int i = 0; i < 8; i++) xb[i] = __ldcg(xp + i * 4);
                mbar_wait(mb, 1);
                if (c == 3 && tid == 0 && pass == 0) GT(1431);
                float d[4][4];
#pragma unroll
                for (int kk = 0; kk < 4; kk++) {
                    const int row = w * 64 + kk * 16 + lrow;
#pragma unroll
                    for (int m = 0; m < 4; m++) {
                        uint32_t a[4];
                        ldsm4t(a, sb + (m >> 1) * F_WU + row * 64 + ((((m & 1) * 2 + lsel) ^ ((row >> 1) & 3)) << 4));
                        MMAF(kk == 0, d[m], a, xb[2 * kk], xb[2 * kk + 1]);
                    }
                }
                const float e0 = t == 0 ? d[0][0] : (t == 1 ? d[1][0] : (t == 2 ? d[2][0] : d[3][0])), e1 = t == 0 ? d[0][1] : (t == 1 ? d[1][1] : (t == 2 ? d[2][1] : d[3][1]));
                const float e2 = t == 0 ? d[0][2] : (t == 1 ? d[1][2] : (t == 2 ? d[2][2] : d[3][2])), e3 = t == 0 ? d[0][3] : (t == 1 ? d[1][3] : (t == 2 ? d[2][3] : d[3][3]));
                red[w * 64 + t * 16 + g] = make_float2(e0, e1); red[w * 64 + t * 16 + g + 8] = make_float2(e2, e3);
            }
            bar_sync(0, 384);
            if (tid < 64) {
                const float* r = (const float*)red + tid;
                float gsum = 0.f, usum = 0.f;
#pragma unroll
                for (int kg = 0; kg < 8; kg++) { gsum += r[kg * 128]; usum += r[kg * 128 + 64]; }
                gsum = rbf(gsum); usum = rbf(usum);
                const float sg = rbf(gsum / (1.f + __expf(-gsum)));
                ((bf16*)(smem + F_ACT))[(tid & 1) * 32 + (tid >> 1)] = __float2bfloat16_rn(sg * usum);
            }
            bar_sync(0, 384);
            if (w < 8) {
                const uint32_t* ap = (const uint32_t*)(smem + F_ACT) + (g & 1) * 16 + t;
                float d[4][4];
#pragma unroll
                for (int kk = 0; kk < 2; kk++) {
                    const uint32_t b0 = ap[kk * 8], b1 = ap[kk * 8 + 4];
#pragma unroll
                    for (int m = 0; m < 4; m++) {
                        uint32_t a[4];
                        ldsm4t(a, sb + F_WD + w * 4096 + (kk * 16 + lrow) * 128 + (((m * 2 + lsel) ^ (lane & 7)) << 4));
                        MMAF(kk == 0, d[m], a, b0, b1);
                    }
                }
                const float e0 = t == 0 ? d[0][0] : (t == 1 ? d[1][0] : (t == 2 ? d[2][0] : d[3][0])), e1 = t == 0 ? d[0][1] : (t == 1 ? d[1][1] : (t == 2 ? d[2][1] : d[3][1]));
                const float e2 = t == 0 ? d[0][2] : (t == 1 ? d[1][2] : (t == 2 ? d[2][2] : d[3][2])), e3 = t == 0 ? d[0][3] : (t == 1 ? d[1][3] : (t == 2 ? d[2][3] : d[3][3]));
                uint4* yp = &g_yp[pass][c][w * 64 + t * 16 + g];
                stg4(yp, make_uint4(FU(e0), ytag, FU(e1), ytag)); stg4(yp + 8, make_uint4(FU(e2), ytag, FU(e3), ytag));
            }
            if (c == 3 && tid == 0 && pass == 0) GT(1432);
        } else {
            const int j = tid & 63, part = tid >> 6, col = (c - NWK) * 64 + j;
            const int tok = part ? t1 : t0, old = part ? p1 : p0;
            float hv = 0.f, nv = 0.f;
            if (part < 2) {
                hv = __bfloat162float(__ldcg(g_h + (size_t)tok * DM + col)); nv = __bfloat162float(__ldcg(g_hn + (size_t)tok * DM + col));
                if (old >= 0 && old != t0 && old != t1)
                    out[(size_t)old * DM + col] = __float2bfloat16_rn(__bfloat162float(__ldcg(g_h + (size_t)old * DM + col)) + __bfloat162float(__ldcg(g_hn + (size_t)old * DM + col)));
            }
            float s0 = 0.f, s1 = 0.f;
            uint4 v[10]; uint32_t n = 0;
            bool ok;
#pragma unroll 1
            do {
                ok = true;
#pragma unroll
                for (int i = 0; i < 10; i++) {
                    const int src = part + 6 * i;
                    v[i] = src < NWK ? ldg_rlx4((const uint32_t*)&g_yp[pass][src][col]) : make_uint4(0, ytag, 0, ytag);
                }
#pragma unroll
                for (int i = 0; i < 10; i++) ok = ok && v[i].y == ytag && v[i].w == ytag;
                if (!ok) __nanosleep(100);
                if (++n > SPIN_LIMIT) { ABORT(7); break; }
            } while (!ok);
#pragma unroll
            for (int i = 0; i < 10; i++) { s0 += __uint_as_float(v[i].x); s1 += __uint_as_float(v[i].z); }
            float2* red = (float2*)(smem + F_RED);
            red[part * 64 + j] = make_float2(s0, s1);
            bar_sync(0, 384);
            if (part < 2) {
                float y = 0.f;
#pragma unroll
                for (int i = 0; i < 6; i++) y += ((const float*)red)[(i * 64 + j) * 2 + part];
                const float rs = rbf(1.f / (1.f + __expf(-((float*)(smem + F_SEL))[2 + part])));
                out[(size_t)tok * DM + col] = __float2bfloat16_rn(hv + rbf(nv + rbf(rbf(y) * rs)));
            }
            if (tid == 0 && pass == 0 && c == NWK) GT(1434);
        }
        p0 = t0; p1 = t1;
        if (c == 3 && tid == 0 && pass == 0) GT(1433);
        bar_sync(0, 384);
    }
}

__device__ __forceinline__ void g_consumer(uint32_t sb_, int g_, int wg_, uint32_t epoch) {
    const uint32_t sb = uni(sb_);
    const int g = uni(g_), wg = uni(wg_), wq = uni((threadIdx.x >> 5) & 3);
    const uint32_t l0 = opaque((threadIdx.x & 31) == 0);
    const uint32_t bar = sb + G_BAR, buf = sb + G_BUF + wg * 32768;
    const int lane = threadIdx.x & 31;
    float acc[64];
    if (wg == 1) bar_arrive(3, 256);
    const int n1 = g < 32 ? HSPLIT / 2 : NT - HSPLIT / 2;
#pragma unroll 1
    for (int i = 0; i < n1; i++) {
        gemm_tile<4>(acc, sb, wg, i, wg, true, l0, []() {});
        if (threadIdx.x == 0 && i == 0) GT((64 + g) * 8 + 1);
        if (threadIdx.x == 128 && i == 3) GT((64 + g) * 8 + 2);
        if (i > 0) mbar_wait_p(bar + 8 * (GB_FREE + wg), (i - 1) & 1);
        stage_bf16(acc, buf, 1.f, 1.f);
        asm volatile("fence.proxy.async.shared::cta;" ::: "memory");
        mbar_arrive(bar + 8 * (GB_STG + wg));
    }
    if (threadIdx.x == 128) GT((64 + g) * 8 + 3);
    if (g < 32) {
#pragma unroll 1
        for (int i = 0; i < NT / 2; i++) {
            const int tile = 2 * i + wg;
            const uint2 rec = ldg_rlx2(&g_f.rec[g][0]);
            uint4 km[4], vm[4];
            gemm_tile<4>(acc, sb, tile, i, wg, tile != NT - 1, l0, [&]() {
                const uint32_t seg = tile * 2 + (wq >> 1);
                const uint32_t* kvf = &g_KVf[seg][g][lane * 4];
                const bool early = (rec.x >> 8) == epoch && (rec.y >> 8) == epoch && (rec.x & 255) > seg && (rec.y & 255) > seg;
#pragma unroll
                for (int j = 0; j < 4; j++) { km[j] = ldg_rlx4_if(kvf + j * 128, early); vm[j] = ldg_rlx4_if(kvf + 512 + j * 128, early); }
            });
            if (threadIdx.x == 0 && i == 0) GT((64 + g) * 8 + 4);
            if (threadIdx.x == 128 && i == 3) GT((64 + g) * 8 + 5);
            if (g == 5 && (threadIdx.x & 127) == 0 && tile < 6) GT(1750 + tile * 8 + 1);
            attention_tile(acc, sb, tile, g, wg, wq, l0, epoch, km, vm);
            if (g == 5 && (threadIdx.x & 127) == 0 && tile < 6) GT(1750 + tile * 8 + 6);
        }
    } else {
#pragma unroll 1
        for (int i = 0; i < NT / 2; i++) {
            const int tile = 2 * i + wg;
            gemm_tile<NS3>(acc, sb, tile, i, wg, tile != NT - 1, l0, []() {});
            if (threadIdx.x == 0 && i == 0) GT((64 + g) * 8 + 4);
            if (threadIdx.x == 128 && i == 3) GT((64 + g) * 8 + 5);
            mbar_wait_p(bar + 8 * (GB_FREE + wg), (i - 1 + PO) & 1);
            store_perm(acc, g_P + (size_t)(((g - 32) >> 2) * SQ + tile * 64 + wq * 16 + (lane >> 2)) * DM + ((g - 32) & 3) * 128 + (lane & 3) * 8, DM, 1.f, 1.f, 0xffffffffu);
            mbar_arrive(bar + 8 * (GB_STG + wg));
        }
    }
}

__device__ __forceinline__ void load_w(uint32_t sb, const CUtensorMap* tm, int col, int k) {
    tma2d_h(sb + G_W + k * 16384, tm, col, k * 128, sb + G_BAR + 8 * (GB_FULL + k), pol_ef(5));
    tma2d_h(sb + G_W + 65536 + k * 16384, tm, col + 64, k * 128, sb + G_BAR + 8 * (GB_FULL + k), pol_ef(5));
}

__device__ __forceinline__ void rbf2(float& a, float& b) { uint32_t w = pack2(a, b); a = bf_lo(w); b = bf_hi(w); }
__device__ __forceinline__ void warp_sum2(float& a, float& b) {
#pragma unroll
    for (int o = 16; o; o >>= 1) { float c = __shfl_xor_sync(0xffffffffu, a, o), d = __shfl_xor_sync(0xffffffffu, b, o); a += c; b += d; }
}
__device__ __forceinline__ float sum16(const float* v) {
    return (((v[0] + v[1]) + (v[2] + v[3])) + ((v[4] + v[5]) + (v[6] + v[7]))) + (((v[8] + v[9]) + (v[10] + v[11])) + ((v[12] + v[13]) + (v[14] + v[15])));
}
__device__ __forceinline__ void ln_row2(float* v, float* u) {
    float sv = sum16(v), su = sum16(u);
    warp_sum2(sv, su);
    const float mv = sv * (1.f / DM), mu = su * (1.f / DM);
    float qv = 0.f, qu = 0.f, qv2 = 0.f, qu2 = 0.f;
#pragma unroll
    for (int i = 0; i < 16; i += 2) {
        float d0 = v[i] - mv, d1 = v[i + 1] - mv, e0 = u[i] - mu, e1 = u[i + 1] - mu;
        qv = fmaf(d0, d0, qv); qv2 = fmaf(d1, d1, qv2); qu = fmaf(e0, e0, qu); qu2 = fmaf(e1, e1, qu2);
    }
    qv += qv2; qu += qu2;
    warp_sum2(qv, qu);
    const float rv = rbf(mv), ru = rbf(mu);
    const float iv = __frcp_rn(rbf(sqrtf(rbf(rbf(qv * (1.f / DM)) + 1e-5f)))), iu = __frcp_rn(rbf(sqrtf(rbf(rbf(qu * (1.f / DM)) + 1e-5f))));
#pragma unroll
    for (int i = 0; i < 16; i += 2) {
        float a = v[i] - rv, b = v[i + 1] - rv, c = u[i] - ru, d = u[i + 1] - ru;
        rbf2(a, b); rbf2(c, d);
        a *= iv; b *= iv; c *= iu; d *= iu;
        rbf2(a, b); rbf2(c, d);
        v[i] = a; v[i + 1] = b; u[i] = c; u[i + 1] = d;
    }
}

__device__ __forceinline__ void ln_row1(float* v) {
    const float pv = __shfl_sync(0xffffffffu, v[0], 0);
    float sv = 0.f, sv2 = 0.f, qv = 0.f, qv2 = 0.f;
#pragma unroll
    for (int i = 0; i < 16; i += 2) { const float d0 = v[i] - pv, d1 = v[i + 1] - pv; sv += d0; sv2 += d1; qv = fmaf(d0, d0, qv); qv2 = fmaf(d1, d1, qv2); }
    sv += sv2; qv += qv2;
    warp_sum2(sv, qv);
    const float dm = sv * (1.f / DM), mv = pv + dm;
    qv = fmaxf(fmaf(-dm, sv, qv), 0.f);
    const float rv = rbf(mv);
    float sq, iv;
    asm("sqrt.approx.f32 %0, %1;" : "=f"(sq) : "f"(rbf(rbf(qv * (1.f / DM)) + 1e-5f)));
    asm("rcp.approx.f32 %0, %1;" : "=f"(iv) : "f"(rbf(sq)));
#pragma unroll
    for (int i = 0; i < 16; i += 2) {
        float a = v[i] - rv, b = v[i + 1] - rv;
        rbf2(a, b);
        a *= iv; b *= iv;
        rbf2(a, b);
        v[i] = a; v[i + 1] = b;
    }
}
constexpr int FSPLIT = 28;
__device__ __forceinline__ int fin_row(int id, int i) {
    if (id < 64) { const int tile = i < FSPLIT / 2 ? 2 * i : i + FSPLIT / 2; return tile < NT ? tile * 64 + id : -1; }
    const int j = id - 64 + i * 48;
    return j < FSPLIT * 32 ? (j >> 6) * 128 + 64 + (j & 63) : -1;
}
__device__ __forceinline__ void finalizer(int id, const bf16* __restrict__ x, const bf16* __restrict__ wr, bf16* __restrict__ out, uint32_t epoch, const bf16* pf) {
    const int lane = threadIdx.x & 31;
    float b0 = -INFINITY, b1 = -INFINITY; int i0 = 0x7fffffff, i1 = 0x7fffffff;
    const uint32_t tag = (epoch & 0xfffffu) << 12;
    uint32_t fl = ~epoch;
    int row = fin_row(id, 0);
    const uint4 ra = *(const uint4*)(wr + lane * 8), rb = *(const uint4*)(wr + 256 + lane * 8);
    uint4 xa = *(const uint4*)(x + (size_t)row * DM + lane * 8), xb = *(const uint4*)(x + (size_t)row * DM + lane * 8 + 256);
#pragma unroll 1
    for (int it = 0; row >= 0; it++) {
        const int tile = row >> 6, nxt = fin_row(id, it + 1);
        const size_t o0 = (size_t)row * DM + lane * 8;
        uint32_t n = 0;
#pragma unroll 1
        while (!__all_sync(0xffffffffu, fl == epoch)) {
            if (n && tile < NT - 1) __nanosleep(it ? 64 : 1000);
            fl = ldg_rlx(&g_f.p[tile][lane]);
            if (++n > SPIN_LIMIT) { ABORT(12); break; }
        }
        if (tile == NT - 1 && id == 63 && lane == 0) GT(1438);
        if ((id == 63 || id == 3 || id == 70) && lane == 0) GT(1800 + (id == 3) * 32 + tile);
        if (PFF && pf && lane == 0 && (unsigned)(it - PFF) < 7u)
            asm volatile("cp.async.bulk.prefetch.L2.global [%0], %1;" :: "l"(pf + (size_t)((id & 15) * 7 + it - PFF) * 8192), "r"(16384) : "memory");
        float v[16];
        {
            uint4 pa[8][2];
            n = 0;
#pragma unroll 1
            while (true) {
#pragma unroll
                for (int k = 0; k < 8; k++) {
                    pa[k][0] = ldg4_h(g_P + (size_t)k * SQ * DM + o0, pol_ef(2));
                    pa[k][1] = ldg4_h(g_P + (size_t)k * SQ * DM + o0 + 256, pol_ef(2));
                }
                fl = ldg_rlx(&g_f.p[max(nxt, 0) >> 6][lane]);
                uint32_t mn = 0xffffffffu;
#pragma unroll
                for (int k = 0; k < 8; k++) mn = min(min(min(mn, min(pa[k][0].x, pa[k][0].y)), min(pa[k][0].z, pa[k][0].w)), min(min(pa[k][1].x, pa[k][1].y), min(pa[k][1].z, pa[k][1].w)));
                if (__all_sync(0xffffffffu, mn != 0)) break;
                if (++n > SPIN_LIMIT) { ABORT(11); break; }
            }
            if (tile == NT - 1 && id == 63 && lane == 0) GT(1443);
#pragma unroll
            for (int j = 0; j < 2; j++) {
#pragma unroll
                for (int i = 0; i < 4; i++) {
                    uint32_t w[8];
#pragma unroll
                    for (int k = 0; k < 8; k++) w[k] = ~(i == 0 ? pa[k][j].x : (i == 1 ? pa[k][j].y : (i == 2 ? pa[k][j].z : pa[k][j].w)));
                    v[j * 8 + 2 * i] = ((bf_lo(w[0]) + bf_lo(w[1])) + (bf_lo(w[2]) + bf_lo(w[3]))) + ((bf_lo(w[4]) + bf_lo(w[5])) + (bf_lo(w[6]) + bf_lo(w[7])));
                    v[j * 8 + 2 * i + 1] = ((bf_hi(w[0]) + bf_hi(w[1])) + (bf_hi(w[2]) + bf_hi(w[3]))) + ((bf_hi(w[4]) + bf_hi(w[5])) + (bf_hi(w[6]) + bf_hi(w[7])));
                }
            }
        }
        uint32_t hw[8];
        {
            const uint32_t xw[8] = {xa.x, xa.y, xa.z, xa.w, xb.x, xb.y, xb.z, xb.w};
            uint32_t aw[8];
#pragma unroll
            for (int i = 0; i < 8; i++) aw[i] = pack2(v[2 * i], v[2 * i + 1]);
#pragma unroll
            for (int d = 1; d <= 2; d++) {
                const bool up = lane & d;
#pragma unroll
                for (int i = 0; i < 8; i++) {
                    if (!(i & d)) {
                        const uint32_t r = __shfl_xor_sync(0xffffffffu, up ? aw[i] : aw[i | d], d);
                        if (up) aw[i] = r; else aw[i | d] = r;
                    }
                }
            }
#pragma unroll
            for (int i = 0; i < 8; i++) {
                hw[i] = pack2(bf_lo(aw[i]) + bf_lo(xw[i]), bf_hi(aw[i]) + bf_hi(xw[i]));
                v[2 * i] = bf_lo(hw[i]); v[2 * i + 1] = bf_hi(hw[i]);
            }
        }
        xa = *(const uint4*)(x + (size_t)max(nxt, 0) * DM + lane * 8); xb = *(const uint4*)(x + (size_t)max(nxt, 0) * DM + lane * 8 + 256);
        ln_row1(v);
        float r0 = 0.f, r1 = 0.f;
        {
            const uint32_t ww[8] = {ra.x, ra.y, ra.z, ra.w, rb.x, rb.y, rb.z, rb.w};
#pragma unroll
            for (int i = 0; i < 8; i++) { r0 = fmaf(v[2 * i], bf_lo(ww[i]), r0); r1 = fmaf(v[2 * i + 1], bf_hi(ww[i]), r1); }
        }
        r0 += r1;
#pragma unroll
        for (int o = 16; o; o >>= 1) r0 += __shfl_xor_sync(0xffffffffu, r0, o);
        r0 = rbf(r0);
        if (cand_better(r0, row, b0, i0)) { b1 = b0; i1 = i0; b0 = r0; i0 = row; }
        else if (cand_better(r0, row, b1, i1)) { b1 = r0; i1 = row; }
        if (tile == NT - 1 && id == 63 && lane == 0) GT(1439);
        const bool keep = i0 == row || i1 == row || i1 >= SQ || row == SQ - 1;
        const bool last = nxt < 0, spec = tile < SPEC_TILES && (last || (nxt >> 6) >= SPEC_TILES);
        const bool pub = (lane == 0 && spec) || (lane == 1 && last);
        if (pub)
            asm volatile("st.relaxed.gpu.global.v4.b32 [%0], {%1,%2,%3,%4};" :: "l"(&g_f.cand[lane][id]),
                         "r"(FU(b0)), "r"(tag | (uint32_t)min(i0, 4095)), "r"(FU(b1)), "r"(tag | (uint32_t)min(i1, 4095)) : "memory");
#pragma unroll
        for (int j = 0; j < 2; j++) {
            const uint32_t* hh = hw + j * 4; const float* nn = v + j * 8;
            stg4_h(out + o0 + j * 256, make_uint4(pack2(bf_lo(hh[0]) + nn[0], bf_hi(hh[0]) + nn[1]), pack2(bf_lo(hh[1]) + nn[2], bf_hi(hh[1]) + nn[3]),
                                                  pack2(bf_lo(hh[2]) + nn[4], bf_hi(hh[2]) + nn[5]), pack2(bf_lo(hh[3]) + nn[6], bf_hi(hh[3]) + nn[7])), pol_ef(4));
            if (keep) {
                *(uint4*)(g_h + o0 + j * 256) = make_uint4(hh[0], hh[1], hh[2], hh[3]);
                *(uint4*)(g_hn + o0 + j * 256) = make_uint4(pack2(nn[0], nn[1]), pack2(nn[2], nn[3]), pack2(nn[4], nn[5]), pack2(nn[6], nn[7]));
            }
        }
        if (keep) { __threadfence(); __syncwarp(); }
        if (pub) stg_rlx(&g_f.rows[lane][id], epoch);
        if (tile >= LLT) {
#pragma unroll
            for (int k = 0; k < 8; k++) { stg4(g_P + (size_t)k * SQ * DM + o0, make_uint4(0, 0, 0, 0)); stg4(g_P + (size_t)k * SQ * DM + o0 + 256, make_uint4(0, 0, 0, 0)); }
        }
        row = nxt;
    }
    if (id == 0 && lane == 0) { g_epoch = epoch; if (epoch == 0xffffffu) { g_ticket[0] = 0; g_ticket[32] = 0; } }
}

__device__ __forceinline__ void g_producer(uint32_t sb, int g, const Maps& maps, uint32_t epoch, const bf16* __restrict__ x, const bf16* __restrict__ wr, bf16* __restrict__ out) {
    const uint32_t bar = sb + G_BAR;
    const int warp = (threadIdx.x >> 5) - 8;
    if (threadIdx.x == 256 && g == 5) GT(1410);
    if (threadIdx.x == 256 && g == 5) GT(1411);
    if (warp == 3) {
        wait_eq4(&g_f.xn[(threadIdx.x & 31) * 4], epoch, 13);
        __syncwarp();
        if ((threadIdx.x & 31) == 0) mbar_arrive(bar + 8 * GB_XN);
        finalizer(g, x, wr, out, epoch, nullptr);
        if (g == 63 && (threadIdx.x & 31) == 0) GT(128 * 8 + 6);
    }
    if ((threadIdx.x & 31) != 0) return;
    if (threadIdx.x == 256 && g == 5) GT(1412);
    if (warp == 0) {
        wait_eq4(&g_f.xn[0], epoch, 13);
        const int rk = g & 1;
        const int m1 = g < 32 ? HSPLIT : 2 * NT - HSPLIT;
        const int mx = g < 32 ? m1 + NT : m1;
#pragma unroll 1
        for (int it = 0; it < mx; it++) {
            const int tile = g < 32 ? (it < m1 ? it : it - m1) : (it < NT ? it : it - NT + HSPLIT);
            if (it == 1) wait_eq4(&g_f.xn[4], epoch, 13);
            if (it == 2) mbar_wait(bar + 8 * GB_XN, 0);
            if (it == HP) mbar_wait(bar + 8 * GB_P0, 0);
            const bool nw = it == 0 || it == (g < 32 ? m1 : NT);
#pragma unroll
            for (int k = 0; k < 4; k++) {
                mbar_wait(bar + 8 * (GB_EMPTY + k), (it & 1) ^ 1);
                mbar_expect_tx(bar + 8 * (GB_FULL + k), nw ? 49152 : 16384);
                tma2d_mc(sb + slot_off(k) + rk * 8192, &maps.xn2, (k * 2 + rk) * 64, tile * 64, bar + 8 * (GB_FULL + k));
                if (nw && (it > 0 || k >= WK0))
                    load_w(sb, it > 0 && g < 32 ? &maps.wq4 : ((g & 1) ? &maps.wv4 : &maps.wk4), it == 0 ? (g >> 1) * 128 : (g < 32 ? g * 128 : ((g - 32) >> 1) * 128), k);
            }
        }
        if (g >= 32) {
            const int u = g - 32, ks = u >> 2, ns = u & 3;
            int slot = 0, ph = 1;
#pragma unroll 1
            for (int tile = 0; tile < NT; tile++) {
                if (tile > 0) wait_eq4(&g_f.o[tile][ks][0], epoch, 9);
                if (g == 40 && tile == NT - 1) GT(1437);
                if (tile == NT - 1) GT(1690 + g - 32);
#pragma unroll 1
                for (int k = 0; k < 4; k++) {
                    mbar_wait(bar + 8 * (GB_EMPTY + slot), slot < 4 ? ph : ph ^ 1);
                    mbar_expect_tx(bar + 8 * (GB_FULL + slot), tile == 0 ? 49152 : 16384);
                    if (tile == 0) {
#pragma unroll
                        for (int nh = 0; nh < 2; nh++)
                            asm volatile("cp.async.bulk.tensor.5d.shared::cluster.global.mbarrier::complete_tx::bytes [%0], [%1, {%3, %4, %4, %4, %5}], [%2];"
                                :: "r"(sb + G_W + nh * 65536 + k * 16384), "l"((uint64_t)&maps.wo2), "r"(bar + 8 * (GB_FULL + k)), "r"(ns * 128 + nh * 64), "r"(0), "r"(ks * 16 + k * 4) : "memory");
                        if (k == 0) wait_eq4(&g_f.o[0][ks][0], epoch, 9);
                    }
                    tma2d_mc_h(sb + slot_off(slot) + rk * 8192, &maps.ox2, (ks * 8 + k * 2 + rk) * 64, tile * 64, bar + 8 * (GB_FULL + slot), pol_ef(1));
                    if (++slot == NS3) { slot = 0; ph ^= 1; }
                }
            }
        }
    } else if (warp < 3) {
        const int wg = warp - 1;
        const uint32_t buf = sb + G_BUF + wg * 32768;
        const CUtensorMap* tkv = (g & 1) ? &maps.vx3 : &maps.kx3;
        const int n1 = g < 32 ? HSPLIT / 2 : NT - HSPLIT / 2;
#pragma unroll 1
        for (int i = 0; i < n1; i++) {
            const int tile = (i < NT / 2 ? 2 * i : 2 * i - NT + HSPLIT) + wg, hd = (i < NT / 2 ? g : g - 32) >> 1;
            mbar_wait(bar + 8 * (GB_STG + wg), i & 1);
            tma_store3d(tkv, buf, tile * 64, hd * 2);
            asm volatile("cp.async.bulk.commit_group;" ::: "memory");
            asm volatile("cp.async.bulk.wait_group.read 0;" ::: "memory");
            mbar_arrive(bar + 8 * (GB_FREE + wg));
            asm volatile("cp.async.bulk.wait_group 0;" ::: "memory");
            PUBLISH(&g_f.kv[tile][hd][g & 1], epoch);
            if (tile == 0) { mbar_arrive(bar + 8 * GB_P0); if (g == 6) GT(1429); }
        }
        if (wg == 0) mbar_arrive(bar + 8 * GB_T1D);
        if (g >= 32) for (int i = 0; i < 4; i++) mbar_arrive2_if(bar + 8 * (GB_EMPTY + 4 + wg), 1);
        if (g < 32 && wg == 1) {
            mbar_wait(bar + 8 * GB_T1D, 0);
#pragma unroll 1
            for (int tile = 0; tile < NT; tile++) {
                wait_eq2(&g_f.kv[tile][g][0], epoch, 10);
                if (tile > 0) mbar_wait(bar + 8 * GB_KVF, (tile - 1) & 1);
                mbar_expect_tx(bar + 8 * (GB_KV + (tile & 1)), 16384);
                tma3d_h(sb + G_BUF, &maps.kx3, tile * 64, g * 2, bar + 8 * (GB_KV + (tile & 1)), pol_ef(0));
                if (tile > 0) mbar_wait(bar + 8 * GB_VF, (tile - 1) & 1);
                mbar_expect_tx(bar + 8 * (GB_VV + (tile & 1)), 16384);
                tma3d_h(sb + G_BUF + 32768, &maps.vx3, tile * 64, g * 2, bar + 8 * (GB_VV + (tile & 1)), pol_ef(0));
                if (PFK && tile + PFK < NT) {
                    const uint2 v = ldg_rlx2(&g_f.kv[tile + PFK][g][0]);
                    if (v.x == epoch && v.y == epoch) { tma_pf3d(&maps.kx3, (tile + PFK) * 64, g * 2); tma_pf3d(&maps.vx3, (tile + PFK) * 64, g * 2); }
                }
            }
        } else {
#pragma unroll 1
            for (int tile = g < 32 ? 0 : wg; tile < NT; tile += g < 32 ? 1 : 2) {
                mbar_wait(bar + 8 * (GB_STG + (tile & 1)), ((tile >> 1) + PO) & 1);
                mbar_arrive(bar + 8 * (GB_FREE + (tile & 1)));
                if (g < 32 || tile < LLT) PUBLISH(g < 32 ? &g_f.o[tile][g >> 2][g & 3] : &g_f.p[tile][g - 32], epoch);
                else stg_rlx(&g_f.p[tile][g - 32], epoch);
                if (g == 3 && tile == NT - 1) GT(1436);
                if (g == 3) GT(1896 + tile);
                if (g < 32 && tile == NT - 1) GT(1610 + g);
                if (g == 40 && tile == NT - 1) GT(1435);
                if (g == 40) GT(1864 + tile);
                if (g >= 32 && tile == NT - 1) GT(1650 + g - 32);
            }
        }
    }
}

struct WPtr { const bf16 *q, *k, *v, *o, *g, *u; };
__device__ __forceinline__ int startup(uint8_t* smem, const bf16* __restrict__ x, const Maps& maps, uint32_t& epoch, const WPtr& pw) {
    const int tid = threadIdx.x, lane = tid & 31, w = tid >> 5, cta = blockIdx.x;
    volatile uint32_t* sh = (volatile uint32_t*)(smem + SH_OFF);
    if (cta == 4 && tid == 0) GT(1399);
    epoch = (ldg_rlx(&g_epoch) + 1) & 0x00ffffffu;
    if (w < 4) {
        if (!(cta & 1)) {
            uint32_t* pp = (uint32_t*)(xpage() + ((XR3 ^ 0x3000u) ^ ((w == 1 || w == 2) ? 0x1000u : 0u) ^ ((w & 2) << 13))) + (cta >> 1) * 8;
            if (lane < 8) stg_rlx(pp + lane, 0u);
            __syncwarp();
            if (lane == 0) {
                uint32_t best = 0xffffffffu, a = 0;
#pragma unroll 1
                for (int r = 0; r < NPROBE; r++) {
                    uint32_t t0 = clk32();
                    asm volatile("atom.relaxed.gpu.global.add.u32 %0, [%1], %2;" : "=r"(a) : "l"(pp), "r"(a + 1) : "memory");
                    if (a == 0x7fffffffu) ABORT(15);
                    uint32_t t1 = clk32();
                    if (cta == 4 && w == 1) GT(1404 + r);
                    if (r > 0) best = min(best, t1 - t0);
                }
                sh[w] = best;
            }
        }
        if (!(cta & 1)) bar_sync(1, 160);
        if (cta == 4 && tid == 0) GT(1400);
        if (w == 0) {
            asm volatile("barrier.cluster.wait.aligned;" ::: "memory");
            if (lane == 0) {
                uint32_t rp;
                if (!(cta & 1)) {
                    uint32_t a = sh[0], b = sh[1], c = sh[2], d = sh[3];
                    uint32_t mid = (min(min(a, b), min(c, d)) + max(max(a, b), max(c, d))) >> 1;
                    const int dd = (int)min(a, d) - (int)min(b, c);
                    uint32_t cls = abs(dd) > 60 ? dd > 0 : a > mid;
                    uint32_t t = atomicAdd(&g_ticket[cls * 32], 1u) & 255;
                    if (t >= (cls ? 34u : 32u)) { cls ^= 1; t = atomicAdd(&g_ticket[cls * 32], 1u) & 255; }
                    rp = min(cls ? 32 + t : t, 65u);
                    asm volatile("st.relaxed.cluster.shared::cluster.u32 [%0], %1;" :: "r"((smem_u32(smem) + SH_OFF + 44) ^ 0x01000000u), "r"(rp) : "memory");
                } else {
                    uint32_t n = 0;
#pragma unroll 1
                    while ((rp = sh[11]) > 255) { if (++n > SPIN_LIMIT * 16) { ABORT(14); rp = 65; break; } }
                }
                if (cta == 4) GT(1407);
                if (cta == 5) GT(1408);
                const int role = rp * 2 + (cta & 1);
                sh[8] = role; sh[9] = epoch;
                while (sh[10] != epoch + 1 && cta < NWAITLN) {}
                if (RDEL && role < 64) __nanosleep(RDEL);
                if (role < 64) rec_first_loads(smem_u32(smem), role, maps);
                else if (role < 128) for (int k = 0; k < WK0; k++) load_w(smem_u32(smem), (role & 1) ? &maps.wv4 : &maps.wk4, ((role - 64) >> 1) * 128, k);
                if (cta == 4) GT(1401);
            }
        }
    } else {
        uint4 u[2][2];
        const int row0 = min(cta, 127) * 16 + (w - 4) * 2;
#pragma unroll
        for (int r = 0; r < 2; r++)
#pragma unroll
            for (int j = 0; j < 2; j++) u[r][j] = *(const uint4*)(x + (size_t)(row0 + r) * DM + j * 256 + lane * 8);
        if (w == 11 && !(cta & 1)) {
            if (lane < 2 && atomicMax(&g_ticket[lane * 32], epoch << 8) == 0xffffffffu) ABORT(15);
            __syncwarp();
            bar_arrive(1, 160);
        }
      if (cta < 128) {
        if (cta < 48) {
            const uint32_t b = cta >> 3, off = (b >= 4 ? 0x8000u + (b & 1) * 0x4000u : ((b & 1) ? 0x3000u : 0u) + ((b & 2) << 13)) ^ aslot(cta & 7);
            *(uint4*)(xpage() + off + (tid - 128) * 16) = make_uint4(0, 0, 0, 0);
        }
        float v[2][16];
#pragma unroll
        for (int r = 0; r < 2; r++)
#pragma unroll
            for (int j = 0; j < 2; j++) {
                uint32_t ww[4] = {u[r][j].x, u[r][j].y, u[r][j].z, u[r][j].w};
#pragma unroll
                for (int i = 0; i < 4; i++) { v[r][j * 8 + 2 * i] = bf_lo(ww[i]); v[r][j * 8 + 2 * i + 1] = bf_hi(ww[i]); }
            }
        ln_row2(v[0], v[1]);
#pragma unroll
        for (int r = 0; r < 2; r++)
#pragma unroll
            for (int j = 0; j < 2; j++)
                *(uint4*)(g_xn + (size_t)(row0 + r) * DM + j * 256 + lane * 8) =
                    make_uint4(pack2(v[r][j * 8], v[r][j * 8 + 1]), pack2(v[r][j * 8 + 2], v[r][j * 8 + 3]), pack2(v[r][j * 8 + 4], v[r][j * 8 + 5]), pack2(v[r][j * 8 + 6], v[r][j * 8 + 7]));
        bar_sync(2, 256);
        if (tid == 160 && cta < NWAITLN) { st_rel(&g_f.xn[cta], epoch); sh[10] = epoch + 1; }
        if (cta == 4 && tid == 160) GT(1403);
        __syncwarp();
      }
    }
    if (cta == 4 && tid == 128) GT(1402);
    __syncthreads();
    if (tid == 160 && cta >= NWAITLN && cta < 128) st_rel(&g_f.xn[cta], epoch);
    __syncwarp();
    const int role = sh[8];
    return role;
}

__global__ void __cluster_dims__(2, 1, 1) __launch_bounds__(384, 1)
main_kernel(const __grid_constant__ Maps maps, const bf16* __restrict__ x, const bf16* __restrict__ mem0, const bf16* __restrict__ wr,
            const bf16* __restrict__ wd, bf16* __restrict__ out, const WPtr pw) {
    extern __shared__ __align__(1024) uint8_t smem[];
    const uint32_t sb = smem_u32(smem);
    if (threadIdx.x == 0) {
        for (int i = 0; i < MB_N; i++) mbar_init(sb + R_BAR + 8 * i, i == MB_V ? 4 : 1);
        for (int i = 0; i < GB_N; i++)
            mbar_init(sb + G_BAR + 8 * i, i >= GB_EMPTY && i < GB_KV ? 8 : (i >= GB_KVF ? 4 : (i >= GB_STG && i < GB_FREE ? 128 : 1)));
        ((volatile uint32_t*)(smem + SH_OFF))[11] = 0xffffffffu;
        asm volatile("fence.mbarrier_init.release.cluster;" ::: "memory");
        if (((volatile uint32_t*)(smem + SH_OFF))[11] != 0xffffffffu) ABORT(14);
    }
    __syncwarp();
    asm volatile("barrier.cluster.arrive.relaxed.aligned;" ::: "memory");
    if (threadIdx.x >= 352 && threadIdx.x < 352 + (int)(sizeof(Maps) / sizeof(CUtensorMap)))
        asm volatile("prefetch.tensormap [%0];" :: "l"((const CUtensorMap*)&maps + (threadIdx.x - 352)) : "memory");
    uint32_t epoch;
    asm volatile("fence.proxy.async.shared::cta;" ::: "memory");
    const int role = uni(startup(smem, x, maps, epoch, pw));
    if (threadIdx.x >= 32) asm volatile("barrier.cluster.wait.aligned;" ::: "memory");
    const int wg = uni(threadIdx.x >> 7);
    if (role < 64) {
#define SETREG(n) do { if ((n) < 168) asm volatile("setmaxnreg.dec.sync.aligned.u32 %0;" :: "n"(n)); if ((n) > 168) asm volatile("setmaxnreg.inc.sync.aligned.u32 %0;" :: "n"(n)); } while (0)
#define RESREG(n) do { if ((n) < 168) asm volatile("setmaxnreg.inc.sync.aligned.u32 168;"); if ((n) > 168) asm volatile("setmaxnreg.dec.sync.aligned.u32 168;"); } while (0)
        if (wg == WGA) {
            SETREG(RGA);
            rec_a(sb, role, mem0, epoch);
            RESREG(RGA);
        } else if (wg == WGB) {
            SETREG(RGB);
            rec_b(sb, role, epoch);
            RESREG(RGB);
        } else {
            SETREG(RGC);
            rec_c(sb, role, mem0, maps, epoch);
            RESREG(RGC);
        }
        ffn_phase(maps, out);
        if (threadIdx.x == 0) GT(((volatile int*)(smem + SH_OFF))[8] * 8 + 6);
    } else if (role < 128) {
        if (wg < 2) {
            asm volatile("setmaxnreg.inc.sync.aligned.u32 184;");
            g_consumer(sb, role - 64, wg, epoch);
            if (threadIdx.x == 128) GT(role * 8 + 6);
        } else {
            asm volatile("setmaxnreg.dec.sync.aligned.u32 136;");
            g_producer(sb, role - 64, maps, epoch, x, wr, out);
        }
    } else {
        const int id = (threadIdx.x >> 5) * 4 + role - 128;
        finalizer(64 + id, x, wr, out, epoch, id < 16 ? pw.g : (id < 32 ? pw.u : wd));

    }
}

typedef CUresult (*EncodeFn)(CUtensorMap*, CUtensorMapDataType, cuuint32_t, void*, const cuuint64_t*, const cuuint64_t*, const cuuint32_t*, const cuuint32_t*,
                             CUtensorMapInterleave, CUtensorMapSwizzle, CUtensorMapL2promotion, CUtensorMapFloatOOBfill);
static void make_map3(EncodeFn fn, CUtensorMap* m, const void* ptr, uint64_t cols, uint64_t rows) {
    cuuint64_t dims[3] = {64, rows, cols / 64};
    cuuint64_t strides[2] = {cols * 2, 128};
    cuuint32_t box[3] = {64, 64, 2};
    cuuint32_t es[3] = {1, 1, 1};
    fn(m, CU_TENSOR_MAP_DATA_TYPE_BFLOAT16, 3, (void*)ptr, dims, strides, box, es, CU_TENSOR_MAP_INTERLEAVE_NONE, CU_TENSOR_MAP_SWIZZLE_128B,
       CU_TENSOR_MAP_L2_PROMOTION_L2_256B, CU_TENSOR_MAP_FLOAT_OOB_FILL_NONE);
}
static void make_map(EncodeFn fn, CUtensorMap* m, const void* ptr, uint64_t cols, uint64_t rows, uint32_t bcols, uint32_t brows,
                     bool f32 = false, CUtensorMapSwizzle sw = CU_TENSOR_MAP_SWIZZLE_128B) {
    cuuint64_t dims[2] = {cols, rows};
    cuuint64_t strides[1] = {cols * (f32 ? 4 : 2)};
    cuuint32_t box[2] = {bcols, brows};
    cuuint32_t es[2] = {1, 1};
    fn(m, f32 ? CU_TENSOR_MAP_DATA_TYPE_FLOAT32 : CU_TENSOR_MAP_DATA_TYPE_BFLOAT16, 2, (void*)ptr, dims, strides, box, es, CU_TENSOR_MAP_INTERLEAVE_NONE, sw,
       CU_TENSOR_MAP_L2_PROMOTION_L2_256B, CU_TENSOR_MAP_FLOAT_OOB_FILL_NONE);
}

extern "C" void kernel_launch(void* const* d_in, const int* in_sizes, int n_in, void* d_out, int out_size) {
    const bf16* x = (const bf16*)d_in[0];
    const bf16* mem0 = (const bf16*)d_in[1];
    const bf16* Wq = (const bf16*)d_in[2];
    const bf16* Wk = (const bf16*)d_in[3];
    const bf16* Wv = (const bf16*)d_in[4];
    const bf16* Wo = (const bf16*)d_in[5];
    const bf16* wr = (const bf16*)d_in[8];
    const bf16* wg = (const bf16*)d_in[9];
    const bf16* wu = (const bf16*)d_in[10];
    const bf16* wd = (const bf16*)d_in[11];
    bf16* out = (bf16*)d_out;

    static EncodeFn enc = nullptr;
    static void *pxn, *pK, *pV, *pO, *pacc;
    if (!enc) {
        cudaDriverEntryPointQueryResult qr;
        void* fn = nullptr;
        cudaGetDriverEntryPoint("cuTensorMapEncodeTiled", &fn, cudaEnableDefault, &qr);
        enc = (EncodeFn)fn;
        cudaGetSymbolAddress(&pxn, g_xn); cudaGetSymbolAddress(&pK, g_K); cudaGetSymbolAddress(&pV, g_V);
        cudaGetSymbolAddress(&pO, g_O); cudaGetSymbolAddress(&pacc, g_P);
        cudaFuncSetAttribute(main_kernel, cudaFuncAttributeMaxDynamicSharedMemorySize, SMEM_TOTAL);
    }
    Maps m;
    make_map(enc, &m.wq, Wq, HD, DM, 64, 256);
    make_map(enc, &m.wk, Wk, HD, DM, 64, 256);
    make_map(enc, &m.wv, Wv, HD, DM, 64, 256);
    make_map(enc, &m.wq4, Wq, HD, DM, 64, 128); make_map(enc, &m.wk4, Wk, HD, DM, 64, 128); make_map(enc, &m.wv4, Wv, HD, DM, 64, 128);
    make_map(enc, &m.wo, Wo, DM, HD, 64, 128);
    {
        cuuint64_t dims[5] = {DM, 2, 4, 4, HD / 32};
        cuuint64_t strides[4] = {DM * 2, 8 * DM * 2, 2 * DM * 2, 32 * DM * 2};
        cuuint32_t box[5] = {64, 2, 4, 4, 4};
        cuuint32_t es[5] = {1, 1, 1, 1, 1};
        enc(&m.wo2, CU_TENSOR_MAP_DATA_TYPE_BFLOAT16, 5, (void*)Wo, dims, strides, box, es, CU_TENSOR_MAP_INTERLEAVE_NONE, CU_TENSOR_MAP_SWIZZLE_128B,
            CU_TENSOR_MAP_L2_PROMOTION_L2_256B, CU_TENSOR_MAP_FLOAT_OOB_FILL_NONE);
    }
    make_map(enc, &m.kx, pK, HD, SQ, 64, 64);
    make_map(enc, &m.ox2, pO, HD, SQ, 64, 64);
    make_map(enc, &m.xn2, pxn, DM, SQ, 64, 64);
    make_map3(enc, &m.kx3, pK, HD, SQ); make_map3(enc, &m.vx3, pV, HD, SQ);
    make_map(enc, &m.wg, wg, FF, DM, 32, 256, false, CU_TENSOR_MAP_SWIZZLE_64B);
    make_map(enc, &m.wu, wu, FF, DM, 32, 256, false, CU_TENSOR_MAP_SWIZZLE_64B);
    make_map(enc, &m.wd, wd, DM, FF, 64, 32);

    cudaStream_t st = cudaStreamPerThread;
    main_kernel<<<NCTA, 384, SMEM_TOTAL, st>>>(m, x, mem0, wr, wd, out, WPtr{Wq, Wk, Wv, Wo, wg, wu});
}
```

```cpp
#include <cuda_runtime.h>
#include <cuda_bf16.h>
#include <cuda.h>
#include <stdint.h>
#include <stddef.h>

typedef __nv_bfloat16 bf16;

constexpr int SQ = 2048, DM = 512, NH = 32, DH = 128, NSEG = 64, HD = 4096, FF = 1792;

constexpr int NT = 32;
#define SPEC_TILES 30
__device__ __align__(1024) bf16 g_xn[SQ * DM];
__device__ __align__(1024) bf16 g_K[SQ * HD];
__device__ __align__(1024) bf16 g_V[SQ * HD];
__device__ __align__(1024) bf16 g_O[SQ * HD];
__device__ __align__(1024) uint32_t g_KVf[NSEG][NH][1024];
__device__ __align__(1024) bf16 g_P[8 * SQ * DM];
__device__ __align__(1024) bf16 g_h[SQ * DM];
__device__ __align__(1024) bf16 g_hn[SQ * DM];
__device__ uint8_t g_xraw[12 << 20];
#define XPG 0
__device__ __forceinline__ uint64_t xpage() { return (((uint64_t)g_xraw + (2 << 20) - 1) & ~(uint64_t)((2 << 20) - 1)) + ((uint64_t)XPG << 21); }
constexpr uint32_t XR3 = (1u << 20) | (1u << 19) | (1u << 12);
__device__ __forceinline__ uint32_t aslot(uint32_t s) { return ((s & 1) << 18) | ((s & 2) << 19) | ((s & 4) * 0xc000u); }
__device__ __forceinline__ uint32_t acc_base(uint32_t W) { return ((W & 2) ? 0x3000u : 0u) + ((W & 4) << 12) + (W & 1) * 2048; }
__device__ __forceinline__ uint32_t ext_base(uint32_t W) { return 0x8000u + ((W & 4) << 12) + (W & 3) * 1024; }
#define XHS 256
#define XSS 32
__device__ __forceinline__ uint32_t zero_off(uint32_t c, uint32_t ln) {
    return ln < 8 ? acc_base(c >> 3) + (c & 7) * 256 + ln * 16 : ext_base(c >> 3) + ((c >> 2) & 1) * XHS + ((c >> 1) & 1) * XSS + (c & 1) * 16;
}
struct Flags {
    uint32_t p[NT][32];
    uint4 cand[2][128];
    uint32_t rows[2][128];
    uint4 norm[64];
    uint32_t pad0[512];
    uint32_t kv[NT][NH][2];
    uint32_t pad1[2048];
    uint32_t o[NT][8][8];
    uint32_t pad2[2048];
    uint32_t rec[NH][32];
    uint32_t xn[128];
};
static_assert(offsetof(Flags, kv) == 0x3000 && offsetof(Flags, o) == 0x7000 && offsetof(Flags, xn) == 0xc000, "flags");
#define FLX 0
#define g_f (*(Flags*)(xpage() + (1u << 19) + FLX))
__device__ __align__(1024) uint4 g_yp[2][FF / 32][DM];
__device__ __align__(256) uint32_t g_ticket[64];
__device__ uint32_t g_epoch;
#define NS3 6
#define HSPLIT 26
#define PFK 0
#define NWAITLN 4
#define WGA 0
#define WGB 1
#define WGC (3 - WGA - WGB)
#define PFF 10
#define FFW 0
#define FFS 200
#define LLT 31
#define HP 3
#define WK0 1
#define RDEL 0
#define NPROBE 3
constexpr int NCTA = 132;
constexpr int NFW = 112;
__device__ uint32_t g_abort;
__device__ long long g_dbg[4096];
#define TR(slot, v)

__device__ __forceinline__ uint32_t smem_u32(const void* p) { return (uint32_t)__cvta_generic_to_shared(p); }
__device__ __forceinline__ void mbar_init(uint32_t a, uint32_t c) { asm volatile("mbarrier.init.shared::cta.b64 [%0], %1;" :: "r"(a), "r"(c) : "memory"); }
__device__ __forceinline__ void mbar_expect_tx(uint32_t a, uint32_t tx) { asm volatile("mbarrier.arrive.expect_tx.shared::cta.b64 _, [%0], %1;" :: "r"(a), "r"(tx) : "memory"); }
__device__ __forceinline__ void mbar_arrive(uint32_t a) { asm volatile("mbarrier.arrive.shared::cta.b64 _, [%0];" :: "r"(a) : "memory"); }
__device__ __forceinline__ void mbar_arrive_if(uint32_t a, uint32_t pred) {
    asm volatile("{\n.reg .pred p;\nsetp.ne.u32 p, %1, 0;\n@p mbarrier.arrive.shared::cta.b64 _, [%0];\n}" :: "r"(a), "r"(pred) : "memory");
}
__device__ __forceinline__ bool mbar_try(uint32_t a, uint32_t ph) {
    uint32_t ok;
    asm volatile("{\n.reg .pred p;\nmbarrier.try_wait.parity.shared::cta.b64 p, [%1], %2;\nselp.u32 %0, 1, 0, p;\n}" : "=r"(ok) : "r"(a), "r"(ph) : "memory");
    return ok != 0;
}
#define SPINLOG 20
constexpr uint32_t SPIN_LIMIT = 1u << SPINLOG;
#define ABORT(code_) atomicCAS(&g_abort, 0u, (code_))
__device__ __forceinline__ void mbar_wait(uint32_t a, uint32_t ph) {
    uint32_t n = 0;
#pragma unroll 1
    while (!mbar_try(a, ph)) { if (++n > SPIN_LIMIT) { ABORT(1); break; } }
}
__device__ __forceinline__ void bar_sync(int id, int n) { asm volatile("bar.sync %0, %1;" :: "r"(id), "r"(n) : "memory"); }
__device__ __forceinline__ void bar_arrive(int id, int n) { asm volatile("bar.arrive %0, %1;" :: "r"(id), "r"(n) : "memory"); }

__device__ __forceinline__ void ldsm4(uint32_t* r, uint32_t a) {
    asm volatile("ldmatrix.sync.aligned.m8n8.x4.shared.b16 {%0,%1,%2,%3}, [%4];" : "=r"(r[0]), "=r"(r[1]), "=r"(r[2]), "=r"(r[3]) : "r"(a) : "memory");
}
__device__ __forceinline__ void ldsm4t(uint32_t* r, uint32_t a) {
    asm volatile("ldmatrix.sync.aligned.m8n8.x4.trans.shared.b16 {%0,%1,%2,%3}, [%4];" : "=r"(r[0]), "=r"(r[1]), "=r"(r[2]), "=r"(r[3]) : "r"(a) : "memory");
}
__device__ __forceinline__ void stsm4t(uint32_t a, uint32_t r0, uint32_t r1, uint32_t r2, uint32_t r3) {
    asm volatile("stmatrix.sync.aligned.m8n8.x4.trans.shared.b16 [%0], {%1,%2,%3,%4};" :: "r"(a), "r"(r0), "r"(r1), "r"(r2), "r"(r3) : "memory");
}
__device__ __forceinline__ void stsm4(uint32_t a, uint32_t r0, uint32_t r1, uint32_t r2, uint32_t r3) {
    asm volatile("stmatrix.sync.aligned.m8n8.x4.shared.b16 [%0], {%1,%2,%3,%4};" :: "r"(a), "r"(r0), "r"(r1), "r"(r2), "r"(r3) : "memory");
}
__device__ __forceinline__ uint32_t movm(uint32_t a) { uint32_t d; asm volatile("movmatrix.sync.aligned.m8n8.trans.b16 %0, %1;" : "=r"(d) : "r"(a)); return d; }
__device__ __forceinline__ void mma16816(float* d, uint32_t a0, uint32_t a1, uint32_t a2, uint32_t a3, uint32_t b0, uint32_t b1) {
    asm volatile("mma.sync.aligned.m16n8k16.row.col.f32.bf16.bf16.f32 {%0,%1,%2,%3}, {%4,%5,%6,%7}, {%8,%9}, {%0,%1,%2,%3};"
        : "+f"(d[0]), "+f"(d[1]), "+f"(d[2]), "+f"(d[3]) : "r"(a0), "r"(a1), "r"(a2), "r"(a3), "r"(b0), "r"(b1));
}
__device__ __forceinline__ void mma1688(float* d, uint32_t a0, uint32_t a1, uint32_t b0) {
    asm volatile("mma.sync.aligned.m16n8k8.row.col.f32.bf16.bf16.f32 {%0,%1,%2,%3}, {%4,%5}, {%6}, {%0,%1,%2,%3};"
        : "+f"(d[0]), "+f"(d[1]), "+f"(d[2]), "+f"(d[3]) : "r"(a0), "r"(a1), "r"(b0));
}
__device__ __forceinline__ uint32_t pack2(float a, float b) { uint32_t d; asm("cvt.rn.bf16x2.f32 %0, %1, %2;" : "=r"(d) : "f"(b), "f"(a)); return d; }
__device__ __forceinline__ float bf_lo(uint32_t w) { return __uint_as_float(w << 16); }
__device__ __forceinline__ float bf_hi(uint32_t w) { return __uint_as_float(w & 0xffff0000u); }
__device__ __forceinline__ float rbf(float x) { return __bfloat162float(__float2bfloat16_rn(x)); }

__device__ __forceinline__ void sts128(uint32_t a, float x, float y, float z, float w) { asm volatile("st.shared.v4.f32 [%0], {%1,%2,%3,%4};" :: "r"(a), "f"(x), "f"(y), "f"(z), "f"(w) : "memory"); }
__device__ __forceinline__ void sts128u(uint32_t a, uint32_t x, uint32_t y, uint32_t z, uint32_t w) { asm volatile("st.shared.v4.b32 [%0], {%1,%2,%3,%4};" :: "r"(a), "r"(x), "r"(y), "r"(z), "r"(w) : "memory"); }
__device__ __forceinline__ void sts64(uint32_t a, float x, float y) { asm volatile("st.shared.v2.f32 [%0], {%1,%2};" :: "r"(a), "f"(x), "f"(y) : "memory"); }
__device__ __forceinline__ float4 lds128(uint32_t a) { float4 v; asm volatile("ld.shared.v4.f32 {%0,%1,%2,%3}, [%4];" : "=f"(v.x), "=f"(v.y), "=f"(v.z), "=f"(v.w) : "r"(a) : "memory"); return v; }
__device__ __forceinline__ float2 lds64(uint32_t a) { float2 v; asm volatile("ld.shared.v2.f32 {%0,%1}, [%2];" : "=f"(v.x), "=f"(v.y) : "r"(a) : "memory"); return v; }
__device__ __forceinline__ uint2 lds64u(uint32_t a) { uint2 v; asm volatile("ld.shared.v2.b32 {%0,%1}, [%2];" : "=r"(v.x), "=r"(v.y) : "r"(a) : "memory"); return v; }
__device__ __forceinline__ float4 lds128v(uint32_t a) { float4 v; asm volatile("ld.volatile.shared.v4.f32 {%0,%1,%2,%3}, [%4];" : "=f"(v.x), "=f"(v.y), "=f"(v.z), "=f"(v.w) : "r"(a) : "memory"); return v; }
__device__ __forceinline__ float2 lds64v(uint32_t a) { float2 v; asm volatile("ld.volatile.shared.v2.f32 {%0,%1}, [%2];" : "=f"(v.x), "=f"(v.y) : "r"(a) : "memory"); return v; }
__device__ __forceinline__ uint4 lds128uv(uint32_t a) { uint4 v; asm volatile("ld.volatile.shared.v4.b32 {%0,%1,%2,%3}, [%4];" : "=r"(v.x), "=r"(v.y), "=r"(v.z), "=r"(v.w) : "r"(a) : "memory"); return v; }
__device__ __forceinline__ void st_async4(uint32_t a, float x, float y, float z, float w, uint32_t mb) {
    asm volatile("st.async.weak.shared::cluster.mbarrier::complete_tx::bytes.v4.f32 [%0], {%1,%2,%3,%4}, [%5];" :: "r"(a), "f"(x), "f"(y), "f"(z), "f"(w), "r"(mb) : "memory");
}
__device__ __forceinline__ void st_async2(uint32_t a, uint32_t x, uint32_t y, uint32_t mb) {
    asm volatile("st.async.weak.shared::cluster.mbarrier::complete_tx::bytes.v2.b32 [%0], {%1,%2}, [%3];" :: "r"(a), "r"(x), "r"(y), "r"(mb) : "memory");
}
__device__ __forceinline__ uint32_t ldg_rlx(const uint32_t* p) { uint32_t v; asm volatile("ld.relaxed.gpu.global.b32 %0, [%1];" : "=r"(v) : "l"(p) : "memory"); return v; }
__device__ __forceinline__ uint4 ldg_rlx4(const uint32_t* p) { uint4 v; asm volatile("ld.relaxed.gpu.global.v4.b32 {%0,%1,%2,%3}, [%4];" : "=r"(v.x), "=r"(v.y), "=r"(v.z), "=r"(v.w) : "l"(p) : "memory"); return v; }
__device__ __forceinline__ uint4 ldg_rlx4_if(const uint32_t* p, bool c) {
    uint4 v;
    asm volatile("{\n.reg .pred p;\nsetp.ne.u32 p, %5, 0;\nmov.b32 %0, 0;\nmov.b32 %1, 0;\nmov.b32 %2, 0;\nmov.b32 %3, 0;\n@p ld.relaxed.gpu.global.v4.b32 {%0,%1,%2,%3}, [%4];\n}"
                 : "=r"(v.x), "=r"(v.y), "=r"(v.z), "=r"(v.w) : "l"(p), "r"((uint32_t)c) : "memory");
    return v;
}
__device__ __forceinline__ void stg_rlx(uint32_t* p, uint32_t v) { asm volatile("st.relaxed.gpu.global.b32 [%0], %1;" :: "l"(p), "r"(v) : "memory"); }
__device__ __forceinline__ void tma2d(uint32_t dst, const CUtensorMap* tm, int c0, int c1, uint32_t mb) {
    asm volatile("cp.async.bulk.tensor.2d.shared::cluster.global.mbarrier::complete_tx::bytes [%0], [%1, {%3, %4}], [%2];"
        :: "r"(dst), "l"((uint64_t)tm), "r"(mb), "r"(c0), "r"(c1) : "memory");
}

__device__ __forceinline__ void tma3d(uint32_t dst, const CUtensorMap* tm, int row, int chunk, uint32_t mb) {
    asm volatile("cp.async.bulk.tensor.3d.shared::cluster.global.mbarrier::complete_tx::bytes [%0], [%1, {%3, %4, %5}], [%2];"
        :: "r"(dst), "l"((uint64_t)tm), "r"(mb), "r"(0), "r"(row), "r"(chunk) : "memory");
}
#define EF 0xff
__device__ __forceinline__ uint64_t pol_ef(int bit) {
    uint64_t p;
    if ((EF >> bit) & 1) asm("createpolicy.fractional.L2::evict_first.b64 %0, 1.0;" : "=l"(p));
    else asm("createpolicy.fractional.L2::evict_normal.b64 %0, 1.0;" : "=l"(p));
    return p;
}
__device__ __forceinline__ void tma3d_h(uint32_t dst, const CUtensorMap* tm, int row, int chunk, uint32_t mb, uint64_t pol) {
    asm volatile("cp.async.bulk.tensor.3d.shared::cluster.global.mbarrier::complete_tx::bytes.L2::cache_hint [%0], [%1, {%3, %4, %5}], [%2], %6;"
        :: "r"(dst), "l"((uint64_t)tm), "r"(mb), "r"(0), "r"(row), "r"(chunk), "l"(pol) : "memory");
}
__device__ __forceinline__ void tma2d_h(uint32_t dst, const CUtensorMap* tm, int c0, int c1, uint32_t mb, uint64_t pol) {
    asm volatile("cp.async.bulk.tensor.2d.shared::cluster.global.mbarrier::complete_tx::bytes.L2::cache_hint [%0], [%1, {%3, %4}], [%2], %5;"
        :: "r"(dst), "l"((uint64_t)tm), "r"(mb), "r"(c0), "r"(c1), "l"(pol) : "memory");
}
__device__ __forceinline__ void tma2d_mc_h(uint32_t dst, const CUtensorMap* tm, int c0, int c1, uint32_t mb, uint64_t pol) {
    asm volatile("cp.async.bulk.tensor.2d.shared::cluster.global.mbarrier::complete_tx::bytes.multicast::cluster.L2::cache_hint [%0], [%1, {%3, %4}], [%2], %5, %6;"
        :: "r"(dst), "l"((uint64_t)tm), "r"(mb), "r"(c0), "r"(c1), "h"((uint16_t)3), "l"(pol) : "memory");
}
__device__ __forceinline__ uint4 ldg4_h(const void* p, uint64_t pol) {
    uint4 v;
    asm volatile("ld.relaxed.gpu.global.L2::cache_hint.v4.b32 {%0,%1,%2,%3}, [%4], %5;" : "=r"(v.x), "=r"(v.y), "=r"(v.z), "=r"(v.w) : "l"(p), "l"(pol) : "memory");
    return v;
}
__device__ __forceinline__ void stg4_h(void* p, uint4 v, uint64_t pol) {
    asm volatile("st.relaxed.gpu.global.L2::cache_hint.v4.b32 [%0], {%1,%2,%3,%4}, %5;" :: "l"(p), "r"(v.x), "r"(v.y), "r"(v.z), "r"(v.w), "l"(pol) : "memory");
}
__device__ __forceinline__ void tma2d_mc(uint32_t dst, const CUtensorMap* tm, int c0, int c1, uint32_t mb) {
    asm volatile("cp.async.bulk.tensor.2d.shared::cluster.global.mbarrier::complete_tx::bytes.multicast::cluster [%0], [%1, {%3, %4}], [%2], %5;"
        :: "r"(dst), "l"((uint64_t)tm), "r"(mb), "r"(c0), "r"(c1), "h"((uint16_t)3) : "memory");
}
__device__ __forceinline__ void mbar_arrive2_if(uint32_t a, uint32_t pred) {
    asm volatile("{\n.reg .pred p;\nsetp.ne.u32 p, %1, 0;\n@p mbarrier.arrive.shared::cta.b64 _, [%0];\n@p mbarrier.arrive.shared::cluster.b64 _, [%2];\n}"
                 :: "r"(a), "r"(pred), "r"(a ^ 0x01000000u) : "memory");
}
__device__ __forceinline__ void tma_pf3d(const CUtensorMap* tm, int row, int chunk) {
    asm volatile("cp.async.bulk.prefetch.tensor.3d.L2.global.tile [%0, {%1, %2, %3}];" :: "l"((uint64_t)tm), "r"(0), "r"(row), "r"(chunk) : "memory");
}
__device__ __forceinline__ void tma_pf2d(const CUtensorMap* tm, int c0, int c1) {
    asm volatile("cp.async.bulk.prefetch.tensor.2d.L2.global.tile [%0, {%1, %2}];" :: "l"((uint64_t)tm), "r"(c0), "r"(c1) : "memory");
}
__device__ __forceinline__ void tma_store3d(const CUtensorMap* tm, uint32_t src, int row, int chunk) {
    asm volatile("cp.async.bulk.tensor.3d.global.shared::cta.bulk_group [%0, {%2, %3, %4}], [%1];" :: "l"((uint64_t)tm), "r"(src), "r"(0), "r"(row), "r"(chunk) : "memory");
}
__device__ __forceinline__ void bulk_store(void* dst, uint32_t src, uint32_t bytes) {
    asm volatile("cp.async.bulk.global.shared::cta.bulk_group [%0], [%1], %2;" :: "l"(dst), "r"(src), "r"(bytes) : "memory");
}
#define GT(slot)
#define CNT(k)
#define CNT2(k, c)
#define TS(i, dep)
#define TSACC()
#define TSDECL
struct Maps { CUtensorMap wq, wk, wv, wo, wo2, kx, ox2, kx3, vx3, xn2, wg, wu, wd, wq4, wk4, wv4; };
typedef Maps RecMaps;
__device__ __forceinline__ void st_rel(uint32_t* p, uint32_t v) { asm volatile("st.release.gpu.global.u32 [%0], %1;" :: "l"(p), "r"(v) : "memory"); }
#define PUBLISH(p, v) st_rel(p, v)
__device__ __forceinline__ uint2 ldg_rlx2(const uint32_t* p) { uint2 v; asm volatile("ld.relaxed.gpu.global.v2.b32 {%0,%1}, [%2];" : "=r"(v.x), "=r"(v.y) : "l"(p) : "memory"); return v; }
__device__ __forceinline__ void wait_eq2(const uint32_t* p, uint32_t e, int code) {
    uint32_t n = 0;
#pragma unroll 1
    while (true) { uint2 v = ldg_rlx2(p); if (v.x == e && v.y == e) break; __nanosleep(64); if (++n > SPIN_LIMIT) { ABORT(code); break; } }
}
__device__ __forceinline__ void wait_eq4(const uint32_t* p, uint32_t e, int code) {
    uint32_t n = 0;
#pragma unroll 1
    while (true) { uint4 v = ldg_rlx4(p); if (v.x == e && v.y == e && v.z == e && v.w == e) break; __nanosleep(64); if (++n > SPIN_LIMIT) { ABORT(code); break; } }
}
__device__ __forceinline__ void wait_rec(const uint32_t* p, uint32_t e, uint32_t steps) {
    uint32_t n = 0;
#pragma unroll 1
    while (true) {
        uint2 v = ldg_rlx2(p);
        if (__all_sync(0xffffffffu, (v.x >> 8) == e && (v.y >> 8) == e && (v.x & 255) >= steps && (v.y & 255) >= steps)) break;
        __nanosleep(64); if (++n > SPIN_LIMIT) { ABORT(8); break; }
    }
}

constexpr int R_QK1 = 0;
constexpr int R_WO = 65536;
constexpr int R_T = 131072;
constexpr int R_SLOT1 = R_T;
constexpr int R_MEMB = R_T + 24576;
constexpr int R_QP = R_MEMB + 8192;
constexpr int R_VRED = R_QP + 4096;
constexpr int R_STG = R_VRED + 2048;
constexpr int R_AX = R_STG + 2048;
constexpr int R_SLOT0 = 196608;
constexpr int R_SLOC = R_SLOT0 + 24576;
constexpr int R_SREM = R_SLOC + 1536;
constexpr int R_VB = R_SREM + 1536;
constexpr int R_MISC = R_VB + 2048;
constexpr int R_LT = R_MISC + 128;
constexpr int R_BAR = 229888;
constexpr int R_TS = 229888 + 128;
static_assert(R_AX + 24576 <= R_SLOT0 && R_LT + 2560 <= 229376, "smem map");
enum { MB_W0 = 0, MB_W1, MB_WV, MB_WO, MB_S, MB_FULL0, MB_FULL1, MB_V, MB_N };

__device__ __forceinline__ float ex2(float x) { float y; asm("ex2.approx.ftz.f32 %0, %1;" : "=f"(y) : "f"(x)); return y; }
__device__ __forceinline__ float rcpf(float x) { float y; asm("rcp.approx.ftz.f32 %0, %1;" : "=f"(y) : "f"(x)); return y; }
__device__ __forceinline__ void mma16816z(float* d, uint32_t a0, uint32_t a1, uint32_t a2, uint32_t a3, uint32_t b0, uint32_t b1) {
    asm volatile("mma.sync.aligned.m16n8k16.row.col.f32.bf16.bf16.f32 {%0,%1,%2,%3}, {%4,%5,%6,%7}, {%8,%9}, {%10,%10,%10,%10};"
        : "=f"(d[0]), "=f"(d[1]), "=f"(d[2]), "=f"(d[3]) : "r"(a0), "r"(a1), "r"(a2), "r"(a3), "r"(b0), "r"(b1), "f"(0.f));
}
__device__ __forceinline__ void mma1688hz(float* d, uint32_t a0, uint32_t a1, uint32_t b0) {
    asm volatile("mma.sync.aligned.m16n8k8.row.col.f32.f16.f16.f32 {%0,%1,%2,%3}, {%4,%5}, {%6}, {%7,%7,%7,%7};"
        : "=f"(d[0]), "=f"(d[1]), "=f"(d[2]), "=f"(d[3]) : "r"(a0), "r"(a1), "r"(b0), "f"(0.f));
}
#define MMA(d, a, b0, b1) mma16816(d, a[0], a[1], a[2], a[3], b0, b1)
#define MMAZ(d, a, b0, b1) mma16816z(d, a[0], a[1], a[2], a[3], b0, b1)
#define MMAF(first, d, a, b0, b1) do { if (first) MMAZ(d, a, b0, b1); else MMA(d, a, b0, b1); } while (0)

__device__ __forceinline__ uint32_t uni(uint32_t x) { return __reduce_max_sync(0xffffffffu, x); }
__device__ __forceinline__ void mbar_wait_u(uint32_t a, uint32_t ph) {
    uint32_t n = 0;
#pragma unroll 1
    while (!__all_sync(0xffffffffu, mbar_try(a, ph))) { if (++n > SPIN_LIMIT) { ABORT(1); break; } }
}
__device__ __forceinline__ void mbar_wait_p(uint32_t a, uint32_t ph) {
    asm volatile("{\n.reg .pred p, q;\n.reg .u32 n;\nmov.u32 n, 0;\nWL: mbarrier.try_wait.parity.shared::cta.b64 p, [%0], %1;\nadd.u32 n, n, 1;\n"
                 "setp.lt.and.u32 q, n, %2, !p;\n@q bra.uni WL;\n}" :: "r"(a), "r"(ph), "n"(SPIN_LIMIT) : "memory");
}
__device__ __forceinline__ uint32_t mbar_test(uint32_t a, uint32_t ph) {
    uint32_t ok;
    asm volatile("{\n.reg .pred p;\nmbarrier.test_wait.parity.shared::cta.b64 p, [%1], %2;\nselp.u32 %0, 1, 0, p;\n}" : "=r"(ok) : "r"(a), "r"(ph) : "memory");
    return ok;
}
__device__ __forceinline__ uint32_t opaque(uint32_t x) { return __shfl_sync(0xffffffffu, x, threadIdx.x & 31); }
__device__ __forceinline__ const uint32_t* mkptr(uint32_t lo, uint32_t hi) { uint64_t r; asm("mov.b64 %0, {%1, %2};" : "=l"(r) : "r"(lo), "r"(hi)); return (const uint32_t*)r; }
__device__ __forceinline__ uint32_t prmt(uint32_t a, uint32_t b, uint32_t s) { uint32_t d; asm("prmt.b32 %0, %1, %2, %3;" : "=r"(d) : "r"(a), "r"(b), "r"(s)); return d; }
__device__ __forceinline__ uint32_t packh2(float a, float b) { uint32_t d; asm("cvt.rn.f16x2.f32 %0, %1, %2;" : "=r"(d) : "f"(b), "f"(a)); return d; }
__device__ __forceinline__ uint32_t hadd2b(uint32_t a, uint32_t b) { uint32_t d; asm("add.rn.bf16x2 %0, %1, %2;" : "=r"(d) : "r"(a), "r"(b)); return d; }
__device__ __forceinline__ uint32_t hmul2b(uint32_t a, uint32_t b) { uint32_t d; asm("mul.rn.bf16x2 %0, %1, %2;" : "=r"(d) : "r"(a), "r"(b)); return d; }
__device__ __forceinline__ uint32_t amax2b(uint32_t a, uint32_t b) { uint32_t d; asm("max.xorsign.abs.bf16x2 %0, %1, %2;" : "=r"(d) : "r"(a), "r"(b)); return d; }
__device__ __forceinline__ uint32_t amax2h(uint32_t a, uint32_t b) { uint32_t d; asm("max.xorsign.abs.f16x2 %0, %1, %2;" : "=r"(d) : "r"(a), "r"(b)); return d; }
__device__ __forceinline__ void sts32(uint32_t a, uint32_t x) { asm volatile("st.shared.b32 [%0], %1;" :: "r"(a), "r"(x) : "memory"); }
__device__ __forceinline__ uint32_t lds32v_(uint32_t a) { uint32_t v; asm volatile("ld.volatile.shared.b32 %0, [%1];" : "=r"(v) : "r"(a) : "memory"); return v; }
__device__ __forceinline__ void stg4(void* p, uint4 v) { asm volatile("st.relaxed.gpu.global.v4.b32 [%0], {%1,%2,%3,%4};" :: "l"(p), "r"(v.x), "r"(v.y), "r"(v.z), "r"(v.w) : "memory"); }
__device__ __forceinline__ void lds_frag(uint32_t* r, uint32_t a) {
    asm volatile("ld.shared.v4.b32 {%0,%1,%2,%3}, [%4];" : "=r"(r[0]), "=r"(r[1]), "=r"(r[2]), "=r"(r[3]) : "r"(a) : "memory");
}
__device__ __forceinline__ void lds_fragv(uint32_t* r, uint32_t a) {
    asm volatile("ld.volatile.shared.v4.b32 {%0,%1,%2,%3}, [%4];" : "=r"(r[0]), "=r"(r[1]), "=r"(r[2]), "=r"(r[3]) : "r"(a) : "memory");
}
__device__ __forceinline__ uint32_t xorv(uint32_t a, uint32_t b) { uint32_t d; asm volatile("xor.b32 %0, %1, %2;" : "=r"(d) : "r"(a), "r"(b)); return d; }
#define SCHED(k) asm volatile("{\n.reg .pred p;\nsetp.eq.u32 p, %0, %1;\n@p exit;\n}" :: "r"(sbu - s), "n"(k) : "memory")
#define PINM() asm volatile("{\n.reg .pred p;\nsetp.eq.u32 p, %0, 1;\n@p st.shared.u32 [%0], 0;\n}" :: "r"(sbu) : "memory")
__device__ __forceinline__ uint32_t or_and(uint32_t a, uint32_t b, uint32_t c) { uint32_t d; asm("lop3.b32 %0, %1, %2, %3, 0xF8;" : "=r"(d) : "r"(a), "r"(b), "r"(c)); return d; }
__device__ __forceinline__ uint32_t pack2v(float a, float b) { uint32_t d; asm volatile("cvt.rn.bf16x2.f32 %0, %1, %2;" : "=r"(d) : "f"(b), "f"(a)); return d; }
#define FU(x) __float_as_uint(x)
__device__ __forceinline__ uint32_t clk32() { uint32_t t; asm volatile("mov.u32 %0, %%clock;" : "=r"(t) :: "memory"); return t; }
__device__ __forceinline__ void spin_until(uint32_t t0, uint32_t d) {
    if (d) {
#pragma unroll 1
        while (__any_sync(0xffffffffu, clk32() - t0 < d)) {}
    }
}
constexpr int SH_OFF = 229376 + 384;
constexpr uint32_t HONE2 = 0x3c003c00u, HCNT2 = 0x50005000u;

__device__ __forceinline__ uint64_t desc_sw128(uint32_t addr, uint32_t lbo, uint32_t sbo) {
    return (uint64_t)((addr & 0x3FFFF) >> 4) | ((uint64_t)(lbo >> 4) << 16) | ((uint64_t)(sbo >> 4) << 32) | (1ull << 62);
}
#define DP 375
#define NAX 3
#define NXL 0
#define NCX 2
#define NCL 1
#define FLIP 1
#define VTA 1
#define KXB 4
#define ANB 3
#define BNB 3
#define CNB 3
#define SMA 0
#define SMB 0
#define SMC 0x01
#define IVA 0
#define RGA 160
#define RGC 160
#define RGB (504 - RGA - RGC)
#define NRW 8
#define NBR 16
#define E0 0
#define E1 6
#define E2 4
#define E3 8
#define IV 2
#define G2V 0
#define G2K 2
#define VDEP 0
#define AEARLY 0
#define VTP 2
#define LORD 1
#define TRK 1
#define T2N 14
#define NB0 0
#define NB1 9
#define DB2 80
#define DITHER 0
#define DB 40

__device__ __forceinline__ uint32_t wrow_off(int kk, int ch) {
    const int lane = threadIdx.x & 31, r = lane & 7;
    const int row = 64 * (kk >> 2) + 32 * (r & 1) + 16 * (kk & 1) + 8 * (lane >> 4) + 4 * ((kk >> 1) & 1) + (r >> 1);
    return row * 128 + ((ch ^ (row & 7)) << 4);
}
template <int K> __device__ __forceinline__ void sched(uint32_t key) {
    asm volatile("{\n.reg .pred p;\nsetp.eq.u32 p, %0, %1;\n@p exit;\n}" :: "r"(key), "n"(K) : "memory");
}
__device__ __forceinline__ void sched_i(int i, uint32_t key) {
    if (i == -1) sched<20>(key); if (i == 0) sched<21>(key); if (i == 1) sched<22>(key); if (i == 2) sched<23>(key);
    if (i == 3) sched<24>(key); if (i == 4) sched<25>(key); if (i == 5) sched<26>(key); if (i == 6) sched<27>(key);
}
template <int NB, int SM, class F>
__device__ __forceinline__ void g1(float* q0, float* k0, uint32_t (*wq)[4], uint32_t (*wk)[4], uint32_t ga, uint32_t key, F&& hook) {
    float q1[4], k1[4];
    uint32_t b[NB][4];
#pragma unroll
    for (int i = 0; i < NB; i++) ldsm4(b[i], ga + i * 512);
    hook(-1, b[0]);
    if (SM & 1) sched_i(-1, key);
#pragma unroll
    for (int i = 0; i < 8; i++) {
        uint32_t* c = b[i % NB];
        MMAF(i == 0, q0, wq[2 * i], c[0], c[1]); MMAF(i == 0, k0, wk[2 * i], c[0], c[1]);
        MMAF(i == 0, q1, wq[2 * i + 1], c[2], c[3]); MMAF(i == 0, k1, wk[2 * i + 1], c[2], c[3]);
        const uint32_t cc_[4] = {c[0], c[1], c[2], c[3]};
        if (i + NB < 8) ldsm4(b[i % NB], ga + (i + NB) * 512);
        hook(i, cc_);
        if ((SM >> (i + 1)) & 1) sched_i(i, key);
    }
#pragma unroll
    for (int i = 0; i < 4; i++) { q0[i] += q1[i]; k0[i] += k1[i]; }
}
__device__ __forceinline__ float frag_norm2(uint32_t (*w)[4]) {
    float d0[4], d1[4];
#pragma unroll
    for (int i = 0; i < 32; i++) { MMAF(i == 0, d0, w[i], w[i][0], w[i][2]); MMAF(i == 0, d1, w[i], w[i][1], w[i][3]); }
    const int lane = threadIdx.x & 31, g = lane >> 2, t = lane & 3;
    float v = g == 2 * t ? d0[0] + d1[2] : (g == 2 * t + 1 ? d0[1] + d1[3] : 0.f);
#pragma unroll
    for (int o = 16; o; o >>= 1) v += __shfl_xor_sync(0xffffffffu, v, o);
    return v;
}
__device__ __forceinline__ void arm_slot(uint32_t sb, int tile) {
    asm volatile("{\n.reg .pred p;\nelect.sync _|p, 0xffffffff;\n@p mbarrier.arrive.expect_tx.shared::cta.b64 _, [%0], 24576;\n}"
                 :: "r"(sb + R_BAR + 8 * (MB_FULL0 + (tile & 1))) : "memory");
}
__device__ __forceinline__ void load_slot(uint32_t sb, int c, int tile, const Maps& maps) {
    const uint32_t dst = sb + ((tile & 1) ? R_SLOT1 : R_SLOT0), mb = sb + R_BAR + 8 * (MB_FULL0 + (tile & 1));
    asm volatile("{\n.reg .pred p;\nelect.sync _|p, 0xffffffff;\n"
                 "@p cp.async.bulk.tensor.2d.shared::cluster.global.mbarrier::complete_tx::bytes [%0], [%2, {%5, %6}], [%4];\n"
                 "@p cp.async.bulk.tensor.3d.shared::cluster.global.mbarrier::complete_tx::bytes [%1], [%3, {%8, %6, %7}], [%4];\n}"
                 :: "r"(dst + 16384), "r"(dst), "l"((uint64_t)&maps.kx), "l"((uint64_t)&maps.vx3), "r"(mb), "r"(c * 64), "r"(tile * 64), "r"((c >> 1) * 2), "r"(0) : "memory");
}
__device__ __forceinline__ uint32_t put_mem0(uint32_t dst, uint4 a, uint4 b) {
    const uint4 m0 = make_uint4(prmt(a.x, b.x, 0x5410u), prmt(a.x, b.x, 0x7632u), prmt(a.y, b.y, 0x5410u), prmt(a.y, b.y, 0x7632u));
    const uint4 m1 = make_uint4(prmt(a.z, b.z, 0x5410u), prmt(a.z, b.z, 0x7632u), prmt(a.w, b.w, 0x5410u), prmt(a.w, b.w, 0x7632u));
    sts128u(dst, m0.x, m0.y, m0.z, m0.w);
    sts128u(dst + 512, m1.x, m1.y, m1.z, m1.w);
    return amax2b(amax2b(amax2b(m0.x, m0.y), amax2b(m0.z, m0.w)), amax2b(amax2b(m1.x, m1.y), amax2b(m1.z, m1.w)));
}
#define PUT_MAX(rL, W) sts32(rL + R_STG + 1024 + ((W) >> 2) * 512 + ((W) & 3) * 4, amax2b(amax2b(mx, my), mz));
__device__ __forceinline__ uint32_t h2b(uint32_t w) {
    uint32_t d;
    asm("{\n.reg .f16 l, h;\n.reg .f32 a, b;\nmov.b32 {l, h}, %1;\ncvt.f32.f16 a, l;\ncvt.f32.f16 b, h;\ncvt.rn.bf16x2.f32 %0, b, a;\n}" : "=r"(d) : "r"(w));
    return d;
}
#define GATHER1(HALF)                                                                                           \
        {                                                                                                       \
            const uint4 x0 = ldg_rlx4(pm), x1 = ldg_rlx4(pm + 256); const uint2 y = ldg_rlx2(px);                 \
            cw = (sel & 0x4000u) ? prmt(x0.w, x1.w, 0x7632u) : prmt(y.x, y.y, 0x5410u);                         \
            const uint32_t p0 = h2b(x0.x), p1 = h2b(x0.y), p2 = h2b(x0.z), p3 = h2b(prmt(x0.w, y.x, sel));      \
            stsm4t(rG + R_MEMB + HALF * 4096, p0, p1, p2, p3);                                                  \
            const uint32_t p4 = h2b(x1.x), p5 = h2b(x1.y), p6 = h2b(x1.z), p7 = h2b(prmt(x1.w, y.y, sel));      \
            stsm4t(rG + R_MEMB + HALF * 4096 + 512, p4, p5, p6, p7);                                            \
            mx = amax2b(amax2b(p0, p1), amax2b(p2, p3)); my = amax2b(p4, p5); mz = amax2b(p6, p7);              \
        }
#define GATHER(HALF, PRE, SYNC, AFTER)                                                                                      \
        {                                                                                                       \
            const uint32_t so = aslot(s);                                                                       \
            const uint32_t ua = (glo + acc_base(HALF * 4 + fo)) ^ so, ux = (glo + ext_base(HALF * 4 + fo)) ^ so; \
            uint2 lt;                                                                                           \
            lt.x = lds32v_(rL + R_LT); lt.y = lds32v_(rL + R_LT + 4);                                           \
            const uint32_t sel = 0x7610u - ((lt.x ^ (lt.x >> 2)) & 16) * 0x440u;                                \
            const uint32_t* pm = mkptr(ua + lt.x, ghi);                                                         \
            const uint32_t* px = mkptr(ux + lt.y, ghi);                                                         \
            PRE                                                                                                 \
            bar_sync(5, 384);                                                                                   \
            const uint32_t t0 = clk32();                                                                        \
            TSACC();                                                                        \
            SYNC                                                                                                \
            spin_until(t0, DP + DITHER);                                                                                 \
            \
            TS(10, 0);                                                                                          \
            uint32_t cw, nr = 0;                                                                                \
            _Pragma("unroll 1") do {                                                                            \
                GATHER1(HALF)                                                                                   \
                nr++;                                                                                           \
            } while (__any_sync(0xffffffffu, cw != HCNT2 && nr < SPIN_LIMIT));                                  \
            TS(11, cw);                                                                                         \
            AFTER                                                                                               \
            CNT2(HALF * 4 + (s & 1) * 2 + (nr > 2), nr > 1); CNT2(64 + s, nr > 1);                                                    \
            \
        }
#define GOBAR (fo == 3 ? 14 : 10 + fo)

__device__ __forceinline__ void rec_a(uint32_t sb, int c, const bf16* __restrict__ mem0, uint32_t epoch) {
    const int tid = threadIdx.x - WGA * 128, lane = tid & 31, f = tid >> 5;
    uint32_t wq[16][4], wk[16][4], mx, my = 0, mz = 0;
    const int lrow = ((lane >> 4) << 3) + (lane & 7), lsel = (lane >> 3) & 1;
    {
        const uint32_t* mp = (const uint32_t*)(mem0 + (lane & 7) * DM + f * 64 + (lane >> 3) * 8);
        const uint4 ma = ldg_rlx4(mp), mb = ldg_rlx4(mp + 16), mc = ldg_rlx4(mp + 128), md = ldg_rlx4(mp + 144);
        mbar_wait(sb + R_BAR + 8 * MB_W0, 0);
        if (c == 7 && tid == 0) GT(1421);
#pragma unroll
        for (int kk = 0; kk < 16; kk++) { const uint32_t a = sb + R_T + wrow_off(kk, 2 * f + lsel); ldsm4t(wq[kk], a); ldsm4t(wk[kk], a + 32768); }
        __syncwarp();
        bar_sync(4, 128);
        mx = put_mem0(sb + R_MEMB + f * 1024 + lane * 16, ma, mb);
        my = put_mem0(sb + R_MEMB + 4096 + f * 1024 + lane * 16, mc, md);
        bar_arrive(5, 256);
    }
    const uint32_t rL = opaque(sb + lane * 16), rG = opaque(sb + lane * 16 + f * 1024);
    const uint32_t sbu = uni(sb), fo = uni(f), cc = uni(c);
    const uint64_t gx = xpage();
    const uint32_t ghi = uni((uint32_t)(gx >> 32)), glo = uni((uint32_t)gx);
#pragma unroll
    for (int i = 0; i < NAX; i++) {
        sts128u(rG + R_AX + 4096 * i, wq[i][0], wq[i][1], wq[i][2], wq[i][3]);
        sts128u(rG + R_AX + 4096 * i + 512, wk[i][0], wk[i][1], wk[i][2], wk[i][3]);
    }
    sts128u(rL + R_LT + 512 + f * 512, (sb + R_SREM + (f >= 2 ? lane * 8 + f * 256 : lane * 16 + f * 1024)) ^ 0x01000000u, (sb + R_BAR + 8 * MB_S) ^ 0x01000000u,
            sb + R_QP + (lane >> 4) * 128 + lsel * 512 + (lane & 7) * 16 + (f == 3 ? 2048 : 0), sb + R_SLOT0 + lrow * 128 + ((lsel ^ (lane & 7)) << 4));
    __syncwarp();
    if (tid == 0) GT(c * 8 + 1);
    TSDECL;
    const float cexp = 0.08838834764831845f * 1.4426950408889634f;
    float cs = cexp;
    auto step = [&](int s, bool first) -> bool {
        bar_sync(1, 128);
        float q0[4], k0[4];
        uint4 ta;
        uint32_t zr, rl2;
        g1<ANB, SMA>(q0, k0, wq, wk, rL + R_MEMB, sbu - s, [&](int i, const uint32_t* c_) {
            if (i == 0) TS(0, c_[0]);
            if (i == -1) {
#pragma unroll
                for (int n = NAX - NXL; n < NAX; n++) { lds_fragv(wq[n], rG + R_AX + 4096 * n); lds_fragv(wk[n], rG + R_AX + 4096 * n + 512); }
                ta = lds128uv(rL + R_LT + 512 + fo * 512);
                zr = ta.w & 1; rl2 = rL | zr;
            }
            if (i == IVA) { PUT_MAX(rl2, fo) bar_arrive(15, 256); bar_arrive(GOBAR, 96); }
        });
        stsm4t(rG + R_QP, pack2(q0[0], q0[1]), pack2(q0[2], q0[3]), pack2(k0[0], k0[1]), pack2(k0[2], k0[3]));
        TS(1, FU(k0[3]));
        if (first) mbar_wait_p(sbu + R_BAR + 8 * MB_FULL0, 0);
        if (fo >= 2) {
            bar_sync(3, 256);
            uint32_t kb[4], kc[4], qa[4], qc[4];
            ldsm4(kb, ta.z + 256); ldsm4(qa, ta.z);
            ldsm4(kc, ta.z + 1280); ldsm4(qc, ta.z + 1024);
            const uint32_t k0_ = hadd2b(kb[0], kb[1]), k1_ = hadd2b(kb[2], kb[3]), k2_ = hadd2b(kc[0], kc[1]), k3_ = hadd2b(kc[2], kc[3]);
            float s0[4], s2[4];
            MMAZ(s0, qa, k0_, k1_); MMAZ(s2, qc, k2_, k3_);
            const float x = ((s0[0] + s0[2]) + (s2[0] + s2[2])) * cs, y = ((s0[1] + s0[3]) + (s2[1] + s2[3])) * cs;
            st_async2(ta.x, FU(x), FU(y), ta.y);
            TS(3, FU(y));
            sts64((ta.x ^ 0x01000000u) + (R_SLOC - R_SREM), x, y);
            sts128u(rl2 + R_STG + (fo & 1) * 512, k0_, k1_, k2_, k3_);
            bar_arrive(9, 192);
        } else {
            uint32_t qa[4][4], kx[4][4];
#pragma unroll
            for (int kk = 0; kk < KXB; kk++) ldsm4(kx[kk], (ta.w ^ (kk * 32)) + (16384 + fo * 2048));
            bar_sync(3, 256);
#pragma unroll
            for (int kk = 0; kk < 4; kk++) {
                if (kk >= KXB) ldsm4(kx[kk], (ta.w ^ (kk * 32)) + (16384 + fo * 2048));
                ldsm4(qa[kk], ta.z + kk * 1024);
            }
            float s0[4], s1[4], s2[4], s3[4];
            MMAZ(s0, qa[0], kx[0][0], kx[0][1]); MMAZ(s1, qa[0], kx[0][2], kx[0][3]);
            MMAZ(s2, qa[1], kx[1][0], kx[1][1]); MMAZ(s3, qa[1], kx[1][2], kx[1][3]);
            MMA(s0, qa[2], kx[2][0], kx[2][1]); MMA(s1, qa[2], kx[2][2], kx[2][3]);
            MMA(s2, qa[3], kx[3][0], kx[3][1]); MMA(s3, qa[3], kx[3][2], kx[3][3]);
            const float x = ((s0[0] + s0[2]) + (s2[0] + s2[2])) * cs, y = ((s0[1] + s0[3]) + (s2[1] + s2[3])) * cs;
            const float z = ((s1[0] + s1[2]) + (s3[0] + s3[2])) * cs, w = ((s1[1] + s1[3]) + (s3[1] + s3[3])) * cs;
            st_async4(ta.x, x, y, z, w, ta.y);
            TS(3, FU(w));
            sts128(rG + R_SLOC, x, y, z, w);
        }
        const uint32_t r8 = (rl2 + sbu) >> 1;
        uint32_t vt00[4], vt01[4], vt10[4], vt11[4];
        const uint32_t rV = ta.w ^ ((fo & 1) * 64), vo = (fo >> 1) * 8192;
        if (!VTA && VTP < 2) { ldsm4t(vt00, rV + vo); ldsm4t(vt10, (rV ^ 32) + vo); }
        if (!VTA && VTP < 1) { ldsm4t(vt01, rV + vo + 2048); ldsm4t(vt11, (rV ^ 32) + vo + 2048); }
        bar_sync(4, 128);
        const float2 l2 = lds64v(r8 + R_SLOC + 512), l3 = lds64v(r8 + R_SLOC + 768);
        const float4 l0 = lds128v(rL + R_SLOC), l1 = lds128v(rL + R_SLOC + 1024);
        if (VTA && VTP < 2) { ldsm4t(vt00, rV + vo); ldsm4t(vt10, (rV ^ 32) + vo); }
        if (VTA && VTP < 1) { ldsm4t(vt01, rV + vo + 2048); ldsm4t(vt11, (rV ^ 32) + vo + 2048); }

        if (s == NSEG - 1) { mbar_wait_u(sbu + R_BAR + 8 * MB_S, 1); mbar_wait_u(sbu + R_BAR + 8 * MB_V, 1); return true; }
        TS(2, FU(l3.y));
        mbar_wait_p(sbu + R_BAR + 8 * MB_S, s & 1);
        TS(4, 0);
        {
            const float2 r2 = lds64v(r8 + R_SREM + 512), r3 = lds64v(r8 + R_SREM + 768);
            const float4 r0 = lds128v(rL + R_SREM), r1 = lds128v(rL + R_SREM + 1024);
            if (VTP >= 1) PINM();
            if (VTP >= 2) { ldsm4t(vt00, rV + vo); ldsm4t(vt10, (rV ^ 32) + vo); }
            if (VTP >= 1) { ldsm4t(vt01, rV + vo + 2048); ldsm4t(vt11, (rV ^ 32) + vo + 2048); }
            float sv[10];
            sv[0] = l0.x + r0.x; sv[1] = l0.y + r0.y; sv[2] = l0.z + r0.z; sv[3] = l0.w + r0.w;
            sv[4] = l1.x + r1.x; sv[5] = l1.y + r1.y; sv[6] = l1.z + r1.z; sv[7] = l1.w + r1.w;
            sv[8] = ((l2.x + l3.x) + r2.x) + r3.x; sv[9] = ((l2.y + l3.y) + r2.y) + r3.y;
            float m = fmaxf(fmaxf(fmaxf(fmaxf(sv[8], sv[9]), sv[0]), fmaxf(fmaxf(sv[2], sv[3]), sv[1])), fmaxf(fmaxf(sv[4], sv[5]), fmaxf(sv[6], sv[7])));
            {
                const float m1 = __shfl_xor_sync(0xffffffffu, m, 1), m2 = __shfl_xor_sync(0xffffffffu, m, 2), m3 = __shfl_xor_sync(0xffffffffu, m, 3);
                m = fmaxf(fmaxf(m, m1), fmaxf(m2, m3));
            }
            TS(5, FU(m));
            const uint32_t ONE2 = 0x3f803f80u;
            float o0[4], o1[4], sm[4];
            const uint32_t pb0 = pack2(ex2(sv[0] - m), ex2(sv[1] - m)), pb1 = pack2(ex2(sv[2] - m), ex2(sv[3] - m));
            mma16816z(sm, ONE2, ONE2, ONE2, ONE2, pb0, pb1);
            MMAZ(o0, vt00, pb0, pb1); MMAZ(o1, vt10, pb0, pb1);
            const uint32_t z = (VDEP == 0 ? FU(m) : pb0) & zr;
            const uint32_t vok = mbar_test(sbu + R_BAR + 8 * MB_V + z, s & 1);
            const uint32_t rv = r8 + vok * 8;
            float2 va = lds64v(rv + R_VB - 8 + fo * 512);
            float2 vb = lds64v(rv + R_VB - 8 + fo * 512 + 256);
            float sig = __uint_as_float(lds32v_(sbu + R_MISC + 40));
            const uint32_t pb2 = pack2(ex2(sv[4] - m), ex2(sv[5] - m)), pb3 = pack2(ex2(sv[6] - m), ex2(sv[7] - m));
            mma16816(sm, ONE2, ONE2, ONE2, ONE2, pb2, pb3);
            const uint32_t pb4 = pack2(ex2(sv[8] - m), ex2(sv[9] - m));
            MMA(o0, vt01, pb2, pb3); MMA(o1, vt11, pb2, pb3);
            mma1688(sm, ONE2, ONE2, pb4);
            const float z0 = rcpf(sm[0]), z1 = rcpf(sm[1]);
#define PUT_O()                                                                                                   \
            {                                                                                                     \
                float a0[4] = {o0[0], o0[1], o0[2], o0[3]}, a1[4] = {o1[0], o1[1], o1[2], o1[3]};                 \
                mma1688(a0, FU(va.x), FU(va.y), pb4); mma1688(a1, FU(vb.x), FU(vb.y), pb4);                       \
                const float i0 = z0 * sig, i1 = z1 * sig;                                                         \
                stsm4t(rG + R_QP, pack2(a0[0] * i0, a0[1] * i1), pack2(a0[2] * i0, a0[3] * i1), pack2(a1[0] * i0, a1[1] * i1), pack2(a1[2] * i0, a1[3] * i1)); \
            }
            PUT_O()
            asm volatile("{\n.reg .pred p;\nsetp.ne.u32 p, %0, 0;\n@p bar.arrive 8, 256;\n}" :: "r"(vok) : "memory");
            if (__builtin_expect(__any_sync(0xffffffffu, vok == 0), 0)) {
                mbar_wait_p(sbu + R_BAR + 8 * MB_V, s & 1);
                va = lds64v(r8 + R_VB + fo * 512); vb = lds64v(r8 + R_VB + fo * 512 + 256);
                sig = __uint_as_float(lds32v_(sbu + R_MISC + 40));
                PUT_O()
                bar_arrive(8, 256);
                CNT(8); CNT(128 + s);
            }
            TS(6, 0);
            const float r = __uint_as_float(0x7f000000u - FU(sig));
            cs = cexp * r * (fo >= 2 ? r : 1.f);
        }
        return false;
    };
    step(0, true);
#pragma unroll 1
    for (int s = 0;; s++) {
        if (s & 1) mbar_wait_p(sbu + R_BAR + 8 * (MB_FULL0 + (((s + 1) >> 1) & 1)), ((s + 1) >> 2) & 1);
        {
            const uint32_t a = rL + R_LT + 512 + 12 + fo * 512;
            sts32(a, lds32v_(a) + ((s & 1) ? ((s & 2) ? R_SLOT0 - R_SLOT1 - 4096 : R_SLOT1 - R_SLOT0 - 4096) : 4096));
        }
        auto early = [&]() {
            SCHED(13);
#pragma unroll
            for (int i = 0; i < NAX - NXL; i++) { lds_fragv(wq[i], rG + R_AX + 4096 * i); lds_fragv(wk[i], rG + R_AX + 4096 * i + 512); }
        };
        GATHER(0, , early();, )
        if (step(s + 1, false)) break;
    }
    CNT(9);
    if (rG == sbu) GT(cc * 8 + 4);
}

__device__ __forceinline__ void rec_b(uint32_t sb, int c, uint32_t epoch) {
    const int tid = threadIdx.x - WGB * 128, lane = tid & 31, f = tid >> 5;
    uint32_t wq[16][4], wk[16][4], wo[32][4];
    const int lrow = ((lane >> 4) << 3) + (lane & 7), lsel = (lane >> 3) & 1;
    const uint32_t rL = opaque(sb + lane * 16), rW = opaque(sb + lane * 16 + f * 16384);
    const uint32_t sbu = uni(sb), fo = uni(f), cc = uni(c), po = cc & 1, ep = uni(epoch);
    {
        mbar_wait(sb + R_BAR + 8 * MB_WO, 0);
        if (c == 7 && tid == 0) GT(1426);
        const uint32_t aO = sb + R_WO + f * 16384 + lrow * 128 + ((lsel ^ (lane & 7)) << 4);
#pragma unroll
        for (int i = 0; i < 32; i++) {
            const int tile = (i >> 4) * 2 + (i & 1), kk = (i >> 1) & 7;
            ldsm4t(wo[i], (aO ^ (32 * tile)) + kk * 2048);
        }
        const float no = frag_norm2(wo);
        if (lane == 0) sts32(sb + R_MISC + 80 + f * 4, FU(no));
        __syncwarp();
        bar_sync(0, 256);
        if (tid == 0) {
            const float4 a = lds128(sb + R_MISC + 64), b = lds128(sb + R_MISC + 80);
            stg4(&g_f.norm[c], make_uint4(FU((a.x + a.y) + (a.z + a.w)), epoch, FU((b.x + b.y) + (b.z + b.w)), epoch));
        }
        __syncwarp();
#pragma unroll
        for (int i = NRW; i < 32; i++) sts128u(rW + R_WO + i * 512, wo[i][0], wo[i][1], wo[i][2], wo[i][3]);
        mbar_wait(sb + R_BAR + 8 * MB_W1, 0);
        if (c == 7 && tid == 0) GT(1422);
        __syncwarp();
#pragma unroll
        for (int kk = 0; kk < 16; kk++) { const uint32_t a = sb + R_QK1 + wrow_off(kk, 2 * f + lsel); ldsm4t(wq[kk], a); ldsm4t(wk[kk], a + 32768); }
        bar_sync(13, 128);
#pragma unroll
        for (int i = 0; i < 16; i++) {
            sts128u(rW + R_QK1 + i * 1024, wq[i][0], wq[i][1], wq[i][2], wq[i][3]);
            sts128u(rW + R_QK1 + i * 1024 + 512, wk[i][0], wk[i][1], wk[i][2], wk[i][3]);
        }
        __syncwarp();
    }
    const uint64_t gx = xpage();
    const uint32_t ghi = uni((uint32_t)(gx >> 32)), glo = uni((uint32_t)gx);
    TSDECL;
#pragma unroll 1
    for (int s = 0;; s++) {
        bar_sync(2, 256);
        float q0[4], k0[4];
        g1<BNB, SMB>(q0, k0, wq, wk, rL + R_MEMB + 4096, sbu - s, [&](int i, const uint32_t* c_) {
            if (i == 0) TS(0, c_[0]);
            if (i >= 2 && i < 6) {
#pragma unroll
                for (int n = NRW + (i - 2) * E0 / 4; n < NRW + (i - 1) * E0 / 4; n++) lds_fragv(wo[n], rW + R_WO + n * 512);
            }
            if (i == IV) bar_arrive(GOBAR, 96);
        });
        stsm4t(rL + fo * 1024 + R_QP + 512, pack2(q0[0], q0[1]), pack2(q0[2], q0[3]), pack2(k0[0], k0[1]), pack2(k0[2], k0[3]));
        bar_arrive(3, 256);
        TS(1, FU(k0[3]));
        const uint32_t so = aslot(s);
        uint2 lt;
        { const float2 t = lds64v(rL + R_LT + 8); lt.x = FU(t.x); lt.y = FU(t.y); }
        const uint32_t sel = 0x3210u + (lt.x & 16) * 0x440u;
        uint32_t* pm = (uint32_t*)mkptr(((glo + acc_base(po * 4 + fo)) ^ so) + lt.x, ghi);
        uint32_t* px = (uint32_t*)mkptr(((glo + ext_base(po * 4 + fo)) ^ so) + lt.y, ghi);
        if (s == NSEG - 1) break;
        {
            const uint32_t z = lt.x & 1;
#pragma unroll
            for (int n = NRW; n < NRW + E0 + E1 + E2 + E3; n++) {
                const int d = n - (n < NRW + T2N ? TRK + 1 : TRK);
                lds_fragv(wo[n], (d >= NRW ? or_and(rW, wo[d][0], z) : rW) + R_WO + n * 512);
            }
        }
        TS(2, wo[NRW + E0 + E1 + E2 + E3 - 1][0]);
        SCHED(4);
        bar_sync(8, 256);
        {
            float o[4][4];
            uint32_t b[4][4];
#pragma unroll
            for (int i = 0; i < 4; i++) ldsm4(b[i], rL + R_QP + i * 1024);
            PINM();
#pragma unroll
            for (int n = NRW + E0 + E1 + E2 + E3; n < 32; n++) lds_fragv(wo[n], rW + R_WO + n * 512);
            float p[4][4];
#define G2_STEP(o, hf, kk) _Pragma("unroll") for (int i = 0; i < 2; i++) MMAF((kk) < 2, o[((kk) & 1) * 2 + i], wo[(hf) * 16 + (kk) * 2 + i], b[(kk) >> 1][((kk) & 1) * 2], b[(kk) >> 1][((kk) & 1) * 2 + 1])
#define G2_RED(o, wl, h) const uint32_t wl = packh2(o[1][2] + o[3][2], o[1][3] + o[3][3]);                            \
                asm volatile("red.relaxed.gpu.global.add.noftz.v4.f16x2 [%0], {%1,%2,%3,%4};" :: "l"(pm + (h) * 16),  \
                    "r"(packh2(o[0][0] + o[2][0], o[0][1] + o[2][1])), "r"(packh2(o[0][2] + o[2][2], o[0][3] + o[2][3])), \
                    "r"(packh2(o[1][0] + o[3][0], o[1][1] + o[3][1])), "r"(prmt(wl, HONE2, (h) ? sel : sel ^ 0x4400u)) : "memory")
            if (G2V == 1) SCHED(11);
#pragma unroll
            for (int kk = 0; kk < 8; kk++) { G2_STEP(o, 0, kk); }
            TS(7, b[0][0]);
            if (G2V == 0) SCHED(11);
            else {
#pragma unroll
                for (int i = 0; i < 4; i++) wo[16 + i][0] = or_and(wo[16 + i][0], FU(o[i][0]), lt.x & 1);
            }
#pragma unroll
            for (int kk = 0; kk < G2K; kk++) { G2_STEP(p, 1, kk); }
#pragma unroll
            for (int i = 0; i < NB0; i++) { lds_fragv(wq[i], rW + R_QK1 + i * 1024); lds_fragv(wk[i], rW + R_QK1 + i * 1024 + 512); }
            G2_RED(o, w3, 0);
            TS(8, w3);
            if (G2V == 0) SCHED(12);
#pragma unroll
            for (int kk = G2K; kk < 8; kk++) { G2_STEP(p, 1, kk); }
            G2_RED(p, w7, 1);
            asm volatile("red.relaxed.gpu.global.add.noftz.f16x2 [%0], %1;" :: "l"(px), "r"(prmt((w3 & 0xffff0000u) | 0x3c00u, w7, sel)) : "memory");
            TS(9, w7);
        }
        bar_arrive(5, 384);
        asm volatile("{\n.reg .pred p;\nsetp.eq.u32 p, %0, %1;\n@p mbarrier.arrive.expect_tx.shared::cta.b64 _, [%2], 1536;\n}"
                     :: "r"(rW), "r"(sbu), "r"(sbu + R_BAR + 8 * MB_S) : "memory");
        const uint32_t tb = clk32();
        TSACC();
        spin_until(tb, DB);
#pragma unroll
        for (int i = NB0; i < NBR; i++) {
            if (i == NB1) spin_until(tb, DP + DB2);
            lds_fragv(wq[i], rW + R_QK1 + i * 1024); lds_fragv(wk[i], rW + R_QK1 + i * 1024 + 512);
        }
    }
}

#undef lds_fragv
__device__ __forceinline__ void rec_first_loads(uint32_t sb, int c, const Maps& maps) {
    const uint32_t bar = sb + R_BAR;
    const int F0 = c * 64;
    mbar_expect_tx(bar + 8 * MB_W0, 65536); mbar_expect_tx(bar + 8 * MB_WO, 65536); mbar_expect_tx(bar + 8 * MB_WV, 65536);
    tma2d(sb + R_QK1, &maps.wv, F0, 0, bar + 8 * MB_WV); tma2d(sb + R_QK1 + 32768, &maps.wv, F0, 256, bar + 8 * MB_WV);
    tma2d(sb + R_T + 32768, &maps.wk, F0, 0, bar + 8 * MB_W0);
    if (!LORD) {
        for (int i = 0; i < 4; i++) tma2d(sb + R_WO + i * 16384, &maps.wo, (c & 1) * 256 + i * 64, (c >> 1) * 128, bar + 8 * MB_WO);
        tma2d(sb + R_T, &maps.wq, F0, 0, bar + 8 * MB_W0);
    }
    mbar_expect_tx(bar + 8 * MB_S, 1536);
}
__device__ __forceinline__ void rec_c(uint32_t sb, int c, const bf16* __restrict__ mem0, const Maps& maps, uint32_t epoch) {
    const int tid = threadIdx.x - WGC * 128, lane = tid & 31, u = tid >> 5;
    const uint32_t bar = sb + R_BAR;
    const int lrow = ((lane >> 4) << 3) + (lane & 7), lsel = (lane >> 3) & 1;
    const int kh = u >> 1, j = u & 1;
    uint32_t wv[32][4], mx = 0, my = 0, mz = 0;
    {
        if (u == 0) {
            sts128u(sb + lane * 16 + R_LT, (lane >> 3) * 256 + (lane & 7) * 16, ((lane >> 2) & 1) * XHS + (lane >> 4) * XSS + (lane & 8) * 2 + (lane & 2) * 4,
                    (lane >> 2) * 256 + (lane & 3) * 16, (lane & 1) * XHS + ((lane >> 3) & 1) * XSS + (lane & 6) * 4 + (lane >> 4) * 4);
        }
        mbar_wait(bar + 8 * MB_WV, 0);
        if (c == 7 && tid == 0) GT(1425);
        if (LORD && tid == 32) {
            for (int i = 0; i < 4; i++) tma2d(sb + R_WO + i * 16384, &maps.wo, (c & 1) * 256 + i * 64, (c >> 1) * 128, bar + 8 * MB_WO);
            tma2d(sb + R_T, &maps.wq, c * 64, 0, bar + 8 * MB_W0);
        }
        __syncwarp();
#pragma unroll
        for (int kk = 0; kk < 16; kk++) {
            const uint32_t aa = sb + R_QK1 + kh * 32768 + wrow_off(kk, 4 * j + 2 * kh + lsel);
            ldsm4t(wv[kk], aa); ldsm4t(wv[16 + kk], aa ^ 32);
        }
        {
            uint32_t x = 0;
#pragma unroll
            for (int i = 0; i < 32; i++) x ^= wv[i][0];
            sts32(sb + R_MISC + 96 + u * 4, __reduce_xor_sync(0xffffffffu, x));
        }
        bar_sync(9, 128);
        if (c == 7 && tid == 0) GT(1423);
        if (tid == 0) {
            mbar_expect_tx(bar + 8 * MB_W1, 65536);
            tma2d(sb + R_QK1 + 32768, &maps.wk, c * 64, 256, bar + 8 * MB_W1); tma2d(sb + R_QK1, &maps.wq, c * 64, 256, bar + 8 * MB_W1);
        }
        __syncwarp();
        const float nv = frag_norm2(wv);
        if (lane == 0) sts32(sb + R_MISC + 64 + u * 4, FU(nv));
        __syncwarp();
        bar_arrive(0, 256);
    }
    const uint32_t rL = opaque(sb + lane * 16), rG = opaque(sb + lane * 16 + u * 1024);
    const uint32_t sbu = uni(sb), fo = uni(u), cc = uni(c), ep = uni(epoch);
    const uint64_t gx = xpage();
    const uint32_t ghi = uni((uint32_t)(gx >> 32)), glo = uni((uint32_t)gx);
    TSDECL;
    uint32_t rpb = 0x3f800000u;
    uint32_t kvq = ~ep;
    auto ring = [&](int s) {
        uint32_t n = 0;
#pragma unroll 1
        while (!__all_sync(0xffffffffu, kvq == ep)) {
            kvq = ldg_rlx(&g_f.kv[(s + 2) >> 1][cc >> 1][(rL >> 4) & 1]);
            if (++n > SPIN_LIMIT) { ABORT(6); break; }
        }
        arm_slot(sbu, (s + 2) >> 1);
    };
    if (fo == 3) { ring(-2); load_slot(sbu, cc, 0, maps); if (cc == 7 && rL == sbu) GT(1427); }
    bar_sync(5, 256);
    bar_arrive(2, 256);
    constexpr int CX = R_AX + NAX * 4096;
    static_assert(NAX + NCX <= 6, "AX");
#pragma unroll
    for (int i = 0; i < NCX; i++) {
        sts128u(rG + CX + 4096 * i, wv[i][0], wv[i][1], wv[i][2], wv[i][3]);
        sts128u(rG + CX + 4096 * i + 512, wv[16 + i][0], wv[16 + i][1], wv[16 + i][2], wv[16 + i][3]);
    }
    __syncwarp();
#pragma unroll 1
    for (int s = 0;; s++) {
        PUT_MAX(rL, 4 + fo)
        if (fo != 0) bar_arrive(15, 256);
        if (fo == 3 && !(s & 1) && s > 0 && s + 2 < NSEG) load_slot(sbu, cc, (s + 2) >> 1, maps);
#pragma unroll
        for (int i = NCX - NCL; i < NCX; i++) { lds_fragv(wv[i], rG + CX + 4096 * i); lds_fragv(wv[16 + i], rG + CX + 4096 * i + 512); }
        if (fo == 0) {
                bar_sync(15, 256);
                if (s == 0) {
                    const uint32_t* np = (const uint32_t*)&g_f.norm[0] + ((rL ^ sbu) >> 2);
                    uint4 r, q; uint32_t n = 0;
#pragma unroll 1
                    while (true) {
                        r = ldg_rlx4(np); q = ldg_rlx4(np + 128);
                        const uint2 z = ldg_rlx2(&g_f.xn[(rL ^ sbu) >> 3]);
                        if (__all_sync(0xffffffffu, r.y == ep && r.w == ep && q.y == ep && q.w == ep && z.x == ep && z.y == ep)) break;
                        if (++n > SPIN_LIMIT) { ABORT(5); break; }
                    }
                    float nv = __uint_as_float(r.x) + __uint_as_float(q.x), no = __uint_as_float(r.z) + __uint_as_float(q.z);
#pragma unroll
                    for (int o = 16; o; o >>= 1) { nv += __shfl_xor_sync(0xffffffffu, nv, o); no += __shfl_xor_sync(0xffffffffu, no, o); }
                    const int lc = ((int)(FU(nv) >> 23) + (int)(FU(no) >> 23) - 252 + 9 + 1) >> 1;
                    sts32(sbu + R_MISC + 32, 140 - lc);
                    __syncwarp();
                }
                const uint4 ma = lds128uv(rL + R_STG + 1024), mb = lds128uv(rL + R_STG + 1536);
                const uint32_t m_ = amax2b(amax2b(amax2b(ma.x, ma.y), amax2b(ma.z, ma.w)), amax2b(amax2b(mb.x, mb.y), amax2b(mb.z, mb.w)));
                const int em = (int)(__reduce_max_sync(0xffffffffu, amax2b(m_, m_ << 16) & 0x7f800000u) >> 23) + (int)(rpb >> 23) - 127;
                const int es = min(max((int)lds32v_(sbu + R_MISC + 32) - max(em, 127), -60), 60);
                sts32(sbu + R_MISC + 40, (127 + es) << 23);
                TS(4, es);
        }
        bar_sync(GOBAR, 96);
        float v0[4], v1[4];
        g1<CNB, SMC>(v0, v1, wv, wv + 16, rL + R_MEMB + (fo >> 1) * 4096, sbu - s, [&](int i, const uint32_t* c_) { if (i == 0) TS(0, c_[0]); });
        TS(1, FU(v1[3]));
        const uint32_t l16 = (rL ^ sbu) | (lds32v_(rL + R_LT + 4) & 1);
        const uint32_t r8 = sbu + (l16 >> 1);
        {
            sts128(rL + R_VRED + fo * 512, v1[0], v1[1], v1[2], v1[3]);
            const uint32_t d = r8 + R_VB + ((cc & 1) * 4 + (fo & 1) * 2 + (fo >> 1)) * 256;
            const uint32_t dr = xorv(d, 0x01000000u), br = xorv(sbu + R_BAR + 8 * MB_V, 0x01000000u);
            bar_sync(6 + (fo & 1), 64);
            const float4 a0 = lds128(rL + R_VRED + (fo ^ 2) * 512);
            const float rp = __uint_as_float(rpb);
            const uint32_t w0 = pack2((v0[0] + a0.x) * rp, (v0[1] + a0.y) * rp), w1 = pack2((v0[2] + a0.z) * rp, (v0[3] + a0.w) * rp);
            st_async2(dr, w0, w1, br);
            TS(3, w1);
            sts64(d, __uint_as_float(w0), __uint_as_float(w1));
            if (fo != 1) bar_arrive(9, 192);
            __syncwarp();
            asm volatile("{\n.reg .pred p;\nsetp.eq.u32 p, %0, %1;\n@p mbarrier.arrive.expect_tx.shared::cta.b64 _, [%2], 256;\n}"
                         :: "r"(rL), "r"(sbu), "r"(sbu + R_BAR + 8 * MB_V) : "memory");
        }
        if (fo == 1) {
            bar_sync(9, 192);
            uint8_t* dst = (uint8_t*)&g_KVf[s][cc >> 1][(cc & 1) * 256] + l16;
            const uint32_t r2 = prmt(rpb, 0, 0x3232u);
#pragma unroll
            for (int i = 0; i < 2; i++) {
                const uint4 a = lds128uv(rL + R_STG + i * 512);
                stg4(dst + i * 512, make_uint4(~hmul2b(a.x, r2), ~hmul2b(a.y, r2), ~hmul2b(a.z, r2), ~hmul2b(a.w, r2)));
                const float2 b0 = lds64v(r8 + R_VB + (cc & 1) * 1024 + i * 512), b1 = lds64v(r8 + R_VB + (cc & 1) * 1024 + i * 512 + 256);
                stg4(dst + 2048 + i * 512, make_uint4(~FU(b0.x), ~FU(b0.y), ~FU(b1.x), ~FU(b1.y)));
            }
            __syncwarp();
            if (l16 == 0) { stg_rlx(&g_f.rec[cc >> 1][cc & 1], (ep << 8) | (s + 1)); if (s == NSEG - 1) GT(1500 + cc); }
            __syncwarp();
        } else {
            if (fo == 2) {
                if (l16 < 144) stg4((void*)mkptr((glo + zero_off(cc, l16 >> 4)) ^ aslot(s + 4), ghi), make_uint4(0, 0, 0, 0));
                __syncwarp();
            } else if (fo == 3) {
                kvq = ldg_rlx(&g_f.kv[min((s + 3) >> 1, NT - 1)][cc >> 1][(l16 >> 4) & 1]);
                if (s == 0) { ring(s); load_slot(sbu, cc, 1, maps); }
            }
        }
        if (s == NSEG - 1) break;
        auto early = [&]() {
#pragma unroll
            for (int i = 0; i < NCX - NCL; i++) { lds_fragv(wv[i], rG + CX + 4096 * i); lds_fragv(wv[16 + i], rG + CX + 4096 * i + 512); }
            if (fo == 3 && (s & 1) && s + 3 < NSEG) ring(s + 1);
        };
        GATHER(1, , early(); rpb = 0x7f000000u - lds32v_(sbu + R_MISC + 40);, bar_arrive(2, 256);)
    }
}

__device__ __forceinline__ bool cand_better(float v, int i, float bv, int bi) { return v > bv || (v == bv && i < bi); }

constexpr int G_W = 0;
constexpr int G_RING = 131072;
constexpr int G_BUF = 163840;
constexpr int G_BAR = 229376;
constexpr int G_SMEM = G_BAR + 512;
enum { GB_FULL = 0, GB_EMPTY = GB_FULL + 8, GB_KV = GB_EMPTY + 8, GB_STG = GB_KV + 2, GB_FREE = GB_STG + 2, GB_XN = GB_FREE + 2, GB_T1D, GB_P0, GB_VV, GB_KVF = GB_VV + 2, GB_VF, GB_N };
constexpr int SMEM_TOTAL = 232448;

__device__ __forceinline__ void wgmma_n128(float* d, uint64_t da, uint64_t db, int scale_d) {
    asm volatile("{\n.reg .pred p;\nsetp.ne.b32 p, %66, 0;\n"
        "wgmma.mma_async.sync.aligned.m64n128k16.f32.bf16.bf16 "
        "{%0,%1,%2,%3,%4,%5,%6,%7,%8,%9,%10,%11,%12,%13,%14,%15,%16,%17,%18,%19,%20,%21,%22,%23,%24,%25,%26,%27,%28,%29,%30,%31,"
        "%32,%33,%34,%35,%36,%37,%38,%39,%40,%41,%42,%43,%44,%45,%46,%47,%48,%49,%50,%51,%52,%53,%54,%55,%56,%57,%58,%59,%60,%61,%62,%63}, "
        "%64, %65, p, 1, 1, 0, 1;\n}"
        : "+f"(d[0]), "+f"(d[1]), "+f"(d[2]), "+f"(d[3]), "+f"(d[4]), "+f"(d[5]), "+f"(d[6]), "+f"(d[7]), "+f"(d[8]), "+f"(d[9]), "+f"(d[10]), "+f"(d[11]),
          "+f"(d[12]), "+f"(d[13]), "+f"(d[14]), "+f"(d[15]), "+f"(d[16]), "+f"(d[17]), "+f"(d[18]), "+f"(d[19]), "+f"(d[20]), "+f"(d[21]), "+f"(d[22]), "+f"(d[23]),
          "+f"(d[24]), "+f"(d[25]), "+f"(d[26]), "+f"(d[27]), "+f"(d[28]), "+f"(d[29]), "+f"(d[30]), "+f"(d[31]), "+f"(d[32]), "+f"(d[33]), "+f"(d[34]), "+f"(d[35]),
          "+f"(d[36]), "+f"(d[37]), "+f"(d[38]), "+f"(d[39]), "+f"(d[40]), "+f"(d[41]), "+f"(d[42]), "+f"(d[43]), "+f"(d[44]), "+f"(d[45]), "+f"(d[46]), "+f"(d[47]),
          "+f"(d[48]), "+f"(d[49]), "+f"(d[50]), "+f"(d[51]), "+f"(d[52]), "+f"(d[53]), "+f"(d[54]), "+f"(d[55]), "+f"(d[56]), "+f"(d[57]), "+f"(d[58]), "+f"(d[59]),
          "+f"(d[60]), "+f"(d[61]), "+f"(d[62]), "+f"(d[63])
        : "l"(da), "l"(db), "r"(scale_d));
}

__device__ __forceinline__ constexpr uint32_t slot_off(int slot) {
    return slot < 2 ? G_RING + slot * 16384 : G_BUF + (slot & 1) * 32768 + (slot < 4 ? 16384 : 0);
}
constexpr int PO = (HSPLIT / 2) & 1;
template <int NSLOT, class F>
__device__ __forceinline__ void gemm_tile(float* acc, uint32_t sb, int tile, int it, int wg, bool pass, uint32_t l0, F&& hook) {
    const uint32_t bar = sb + G_BAR;
    bar_sync(3 + wg, 256);
    int prev = 0;
#pragma unroll
    for (int k = 0; k < 4; k++) {
        const int n = tile * 4 + k, slot = NSLOT == 4 ? k : n % NSLOT;
        const uint32_t sz = sb + (((it + k) << 4) & sb & 0x3f0);
        const uint64_t da = desc_sw128(sz + slot_off(slot), 16, 1024), db0 = desc_sw128(sz + G_W, 65536, 1024);
        mbar_wait_p(bar + 8 * (GB_FULL + slot), NSLOT == 4 ? (tile & 1) : ((n / NSLOT) & 1));
        if (k == 3 && pass) bar_arrive(3 + (wg ^ 1), 256);
        asm volatile("wgmma.fence.sync.aligned;" ::: "memory");
#pragma unroll
        for (int kk = 0; kk < 4; kk++) wgmma_n128(acc, da + kk * 2, db0 + k * 1024 + kk * 128, (k | kk) != 0);
        asm volatile("wgmma.commit_group.sync.aligned;" ::: "memory");
        if (k > 0) {
            asm volatile("wgmma.wait_group.sync.aligned 1;" ::: "memory");
            mbar_arrive2_if(bar + 8 * (GB_EMPTY + prev), l0);
        }
#pragma unroll
        for (int kk = 0; kk < 4; kk++) wgmma_n128(acc, da + 512 + kk * 2, db0 + k * 1024 + 512 + kk * 128, 1);
        asm volatile("wgmma.commit_group.sync.aligned;" ::: "memory");
        if (k == 1) hook();
        prev = slot;
    }
    asm volatile("wgmma.wait_group.sync.aligned 0;" ::: "memory");
    mbar_arrive2_if(bar + 8 * (GB_EMPTY + prev), l0);
}
__device__ __forceinline__ void stage_bf16(const float* acc, uint32_t buf, float s0, float s1) {
    const int lane = threadIdx.x & 31, wq = (threadIdx.x >> 5) & 3;
    const int row = wq * 16 + (lane & 7) + ((lane >> 3) & 1) * 8;
    const uint32_t base = buf + row * 128;
#pragma unroll
    for (int j = 0; j < 16; j += 2) {
        const int ch = (j & 7) + (lane >> 4);
        stsm4(base + (j >> 3) * 8192 + ((ch ^ (row & 7)) << 4),
              pack2(acc[4 * j] * s0, acc[4 * j + 1] * s0), pack2(acc[4 * j + 2] * s1, acc[4 * j + 3] * s1),
              pack2(acc[4 * j + 4] * s0, acc[4 * j + 5] * s0), pack2(acc[4 * j + 6] * s1, acc[4 * j + 7] * s1));
    }
}

__device__ __forceinline__ void store_perm(const float* acc, bf16* dst, int ld, float s0, float s1, uint32_t m) {
#pragma unroll
    for (int i = 0; i < 4; i++) {
        const float* a = acc + 16 * i;
        stg4(dst + i * 32, make_uint4(pack2(a[0] * s0, a[1] * s0) ^ m, pack2(a[4] * s0, a[5] * s0) ^ m, pack2(a[8] * s0, a[9] * s0) ^ m, pack2(a[12] * s0, a[13] * s0) ^ m));
        stg4(dst + 8 * ld + i * 32, make_uint4(pack2(a[2] * s1, a[3] * s1) ^ m, pack2(a[6] * s1, a[7] * s1) ^ m, pack2(a[10] * s1, a[11] * s1) ^ m, pack2(a[14] * s1, a[15] * s1) ^ m));
    }
}
template <int ACC>
__device__ __forceinline__ void wgmma_rs64(float* d, const uint32_t* a, uint64_t db) {
    asm volatile("{\n.reg .pred p;\nsetp.ne.b32 p, %37, 0;\n"
        "wgmma.mma_async.sync.aligned.m64n64k16.f32.bf16.bf16 {%0,%1,%2,%3,%4,%5,%6,%7,%8,%9,%10,%11,%12,%13,%14,%15,%16,%17,%18,%19,%20,%21,%22,%23,%24,%25,%26,%27,%28,%29,%30,%31}, {%32,%33,%34,%35}, %36, p, 1, 1, 0;\n}"
        : "+f"(d[0]), "+f"(d[1]), "+f"(d[2]), "+f"(d[3]), "+f"(d[4]), "+f"(d[5]), "+f"(d[6]), "+f"(d[7]), "+f"(d[8]), "+f"(d[9]), "+f"(d[10]), "+f"(d[11]), "+f"(d[12]), "+f"(d[13]), "+f"(d[14]), "+f"(d[15]), "+f"(d[16]), "+f"(d[17]), "+f"(d[18]), "+f"(d[19]), "+f"(d[20]), "+f"(d[21]), "+f"(d[22]), "+f"(d[23]), "+f"(d[24]), "+f"(d[25]), "+f"(d[26]), "+f"(d[27]), "+f"(d[28]), "+f"(d[29]), "+f"(d[30]), "+f"(d[31])
        : "r"(a[0]), "r"(a[1]), "r"(a[2]), "r"(a[3]), "l"(db), "n"(ACC));
}
template <int ACC>
__device__ __forceinline__ void wgmma_rs128t(float* d, const uint32_t* a, uint64_t db) {
    asm volatile("{\n.reg .pred p;\nsetp.ne.b32 p, %69, 0;\n"
        "wgmma.mma_async.sync.aligned.m64n128k16.f32.bf16.bf16 {%0,%1,%2,%3,%4,%5,%6,%7,%8,%9,%10,%11,%12,%13,%14,%15,%16,%17,%18,%19,%20,%21,%22,%23,%24,%25,%26,%27,%28,%29,%30,%31,%32,%33,%34,%35,%36,%37,%38,%39,%40,%41,%42,%43,%44,%45,%46,%47,%48,%49,%50,%51,%52,%53,%54,%55,%56,%57,%58,%59,%60,%61,%62,%63}, {%64,%65,%66,%67}, %68, p, 1, 1, 1;\n}"
        : "+f"(d[0]), "+f"(d[1]), "+f"(d[2]), "+f"(d[3]), "+f"(d[4]), "+f"(d[5]), "+f"(d[6]), "+f"(d[7]), "+f"(d[8]), "+f"(d[9]), "+f"(d[10]), "+f"(d[11]), "+f"(d[12]), "+f"(d[13]), "+f"(d[14]), "+f"(d[15]), "+f"(d[16]), "+f"(d[17]), "+f"(d[18]), "+f"(d[19]), "+f"(d[20]), "+f"(d[21]), "+f"(d[22]), "+f"(d[23]), "+f"(d[24]), "+f"(d[25]), "+f"(d[26]), "+f"(d[27]), "+f"(d[28]), "+f"(d[29]), "+f"(d[30]), "+f"(d[31]), "+f"(d[32]), "+f"(d[33]), "+f"(d[34]), "+f"(d[35]), "+f"(d[36]), "+f"(d[37]), "+f"(d[38]), "+f"(d[39]), "+f"(d[40]), "+f"(d[41]), "+f"(d[42]), "+f"(d[43]), "+f"(d[44]), "+f"(d[45]), "+f"(d[46]), "+f"(d[47]), "+f"(d[48]), "+f"(d[49]), "+f"(d[50]), "+f"(d[51]), "+f"(d[52]), "+f"(d[53]), "+f"(d[54]), "+f"(d[55]), "+f"(d[56]), "+f"(d[57]), "+f"(d[58]), "+f"(d[59]), "+f"(d[60]), "+f"(d[61]), "+f"(d[62]), "+f"(d[63])
        : "r"(a[0]), "r"(a[1]), "r"(a[2]), "r"(a[3]), "l"(db), "n"(ACC));
}
__device__ __forceinline__ void attention_tile(float* acc, uint32_t sb, int tile, int h, int wg, int wq, uint32_t l0, uint32_t epoch, uint4* km, uint4* vm) {
    const uint32_t buf = sb + G_BUF + ((tile << 4) & sb & 0x3f0);
    const int lane = threadIdx.x & 31, g = lane >> 2, t = lane & 3;
    const int sg = wq >> 1, hf = wq & 1, seg = tile * 2 + sg;
    uint32_t qf[8][4];
#pragma unroll
    for (int kk = 0; kk < 8; kk++) {
        qf[kk][0] = pack2(acc[8 * kk], acc[8 * kk + 1]); qf[kk][1] = pack2(acc[8 * kk + 2], acc[8 * kk + 3]);
        qf[kk][2] = pack2(acc[8 * kk + 4], acc[8 * kk + 5]); qf[kk][3] = pack2(acc[8 * kk + 6], acc[8 * kk + 7]);
    }
    uint32_t* kvf = &g_KVf[seg][h][lane * 4];
    auto kv_valid = [&]() {
        uint32_t mn = 0xffffffffu;
#pragma unroll
        for (int i = 0; i < 4; i++) mn = min(min(min(mn, min(km[i].x, km[i].y)), min(km[i].z, km[i].w)), min(min(vm[i].x, vm[i].y), min(vm[i].z, vm[i].w)));
        return __all_sync(0xffffffffu, mn != 0);
    };
    float sc[5][4];
    auto mem_scores = [&]() {
        float sb_[4];
#pragma unroll
        for (int i = 0; i < 4; i++) { MMAF(i == 0, sc[4], qf[2 * i], ~km[i].x, ~km[i].y); MMAF(i == 0, sb_, qf[2 * i + 1], ~km[i].z, ~km[i].w); }
#pragma unroll
        for (int i = 0; i < 4; i++) sc[4][i] += sb_[i];
    };
    mbar_wait_p(sb + G_BAR + 8 * (GB_KV + wg), (tile >> 1) & 1);
    if (h == 5 && (threadIdx.x & 127) == 0 && tile < 6) GT(1750 + tile * 8 + 2);
    bool fast;
    {
        const uint64_t dk = desc_sw128(buf, 16, 1024);
        asm volatile("wgmma.fence.sync.aligned;" ::: "memory");
#pragma unroll
        for (int kk = 0; kk < 8; kk++) {
            if (kk == 0) wgmma_rs64<0>(acc, qf[kk], dk); else wgmma_rs64<1>(acc, qf[kk], dk + (kk >> 2) * 512 + (kk & 3) * 2);
        }
        asm volatile("wgmma.commit_group.sync.aligned;" ::: "memory");
        mem_scores();
        fast = kv_valid();
        asm volatile("wgmma.wait_group.sync.aligned 0;" ::: "memory");
        mbar_arrive_if(sb + G_BAR + 8 * GB_KVF, l0);
#pragma unroll
        for (int i = 0; i < 32; i++) asm volatile("" : "+f"(acc[i]) :: "memory");
#pragma unroll
        for (int b = 0; b < 4; b++)
#pragma unroll
            for (int i = 0; i < 4; i++) sc[b][i] = sg ? acc[16 + 4 * b + i] : acc[4 * b + i];
#pragma unroll
        for (int i = 0; i < 4; i++) sc[4][i] = fast ? sc[4][i] : -INFINITY;
    }
    const float cexp = 0.08838834764831845f * 1.4426950408889634f;
    const int r0 = hf * 16 + g, r1 = r0 + 8;
#pragma unroll
    for (int b = 0; b < 4; b++) {
        const int j = b * 8 + 2 * t;
        if (j > r0) sc[b][0] = -INFINITY;
        if (j + 1 > r0) sc[b][1] = -INFINITY;
        if (j > r1) sc[b][2] = -INFINITY;
        if (j + 1 > r1) sc[b][3] = -INFINITY;
    }
    float m0 = -INFINITY, m1 = -INFINITY;
#pragma unroll
    for (int b = 0; b < 5; b++) { m0 = fmaxf(m0, fmaxf(sc[b][0], sc[b][1])); m1 = fmaxf(m1, fmaxf(sc[b][2], sc[b][3])); }
    m0 = fmaxf(m0, __shfl_xor_sync(0xffffffffu, m0, 1)); m1 = fmaxf(m1, __shfl_xor_sync(0xffffffffu, m1, 1));
    m0 = fmaxf(m0, __shfl_xor_sync(0xffffffffu, m0, 2)); m1 = fmaxf(m1, __shfl_xor_sync(0xffffffffu, m1, 2));
    float z0 = 0.f, z1 = 0.f;
    uint32_t p0, p1;
    {
        const float c0 = -m0 * cexp, c1 = -m1 * cexp;
        uint32_t pf[5][2];
#pragma unroll
        for (int b = 0; b < 5; b++) {
            pf[b][0] = pack2(ex2(fmaf(sc[b][0], cexp, c0)), ex2(fmaf(sc[b][1], cexp, c0)));
            pf[b][1] = pack2(ex2(fmaf(sc[b][2], cexp, c1)), ex2(fmaf(sc[b][3], cexp, c1)));
        }
        p0 = pf[4][0]; p1 = pf[4][1];
        uint32_t pa[4][4];
#pragma unroll
        for (int kk = 0; kk < 4; kk++)
#pragma unroll
            for (int i = 0; i < 4; i++) pa[kk][i] = (kk >> 1) == sg ? pf[(kk & 1) * 2 + (i >> 1)][i & 1] : 0u;
        const uint64_t dv = desc_sw128(buf + 32768, 8192, 1024);
        mbar_wait_p(sb + G_BAR + 8 * (GB_VV + wg), (tile >> 1) & 1);
        asm volatile("wgmma.fence.sync.aligned;" ::: "memory");
#pragma unroll
        for (int kk = 0; kk < 4; kk++) { if (kk == 0) wgmma_rs128t<0>(acc, pa[kk], dv); else wgmma_rs128t<1>(acc, pa[kk], dv + kk * 128); }
        asm volatile("wgmma.commit_group.sync.aligned;" ::: "memory");
#pragma unroll
        for (int b = 0; b < 5; b++) { z0 += bf_lo(pf[b][0]) + bf_hi(pf[b][0]); z1 += bf_lo(pf[b][1]) + bf_hi(pf[b][1]); }
        asm volatile("wgmma.wait_group.sync.aligned 0;" ::: "memory");
#pragma unroll
        for (int i = 0; i < 64; i++) asm volatile("" : "+f"(acc[i]) :: "memory");
    }
    mbar_arrive_if(sb + G_BAR + 8 * GB_VF, l0);
    if (h == 5 && (threadIdx.x & 127) == 0 && tile < 6) GT(1750 + tile * 8 + 3);
    if (!fast) {
        wait_rec(&g_f.rec[h][0], epoch, seg + 1);
        if (seg == 63 && (threadIdx.x & 63) == 0) GT(1570 + h);
        uint32_t n = 0;
#pragma unroll 1
        do {
#pragma unroll
            for (int i = 0; i < 4; i++) { km[i] = ldg_rlx4(kvf + i * 128); vm[i] = ldg_rlx4(kvf + 512 + i * 128); }
            if (++n > SPIN_LIMIT) { ABORT(4); break; }
        } while (!kv_valid());
        mem_scores();
        float n0 = fmaxf(sc[4][0], sc[4][1]), n1 = fmaxf(sc[4][2], sc[4][3]);
        n0 = fmaxf(n0, __shfl_xor_sync(0xffffffffu, n0, 1)); n1 = fmaxf(n1, __shfl_xor_sync(0xffffffffu, n1, 1));
        n0 = fmaxf(n0, __shfl_xor_sync(0xffffffffu, n0, 2)); n1 = fmaxf(n1, __shfl_xor_sync(0xffffffffu, n1, 2));
        n0 = fmaxf(n0, m0); n1 = fmaxf(n1, m1);
        const float a0 = ex2((m0 - n0) * cexp), a1 = ex2((m1 - n1) * cexp);
        const float c0 = -n0 * cexp, c1 = -n1 * cexp;
        p0 = pack2(ex2(fmaf(sc[4][0], cexp, c0)), ex2(fmaf(sc[4][1], cexp, c0)));
        p1 = pack2(ex2(fmaf(sc[4][2], cexp, c1)), ex2(fmaf(sc[4][3], cexp, c1)));
        z0 = fmaf(z0, a0, bf_lo(p0) + bf_hi(p0)); z1 = fmaf(z1, a1, bf_lo(p1) + bf_hi(p1));
#pragma unroll
        for (int j = 0; j < 16; j++) { float* o = acc + 4 * j; o[0] *= a0; o[1] *= a0; o[2] *= a1; o[3] *= a1; }
    }
    if (h == 5 && (threadIdx.x & 127) == 0 && tile < 6) GT(1750 + tile * 8 + 4);
    if (hf) bar_arrive(5 + wg * 2 + sg, 64);
#pragma unroll
    for (int i = 0; i < 4; i++) {
        mma1688(acc + 16 * i, p0, p1, ~vm[i].x); mma1688(acc + 16 * i + 4, p0, p1, ~vm[i].y);
        mma1688(acc + 16 * i + 8, p0, p1, ~vm[i].z); mma1688(acc + 16 * i + 12, p0, p1, ~vm[i].w);
    }
    z0 += __shfl_xor_sync(0xffffffffu, z0, 1); z1 += __shfl_xor_sync(0xffffffffu, z1, 1);
    z0 += __shfl_xor_sync(0xffffffffu, z0, 2); z1 += __shfl_xor_sync(0xffffffffu, z1, 2);
    if (h == 5 && (threadIdx.x & 127) == 0 && tile < 6) GT(1750 + tile * 8 + 5);
    if (tile >= 2) mbar_wait_p(sb + G_BAR + 8 * (GB_FREE + wg), ((tile >> 1) - 1 + PO) & 1);
    store_perm(acc, g_O + (size_t)(tile * 64 + wq * 16 + g) * HD + h * 128 + t * 8, HD, rcpf(z0), rcpf(z1), 0);
    mbar_arrive(sb + G_BAR + 8 * (GB_STG + wg));
    if (!hf) {
        bar_sync(5 + wg * 2 + sg, 64);
#pragma unroll
        for (int i = 0; i < 8; i++) stg4_h(kvf + i * 128, make_uint4(0, 0, 0, 0), pol_ef(3));
    }
}

constexpr int NWK = FF / 32;
constexpr int F_WG = 0, F_WU = 32768, F_WD = 65536, F_RED = 98304, F_ACT = F_RED + 8192, F_SEL = F_ACT + 256;
__device__ __noinline__ void ffn_phase(const Maps& maps, bf16* __restrict__ out) {
    extern __shared__ __align__(1024) uint8_t smem[];
    const uint32_t sb = smem_u32(smem);
    const int c = ((volatile int*)(smem + SH_OFF))[8];
    const uint32_t epoch = ((volatile uint32_t*)(smem + SH_OFF))[9];
    const int tid = threadIdx.x;
    const bool worker = c < NWK;
    bar_sync(0, 384);
    const uint32_t mb = sb + R_BAR + 8 * MB_W0;
    if (tid == 352 && worker) {
        if (FFW) __nanosleep(FFW);
        asm volatile("fence.proxy.async.shared::cta;" ::: "memory");
        mbar_expect_tx(mb, 98304);
#pragma unroll 1
        for (int j = 0; j < 6; j++) {
            if (j < 4) tma2d_h(sb + j * 16384, j < 2 ? &maps.wg : &maps.wu, c * 32, (j & 1) * 256, mb, pol_ef(5));
            else for (int i = 0; i < 4; i++) tma2d_h(sb + F_WD + ((j - 4) * 4 + i) * 4096, &maps.wd, ((j - 4) * 4 + i) * 64, c * 32, mb, pol_ef(5));
            if (FFS) __nanosleep(FFS);
        }
    }
    int p0 = -1, p1 = -1;
    float pb = 0.f;
#pragma unroll 1
    for (int pass = 0; pass < 2; pass++) {
        if (tid < 32) {
            const uint32_t tag = epoch & 0xfffffu;
            uint4 r[4]; uint32_t n = 0;
            const int t3 = tid + 96 < NFW ? tid + 96 : tid;
#pragma unroll 1
            while (true) {
                bool ok = true;
#pragma unroll
                for (int i = 0; i < 4; i++) r[i] = ldg_rlx4((const uint32_t*)&g_f.cand[pass][i < 3 ? tid + 32 * i : t3]);
#pragma unroll
                for (int i = 0; i < 4; i++) ok = ok && (r[i].y >> 12) == tag && (r[i].w >> 12) == tag;
                if (__all_sync(0xffffffffu, ok)) break;
                if (pass == 0) __nanosleep(100);
                if (++n > SPIN_LIMIT) { ABORT(7); break; }
            }
            bool chg = pass == 0;
#pragma unroll
            for (int i = 0; i < 4; i++) {
                const int j0 = r[i].y & 4095, j1 = r[i].w & 4095;
                chg = chg || (j0 != p0 && cand_better(__uint_as_float(r[i].x), j0, pb, p1)) || (j1 != p0 && cand_better(__uint_as_float(r[i].z), j1, pb, p1));
            }
            int* sel = (int*)(smem + F_SEL);
            if (__any_sync(0xffffffffu, chg)) {
                float b0 = __uint_as_float(r[0].x), b1 = __uint_as_float(r[0].z); int i0 = r[0].y & 4095, i1 = r[0].w & 4095;
#pragma unroll
                for (int i = 1; i < 9; i++) {
                    float c0, c1; int j0, j1;
                    if (i < 4) { c0 = __uint_as_float(r[i].x); c1 = __uint_as_float(r[i].z); j0 = r[i].y & 4095; j1 = r[i].w & 4095; }
                    else {
                        const int o = 1 << (i - 4);
                        c0 = __shfl_xor_sync(0xffffffffu, b0, o); c1 = __shfl_xor_sync(0xffffffffu, b1, o);
                        j0 = __shfl_xor_sync(0xffffffffu, i0, o); j1 = __shfl_xor_sync(0xffffffffu, i1, o);
                    }
                    if (i != 3 || t3 != tid) {
                        if (cand_better(c0, j0, b0, i0)) {
                            if (cand_better(c1, j1, b0, i0)) { b1 = c1; i1 = j1; } else { b1 = b0; i1 = i0; }
                            b0 = c0; i0 = j0;
                        } else if (cand_better(c0, j0, b1, i1)) { b1 = c0; i1 = j0; }
                    }
                }
                n = 0;
#pragma unroll 1
                while (!__all_sync(0xffffffffu, (ldg_rlx(&g_f.rows[pass][tid]) == epoch) & (ldg_rlx(&g_f.rows[pass][tid + 32]) == epoch) &
                                                   (ldg_rlx(&g_f.rows[pass][tid + 64]) == epoch) & (ldg_rlx(&g_f.rows[pass][t3]) == epoch))) { if (++n > SPIN_LIMIT) { ABORT(7); break; } }
                if (tid == 0) { sel[0] = min(i0, SQ - 1); sel[1] = min(i1, SQ - 1); ((float*)sel)[2] = b0; ((float*)sel)[3] = b1; }
            }
            if (pass && tid == 0 && c == 3) GT(1440);
        }
        bar_sync(0, 384);
        const int t0 = ((int*)(smem + F_SEL))[0], t1 = ((int*)(smem + F_SEL))[1];
        if (c == 3 && tid == 0 && pass == 0) GT(1430);
        if (t0 == p0 && t1 == p1) break;
        pb = ((float*)(smem + F_SEL))[3];
        const uint32_t ytag = epoch * 2 + pass + 1;
        if (worker) {
            const int lane = tid & 31, w = tid >> 5, g = lane >> 2, t = lane & 3;
            const int lrow = ((lane >> 4) << 3) + (lane & 7), lsel = (lane >> 3) & 1;
            float2* red = (float2*)(smem + F_RED);
            if (w < 8) {
                const uint32_t* xp = (const uint32_t*)(g_hn + (size_t)((g & 1) ? t1 : t0) * DM) + w * 32 + t;
                uint32_t xb[8];
#pragma unroll
                for (int i = 0; i < 8; i++) xb[i] = __ldcg(xp + i * 4);
                mbar_wait(mb, 1);
                if (c == 3 && tid == 0 && pass == 0) GT(1431);
                float d[4][4];
#pragma unroll
                for (int kk = 0; kk < 4; kk++) {
                    const int row = w * 64 + kk * 16 + lrow;
#pragma unroll
                    for (int m = 0; m < 4; m++) {
                        uint32_t a[4];
                        ldsm4t(a, sb + (m >> 1) * F_WU + row * 64 + ((((m & 1) * 2 + lsel) ^ ((row >> 1) & 3)) << 4));
                        MMAF(kk == 0, d[m], a, xb[2 * kk], xb[2 * kk + 1]);
                    }
                }
                const float e0 = t == 0 ? d[0][0] : (t == 1 ? d[1][0] : (t == 2 ? d[2][0] : d[3][0])), e1 = t == 0 ? d[0][1] : (t == 1 ? d[1][1] : (t == 2 ? d[2][1] : d[3][1]));
                const float e2 = t == 0 ? d[0][2] : (t == 1 ? d[1][2] : (t == 2 ? d[2][2] : d[3][2])), e3 = t == 0 ? d[0][3] : (t == 1 ? d[1][3] : (t == 2 ? d[2][3] : d[3][3]));
                red[w * 64 + t * 16 + g] = make_float2(e0, e1); red[w * 64 + t * 16 + g + 8] = make_float2(e2, e3);
            }
            bar_sync(0, 384);
            if (tid < 64) {
                const float* r = (const float*)red + tid;
                float gsum = 0.f, usum = 0.f;
#pragma unroll
                for (int kg = 0; kg < 8; kg++) { gsum += r[kg * 128]; usum += r[kg * 128 + 64]; }
                gsum = rbf(gsum); usum = rbf(usum);
                const float sg = rbf(gsum / (1.f + __expf(-gsum)));
                ((bf16*)(smem + F_ACT))[(tid & 1) * 32 + (tid >> 1)] = __float2bfloat16_rn(sg * usum);
            }
            bar_sync(0, 384);
            if (w < 8) {
                const uint32_t* ap = (const uint32_t*)(smem + F_ACT) + (g & 1) * 16 + t;
                float d[4][4];
#pragma unroll
                for (int kk = 0; kk < 2; kk++) {
                    const uint32_t b0 = ap[kk * 8], b1 = ap[kk * 8 + 4];
#pragma unroll
                    for (int m = 0; m < 4; m++) {
                        uint32_t a[4];
                        ldsm4t(a, sb + F_WD + w * 4096 + (kk * 16 + lrow) * 128 + (((m * 2 + lsel) ^ (lane & 7)) << 4));
                        MMAF(kk == 0, d[m], a, b0, b1);
                    }
                }
                const float e0 = t == 0 ? d[0][0] : (t == 1 ? d[1][0] : (t == 2 ? d[2][0] : d[3][0])), e1 = t == 0 ? d[0][1] : (t == 1 ? d[1][1] : (t == 2 ? d[2][1] : d[3][1]));
                const float e2 = t == 0 ? d[0][2] : (t == 1 ? d[1][2] : (t == 2 ? d[2][2] : d[3][2])), e3 = t == 0 ? d[0][3] : (t == 1 ? d[1][3] : (t == 2 ? d[2][3] : d[3][3]));
                uint4* yp = &g_yp[pass][c][w * 64 + t * 16 + g];
                stg4(yp, make_uint4(FU(e0), ytag, FU(e1), ytag)); stg4(yp + 8, make_uint4(FU(e2), ytag, FU(e3), ytag));
            }
            if (c == 3 && tid == 0 && pass == 0) GT(1432);
        } else {
            const int j = tid & 63, part = tid >> 6, col = (c - NWK) * 64 + j;
            const int tok = part ? t1 : t0, old = part ? p1 : p0;
            float hv = 0.f, nv = 0.f;
            if (part < 2) {
                hv = __bfloat162float(__ldcg(g_h + (size_t)tok * DM + col)); nv = __bfloat162float(__ldcg(g_hn + (size_t)tok * DM + col));
                if (old >= 0 && old != t0 && old != t1)
                    out[(size_t)old * DM + col] = __float2bfloat16_rn(__bfloat162float(__ldcg(g_h + (size_t)old * DM + col)) + __bfloat162float(__ldcg(g_hn + (size_t)old * DM + col)));
            }
            float s0 = 0.f, s1 = 0.f;
            uint4 v[10]; uint32_t n = 0;
            bool ok;
#pragma unroll 1
            do {
                ok = true;
#pragma unroll
                for (int i = 0; i < 10; i++) {
                    const int src = part + 6 * i;
                    v[i] = src < NWK ? ldg_rlx4((const uint32_t*)&g_yp[pass][src][col]) : make_uint4(0, ytag, 0, ytag);
                }
#pragma unroll
                for (int i = 0; i < 10; i++) ok = ok && v[i].y == ytag && v[i].w == ytag;
                if (!ok) __nanosleep(100);
                if (++n > SPIN_LIMIT) { ABORT(7); break; }
            } while (!ok);
#pragma unroll
            for (int i = 0; i < 10; i++) { s0 += __uint_as_float(v[i].x); s1 += __uint_as_float(v[i].z); }
            float2* red = (float2*)(smem + F_RED);
            red[part * 64 + j] = make_float2(s0, s1);
            bar_sync(0, 384);
            if (part < 2) {
                float y = 0.f;
#pragma unroll
                for (int i = 0; i < 6; i++) y += ((const float*)red)[(i * 64 + j) * 2 + part];
                const float rs = rbf(1.f / (1.f + __expf(-((float*)(smem + F_SEL))[2 + part])));
                out[(size_t)tok * DM + col] = __float2bfloat16_rn(hv + rbf(nv + rbf(rbf(y) * rs)));
            }
            if (tid == 0 && pass == 0 && c == NWK) GT(1434);
        }
        p0 = t0; p1 = t1;
        if (c == 3 && tid == 0 && pass == 0) GT(1433);
        bar_sync(0, 384);
    }
}

__device__ __forceinline__ void g_consumer(uint32_t sb_, int g_, int wg_, uint32_t epoch) {
    const uint32_t sb = uni(sb_);
    const int g = uni(g_), wg = uni(wg_), wq = uni((threadIdx.x >> 5) & 3);
    const uint32_t l0 = opaque((threadIdx.x & 31) == 0);
    const uint32_t bar = sb + G_BAR, buf = sb + G_BUF + wg * 32768;
    const int lane = threadIdx.x & 31;
    float acc[64];
    if (wg == 1) bar_arrive(3, 256);
    const int n1 = g < 32 ? HSPLIT / 2 : NT - HSPLIT / 2;
#pragma unroll 1
    for (int i = 0; i < n1; i++) {
        gemm_tile<4>(acc, sb, wg, i, wg, true, l0, []() {});
        if (threadIdx.x == 0 && i == 0) GT((64 + g) * 8 + 1);
        if (threadIdx.x == 128 && i == 3) GT((64 + g) * 8 + 2);
        if (i > 0) mbar_wait_p(bar + 8 * (GB_FREE + wg), (i - 1) & 1);
        stage_bf16(acc, buf, 1.f, 1.f);
        asm volatile("fence.proxy.async.shared::cta;" ::: "memory");
        mbar_arrive(bar + 8 * (GB_STG + wg));
    }
    if (threadIdx.x == 128) GT((64 + g) * 8 + 3);
    if (g < 32) {
#pragma unroll 1
        for (int i = 0; i < NT / 2; i++) {
            const int tile = 2 * i + wg;
            const uint2 rec = ldg_rlx2(&g_f.rec[g][0]);
            uint4 km[4], vm[4];
            gemm_tile<4>(acc, sb, tile, i, wg, tile != NT - 1, l0, [&]() {
                const uint32_t seg = tile * 2 + (wq >> 1);
                const uint32_t* kvf = &g_KVf[seg][g][lane * 4];
                const bool early = (rec.x >> 8) == epoch && (rec.y >> 8) == epoch && (rec.x & 255) > seg && (rec.y & 255) > seg;
#pragma unroll
                for (int j = 0; j < 4; j++) { km[j] = ldg_rlx4_if(kvf + j * 128, early); vm[j] = ldg_rlx4_if(kvf + 512 + j * 128, early); }
            });
            if (threadIdx.x == 0 && i == 0) GT((64 + g) * 8 + 4);
            if (threadIdx.x == 128 && i == 3) GT((64 + g) * 8 + 5);
            if (g == 5 && (threadIdx.x & 127) == 0 && tile < 6) GT(1750 + tile * 8 + 1);
            attention_tile(acc, sb, tile, g, wg, wq, l0, epoch, km, vm);
            if (g == 5 && (threadIdx.x & 127) == 0 && tile < 6) GT(1750 + tile * 8 + 6);
        }
    } else {
#pragma unroll 1
        for (int i = 0; i < NT / 2; i++) {
            const int tile = 2 * i + wg;
            gemm_tile<NS3>(acc, sb, tile, i, wg, tile != NT - 1, l0, []() {});
            if (threadIdx.x == 0 && i == 0) GT((64 + g) * 8 + 4);
            if (threadIdx.x == 128 && i == 3) GT((64 + g) * 8 + 5);
            mbar_wait_p(bar + 8 * (GB_FREE + wg), (i - 1 + PO) & 1);
            store_perm(acc, g_P + (size_t)(((g - 32) >> 2) * SQ + tile * 64 + wq * 16 + (lane >> 2)) * DM + ((g - 32) & 3) * 128 + (lane & 3) * 8, DM, 1.f, 1.f, 0xffffffffu);
            mbar_arrive(bar + 8 * (GB_STG + wg));
        }
    }
}

__device__ __forceinline__ void load_w(uint32_t sb, const CUtensorMap* tm, int col, int k) {
    tma2d_h(sb + G_W + k * 16384, tm, col, k * 128, sb + G_BAR + 8 * (GB_FULL + k), pol_ef(5));
    tma2d_h(sb + G_W + 65536 + k * 16384, tm, col + 64, k * 128, sb + G_BAR + 8 * (GB_FULL + k), pol_ef(5));
}

__device__ __forceinline__ void rbf2(float& a, float& b) { uint32_t w = pack2(a, b); a = bf_lo(w); b = bf_hi(w); }
__device__ __forceinline__ void warp_sum2(float& a, float& b) {
#pragma unroll
    for (int o = 16; o; o >>= 1) { float c = __shfl_xor_sync(0xffffffffu, a, o), d = __shfl_xor_sync(0xffffffffu, b, o); a += c; b += d; }
}
__device__ __forceinline__ float sum16(const float* v) {
    return (((v[0] + v[1]) + (v[2] + v[3])) + ((v[4] + v[5]) + (v[6] + v[7]))) + (((v[8] + v[9]) + (v[10] + v[11])) + ((v[12] + v[13]) + (v[14] + v[15])));
}
__device__ __forceinline__ void ln_row2(float* v, float* u) {
    float sv = sum16(v), su = sum16(u);
    warp_sum2(sv, su);
    const float mv = sv * (1.f / DM), mu = su * (1.f / DM);
    float qv = 0.f, qu = 0.f, qv2 = 0.f, qu2 = 0.f;
#pragma unroll
    for (int i = 0; i < 16; i += 2) {
        float d0 = v[i] - mv, d1 = v[i + 1] - mv, e0 = u[i] - mu, e1 = u[i + 1] - mu;
        qv = fmaf(d0, d0, qv); qv2 = fmaf(d1, d1, qv2); qu = fmaf(e0, e0, qu); qu2 = fmaf(e1, e1, qu2);
    }
    qv += qv2; qu += qu2;
    warp_sum2(qv, qu);
    const float rv = rbf(mv), ru = rbf(mu);
    const float iv = __frcp_rn(rbf(sqrtf(rbf(rbf(qv * (1.f / DM)) + 1e-5f)))), iu = __frcp_rn(rbf(sqrtf(rbf(rbf(qu * (1.f / DM)) + 1e-5f))));
#pragma unroll
    for (int i = 0; i < 16; i += 2) {
        float a = v[i] - rv, b = v[i + 1] - rv, c = u[i] - ru, d = u[i + 1] - ru;
        rbf2(a, b); rbf2(c, d);
        a *= iv; b *= iv; c *= iu; d *= iu;
        rbf2(a, b); rbf2(c, d);
        v[i] = a; v[i + 1] = b; u[i] = c; u[i + 1] = d;
    }
}

__device__ __forceinline__ void ln_row1(float* v) {
    const float pv = __shfl_sync(0xffffffffu, v[0], 0);
    float sv = 0.f, sv2 = 0.f, qv = 0.f, qv2 = 0.f;
#pragma unroll
    for (int i = 0; i < 16; i += 2) { const float d0 = v[i] - pv, d1 = v[i + 1] - pv; sv += d0; sv2 += d1; qv = fmaf(d0, d0, qv); qv2 = fmaf(d1, d1, qv2); }
    sv += sv2; qv += qv2;
    warp_sum2(sv, qv);
    const float dm = sv * (1.f / DM), mv = pv + dm;
    qv = fmaxf(fmaf(-dm, sv, qv), 0.f);
    const float rv = rbf(mv);
    float sq, iv;
    asm("sqrt.approx.f32 %0, %1;" : "=f"(sq) : "f"(rbf(rbf(qv * (1.f / DM)) + 1e-5f)));
    asm("rcp.approx.f32 %0, %1;" : "=f"(iv) : "f"(rbf(sq)));
#pragma unroll
    for (int i = 0; i < 16; i += 2) {
        float a = v[i] - rv, b = v[i + 1] - rv;
        rbf2(a, b);
        a *= iv; b *= iv;
        rbf2(a, b);
        v[i] = a; v[i + 1] = b;
    }
}
constexpr int FSPLIT = 28;
__device__ __forceinline__ int fin_row(int id, int i) {
    if (id < 64) { const int tile = i < FSPLIT / 2 ? 2 * i : i + FSPLIT / 2; return tile < NT ? tile * 64 + id : -1; }
    const int j = id - 64 + i * 48;
    return j < FSPLIT * 32 ? (j >> 6) * 128 + 64 + (j & 63) : -1;
}
__device__ __forceinline__ void finalizer(int id, const bf16* __restrict__ x, const bf16* __restrict__ wr, bf16* __restrict__ out, uint32_t epoch, const bf16* pf) {
    const int lane = threadIdx.x & 31;
    float b0 = -INFINITY, b1 = -INFINITY; int i0 = 0x7fffffff, i1 = 0x7fffffff;
    const uint32_t tag = (epoch & 0xfffffu) << 12;
    uint32_t fl = ~epoch;
    int row = fin_row(id, 0);
    const uint4 ra = *(const uint4*)(wr + lane * 8), rb = *(const uint4*)(wr + 256 + lane * 8);
    uint4 xa = *(const uint4*)(x + (size_t)row * DM + lane * 8), xb = *(const uint4*)(x + (size_t)row * DM + lane * 8 + 256);
#pragma unroll 1
    for (int it = 0; row >= 0; it++) {
        const int tile = row >> 6, nxt = fin_row(id, it + 1);
        const size_t o0 = (size_t)row * DM + lane * 8;
        uint32_t n = 0;
#pragma unroll 1
        while (!__all_sync(0xffffffffu, fl == epoch)) {
            if (n && tile < NT - 1) __nanosleep(it ? 64 : 1000);
            fl = ldg_rlx(&g_f.p[tile][lane]);
            if (++n > SPIN_LIMIT) { ABORT(12); break; }
        }
        if (tile == NT - 1 && id == 63 && lane == 0) GT(1438);
        if ((id == 63 || id == 3 || id == 70) && lane == 0) GT(1800 + (id == 3) * 32 + tile);
        if (PFF && pf && lane == 0 && (unsigned)(it - PFF) < 7u)
            asm volatile("cp.async.bulk.prefetch.L2.global [%0], %1;" :: "l"(pf + (size_t)((id & 15) * 7 + it - PFF) * 8192), "r"(16384) : "memory");
        float v[16];
        {
            uint4 pa[8][2];
            n = 0;
#pragma unroll 1
            while (true) {
#pragma unroll
                for (int k = 0; k < 8; k++) {
                    pa[k][0] = ldg4_h(g_P + (size_t)k * SQ * DM + o0, pol_ef(2));
                    pa[k][1] = ldg4_h(g_P + (size_t)k * SQ * DM + o0 + 256, pol_ef(2));
                }
                fl = ldg_rlx(&g_f.p[max(nxt, 0) >> 6][lane]);
                uint32_t mn = 0xffffffffu;
#pragma unroll
                for (int k = 0; k < 8; k++) mn = min(min(min(mn, min(pa[k][0].x, pa[k][0].y)), min(pa[k][0].z, pa[k][0].w)), min(min(pa[k][1].x, pa[k][1].y), min(pa[k][1].z, pa[k][1].w)));
                if (__all_sync(0xffffffffu, mn != 0)) break;
                if (++n > SPIN_LIMIT) { ABORT(11); break; }
            }
            if (tile == NT - 1 && id == 63 && lane == 0) GT(1443);
#pragma unroll
            for (int j = 0; j < 2; j++) {
#pragma unroll
                for (int i = 0; i < 4; i++) {
                    uint32_t w[8];
#pragma unroll
                    for (int k = 0; k < 8; k++) w[k] = ~(i == 0 ? pa[k][j].x : (i == 1 ? pa[k][j].y : (i == 2 ? pa[k][j].z : pa[k][j].w)));
                    v[j * 8 + 2 * i] = ((bf_lo(w[0]) + bf_lo(w[1])) + (bf_lo(w[2]) + bf_lo(w[3]))) + ((bf_lo(w[4]) + bf_lo(w[5])) + (bf_lo(w[6]) + bf_lo(w[7])));
                    v[j * 8 + 2 * i + 1] = ((bf_hi(w[0]) + bf_hi(w[1])) + (bf_hi(w[2]) + bf_hi(w[3]))) + ((bf_hi(w[4]) + bf_hi(w[5])) + (bf_hi(w[6]) + bf_hi(w[7])));
                }
            }
        }
        uint32_t hw[8];
        {
            const uint32_t xw[8] = {xa.x, xa.y, xa.z, xa.w, xb.x, xb.y, xb.z, xb.w};
            uint32_t aw[8];
#pragma unroll
            for (int i = 0; i < 8; i++) aw[i] = pack2(v[2 * i], v[2 * i + 1]);
#pragma unroll
            for (int d = 1; d <= 2; d++) {
                const bool up = lane & d;
#pragma unroll
                for (int i = 0; i < 8; i++) {
                    if (!(i & d)) {
                        const uint32_t r = __shfl_xor_sync(0xffffffffu, up ? aw[i] : aw[i | d], d);
                        if (up) aw[i] = r; else aw[i | d] = r;
                    }
                }
            }
#pragma unroll
            for (int i = 0; i < 8; i++) {
                hw[i] = pack2(bf_lo(aw[i]) + bf_lo(xw[i]), bf_hi(aw[i]) + bf_hi(xw[i]));
                v[2 * i] = bf_lo(hw[i]); v[2 * i + 1] = bf_hi(hw[i]);
            }
        }
        xa = *(const uint4*)(x + (size_t)max(nxt, 0) * DM + lane * 8); xb = *(const uint4*)(x + (size_t)max(nxt, 0) * DM + lane * 8 + 256);
        ln_row1(v);
        float r0 = 0.f, r1 = 0.f;
        {
            const uint32_t ww[8] = {ra.x, ra.y, ra.z, ra.w, rb.x, rb.y, rb.z, rb.w};
#pragma unroll
            for (int i = 0; i < 8; i++) { r0 = fmaf(v[2 * i], bf_lo(ww[i]), r0); r1 = fmaf(v[2 * i + 1], bf_hi(ww[i]), r1); }
        }
        r0 += r1;
#pragma unroll
        for (int o = 16; o; o >>= 1) r0 += __shfl_xor_sync(0xffffffffu, r0, o);
        r0 = rbf(r0);
        if (cand_better(r0, row, b0, i0)) { b1 = b0; i1 = i0; b0 = r0; i0 = row; }
        else if (cand_better(r0, row, b1, i1)) { b1 = r0; i1 = row; }
        if (tile == NT - 1 && id == 63 && lane == 0) GT(1439);
        const bool keep = i0 == row || i1 == row || i1 >= SQ || row == SQ - 1;
        const bool last = nxt < 0, spec = tile < SPEC_TILES && (last || (nxt >> 6) >= SPEC_TILES);
        const bool pub = (lane == 0 && spec) || (lane == 1 && last);
        if (pub)
            asm volatile("st.relaxed.gpu.global.v4.b32 [%0], {%1,%2,%3,%4};" :: "l"(&g_f.cand[lane][id]),
                         "r"(FU(b0)), "r"(tag | (uint32_t)min(i0, 4095)), "r"(FU(b1)), "r"(tag | (uint32_t)min(i1, 4095)) : "memory");
#pragma unroll
        for (int j = 0; j < 2; j++) {
            const uint32_t* hh = hw + j * 4; const float* nn = v + j * 8;
            stg4_h(out + o0 + j * 256, make_uint4(pack2(bf_lo(hh[0]) + nn[0], bf_hi(hh[0]) + nn[1]), pack2(bf_lo(hh[1]) + nn[2], bf_hi(hh[1]) + nn[3]),
                                                  pack2(bf_lo(hh[2]) + nn[4], bf_hi(hh[2]) + nn[5]), pack2(bf_lo(hh[3]) + nn[6], bf_hi(hh[3]) + nn[7])), pol_ef(4));
            if (keep) {
                *(uint4*)(g_h + o0 + j * 256) = make_uint4(hh[0], hh[1], hh[2], hh[3]);
                *(uint4*)(g_hn + o0 + j * 256) = make_uint4(pack2(nn[0], nn[1]), pack2(nn[2], nn[3]), pack2(nn[4], nn[5]), pack2(nn[6], nn[7]));
            }
        }
        if (keep) { __threadfence(); __syncwarp(); }
        if (pub) stg_rlx(&g_f.rows[lane][id], epoch);
        if (tile >= LLT) {
#pragma unroll
            for (int k = 0; k < 8; k++) { stg4(g_P + (size_t)k * SQ * DM + o0, make_uint4(0, 0, 0, 0)); stg4(g_P + (size_t)k * SQ * DM + o0 + 256, make_uint4(0, 0, 0, 0)); }
        }
        row = nxt;
    }
    if (id == 0 && lane == 0) { g_epoch = epoch; if (epoch == 0xffffffu) { g_ticket[0] = 0; g_ticket[32] = 0; } }
}

__device__ __forceinline__ void g_producer(uint32_t sb, int g, const Maps& maps, uint32_t epoch, const bf16* __restrict__ x, const bf16* __restrict__ wr, bf16* __restrict__ out) {
    const uint32_t bar = sb + G_BAR;
    const int warp = (threadIdx.x >> 5) - 8;
    if (threadIdx.x == 256 && g == 5) GT(1410);
    if (threadIdx.x == 256 && g == 5) GT(1411);
    if (warp == 3) {
        wait_eq4(&g_f.xn[(threadIdx.x & 31) * 4], epoch, 13);
        __syncwarp();
        if ((threadIdx.x & 31) == 0) mbar_arrive(bar + 8 * GB_XN);
        finalizer(g, x, wr, out, epoch, nullptr);
        if (g == 63 && (threadIdx.x & 31) == 0) GT(128 * 8 + 6);
    }
    if ((threadIdx.x & 31) != 0) return;
    if (threadIdx.x == 256 && g == 5) GT(1412);
    if (warp == 0) {
        wait_eq4(&g_f.xn[0], epoch, 13);
        const int rk = g & 1;
        const int m1 = g < 32 ? HSPLIT : 2 * NT - HSPLIT;
        const int mx = g < 32 ? m1 + NT : m1;
#pragma unroll 1
        for (int it = 0; it < mx; it++) {
            const int tile = g < 32 ? (it < m1 ? it : it - m1) : (it < NT ? it : it - NT + HSPLIT);
            if (it == 1) wait_eq4(&g_f.xn[4], epoch, 13);
            if (it == 2) mbar_wait(bar + 8 * GB_XN, 0);
            if (it == HP) mbar_wait(bar + 8 * GB_P0, 0);
            const bool nw = it == 0 || it == (g < 32 ? m1 : NT);
#pragma unroll
            for (int k = 0; k < 4; k++) {
                mbar_wait(bar + 8 * (GB_EMPTY + k), (it & 1) ^ 1);
                mbar_expect_tx(bar + 8 * (GB_FULL + k), nw ? 49152 : 16384);
                tma2d_mc(sb + slot_off(k) + rk * 8192, &maps.xn2, (k * 2 + rk) * 64, tile * 64, bar + 8 * (GB_FULL + k));
                if (nw && (it > 0 || k >= WK0))
                    load_w(sb, it > 0 && g < 32 ? &maps.wq4 : ((g & 1) ? &maps.wv4 : &maps.wk4), it == 0 ? (g >> 1) * 128 : (g < 32 ? g * 128 : ((g - 32) >> 1) * 128), k);
            }
        }
        if (g >= 32) {
            const int u = g - 32, ks = u >> 2, ns = u & 3;
            int slot = 0, ph = 1;
#pragma unroll 1
            for (int tile = 0; tile < NT; tile++) {
                if (tile > 0) wait_eq4(&g_f.o[tile][ks][0], epoch, 9);
                if (g == 40 && tile == NT - 1) GT(1437);
                if (tile == NT - 1) GT(1690 + g - 32);
#pragma unroll 1
                for (int k = 0; k < 4; k++) {
                    mbar_wait(bar + 8 * (GB_EMPTY + slot), slot < 4 ? ph : ph ^ 1);
                    mbar_expect_tx(bar + 8 * (GB_FULL + slot), tile == 0 ? 49152 : 16384);
                    if (tile == 0) {
#pragma unroll
                        for (int nh = 0; nh < 2; nh++)
                            asm volatile("cp.async.bulk.tensor.5d.shared::cluster.global.mbarrier::complete_tx::bytes [%0], [%1, {%3, %4, %4, %4, %5}], [%2];"
                                :: "r"(sb + G_W + nh * 65536 + k * 16384), "l"((uint64_t)&maps.wo2), "r"(bar + 8 * (GB_FULL + k)), "r"(ns * 128 + nh * 64), "r"(0), "r"(ks * 16 + k * 4) : "memory");
                        if (k == 0) wait_eq4(&g_f.o[0][ks][0], epoch, 9);
                    }
                    tma2d_mc_h(sb + slot_off(slot) + rk * 8192, &maps.ox2, (ks * 8 + k * 2 + rk) * 64, tile * 64, bar + 8 * (GB_FULL + slot), pol_ef(1));
                    if (++slot == NS3) { slot = 0; ph ^= 1; }
                }
            }
        }
    } else if (warp < 3) {
        const int wg = warp - 1;
        const uint32_t buf = sb + G_BUF + wg * 32768;
        const CUtensorMap* tkv = (g & 1) ? &maps.vx3 : &maps.kx3;
        const int n1 = g < 32 ? HSPLIT / 2 : NT - HSPLIT / 2;
#pragma unroll 1
        for (int i = 0; i < n1; i++) {
            const int tile = (i < NT / 2 ? 2 * i : 2 * i - NT + HSPLIT) + wg, hd = (i < NT / 2 ? g : g - 32) >> 1;
            mbar_wait(bar + 8 * (GB_STG + wg), i & 1);
            tma_store3d(tkv, buf, tile * 64, hd * 2);
            asm volatile("cp.async.bulk.commit_group;" ::: "memory");
            asm volatile("cp.async.bulk.wait_group.read 0;" ::: "memory");
            mbar_arrive(bar + 8 * (GB_FREE + wg));
            asm volatile("cp.async.bulk.wait_group 0;" ::: "memory");
            PUBLISH(&g_f.kv[tile][hd][g & 1], epoch);
            if (tile == 0) { mbar_arrive(bar + 8 * GB_P0); if (g == 6) GT(1429); }
        }
        if (wg == 0) mbar_arrive(bar + 8 * GB_T1D);
        if (g >= 32) for (int i = 0; i < 4; i++) mbar_arrive2_if(bar + 8 * (GB_EMPTY + 4 + wg), 1);
        if (g < 32 && wg == 1) {
            mbar_wait(bar + 8 * GB_T1D, 0);
#pragma unroll 1
            for (int tile = 0; tile < NT; tile++) {
                wait_eq2(&g_f.kv[tile][g][0], epoch, 10);
                if (tile > 0) mbar_wait(bar + 8 * GB_KVF, (tile - 1) & 1);
                mbar_expect_tx(bar + 8 * (GB_KV + (tile & 1)), 16384);
                tma3d_h(sb + G_BUF, &maps.kx3, tile * 64, g * 2, bar + 8 * (GB_KV + (tile & 1)), pol_ef(0));
                if (tile > 0) mbar_wait(bar + 8 * GB_VF, (tile - 1) & 1);
                mbar_expect_tx(bar + 8 * (GB_VV + (tile & 1)), 16384);
                tma3d_h(sb + G_BUF + 32768, &maps.vx3, tile * 64, g * 2, bar + 8 * (GB_VV + (tile & 1)), pol_ef(0));
                if (PFK && tile + PFK < NT) {
                    const uint2 v = ldg_rlx2(&g_f.kv[tile + PFK][g][0]);
                    if (v.x == epoch && v.y == epoch) { tma_pf3d(&maps.kx3, (tile + PFK) * 64, g * 2); tma_pf3d(&maps.vx3, (tile + PFK) * 64, g * 2); }
                }
            }
        } else {
#pragma unroll 1
            for (int tile = g < 32 ? 0 : wg; tile < NT; tile += g < 32 ? 1 : 2) {
                mbar_wait(bar + 8 * (GB_STG + (tile & 1)), ((tile >> 1) + PO) & 1);
                mbar_arrive(bar + 8 * (GB_FREE + (tile & 1)));
                if (g < 32 || tile < LLT) PUBLISH(g < 32 ? &g_f.o[tile][g >> 2][g & 3] : &g_f.p[tile][g - 32], epoch);
                else stg_rlx(&g_f.p[tile][g - 32], epoch);
                if (g == 3 && tile == NT - 1) GT(1436);
                if (g == 3) GT(1896 + tile);
                if (g < 32 && tile == NT - 1) GT(1610 + g);
                if (g == 40 && tile == NT - 1) GT(1435);
                if (g == 40) GT(1864 + tile);
                if (g >= 32 && tile == NT - 1) GT(1650 + g - 32);
            }
        }
    }
}

struct WPtr { const bf16 *q, *k, *v, *o, *g, *u; };
__device__ __forceinline__ int startup(uint8_t* smem, const bf16* __restrict__ x, const Maps& maps, uint32_t& epoch, const WPtr& pw) {
    const int tid = threadIdx.x, lane = tid & 31, w = tid >> 5, cta = blockIdx.x;
    volatile uint32_t* sh = (volatile uint32_t*)(smem + SH_OFF);
    if (cta == 4 && tid == 0) GT(1399);
    epoch = (ldg_rlx(&g_epoch) + 1) & 0x00ffffffu;
    if (w < 4) {
        if (!(cta & 1)) {
            uint32_t* pp = (uint32_t*)(xpage() + ((XR3 ^ 0x3000u) ^ ((w == 1 || w == 2) ? 0x1000u : 0u) ^ ((w & 2) << 13))) + (cta >> 1) * 8;
            if (lane < 8) stg_rlx(pp + lane, 0u);
            __syncwarp();
            if (lane == 0) {
                uint32_t best = 0xffffffffu, a = 0;
#pragma unroll 1
                for (int r = 0; r < NPROBE; r++) {
                    uint32_t t0 = clk32();
                    asm volatile("atom.relaxed.gpu.global.add.u32 %0, [%1], %2;" : "=r"(a) : "l"(pp), "r"(a + 1) : "memory");
                    if (a == 0x7fffffffu) ABORT(15);
                    uint32_t t1 = clk32();
                    if (cta == 4 && w == 1) GT(1404 + r);
                    if (r > 0) best = min(best, t1 - t0);
                }
                sh[w] = best;
            }
        }
        if (!(cta & 1)) bar_sync(1, 160);
        if (cta == 4 && tid == 0) GT(1400);
        if (w == 0) {
            asm volatile("barrier.cluster.wait.aligned;" ::: "memory");
            if (lane == 0) {
                uint32_t rp;
                if (!(cta & 1)) {
                    uint32_t a = sh[0], b = sh[1], c = sh[2], d = sh[3];
                    uint32_t mid = (min(min(a, b), min(c, d)) + max(max(a, b), max(c, d))) >> 1;
                    const int dd = (int)min(a, d) - (int)min(b, c);
                    uint32_t cls = abs(dd) > 60 ? dd > 0 : a > mid;
                    uint32_t t = atomicAdd(&g_ticket[cls * 32], 1u) & 255;
                    if (t >= (cls ? 34u : 32u)) { cls ^= 1; t = atomicAdd(&g_ticket[cls * 32], 1u) & 255; }
                    rp = min(cls ? 32 + t : t, 65u);
                    asm volatile("st.relaxed.cluster.shared::cluster.u32 [%0], %1;" :: "r"((smem_u32(smem) + SH_OFF + 44) ^ 0x01000000u), "r"(rp) : "memory");
                } else {
                    uint32_t n = 0;
#pragma unroll 1
                    while ((rp = sh[11]) > 255) { if (++n > SPIN_LIMIT * 16) { ABORT(14); rp = 65; break; } }
                }
                if (cta == 4) GT(1407);
                if (cta == 5) GT(1408);
                const int role = rp * 2 + (cta & 1);
                sh[8] = role; sh[9] = epoch;
                while (sh[10] != epoch + 1 && cta < NWAITLN) {}
                if (RDEL && role < 64) __nanosleep(RDEL);
                if (role < 64) rec_first_loads(smem_u32(smem), role, maps);
                else if (role < 128) for (int k = 0; k < WK0; k++) load_w(smem_u32(smem), (role & 1) ? &maps.wv4 : &maps.wk4, ((role - 64) >> 1) * 128, k);
                if (cta == 4) GT(1401);
            }
        }
    } else {
        uint4 u[2][2];
        const int row0 = min(cta, 127) * 16 + (w - 4) * 2;
#pragma unroll
        for (int r = 0; r < 2; r++)
#pragma unroll
            for (int j = 0; j < 2; j++) u[r][j] = *(const uint4*)(x + (size_t)(row0 + r) * DM + j * 256 + lane * 8);
        if (w == 11 && !(cta & 1)) {
            if (lane < 2 && atomicMax(&g_ticket[lane * 32], epoch << 8) == 0xffffffffu) ABORT(15);
            __syncwarp();
            bar_arrive(1, 160);
        }
      if (cta < 128) {
        if (cta < 48) {
            const uint32_t b = cta >> 3, off = (b >= 4 ? 0x8000u + (b & 1) * 0x4000u : ((b & 1) ? 0x3000u : 0u) + ((b & 2) << 13)) ^ aslot(cta & 7);
            *(uint4*)(xpage() + off + (tid - 128) * 16) = make_uint4(0, 0, 0, 0);
        }
        float v[2][16];
#pragma unroll
        for (int r = 0; r < 2; r++)
#pragma unroll
            for (int j = 0; j < 2; j++) {
                uint32_t ww[4] = {u[r][j].x, u[r][j].y, u[r][j].z, u[r][j].w};
#pragma unroll
                for (int i = 0; i < 4; i++) { v[r][j * 8 + 2 * i] = bf_lo(ww[i]); v[r][j * 8 + 2 * i + 1] = bf_hi(ww[i]); }
            }
        ln_row2(v[0], v[1]);
#pragma unroll
        for (int r = 0; r < 2; r++)
#pragma unroll
            for (int j = 0; j < 2; j++)
                *(uint4*)(g_xn + (size_t)(row0 + r) * DM + j * 256 + lane * 8) =
                    make_uint4(pack2(v[r][j * 8], v[r][j * 8 + 1]), pack2(v[r][j * 8 + 2], v[r][j * 8 + 3]), pack2(v[r][j * 8 + 4], v[r][j * 8 + 5]), pack2(v[r][j * 8 + 6], v[r][j * 8 + 7]));
        bar_sync(2, 256);
        if (tid == 160 && cta < NWAITLN) { st_rel(&g_f.xn[cta], epoch); sh[10] = epoch + 1; }
        if (cta == 4 && tid == 160) GT(1403);
        __syncwarp();
      }
    }
    if (cta == 4 && tid == 128) GT(1402);
    __syncthreads();
    if (tid == 160 && cta >= NWAITLN && cta < 128) st_rel(&g_f.xn[cta], epoch);
    __syncwarp();
    const int role = sh[8];
    return role;
}

__global__ void __cluster_dims__(2, 1, 1) __launch_bounds__(384, 1)
main_kernel(const __grid_constant__ Maps maps, const bf16* __restrict__ x, const bf16* __restrict__ mem0, const bf16* __restrict__ wr,
            const bf16* __restrict__ wd, bf16* __restrict__ out, const WPtr pw) {
    extern __shared__ __align__(1024) uint8_t smem[];
    const uint32_t sb = smem_u32(smem);
    if (threadIdx.x == 0) {
        for (int i = 0; i < MB_N; i++) mbar_init(sb + R_BAR + 8 * i, i == MB_V ? 4 : 1);
        for (int i = 0; i < GB_N; i++)
            mbar_init(sb + G_BAR + 8 * i, i >= GB_EMPTY && i < GB_KV ? 8 : (i >= GB_KVF ? 4 : (i >= GB_STG && i < GB_FREE ? 128 : 1)));
        ((volatile uint32_t*)(smem + SH_OFF))[11] = 0xffffffffu;
        asm volatile("fence.mbarrier_init.release.cluster;" ::: "memory");
        if (((volatile uint32_t*)(smem + SH_OFF))[11] != 0xffffffffu) ABORT(14);
    }
    __syncwarp();
    asm volatile("barrier.cluster.arrive.relaxed.aligned;" ::: "memory");
    if (threadIdx.x >= 352 && threadIdx.x < 352 + (int)(sizeof(Maps) / sizeof(CUtensorMap)))
        asm volatile("prefetch.tensormap [%0];" :: "l"((const CUtensorMap*)&maps + (threadIdx.x - 352)) : "memory");
    uint32_t epoch;
    asm volatile("fence.proxy.async.shared::cta;" ::: "memory");
    const int role = uni(startup(smem, x, maps, epoch, pw));
    if (threadIdx.x >= 32) asm volatile("barrier.cluster.wait.aligned;" ::: "memory");
    const int wg = uni(threadIdx.x >> 7);
    if (role < 64) {
#define SETREG(n) do { if ((n) < 168) asm volatile("setmaxnreg.dec.sync.aligned.u32 %0;" :: "n"(n)); if ((n) > 168) asm volatile("setmaxnreg.inc.sync.aligned.u32 %0;" :: "n"(n)); } while (0)
#define RESREG(n) do { if ((n) < 168) asm volatile("setmaxnreg.inc.sync.aligned.u32 168;"); if ((n) > 168) asm volatile("setmaxnreg.dec.sync.aligned.u32 168;"); } while (0)
        if (wg == WGA) {
            SETREG(RGA);
            rec_a(sb, role, mem0, epoch);
            RESREG(RGA);
        } else if (wg == WGB) {
            SETREG(RGB);
            rec_b(sb, role, epoch);
            RESREG(RGB);
        } else {
            SETREG(RGC);
            rec_c(sb, role, mem0, maps, epoch);
            RESREG(RGC);
        }
        ffn_phase(maps, out);
        if (threadIdx.x == 0) GT(((volatile int*)(smem + SH_OFF))[8] * 8 + 6);
    } else if (role < 128) {
        if (wg < 2) {
            asm volatile("setmaxnreg.inc.sync.aligned.u32 184;");
            g_consumer(sb, role - 64, wg, epoch);
            if (threadIdx.x == 128) GT(role * 8 + 6);
        } else {
            asm volatile("setmaxnreg.dec.sync.aligned.u32 136;");
            g_producer(sb, role - 64, maps, epoch, x, wr, out);
        }
    } else {
        const int id = (threadIdx.x >> 5) * 4 + role - 128;
        finalizer(64 + id, x, wr, out, epoch, id < 16 ? pw.g : (id < 32 ? pw.u : wd));

    }
}

typedef CUresult (*EncodeFn)(CUtensorMap*, CUtensorMapDataType, cuuint32_t, void*, const cuuint64_t*, const cuuint64_t*, const cuuint32_t*, const cuuint32_t*,
                             CUtensorMapInterleave, CUtensorMapSwizzle, CUtensorMapL2promotion, CUtensorMapFloatOOBfill);
static void make_map3(EncodeFn fn, CUtensorMap* m, const void* ptr, uint64_t cols, uint64_t rows) {
    cuuint64_t dims[3] = {64, rows, cols / 64};
    cuuint64_t strides[2] = {cols * 2, 128};
    cuuint32_t box[3] = {64, 64, 2};
    cuuint32_t es[3] = {1, 1, 1};
    fn(m, CU_TENSOR_MAP_DATA_TYPE_BFLOAT16, 3, (void*)ptr, dims, strides, box, es, CU_TENSOR_MAP_INTERLEAVE_NONE, CU_TENSOR_MAP_SWIZZLE_128B,
       CU_TENSOR_MAP_L2_PROMOTION_L2_256B, CU_TENSOR_MAP_FLOAT_OOB_FILL_NONE);
}
static void make_map(EncodeFn fn, CUtensorMap* m, const void* ptr, uint64_t cols, uint64_t rows, uint32_t bcols, uint32_t brows,
                     bool f32 = false, CUtensorMapSwizzle sw = CU_TENSOR_MAP_SWIZZLE_128B) {
    cuuint64_t dims[2] = {cols, rows};
    cuuint64_t strides[1] = {cols * (f32 ? 4 : 2)};
    cuuint32_t box[2] = {bcols, brows};
    cuuint32_t es[2] = {1, 1};
    fn(m, f32 ? CU_TENSOR_MAP_DATA_TYPE_FLOAT32 : CU_TENSOR_MAP_DATA_TYPE_BFLOAT16, 2, (void*)ptr, dims, strides, box, es, CU_TENSOR_MAP_INTERLEAVE_NONE, sw,
       CU_TENSOR_MAP_L2_PROMOTION_L2_256B, CU_TENSOR_MAP_FLOAT_OOB_FILL_NONE);
}

extern "C" void kernel_launch(void* const* d_in, const int* in_sizes, int n_in, void* d_out, int out_size) {
    const bf16* x = (const bf16*)d_in[0];
    const bf16* mem0 = (const bf16*)d_in[1];
    const bf16* Wq = (const bf16*)d_in[2];
    const bf16* Wk = (const bf16*)d_in[3];
    const bf16* Wv = (const bf16*)d_in[4];
    const bf16* Wo = (const bf16*)d_in[5];
    const bf16* wr = (const bf16*)d_in[8];
    const bf16* wg = (const bf16*)d_in[9];
    const bf16* wu = (const bf16*)d_in[10];
    const bf16* wd = (const bf16*)d_in[11];
    bf16* out = (bf16*)d_out;

    static EncodeFn enc = nullptr;
    static void *pxn, *pK, *pV, *pO, *pacc;
    if (!enc) {
        cudaDriverEntryPointQueryResult qr;
        void* fn = nullptr;
        cudaGetDriverEntryPoint("cuTensorMapEncodeTiled", &fn, cudaEnableDefault, &qr);
        enc = (EncodeFn)fn;
        cudaGetSymbolAddress(&pxn, g_xn); cudaGetSymbolAddress(&pK, g_K); cudaGetSymbolAddress(&pV, g_V);
        cudaGetSymbolAddress(&pO, g_O); cudaGetSymbolAddress(&pacc, g_P);
        cudaFuncSetAttribute(main_kernel, cudaFuncAttributeMaxDynamicSharedMemorySize, SMEM_TOTAL);
    }
    Maps m;
    make_map(enc, &m.wq, Wq, HD, DM, 64, 256);
    make_map(enc, &m.wk, Wk, HD, DM, 64, 256);
    make_map(enc, &m.wv, Wv, HD, DM, 64, 256);
    make_map(enc, &m.wq4, Wq, HD, DM, 64, 128); make_map(enc, &m.wk4, Wk, HD, DM, 64, 128); make_map(enc, &m.wv4, Wv, HD, DM, 64, 128);
    make_map(enc, &m.wo, Wo, DM, HD, 64, 128);
    {
        cuuint64_t dims[5] = {DM, 2, 4, 4, HD / 32};
        cuuint64_t strides[4] = {DM * 2, 8 * DM * 2, 2 * DM * 2, 32 * DM * 2};
        cuuint32_t box[5] = {64, 2, 4, 4, 4};
        cuuint32_t es[5] = {1, 1, 1, 1, 1};
        enc(&m.wo2, CU_TENSOR_MAP_DATA_TYPE_BFLOAT16, 5, (void*)Wo, dims, strides, box, es, CU_TENSOR_MAP_INTERLEAVE_NONE, CU_TENSOR_MAP_SWIZZLE_128B,
            CU_TENSOR_MAP_L2_PROMOTION_L2_256B, CU_TENSOR_MAP_FLOAT_OOB_FILL_NONE);
    }
    make_map(enc, &m.kx, pK, HD, SQ, 64, 64);
    make_map(enc, &m.ox2, pO, HD, SQ, 64, 64);
    make_map(enc, &m.xn2, pxn, DM, SQ, 64, 64);
    make_map3(enc, &m.kx3, pK, HD, SQ); make_map3(enc, &m.vx3, pV, HD, SQ);
    make_map(enc, &m.wg, wg, FF, DM, 32, 256, false, CU_TENSOR_MAP_SWIZZLE_64B);
    make_map(enc, &m.wu, wu, FF, DM, 32, 256, false, CU_TENSOR_MAP_SWIZZLE_64B);
    make_map(enc, &m.wd, wd, DM, FF, 64, 32);

    cudaStream_t st = cudaStreamPerThread;
    main_kernel<<<NCTA, 384, SMEM_TOTAL, st>>>(m, x, mem0, wr, wd, out, WPtr{Wq, Wk, Wv, Wo, wg, wu});
}
```

```cpp
#include <cuda_runtime.h>
#include <cuda_bf16.h>
#include <cuda.h>
#include <stdint.h>
#include <stddef.h>

typedef __nv_bfloat16 bf16;

constexpr int SQ = 2048, DM = 512, NH = 32, DH = 128, NSEG = 64, HD = 4096, FF = 1792;

constexpr int NT = 32;
#define SPEC_TILES 30
__device__ __align__(1024) bf16 g_xn[SQ * DM];
__device__ __align__(1024) bf16 g_K[SQ * HD];
__device__ __align__(1024) bf16 g_V[SQ * HD];
__device__ __align__(1024) bf16 g_O[SQ * HD];
__device__ __align__(1024) uint32_t g_KVf[NSEG][NH][1024];
__device__ __align__(1024) bf16 g_P[8 * SQ * DM];
__device__ __align__(1024) bf16 g_h[SQ * DM];
__device__ __align__(1024) bf16 g_hn[SQ * DM];
__device__ uint8_t g_xraw[12 << 20];
#define XPG 0
__device__ __forceinline__ uint64_t xpage() { return (((uint64_t)g_xraw + (2 << 20) - 1) & ~(uint64_t)((2 << 20) - 1)) + ((uint64_t)XPG << 21); }
constexpr uint32_t XR3 = (1u << 20) | (1u << 19) | (1u << 12);
__device__ __forceinline__ uint32_t aslot(uint32_t s) { return ((s & 1) << 18) | ((s & 2) << 19) | ((s & 4) * 0xc000u); }
__device__ __forceinline__ uint32_t acc_base(uint32_t W) { return ((W & 2) ? 0x3000u : 0u) + ((W & 4) << 12) + (W & 1) * 2048; }
__device__ __forceinline__ uint32_t slice_off(uint32_t i) { return (i & 1) * 256 + (i & 2) * 512; }
__device__ __forceinline__ uint32_t zero_off(uint32_t c) { return acc_base(c >> 3) + slice_off((c >> 1) & 3) + (c & 1) * 512; }
struct Flags {
    uint32_t p[NT][32];
    uint4 cand[2][128];
    uint32_t rows[2][128];
    uint4 norm[64];
    uint32_t pad0[512];
    uint32_t kv[NT][NH][2];
    uint32_t pad1[2048];
    uint32_t o[NT][8][8];
    uint32_t pad2[2048];
    uint32_t rec[NH][32];
    uint32_t xn[128];
};
static_assert(offsetof(Flags, kv) == 0x3000 && offsetof(Flags, o) == 0x7000 && offsetof(Flags, xn) == 0xc000, "flags");
#define FLX 0
#define g_f (*(Flags*)(xpage() + (1u << 19) + FLX))
__device__ __align__(1024) uint4 g_yp[2][FF / 32][DM];
__device__ __align__(256) uint32_t g_ticket[64];
__device__ uint32_t g_epoch;
#define NS3 6
#define HSPLIT 26
#define PFK 0
#define NWAITLN 4
#define WGA 0
#define WGB 1
#define WGC (3 - WGA - WGB)
#define PFF 10
#define FFW 0
#define FFS 200
#define LLT 31
#define HP 3
#define WK0 1
#define RDEL 0
#define NPROBE 3
constexpr int NCTA = 132;
constexpr int NFW = 112;
__device__ uint32_t g_abort;
__device__ long long g_dbg[4096];
#define TR(slot, v)

__device__ __forceinline__ uint32_t smem_u32(const void* p) { return (uint32_t)__cvta_generic_to_shared(p); }
__device__ __forceinline__ void mbar_init(uint32_t a, uint32_t c) { asm volatile("mbarrier.init.shared::cta.b64 [%0], %1;" :: "r"(a), "r"(c) : "memory"); }
__device__ __forceinline__ void mbar_expect_tx(uint32_t a, uint32_t tx) { asm volatile("mbarrier.arrive.expect_tx.shared::cta.b64 _, [%0], %1;" :: "r"(a), "r"(tx) : "memory"); }
__device__ __forceinline__ void mbar_arrive(uint32_t a) { asm volatile("mbarrier.arrive.shared::cta.b64 _, [%0];" :: "r"(a) : "memory"); }
__device__ __forceinline__ void mbar_arrive_if(uint32_t a, uint32_t pred) {
    asm volatile("{\n.reg .pred p;\nsetp.ne.u32 p, %1, 0;\n@p mbarrier.arrive.shared::cta.b64 _, [%0];\n}" :: "r"(a), "r"(pred) : "memory");
}
__device__ __forceinline__ bool mbar_try(uint32_t a, uint32_t ph) {
    uint32_t ok;
    asm volatile("{\n.reg .pred p;\nmbarrier.try_wait.parity.shared::cta.b64 p, [%1], %2;\nselp.u32 %0, 1, 0, p;\n}" : "=r"(ok) : "r"(a), "r"(ph) : "memory");
    return ok != 0;
}
#define SPINLOG 20
constexpr uint32_t SPIN_LIMIT = 1u << SPINLOG;
#define ABORT(code_) atomicCAS(&g_abort, 0u, (code_))
__device__ __forceinline__ void mbar_wait(uint32_t a, uint32_t ph) {
    uint32_t n = 0;
#pragma unroll 1
    while (!mbar_try(a, ph)) { if (++n > SPIN_LIMIT) { ABORT(1); break; } }
}
__device__ __forceinline__ void bar_sync(int id, int n) { asm volatile("bar.sync %0, %1;" :: "r"(id), "r"(n) : "memory"); }
__device__ __forceinline__ void bar_arrive(int id, int n) { asm volatile("bar.arrive %0, %1;" :: "r"(id), "r"(n) : "memory"); }

__device__ __forceinline__ void ldsm4(uint32_t* r, uint32_t a) {
    asm volatile("ldmatrix.sync.aligned.m8n8.x4.shared.b16 {%0,%1,%2,%3}, [%4];" : "=r"(r[0]), "=r"(r[1]), "=r"(r[2]), "=r"(r[3]) : "r"(a) : "memory");
}
__device__ __forceinline__ void ldsm4t(uint32_t* r, uint32_t a) {
    asm volatile("ldmatrix.sync.aligned.m8n8.x4.trans.shared.b16 {%0,%1,%2,%3}, [%4];" : "=r"(r[0]), "=r"(r[1]), "=r"(r[2]), "=r"(r[3]) : "r"(a) : "memory");
}
__device__ __forceinline__ void stsm4t(uint32_t a, uint32_t r0, uint32_t r1, uint32_t r2, uint32_t r3) {
    asm volatile("stmatrix.sync.aligned.m8n8.x4.trans.shared.b16 [%0], {%1,%2,%3,%4};" :: "r"(a), "r"(r0), "r"(r1), "r"(r2), "r"(r3) : "memory");
}
__device__ __forceinline__ void stsm4(uint32_t a, uint32_t r0, uint32_t r1, uint32_t r2, uint32_t r3) {
    asm volatile("stmatrix.sync.aligned.m8n8.x4.shared.b16 [%0], {%1,%2,%3,%4};" :: "r"(a), "r"(r0), "r"(r1), "r"(r2), "r"(r3) : "memory");
}
__device__ __forceinline__ uint32_t movm(uint32_t a) { uint32_t d; asm volatile("movmatrix.sync.aligned.m8n8.trans.b16 %0, %1;" : "=r"(d) : "r"(a)); return d; }
__device__ __forceinline__ void mma16816(float* d, uint32_t a0, uint32_t a1, uint32_t a2, uint32_t a3, uint32_t b0, uint32_t b1) {
    asm volatile("mma.sync.aligned.m16n8k16.row.col.f32.bf16.bf16.f32 {%0,%1,%2,%3}, {%4,%5,%6,%7}, {%8,%9}, {%0,%1,%2,%3};"
        : "+f"(d[0]), "+f"(d[1]), "+f"(d[2]), "+f"(d[3]) : "r"(a0), "r"(a1), "r"(a2), "r"(a3), "r"(b0), "r"(b1));
}
__device__ __forceinline__ void mma1688(float* d, uint32_t a0, uint32_t a1, uint32_t b0) {
    asm volatile("mma.sync.aligned.m16n8k8.row.col.f32.bf16.bf16.f32 {%0,%1,%2,%3}, {%4,%5}, {%6}, {%0,%1,%2,%3};"
        : "+f"(d[0]), "+f"(d[1]), "+f"(d[2]), "+f"(d[3]) : "r"(a0), "r"(a1), "r"(b0));
}
__device__ __forceinline__ uint32_t pack2(float a, float b) { uint32_t d; asm("cvt.rn.bf16x2.f32 %0, %1, %2;" : "=r"(d) : "f"(b), "f"(a)); return d; }
__device__ __forceinline__ float bf_lo(uint32_t w) { return __uint_as_float(w << 16); }
__device__ __forceinline__ float bf_hi(uint32_t w) { return __uint_as_float(w & 0xffff0000u); }
__device__ __forceinline__ float rbf(float x) { return __bfloat162float(__float2bfloat16_rn(x)); }

__device__ __forceinline__ void sts128(uint32_t a, float x, float y, float z, float w) { asm volatile("st.shared.v4.f32 [%0], {%1,%2,%3,%4};" :: "r"(a), "f"(x), "f"(y), "f"(z), "f"(w) : "memory"); }
__device__ __forceinline__ void sts128u(uint32_t a, uint32_t x, uint32_t y, uint32_t z, uint32_t w) { asm volatile("st.shared.v4.b32 [%0], {%1,%2,%3,%4};" :: "r"(a), "r"(x), "r"(y), "r"(z), "r"(w) : "memory"); }
__device__ __forceinline__ void sts64(uint32_t a, float x, float y) { asm volatile("st.shared.v2.f32 [%0], {%1,%2};" :: "r"(a), "f"(x), "f"(y) : "memory"); }
__device__ __forceinline__ float4 lds128(uint32_t a) { float4 v; asm volatile("ld.shared.v4.f32 {%0,%1,%2,%3}, [%4];" : "=f"(v.x), "=f"(v.y), "=f"(v.z), "=f"(v.w) : "r"(a) : "memory"); return v; }
__device__ __forceinline__ float2 lds64(uint32_t a) { float2 v; asm volatile("ld.shared.v2.f32 {%0,%1}, [%2];" : "=f"(v.x), "=f"(v.y) : "r"(a) : "memory"); return v; }
__device__ __forceinline__ uint2 lds64u(uint32_t a) { uint2 v; asm volatile("ld.shared.v2.b32 {%0,%1}, [%2];" : "=r"(v.x), "=r"(v.y) : "r"(a) : "memory"); return v; }
__device__ __forceinline__ float4 lds128v(uint32_t a) { float4 v; asm volatile("ld.volatile.shared.v4.f32 {%0,%1,%2,%3}, [%4];" : "=f"(v.x), "=f"(v.y), "=f"(v.z), "=f"(v.w) : "r"(a) : "memory"); return v; }
__device__ __forceinline__ float2 lds64v(uint32_t a) { float2 v; asm volatile("ld.volatile.shared.v2.f32 {%0,%1}, [%2];" : "=f"(v.x), "=f"(v.y) : "r"(a) : "memory"); return v; }
__device__ __forceinline__ uint4 lds128uv(uint32_t a) { uint4 v; asm volatile("ld.volatile.shared.v4.b32 {%0,%1,%2,%3}, [%4];" : "=r"(v.x), "=r"(v.y), "=r"(v.z), "=r"(v.w) : "r"(a) : "memory"); return v; }
__device__ __forceinline__ void st_async4(uint32_t a, float x, float y, float z, float w, uint32_t mb) {
    asm volatile("st.async.weak.shared::cluster.mbarrier::complete_tx::bytes.v4.f32 [%0], {%1,%2,%3,%4}, [%5];" :: "r"(a), "f"(x), "f"(y), "f"(z), "f"(w), "r"(mb) : "memory");
}
__device__ __forceinline__ void st_async2(uint32_t a, uint32_t x, uint32_t y, uint32_t mb) {
    asm volatile("st.async.weak.shared::cluster.mbarrier::complete_tx::bytes.v2.b32 [%0], {%1,%2}, [%3];" :: "r"(a), "r"(x), "r"(y), "r"(mb) : "memory");
}
__device__ __forceinline__ uint32_t ldg_rlx(const uint32_t* p) { uint32_t v; asm volatile("ld.relaxed.gpu.global.b32 %0, [%1];" : "=r"(v) : "l"(p) : "memory"); return v; }
__device__ __forceinline__ uint4 ldg_rlx4(const uint32_t* p) { uint4 v; asm volatile("ld.relaxed.gpu.global.v4.b32 {%0,%1,%2,%3}, [%4];" : "=r"(v.x), "=r"(v.y), "=r"(v.z), "=r"(v.w) : "l"(p) : "memory"); return v; }
__device__ __forceinline__ uint4 ldg_rlx4_if(const uint32_t* p, bool c) {
    uint4 v;
    asm volatile("{\n.reg .pred p;\nsetp.ne.u32 p, %5, 0;\nmov.b32 %0, 0;\nmov.b32 %1, 0;\nmov.b32 %2, 0;\nmov.b32 %3, 0;\n@p ld.relaxed.gpu.global.v4.b32 {%0,%1,%2,%3}, [%4];\n}"
                 : "=r"(v.x), "=r"(v.y), "=r"(v.z), "=r"(v.w) : "l"(p), "r"((uint32_t)c) : "memory");
    return v;
}
__device__ __forceinline__ void stg_rlx(uint32_t* p, uint32_t v) { asm volatile("st.relaxed.gpu.global.b32 [%0], %1;" :: "l"(p), "r"(v) : "memory"); }
__device__ __forceinline__ void tma2d(uint32_t dst, const CUtensorMap* tm, int c0, int c1, uint32_t mb) {
    asm volatile("cp.async.bulk.tensor.2d.shared::cluster.global.mbarrier::complete_tx::bytes [%0], [%1, {%3, %4}], [%2];"
        :: "r"(dst), "l"((uint64_t)tm), "r"(mb), "r"(c0), "r"(c1) : "memory");
}

__device__ __forceinline__ void tma3d(uint32_t dst, const CUtensorMap* tm, int row, int chunk, uint32_t mb) {
    asm volatile("cp.async.bulk.tensor.3d.shared::cluster.global.mbarrier::complete_tx::bytes [%0], [%1, {%3, %4, %5}], [%2];"
        :: "r"(dst), "l"((uint64_t)tm), "r"(mb), "r"(0), "r"(row), "r"(chunk) : "memory");
}
#define EF 0xff
__device__ __forceinline__ uint64_t pol_ef(int bit) {
    uint64_t p;
    if ((EF >> bit) & 1) asm("createpolicy.fractional.L2::evict_first.b64 %0, 1.0;" : "=l"(p));
    else asm("createpolicy.fractional.L2::evict_normal.b64 %0, 1.0;" : "=l"(p));
    return p;
}
__device__ __forceinline__ void tma3d_h(uint32_t dst, const CUtensorMap* tm, int row, int chunk, uint32_t mb, uint64_t pol) {
    asm volatile("cp.async.bulk.tensor.3d.shared::cluster.global.mbarrier::complete_tx::bytes.L2::cache_hint [%0], [%1, {%3, %4, %5}], [%2], %6;"
        :: "r"(dst), "l"((uint64_t)tm), "r"(mb), "r"(0), "r"(row), "r"(chunk), "l"(pol) : "memory");
}
__device__ __forceinline__ void tma2d_h(uint32_t dst, const CUtensorMap* tm, int c0, int c1, uint32_t mb, uint64_t pol) {
    asm volatile("cp.async.bulk.tensor.2d.shared::cluster.global.mbarrier::complete_tx::bytes.L2::cache_hint [%0], [%1, {%3, %4}], [%2], %5;"
        :: "r"(dst), "l"((uint64_t)tm), "r"(mb), "r"(c0), "r"(c1), "l"(pol) : "memory");
}
__device__ __forceinline__ void tma2d_mc_h(uint32_t dst, const CUtensorMap* tm, int c0, int c1, uint32_t mb, uint64_t pol) {
    asm volatile("cp.async.bulk.tensor.2d.shared::cluster.global.mbarrier::complete_tx::bytes.multicast::cluster.L2::cache_hint [%0], [%1, {%3, %4}], [%2], %5, %6;"
        :: "r"(dst), "l"((uint64_t)tm), "r"(mb), "r"(c0), "r"(c1), "h"((uint16_t)3), "l"(pol) : "memory");
}
__device__ __forceinline__ uint4 ldg4_h(const void* p, uint64_t pol) {
    uint4 v;
    asm volatile("ld.relaxed.gpu.global.L2::cache_hint.v4.b32 {%0,%1,%2,%3}, [%4], %5;" : "=r"(v.x), "=r"(v.y), "=r"(v.z), "=r"(v.w) : "l"(p), "l"(pol) : "memory");
    return v;
}
__device__ __forceinline__ void stg4_h(void* p, uint4 v, uint64_t pol) {
    asm volatile("st.relaxed.gpu.global.L2::cache_hint.v4.b32 [%0], {%1,%2,%3,%4}, %5;" :: "l"(p), "r"(v.x), "r"(v.y), "r"(v.z), "r"(v.w), "l"(pol) : "memory");
}
__device__ __forceinline__ void tma2d_mc(uint32_t dst, const CUtensorMap* tm, int c0, int c1, uint32_t mb) {
    asm volatile("cp.async.bulk.tensor.2d.shared::cluster.global.mbarrier::complete_tx::bytes.multicast::cluster [%0], [%1, {%3, %4}], [%2], %5;"
        :: "r"(dst), "l"((uint64_t)tm), "r"(mb), "r"(c0), "r"(c1), "h"((uint16_t)3) : "memory");
}
__device__ __forceinline__ void mbar_arrive2_if(uint32_t a, uint32_t pred) {
    asm volatile("{\n.reg .pred p;\nsetp.ne.u32 p, %1, 0;\n@p mbarrier.arrive.shared::cta.b64 _, [%0];\n@p mbarrier.arrive.shared::cluster.b64 _, [%2];\n}"
                 :: "r"(a), "r"(pred), "r"(a ^ 0x01000000u) : "memory");
}
__device__ __forceinline__ void tma_pf3d(const CUtensorMap* tm, int row, int chunk) {
    asm volatile("cp.async.bulk.prefetch.tensor.3d.L2.global.tile [%0, {%1, %2, %3}];" :: "l"((uint64_t)tm), "r"(0), "r"(row), "r"(chunk) : "memory");
}
__device__ __forceinline__ void tma_pf2d(const CUtensorMap* tm, int c0, int c1) {
    asm volatile("cp.async.bulk.prefetch.tensor.2d.L2.global.tile [%0, {%1, %2}];" :: "l"((uint64_t)tm), "r"(c0), "r"(c1) : "memory");
}
__device__ __forceinline__ void tma_store3d(const CUtensorMap* tm, uint32_t src, int row, int chunk) {
    asm volatile("cp.async.bulk.tensor.3d.global.shared::cta.bulk_group [%0, {%2, %3, %4}], [%1];" :: "l"((uint64_t)tm), "r"(src), "r"(0), "r"(row), "r"(chunk) : "memory");
}
__device__ __forceinline__ void bulk_store(void* dst, uint32_t src, uint32_t bytes) {
    asm volatile("cp.async.bulk.global.shared::cta.bulk_group [%0], [%1], %2;" :: "l"(dst), "r"(src), "r"(bytes) : "memory");
}
#define GT(slot)
#define CNT(k)
#define CNT2(k, c)
#define TS(i, dep)
#define TSACC()
#define TSDECL
struct Maps { CUtensorMap wq, wk, wv, wo, wo2, kx, ox2, kx3, vx3, xn2, wg, wu, wd, wq4, wk4, wv4; };
typedef Maps RecMaps;
__device__ __forceinline__ void st_rel(uint32_t* p, uint32_t v) { asm volatile("st.release.gpu.global.u32 [%0], %1;" :: "l"(p), "r"(v) : "memory"); }
#define PUBLISH(p, v) st_rel(p, v)
__device__ __forceinline__ uint2 ldg_rlx2(const uint32_t* p) { uint2 v; asm volatile("ld.relaxed.gpu.global.v2.b32 {%0,%1}, [%2];" : "=r"(v.x), "=r"(v.y) : "l"(p) : "memory"); return v; }
__device__ __forceinline__ void wait_eq2(const uint32_t* p, uint32_t e, int code) {
    uint32_t n = 0;
#pragma unroll 1
    while (true) { uint2 v = ldg_rlx2(p); if (v.x == e && v.y == e) break; __nanosleep(64); if (++n > SPIN_LIMIT) { ABORT(code); break; } }
}
__device__ __forceinline__ void wait_eq4(const uint32_t* p, uint32_t e, int code) {
    uint32_t n = 0;
#pragma unroll 1
    while (true) { uint4 v = ldg_rlx4(p); if (v.x == e && v.y == e && v.z == e && v.w == e) break; __nanosleep(64); if (++n > SPIN_LIMIT) { ABORT(code); break; } }
}
__device__ __forceinline__ void wait_rec(const uint32_t* p, uint32_t e, uint32_t steps) {
    uint32_t n = 0;
#pragma unroll 1
    while (true) {
        uint2 v = ldg_rlx2(p);
        if (__all_sync(0xffffffffu, (v.x >> 8) == e && (v.y >> 8) == e && (v.x & 255) >= steps && (v.y & 255) >= steps)) break;
        __nanosleep(64); if (++n > SPIN_LIMIT) { ABORT(8); break; }
    }
}

constexpr int R_QK1 = 0;
constexpr int R_WO = 65536;
constexpr int R_T = 131072;
constexpr int R_SLOT1 = R_T;
constexpr int R_MEMB = R_T + 24576;
constexpr int R_QP = R_MEMB + 8192;
constexpr int R_VRED = R_QP + 4096;
constexpr int R_STG = R_VRED + 2048;
constexpr int R_AX = R_STG + 2048;
constexpr int R_SLOT0 = 196608;
constexpr int R_SLOC = R_SLOT0 + 24576;
constexpr int R_SREM = R_SLOC + 1536;
constexpr int R_VB = R_SREM + 1536;
constexpr int R_MISC = R_VB + 2048;
constexpr int R_LT = R_MISC + 128;
constexpr int R_BAR = 229888;
constexpr int R_TS = 229888 + 128;
static_assert(R_AX + 24576 <= R_SLOT0 && R_LT + 2560 <= 229376, "smem map");
enum { MB_W0 = 0, MB_W1, MB_WV, MB_WO, MB_S, MB_FULL0, MB_FULL1, MB_V, MB_N };

__device__ __forceinline__ float ex2(float x) { float y; asm("ex2.approx.ftz.f32 %0, %1;" : "=f"(y) : "f"(x)); return y; }
__device__ __forceinline__ float rcpf(float x) { float y; asm("rcp.approx.ftz.f32 %0, %1;" : "=f"(y) : "f"(x)); return y; }
__device__ __forceinline__ void mma16816z(float* d, uint32_t a0, uint32_t a1, uint32_t a2, uint32_t a3, uint32_t b0, uint32_t b1) {
    asm volatile("mma.sync.aligned.m16n8k16.row.col.f32.bf16.bf16.f32 {%0,%1,%2,%3}, {%4,%5,%6,%7}, {%8,%9}, {%10,%10,%10,%10};"
        : "=f"(d[0]), "=f"(d[1]), "=f"(d[2]), "=f"(d[3]) : "r"(a0), "r"(a1), "r"(a2), "r"(a3), "r"(b0), "r"(b1), "f"(0.f));
}
__device__ __forceinline__ void mma1688hz(float* d, uint32_t a0, uint32_t a1, uint32_t b0) {
    asm volatile("mma.sync.aligned.m16n8k8.row.col.f32.f16.f16.f32 {%0,%1,%2,%3}, {%4,%5}, {%6}, {%7,%7,%7,%7};"
        : "=f"(d[0]), "=f"(d[1]), "=f"(d[2]), "=f"(d[3]) : "r"(a0), "r"(a1), "r"(b0), "f"(0.f));
}
#define MMA(d, a, b0, b1) mma16816(d, a[0], a[1], a[2], a[3], b0, b1)
#define MMAZ(d, a, b0, b1) mma16816z(d, a[0], a[1], a[2], a[3], b0, b1)
#define MMAF(first, d, a, b0, b1) do { if (first) MMAZ(d, a, b0, b1); else MMA(d, a, b0, b1); } while (0)

__device__ __forceinline__ uint32_t uni(uint32_t x) { return __reduce_max_sync(0xffffffffu, x); }
__device__ __forceinline__ void mbar_wait_u(uint32_t a, uint32_t ph) {
    uint32_t n = 0;
#pragma unroll 1
    while (!__all_sync(0xffffffffu, mbar_try(a, ph))) { if (++n > SPIN_LIMIT) { ABORT(1); break; } }
}
__device__ __forceinline__ void mbar_wait_p(uint32_t a, uint32_t ph) {
    asm volatile("{\n.reg .pred p, q;\n.reg .u32 n;\nmov.u32 n, 0;\nWL: mbarrier.try_wait.parity.shared::cta.b64 p, [%0], %1;\nadd.u32 n, n, 1;\n"
                 "setp.lt.and.u32 q, n, %2, !p;\n@q bra.uni WL;\n}" :: "r"(a), "r"(ph), "n"(SPIN_LIMIT) : "memory");
}
__device__ __forceinline__ uint32_t mbar_test(uint32_t a, uint32_t ph) {
    uint32_t ok;
    asm volatile("{\n.reg .pred p;\nmbarrier.test_wait.parity.shared::cta.b64 p, [%1], %2;\nselp.u32 %0, 1, 0, p;\n}" : "=r"(ok) : "r"(a), "r"(ph) : "memory");
    return ok;
}
__device__ __forceinline__ uint32_t opaque(uint32_t x) { return __shfl_sync(0xffffffffu, x, threadIdx.x & 31); }
__device__ __forceinline__ const uint32_t* mkptr(uint32_t lo, uint32_t hi) { uint64_t r; asm("mov.b64 %0, {%1, %2};" : "=l"(r) : "r"(lo), "r"(hi)); return (const uint32_t*)r; }
__device__ __forceinline__ uint32_t prmt(uint32_t a, uint32_t b, uint32_t s) { uint32_t d; asm("prmt.b32 %0, %1, %2, %3;" : "=r"(d) : "r"(a), "r"(b), "r"(s)); return d; }
__device__ __forceinline__ uint32_t packh2(float a, float b) { uint32_t d; asm("cvt.rn.f16x2.f32 %0, %1, %2;" : "=r"(d) : "f"(b), "f"(a)); return d; }
__device__ __forceinline__ uint32_t hadd2b(uint32_t a, uint32_t b) { uint32_t d; asm("add.rn.bf16x2 %0, %1, %2;" : "=r"(d) : "r"(a), "r"(b)); return d; }
__device__ __forceinline__ uint32_t hadd2h(uint32_t a, uint32_t b) { uint32_t d; asm("add.rn.f16x2 %0, %1, %2;" : "=r"(d) : "r"(a), "r"(b)); return d; }
__device__ __forceinline__ uint32_t hmul2b(uint32_t a, uint32_t b) { uint32_t d; asm("mul.rn.bf16x2 %0, %1, %2;" : "=r"(d) : "r"(a), "r"(b)); return d; }
__device__ __forceinline__ uint32_t amax2b(uint32_t a, uint32_t b) { uint32_t d; asm("max.xorsign.abs.bf16x2 %0, %1, %2;" : "=r"(d) : "r"(a), "r"(b)); return d; }
__device__ __forceinline__ uint32_t amax2h(uint32_t a, uint32_t b) { uint32_t d; asm("max.xorsign.abs.f16x2 %0, %1, %2;" : "=r"(d) : "r"(a), "r"(b)); return d; }
__device__ __forceinline__ void sts32(uint32_t a, uint32_t x) { asm volatile("st.shared.b32 [%0], %1;" :: "r"(a), "r"(x) : "memory"); }
__device__ __forceinline__ uint32_t lds32v_(uint32_t a) { uint32_t v; asm volatile("ld.volatile.shared.b32 %0, [%1];" : "=r"(v) : "r"(a) : "memory"); return v; }
__device__ __forceinline__ void stg4(void* p, uint4 v) { asm volatile("st.relaxed.gpu.global.v4.b32 [%0], {%1,%2,%3,%4};" :: "l"(p), "r"(v.x), "r"(v.y), "r"(v.z), "r"(v.w) : "memory"); }
__device__ __forceinline__ void lds_frag(uint32_t* r, uint32_t a) {
    asm volatile("ld.shared.v4.b32 {%0,%1,%2,%3}, [%4];" : "=r"(r[0]), "=r"(r[1]), "=r"(r[2]), "=r"(r[3]) : "r"(a) : "memory");
}
__device__ __forceinline__ void lds_fragv(uint32_t* r, uint32_t a) {
    asm volatile("ld.volatile.shared.v4.b32 {%0,%1,%2,%3}, [%4];" : "=r"(r[0]), "=r"(r[1]), "=r"(r[2]), "=r"(r[3]) : "r"(a) : "memory");
}
__device__ __forceinline__ uint32_t xorv(uint32_t a, uint32_t b) { uint32_t d; asm volatile("xor.b32 %0, %1, %2;" : "=r"(d) : "r"(a), "r"(b)); return d; }
#define SCHED(k) asm volatile("{\n.reg .pred p;\nsetp.eq.u32 p, %0, %1;\n@p exit;\n}" :: "r"(sbu - s), "n"(k) : "memory")
#define PINM() asm volatile("{\n.reg .pred p;\nsetp.eq.u32 p, %0, 1;\n@p st.shared.u32 [%0], 0;\n}" :: "r"(sbu) : "memory")
__device__ __forceinline__ uint32_t or_and(uint32_t a, uint32_t b, uint32_t c) { uint32_t d; asm("lop3.b32 %0, %1, %2, %3, 0xF8;" : "=r"(d) : "r"(a), "r"(b), "r"(c)); return d; }
__device__ __forceinline__ uint32_t pack2v(float a, float b) { uint32_t d; asm volatile("cvt.rn.bf16x2.f32 %0, %1, %2;" : "=r"(d) : "f"(b), "f"(a)); return d; }
#define FU(x) __float_as_uint(x)
__device__ __forceinline__ uint32_t clk32() { uint32_t t; asm volatile("mov.u32 %0, %%clock;" : "=r"(t) :: "memory"); return t; }
__device__ __forceinline__ void spin_until(uint32_t t0, uint32_t d) {
    if (d) {
#pragma unroll 1
        while (__any_sync(0xffffffffu, clk32() - t0 < d)) {}
    }
}
constexpr int SH_OFF = 229376 + 384;
constexpr uint32_t HONE2 = 0x3c003c00u, HCNT2 = 0x50005000u;

__device__ __forceinline__ uint64_t desc_sw128(uint32_t addr, uint32_t lbo, uint32_t sbo) {
    return (uint64_t)((addr & 0x3FFFF) >> 4) | ((uint64_t)(lbo >> 4) << 16) | ((uint64_t)(sbo >> 4) << 32) | (1ull << 62);
}
#define DP 375
#define NAX 3
#define NXL 0
#define NCX 2
#define NCL 1
#define FLIP 1
#define VTA 1
#define KXB 4
#define ANB 3
#define BNB 3
#define CNB 3
#define SMA 0
#define SMB 0
#define SMC 0x01
#define IVA 0
#define RGA 160
#define RGC 160
#define RGB (504 - RGA - RGC)
#define NRW 8
#define NBR 16
#define E0 0
#define E1 6
#define E2 4
#define E3 8
#define IV 2
#define DN 0
#define XF 1
#define YF 0
#define RB 0
#define WI(n) ((n) - NRW < RB ? (n) - NRW : (n))
#define G2V 0
#define G2K 2
#define VDEP 0
#define AEARLY 0
#define VTP 2
#define LORD 1
#define TRK 1
#define T2N 14
#define NB0 0
#define NB1 9
#define DB2 80
#define DITHER 0
#define DB 40

__device__ __forceinline__ uint32_t wrow_off(int kk, int ch) {
    const int lane = threadIdx.x & 31;
    return (16 * kk + 8 * (lane >> 4) + (lane & 7)) * 128 + ((ch ^ (lane & 7)) << 4);
}
template <int K> __device__ __forceinline__ void sched(uint32_t key) {
    asm volatile("{\n.reg .pred p;\nsetp.eq.u32 p, %0, %1;\n@p exit;\n}" :: "r"(key), "n"(K) : "memory");
}
__device__ __forceinline__ void sched_i(int i, uint32_t key) {
    if (i == -1) sched<20>(key); if (i == 0) sched<21>(key); if (i == 1) sched<22>(key); if (i == 2) sched<23>(key);
    if (i == 3) sched<24>(key); if (i == 4) sched<25>(key); if (i == 5) sched<26>(key); if (i == 6) sched<27>(key);
}
template <int NB, int SM, class F>
__device__ __forceinline__ void g1(float* q0, float* k0, uint32_t (*wq)[4], uint32_t (*wk)[4], uint32_t ga, uint32_t key, F&& hook) {
    float q1[4], k1[4];
    uint32_t b[NB][4];
#pragma unroll
    for (int i = 0; i < NB; i++) ldsm4(b[i], ga + i * 512);
    hook(-1, b[0]);
    if (SM & 1) sched_i(-1, key);
#pragma unroll
    for (int i = 0; i < 8; i++) {
        uint32_t* c = b[i % NB];
        MMAF(i == 0, q0, wq[2 * i], c[0], c[1]); MMAF(i == 0, k0, wk[2 * i], c[0], c[1]);
        MMAF(i == 0, q1, wq[2 * i + 1], c[2], c[3]); MMAF(i == 0, k1, wk[2 * i + 1], c[2], c[3]);
        const uint32_t cc_[4] = {c[0], c[1], c[2], c[3]};
        if (i + NB < 8) ldsm4(b[i % NB], ga + (i + NB) * 512);
        hook(i, cc_);
        if ((SM >> (i + 1)) & 1) sched_i(i, key);
    }
#pragma unroll
    for (int i = 0; i < 4; i++) { q0[i] += q1[i]; k0[i] += k1[i]; }
}
__device__ __forceinline__ float frag_norm2(uint32_t (*w)[4]) {
    float d0[4], d1[4];
#pragma unroll
    for (int i = 0; i < 32; i++) { MMAF(i == 0, d0, w[i], w[i][0], w[i][2]); MMAF(i == 0, d1, w[i], w[i][1], w[i][3]); }
    const int lane = threadIdx.x & 31, g = lane >> 2, t = lane & 3;
    float v = g == 2 * t ? d0[0] + d1[2] : (g == 2 * t + 1 ? d0[1] + d1[3] : 0.f);
#pragma unroll
    for (int o = 16; o; o >>= 1) v += __shfl_xor_sync(0xffffffffu, v, o);
    return v;
}
__device__ __forceinline__ void arm_slot(uint32_t sb, int tile) {
    asm volatile("{\n.reg .pred p;\nelect.sync _|p, 0xffffffff;\n@p mbarrier.arrive.expect_tx.shared::cta.b64 _, [%0], 24576;\n}"
                 :: "r"(sb + R_BAR + 8 * (MB_FULL0 + (tile & 1))) : "memory");
}
__device__ __forceinline__ void load_slot(uint32_t sb, int c, int tile, const Maps& maps) {
    const uint32_t dst = sb + ((tile & 1) ? R_SLOT1 : R_SLOT0), mb = sb + R_BAR + 8 * (MB_FULL0 + (tile & 1));
    asm volatile("{\n.reg .pred p;\nelect.sync _|p, 0xffffffff;\n"
                 "@p cp.async.bulk.tensor.2d.shared::cluster.global.mbarrier::complete_tx::bytes [%0], [%2, {%5, %6}], [%4];\n"
                 "@p cp.async.bulk.tensor.3d.shared::cluster.global.mbarrier::complete_tx::bytes [%1], [%3, {%8, %6, %7}], [%4];\n}"
                 :: "r"(dst + 16384), "r"(dst), "l"((uint64_t)&maps.kx), "l"((uint64_t)&maps.vx3), "r"(mb), "r"(c * 64), "r"(tile * 64), "r"((c >> 1) * 2), "r"(0) : "memory");
}
__device__ __forceinline__ uint32_t put_mem0(uint32_t dst, uint4 m0, uint4 m1) {
    sts128u(dst, m0.x, m0.y, m0.z, m0.w);
    sts128u(dst + 512, m1.x, m1.y, m1.z, m1.w);
    return amax2b(amax2b(amax2b(m0.x, m0.y), amax2b(m0.z, m0.w)), amax2b(amax2b(m1.x, m1.y), amax2b(m1.z, m1.w)));
}
#define PUT_MAX(rL, W) sts32(rL + R_STG + 1024 + ((W) >> 2) * 512 + ((W) & 3) * 4, amax2b(amax2b(mx, my), mz));
__device__ __forceinline__ uint32_t h2b(uint32_t w) {
    uint32_t d;
    asm("{\n.reg .f16 l, h;\n.reg .f32 a, b;\nmov.b32 {l, h}, %1;\ncvt.f32.f16 a, l;\ncvt.f32.f16 b, h;\ncvt.rn.bf16x2.f32 %0, b, a;\n}" : "=r"(d) : "r"(w));
    return d;
}
#define GATHER1(HALF)                                                                                           \
        {                                                                                                       \
            const uint4 x0 = ldg_rlx4(pm), x1 = ldg_rlx4(pm + 32);                                              \
            const uint32_t y0 = ldg_rlx(px), y1 = ldg_rlx(px + 64), y2 = ldg_rlx(px + 256), y3 = ldg_rlx(px + 320); \
            const uint32_t y = hadd2h(hadd2h(y0, y1), hadd2h(y2, y3));                                          \
            cw = (sel & 0x4000u) ? prmt(x0.w, x1.w, 0x7632u) : y;                                               \
            const uint32_t p0 = h2b(x0.x), p1 = h2b(x0.y), p2 = h2b(x0.z), p3 = h2b(prmt(x0.w, y, sel));        \
            stsm4t(rG + R_MEMB + HALF * 4096, p0, p1, p2, p3);                                                  \
            const uint32_t p4 = h2b(x1.x), p5 = h2b(x1.y), p6 = h2b(x1.z), p7 = h2b(prmt(x1.w, y, sel | 0x2200u)); \
            stsm4t(rG + R_MEMB + HALF * 4096 + 512, p4, p5, p6, p7);                                            \
            mx = amax2b(amax2b(p0, p1), amax2b(p2, p3)); my = amax2b(p4, p5); mz = amax2b(p6, p7);              \
        }
#define GATHER(HALF, PRE, SYNC, AFTER)                                                                                      \
        {                                                                                                       \
            const uint32_t so = aslot(s);                                                                       \
            const uint32_t ua = (glo + acc_base(HALF * 4 + fo)) ^ so; \
            uint2 lt;                                                                                           \
            lt.x = lds32v_(rL + R_LT); lt.y = lds32v_(rL + R_LT + 4);                                           \
            const uint32_t sel = 0x3210u + (lt.x & 16) * 0x220u;                                \
            const uint32_t* pm = mkptr(ua + lt.x, ghi);                                                         \
            const uint32_t* px = mkptr(ua + lt.y, ghi);                                                         \
            PRE                                                                                                 \
            bar_sync(5, 384);                                                                                   \
            const uint32_t t0 = clk32();                                                                        \
            TSACC();                                                                        \
            SYNC                                                                                                \
            spin_until(t0, DP + DITHER);                                                                                 \
            \
            TS(10, 0);                                                                                          \
            uint32_t cw, nr = 0;                                                                                \
            _Pragma("unroll 1") do {                                                                            \
                GATHER1(HALF)                                                                                   \
                nr++;                                                                                           \
            } while (__any_sync(0xffffffffu, cw != HCNT2 && nr < SPIN_LIMIT));                                  \
            TS(11, cw);                                                                                         \
            AFTER                                                                                               \
            CNT2(HALF * 4 + (s & 1) * 2 + (nr > 2), nr > 1); CNT2(64 + s, nr > 1);                                                    \
            \
        }
#define GOBAR (fo == 3 ? 14 : 10 + fo)

__device__ __forceinline__ void rec_a(uint32_t sb, int c, const bf16* __restrict__ mem0, uint32_t epoch) {
    const int tid = threadIdx.x - WGA * 128, lane = tid & 31, f = tid >> 5;
    uint32_t wq[16][4], wk[16][4], mx, my = 0, mz = 0;
    const int lrow = ((lane >> 4) << 3) + (lane & 7), lsel = (lane >> 3) & 1;
    {
        const uint32_t* mp = (const uint32_t*)(mem0 + (lane & 7) * DM + f * 64 + (lane >> 3) * 8);
        const uint4 ma = ldg_rlx4(mp), mb = ldg_rlx4(mp + 16), mc = ldg_rlx4(mp + 128), md = ldg_rlx4(mp + 144);
        mbar_wait(sb + R_BAR + 8 * MB_W0, 0);
        if (c == 7 && tid == 0) GT(1421);
#pragma unroll
        for (int kk = 0; kk < 16; kk++) { const uint32_t a = sb + R_T + wrow_off(kk, 2 * f + lsel); ldsm4t(wq[kk], a); ldsm4t(wk[kk], a + 32768); }
        __syncwarp();
        bar_sync(4, 128);
        mx = put_mem0(sb + R_MEMB + f * 1024 + lane * 16, ma, mb);
        my = put_mem0(sb + R_MEMB + 4096 + f * 1024 + lane * 16, mc, md);
        bar_arrive(5, 256);
    }
    const uint32_t rL = opaque(sb + lane * 16), rG = opaque(sb + lane * 16 + f * 1024);
    const uint32_t sbu = uni(sb), fo = uni(f), cc = uni(c);
    const uint64_t gx = xpage();
    const uint32_t ghi = uni((uint32_t)(gx >> 32)), glo = uni((uint32_t)gx);
#pragma unroll
    for (int i = 0; i < NAX; i++) {
        sts128u(rG + R_AX + 4096 * i, wq[i][0], wq[i][1], wq[i][2], wq[i][3]);
        sts128u(rG + R_AX + 4096 * i + 512, wk[i][0], wk[i][1], wk[i][2], wk[i][3]);
    }
    sts128u(rL + R_LT + 512 + f * 512, (sb + R_SREM + (f >= 2 ? lane * 8 + f * 256 : lane * 16 + f * 1024)) ^ 0x01000000u, (sb + R_BAR + 8 * MB_S) ^ 0x01000000u,
            sb + R_QP + (lane >> 4) * 128 + lsel * 512 + (lane & 7) * 16 + (f == 3 ? 2048 : 0), sb + R_SLOT0 + lrow * 128 + ((lsel ^ (lane & 7)) << 4));
    __syncwarp();
    if (tid == 0) GT(c * 8 + 1);
    TSDECL;
    const float cexp = 0.08838834764831845f * 1.4426950408889634f;
    float cs = cexp;
    auto step = [&](int s, bool first) -> bool {
        bar_sync(1, 128);
        float q0[4], k0[4];
        uint4 ta;
        uint32_t zr, rl2;
        g1<ANB, SMA>(q0, k0, wq, wk, rL + R_MEMB, sbu - s, [&](int i, const uint32_t* c_) {
            if (i == 0) TS(0, c_[0]);
            if (i == -1) {
#pragma unroll
                for (int n = NAX - NXL; n < NAX; n++) { lds_fragv(wq[n], rG + R_AX + 4096 * n); lds_fragv(wk[n], rG + R_AX + 4096 * n + 512); }
                ta = lds128uv(rL + R_LT + 512 + fo * 512);
                zr = ta.w & 1; rl2 = rL | zr;
            }
            if (i == IVA) { PUT_MAX(rl2, fo) bar_arrive(15, 256); bar_arrive(GOBAR, 96); }
        });
        stsm4t(rG + R_QP, pack2(q0[0], q0[1]), pack2(q0[2], q0[3]), pack2(k0[0], k0[1]), pack2(k0[2], k0[3]));
        TS(1, FU(k0[3]));
        if (first) mbar_wait_p(sbu + R_BAR + 8 * MB_FULL0, 0);
        if (fo >= 2) {
            bar_sync(3, 256);
            uint32_t kb[4], kc[4], qa[4], qc[4];
            ldsm4(kb, ta.z + 256); ldsm4(qa, ta.z);
            ldsm4(kc, ta.z + 1280); ldsm4(qc, ta.z + 1024);
            const uint32_t k0_ = hadd2b(kb[0], kb[1]), k1_ = hadd2b(kb[2], kb[3]), k2_ = hadd2b(kc[0], kc[1]), k3_ = hadd2b(kc[2], kc[3]);
            float s0[4], s2[4];
            MMAZ(s0, qa, k0_, k1_); MMAZ(s2, qc, k2_, k3_);
            const float x = ((s0[0] + s0[2]) + (s2[0] + s2[2])) * cs, y = ((s0[1] + s0[3]) + (s2[1] + s2[3])) * cs;
            st_async2(ta.x, FU(x), FU(y), ta.y);
            TS(3, FU(y));
            sts64((ta.x ^ 0x01000000u) + (R_SLOC - R_SREM), x, y);
            sts128u(rl2 + R_STG + (fo & 1) * 512, k0_, k1_, k2_, k3_);
            bar_arrive(9, 192);
        } else {
            uint32_t qa[4][4], kx[4][4];
#pragma unroll
            for (int kk = 0; kk < KXB; kk++) ldsm4(kx[kk], (ta.w ^ (kk * 32)) + (16384 + fo * 2048));
            bar_sync(3, 256);
#pragma unroll
            for (int kk = 0; kk < 4; kk++) {
                if (kk >= KXB) ldsm4(kx[kk], (ta.w ^ (kk * 32)) + (16384 + fo * 2048));
                ldsm4(qa[kk], ta.z + kk * 1024);
            }
            float s0[4], s1[4], s2[4], s3[4];
            MMAZ(s0, qa[0], kx[0][0], kx[0][1]); MMAZ(s1, qa[0], kx[0][2], kx[0][3]);
            MMAZ(s2, qa[1], kx[1][0], kx[1][1]); MMAZ(s3, qa[1], kx[1][2], kx[1][3]);
            MMA(s0, qa[2], kx[2][0], kx[2][1]); MMA(s1, qa[2], kx[2][2], kx[2][3]);
            MMA(s2, qa[3], kx[3][0], kx[3][1]); MMA(s3, qa[3], kx[3][2], kx[3][3]);
            const float x = ((s0[0] + s0[2]) + (s2[0] + s2[2])) * cs, y = ((s0[1] + s0[3]) + (s2[1] + s2[3])) * cs;
            const float z = ((s1[0] + s1[2]) + (s3[0] + s3[2])) * cs, w = ((s1[1] + s1[3]) + (s3[1] + s3[3])) * cs;
            st_async4(ta.x, x, y, z, w, ta.y);
            TS(3, FU(w));
            sts128(rG + R_SLOC, x, y, z, w);
        }
        const uint32_t r8 = (rl2 + sbu) >> 1;
        uint32_t vt00[4], vt01[4], vt10[4], vt11[4];
        const uint32_t rV = ta.w ^ ((fo & 1) * 64), vo = (fo >> 1) * 8192;
        if (!VTA && VTP < 2) { ldsm4t(vt00, rV + vo); ldsm4t(vt10, (rV ^ 32) + vo); }
        if (!VTA && VTP < 1) { ldsm4t(vt01, rV + vo + 2048); ldsm4t(vt11, (rV ^ 32) + vo + 2048); }
        bar_sync(4, 128);
        const float2 l2 = lds64v(r8 + R_SLOC + 512), l3 = lds64v(r8 + R_SLOC + 768);
        const float4 l0 = lds128v(rL + R_SLOC), l1 = lds128v(rL + R_SLOC + 1024);
        if (VTA && VTP < 2) { ldsm4t(vt00, rV + vo); ldsm4t(vt10, (rV ^ 32) + vo); }
        if (VTA && VTP < 1) { ldsm4t(vt01, rV + vo + 2048); ldsm4t(vt11, (rV ^ 32) + vo + 2048); }

        if (s == NSEG - 1) { mbar_wait_u(sbu + R_BAR + 8 * MB_S, 1); mbar_wait_u(sbu + R_BAR + 8 * MB_V, 1); return true; }
        TS(2, FU(l3.y));
        mbar_wait_p(sbu + R_BAR + 8 * MB_S, s & 1);
        TS(4, 0);
        {
            const float2 r2 = lds64v(r8 + R_SREM + 512), r3 = lds64v(r8 + R_SREM + 768);
            const float4 r0 = lds128v(rL + R_SREM), r1 = lds128v(rL + R_SREM + 1024);
            if (VTP >= 1) PINM();
            if (VTP >= 2) { ldsm4t(vt00, rV + vo); ldsm4t(vt10, (rV ^ 32) + vo); }
            if (VTP >= 1) { ldsm4t(vt01, rV + vo + 2048); ldsm4t(vt11, (rV ^ 32) + vo + 2048); }
            float sv[10];
            sv[0] = l0.x + r0.x; sv[1] = l0.y + r0.y; sv[2] = l0.z + r0.z; sv[3] = l0.w + r0.w;
            sv[4] = l1.x + r1.x; sv[5] = l1.y + r1.y; sv[6] = l1.z + r1.z; sv[7] = l1.w + r1.w;
            sv[8] = ((l2.x + l3.x) + r2.x) + r3.x; sv[9] = ((l2.y + l3.y) + r2.y) + r3.y;
            float m = fmaxf(fmaxf(fmaxf(fmaxf(sv[8], sv[9]), sv[0]), fmaxf(fmaxf(sv[2], sv[3]), sv[1])), fmaxf(fmaxf(sv[4], sv[5]), fmaxf(sv[6], sv[7])));
            {
                const float m1 = __shfl_xor_sync(0xffffffffu, m, 1), m2 = __shfl_xor_sync(0xffffffffu, m, 2), m3 = __shfl_xor_sync(0xffffffffu, m, 3);
                m = fmaxf(fmaxf(m, m1), fmaxf(m2, m3));
            }
            TS(5, FU(m));
            const uint32_t ONE2 = 0x3f803f80u;
            float o0[4], o1[4], sm[4];
            const uint32_t pb0 = pack2(ex2(sv[0] - m), ex2(sv[1] - m)), pb1 = pack2(ex2(sv[2] - m), ex2(sv[3] - m));
            mma16816z(sm, ONE2, ONE2, ONE2, ONE2, pb0, pb1);
            MMAZ(o0, vt00, pb0, pb1); MMAZ(o1, vt10, pb0, pb1);
            const uint32_t z = (VDEP == 0 ? FU(m) : pb0) & zr;
            const uint32_t vok = mbar_test(sbu + R_BAR + 8 * MB_V + z, s & 1);
            const uint32_t rv = r8 + vok * 8;
            float2 va = lds64v(rv + R_VB - 8 + fo * 512);
            float2 vb = lds64v(rv + R_VB - 8 + fo * 512 + 256);
            float sig = __uint_as_float(lds32v_(sbu + R_MISC + 40));
            const uint32_t pb2 = pack2(ex2(sv[4] - m), ex2(sv[5] - m)), pb3 = pack2(ex2(sv[6] - m), ex2(sv[7] - m));
            mma16816(sm, ONE2, ONE2, ONE2, ONE2, pb2, pb3);
            const uint32_t pb4 = pack2(ex2(sv[8] - m), ex2(sv[9] - m));
            MMA(o0, vt01, pb2, pb3); MMA(o1, vt11, pb2, pb3);
            mma1688(sm, ONE2, ONE2, pb4);
            const float z0 = rcpf(sm[0]), z1 = rcpf(sm[1]);
#define PUT_O()                                                                                                   \
            {                                                                                                     \
                float a0[4] = {o0[0], o0[1], o0[2], o0[3]}, a1[4] = {o1[0], o1[1], o1[2], o1[3]};                 \
                mma1688(a0, FU(va.x), FU(va.y), pb4); mma1688(a1, FU(vb.x), FU(vb.y), pb4);                       \
                const float i0 = DN ? 1.f : z0 * sig, i1 = DN ? 1.f : z1 * sig;                                   \
                stsm4t(rG + R_QP, pack2(a0[0] * i0, a0[1] * i1), pack2(a0[2] * i0, a0[3] * i1), pack2(a1[0] * i0, a1[1] * i1), pack2(a1[2] * i0, a1[3] * i1)); \
            }
            PUT_O()
            asm volatile("{\n.reg .pred p;\nsetp.ne.u32 p, %0, 0;\n@p bar.arrive 8, 256;\n}" :: "r"(vok) : "memory");
            if (__builtin_expect(__any_sync(0xffffffffu, vok == 0), 0)) {
                mbar_wait_p(sbu + R_BAR + 8 * MB_V, s & 1);
                va = lds64v(r8 + R_VB + fo * 512); vb = lds64v(r8 + R_VB + fo * 512 + 256);
                sig = __uint_as_float(lds32v_(sbu + R_MISC + 40));
                PUT_O()
                bar_arrive(8, 256);
                CNT(8); CNT(128 + s);
            }
            if (DN) { sts64(r8 + R_VRED + fo * 256, z0 * sig, z1 * sig); bar_arrive(13, 256); }
            TS(6, 0);
            const float r = __uint_as_float(0x7f000000u - FU(sig));
            cs = cexp * r * (fo >= 2 ? r : 1.f);
        }
        return false;
    };
    step(0, true);
#pragma unroll 1
    for (int s = 0;; s++) {
        if (s & 1) mbar_wait_p(sbu + R_BAR + 8 * (MB_FULL0 + (((s + 1) >> 1) & 1)), ((s + 1) >> 2) & 1);
        {
            const uint32_t a = rL + R_LT + 512 + 12 + fo * 512;
            sts32(a, lds32v_(a) + ((s & 1) ? ((s & 2) ? R_SLOT0 - R_SLOT1 - 4096 : R_SLOT1 - R_SLOT0 - 4096) : 4096));
        }
        auto early = [&]() {
            SCHED(13);
#pragma unroll
            for (int i = 0; i < NAX - NXL; i++) { lds_fragv(wq[i], rG + R_AX + 4096 * i); lds_fragv(wk[i], rG + R_AX + 4096 * i + 512); }
        };
        GATHER(0, , early();, )
        if (step(s + 1, false)) break;
    }
    CNT(9);
    if (rG == sbu) GT(cc * 8 + 4);
}

__device__ __forceinline__ void rec_b(uint32_t sb, int c, uint32_t epoch) {
    const int tid = threadIdx.x - WGB * 128, lane = tid & 31, f = tid >> 5;
    uint32_t wq[16][4], wk[16][4], wo[32][4];
    const int lrow = ((lane >> 4) << 3) + (lane & 7), lsel = (lane >> 3) & 1;
    const uint32_t rL = opaque(sb + lane * 16), rW = opaque(sb + lane * 16 + f * 16384);
    const uint32_t sbu = uni(sb), fo = uni(f), cc = uni(c), po = cc & 1, ep = uni(epoch);
    {
        mbar_wait(sb + R_BAR + 8 * MB_WO, 0);
        if (c == 7 && tid == 0) GT(1426);
        const uint32_t aO = sb + R_WO + f * 16384 + lrow * 128 + ((lsel ^ (lane & 7)) << 4);
#pragma unroll
        for (int i = 0; i < 32; i++) {
            const int tile = (i >> 4) * 2 + (i & 1), kk = (i >> 1) & 7;
            ldsm4t(wo[i], (aO ^ (32 * tile)) + kk * 2048);
        }
        const float no = frag_norm2(wo);
        if (lane == 0) sts32(sb + R_MISC + 80 + f * 4, FU(no));
        __syncwarp();
        bar_sync(0, 256);
        if (tid == 0) {
            const float4 a = lds128(sb + R_MISC + 64), b = lds128(sb + R_MISC + 80);
            stg4(&g_f.norm[c], make_uint4(FU((a.x + a.y) + (a.z + a.w)), epoch, FU((b.x + b.y) + (b.z + b.w)), epoch));
        }
        __syncwarp();
#pragma unroll
        for (int i = 0; i < 32; i++) sts128u(rW + R_WO + i * 512, wo[i][0], wo[i][1], wo[i][2], wo[i][3]);
        mbar_wait(sb + R_BAR + 8 * MB_W1, 0);
        if (c == 7 && tid == 0) GT(1422);
        __syncwarp();
#pragma unroll
        for (int kk = 0; kk < 16; kk++) { const uint32_t a = sb + R_QK1 + wrow_off(kk, 2 * f + lsel); ldsm4t(wq[kk], a); ldsm4t(wk[kk], a + 32768); }
        bar_sync(13, 128);
#pragma unroll
        for (int i = 0; i < 16; i++) {
            sts128u(rW + R_QK1 + i * 1024, wq[i][0], wq[i][1], wq[i][2], wq[i][3]);
            sts128u(rW + R_QK1 + i * 1024 + 512, wk[i][0], wk[i][1], wk[i][2], wk[i][3]);
        }
        __syncwarp();
    }
    const uint64_t gx = xpage();
    const uint32_t ghi = uni((uint32_t)(gx >> 32)), glo = uni((uint32_t)gx);
    TSDECL;
#pragma unroll 1
    for (int s = 0;; s++) {
        bar_sync(2, 256);
        float q0[4], k0[4];
        g1<BNB, SMB>(q0, k0, wq, wk, rL + R_MEMB + 4096, sbu - s, [&](int i, const uint32_t* c_) {
            if (i == 0) TS(0, c_[0]);
            if (i == IV) bar_arrive(GOBAR, 96);
        });
        stsm4t(rL + fo * 1024 + R_QP + 512, pack2(q0[0], q0[1]), pack2(q0[2], q0[3]), pack2(k0[0], k0[1]), pack2(k0[2], k0[3]));
        bar_arrive(3, 256);
        TS(1, FU(k0[3]));
        const uint32_t so = aslot(s);
        uint2 lt;
        { const float2 t = lds64v(rL + R_LT); lt.x = FU(t.x); lt.y = FU(t.y); }
        const uint32_t sel = 0x3210u + (lt.x & 16) * 0x220u;
        uint32_t* pm = (uint32_t*)mkptr(((glo + acc_base(po * 4 + fo)) ^ so) + lt.x, ghi);
        uint32_t* px = (uint32_t*)mkptr(((glo + acc_base(po * 4 + fo) + slice_off(cc >> 1)) ^ so) + lt.y, ghi);
        if (s == NSEG - 1) break;
        {
            const uint32_t z = lt.x & 1;
#pragma unroll
            for (int n = NRW; n < NRW + E0 + E1 + E2 + E3; n++) {
                const int d = n - (n < NRW + T2N ? TRK + 1 : TRK);
                lds_fragv(wo[WI(n)], (d >= NRW ? or_and(rW, wo[WI(d)][0], z) : rW) + R_WO + WI(n) * 512);
            }
        }
        TS(2, wo[WI(NRW + E0 + E1 + E2 + E3 - 1)][0]);
        SCHED(4);
        bar_sync(8, 256);
        {
            float o[4][4];
            uint32_t b[4][4];
#pragma unroll
            for (int i = 0; i < (G2V == 3 ? 3 : 4); i++) ldsm4(b[i], rL + R_QP + i * 1024);
            PINM();
#pragma unroll
            for (int n = NRW + E0 + E1 + E2 + E3; n < 32; n++) lds_fragv(wo[WI(n)], rW + R_WO + WI(n) * 512);
            if (G2V == 3) { PINM(); ldsm4(b[3], rL + R_QP + 3072); }
            float p[4][4];
#define G2_STEP(o, hf, kk) _Pragma("unroll") for (int i = 0; i < 2; i++) MMAF((kk) < 2, o[((kk) & 1) * 2 + i], wo[(hf) * 16 + (kk) * 2 + i], b[(kk) >> 1][((kk) & 1) * 2], b[(kk) >> 1][((kk) & 1) * 2 + 1])
#define G2_RED(o, wl, h) const uint32_t wl = packh2((o[1][2] + o[3][2]) * nz.x, (o[1][3] + o[3][3]) * nz.y);                            \
                if ((h) && XF) asm volatile("red.relaxed.gpu.global.add.noftz.f16x2 [%0], %1;" :: "l"(px), "r"((sel & 0x4000u) ? prmt(w3, wl, 0x7632u) : HONE2) : "memory"); \
                asm volatile("red.relaxed.gpu.global.add.noftz.v4.f16x2 [%0], {%1,%2,%3,%4};" :: "l"(pm + (h) * 32),  \
                    "r"(packh2((o[0][0] + o[2][0]) * nz.x, (o[0][1] + o[2][1]) * nz.y)), "r"(packh2((o[0][2] + o[2][2]) * nz.x, (o[0][3] + o[2][3]) * nz.y)), \
                    "r"(packh2((o[1][0] + o[3][0]) * nz.x, (o[1][1] + o[3][1]) * nz.y)), "r"(prmt(wl, HONE2, sel)) : "memory")
            if (G2V == 1) SCHED(11);
#pragma unroll
            for (int kk = 0; kk < 8; kk++) { G2_STEP(o, 0, kk); }
            TS(7, b[0][0]);
            float2 nz = make_float2(1.f, 1.f);
            if (DN) { bar_sync(13, 256); nz = lds64v(((rL + sbu) >> 1) + R_VRED + fo * 256); }
            if (G2V == 0) SCHED(11);
            else {
#pragma unroll
                for (int i = 0; i < 4; i++) wo[16 + i][0] = or_and(wo[16 + i][0], FU(o[i][0]), lt.x & 1);
            }
#pragma unroll
            for (int kk = 0; kk < G2K; kk++) { G2_STEP(p, 1, kk); }
#pragma unroll
            for (int i = 0; i < NB0; i++) { lds_fragv(wq[i], rW + R_QK1 + i * 1024); lds_fragv(wk[i], rW + R_QK1 + i * 1024 + 512); }
            G2_RED(o, w3, 0);
            TS(8, w3);
            if (G2V == 0) SCHED(12);
#pragma unroll
            for (int kk = G2K; kk < 8; kk++) { G2_STEP(p, 1, kk); }
            G2_RED(p, w7, 1);
            if (!XF) asm volatile("red.relaxed.gpu.global.add.noftz.f16x2 [%0], %1;" :: "l"(px), "r"((sel & 0x4000u) ? prmt(w3, w7, 0x7632u) : HONE2) : "memory");
            TS(9, w7);
        }
        bar_arrive(5, 384);
        asm volatile("{\n.reg .pred p;\nsetp.eq.u32 p, %0, %1;\n@p mbarrier.arrive.expect_tx.shared::cta.b64 _, [%2], 1536;\n}"
                     :: "r"(rW), "r"(sbu), "r"(sbu + R_BAR + 8 * MB_S) : "memory");
        const uint32_t tb = clk32();
        TSACC();
        spin_until(tb, DB);
#pragma unroll
        for (int i = NB0; i < NBR; i++) {
            if (i == NB1) spin_until(tb, DP + DB2);
            lds_fragv(wq[i], rW + R_QK1 + i * 1024); lds_fragv(wk[i], rW + R_QK1 + i * 1024 + 512);
        }
    }
}

#undef lds_fragv
__device__ __forceinline__ void rec_first_loads(uint32_t sb, int c, const Maps& maps) {
    const uint32_t bar = sb + R_BAR;
    const int F0 = c * 64;
    mbar_expect_tx(bar + 8 * MB_W0, 65536); mbar_expect_tx(bar + 8 * MB_WO, 65536); mbar_expect_tx(bar + 8 * MB_WV, 65536);
    tma2d(sb + R_QK1, &maps.wv, F0, 0, bar + 8 * MB_WV); tma2d(sb + R_QK1 + 32768, &maps.wv, F0, 256, bar + 8 * MB_WV);
    tma2d(sb + R_T + 32768, &maps.wk, F0, 0, bar + 8 * MB_W0);
    if (!LORD) {
        for (int i = 0; i < 4; i++) tma2d(sb + R_WO + i * 16384, &maps.wo, (c & 1) * 256 + i * 64, (c >> 1) * 128, bar + 8 * MB_WO);
        tma2d(sb + R_T, &maps.wq, F0, 0, bar + 8 * MB_W0);
    }
    mbar_expect_tx(bar + 8 * MB_S, 1536);
}
__device__ __forceinline__ void rec_c(uint32_t sb, int c, const bf16* __restrict__ mem0, const Maps& maps, uint32_t epoch) {
    const int tid = threadIdx.x - WGC * 128, lane = tid & 31, u = tid >> 5;
    const uint32_t bar = sb + R_BAR;
    const int lrow = ((lane >> 4) << 3) + (lane & 7), lsel = (lane >> 3) & 1;
    const int kh = u >> 1, j = u & 1;
    uint32_t wv[32][4], mx = 0, my = 0, mz = 0;
    {
        if (u == 0) {
            sts128u(sb + lane * 16 + R_LT, slice_off(lane >> 3) + (lane & 7) * 16, 512 + lane * 4, 0, 0);
        }
        mbar_wait(bar + 8 * MB_WV, 0);
        if (c == 7 && tid == 0) GT(1425);
        if (LORD && tid == 32) {
            for (int i = 0; i < 4; i++) tma2d(sb + R_WO + i * 16384, &maps.wo, (c & 1) * 256 + i * 64, (c >> 1) * 128, bar + 8 * MB_WO);
            tma2d(sb + R_T, &maps.wq, c * 64, 0, bar + 8 * MB_W0);
        }
        __syncwarp();
#pragma unroll
        for (int kk = 0; kk < 16; kk++) {
            const uint32_t aa = sb + R_QK1 + kh * 32768 + wrow_off(kk, 4 * j + 2 * kh + lsel);
            ldsm4t(wv[kk], aa); ldsm4t(wv[16 + kk], aa ^ 32);
        }
        {
            uint32_t x = 0;
#pragma unroll
            for (int i = 0; i < 32; i++) x ^= wv[i][0];
            sts32(sb + R_MISC + 96 + u * 4, __reduce_xor_sync(0xffffffffu, x));
        }
        bar_sync(9, 128);
        if (c == 7 && tid == 0) GT(1423);
        if (tid == 0) {
            mbar_expect_tx(bar + 8 * MB_W1, 65536);
            tma2d(sb + R_QK1 + 32768, &maps.wk, c * 64, 256, bar + 8 * MB_W1); tma2d(sb + R_QK1, &maps.wq, c * 64, 256, bar + 8 * MB_W1);
        }
        __syncwarp();
        const float nv = frag_norm2(wv);
        if (lane == 0) sts32(sb + R_MISC + 64 + u * 4, FU(nv));
        __syncwarp();
        bar_arrive(0, 256);
    }
    const uint32_t rL = opaque(sb + lane * 16), rG = opaque(sb + lane * 16 + u * 1024);
    const uint32_t sbu = uni(sb), fo = uni(u), cc = uni(c), ep = uni(epoch);
    const uint64_t gx = xpage();
    const uint32_t ghi = uni((uint32_t)(gx >> 32)), glo = uni((uint32_t)gx);
    TSDECL;
    uint32_t rpb = 0x3f800000u;
    uint32_t kvq = ~ep;
    auto ring = [&](int s) {
        uint32_t n = 0;
#pragma unroll 1
        while (!__all_sync(0xffffffffu, kvq == ep)) {
            kvq = ldg_rlx(&g_f.kv[(s + 2) >> 1][cc >> 1][(rL >> 4) & 1]);
            if (++n > SPIN_LIMIT) { ABORT(6); break; }
        }
        arm_slot(sbu, (s + 2) >> 1);
    };
    if (fo == 3) { ring(-2); load_slot(sbu, cc, 0, maps); if (cc == 7 && rL == sbu) GT(1427); }
    bar_sync(5, 256);
    bar_arrive(2, 256);
    constexpr int CX = R_AX + NAX * 4096;
    static_assert(NAX + NCX <= 6, "AX");
#pragma unroll
    for (int i = 0; i < NCX; i++) {
        sts128u(rG + CX + 4096 * i, wv[i][0], wv[i][1], wv[i][2], wv[i][3]);
        sts128u(rG + CX + 4096 * i + 512, wv[16 + i][0], wv[16 + i][1], wv[16 + i][2], wv[16 + i][3]);
    }
    __syncwarp();
#pragma unroll 1
    for (int s = 0;; s++) {
        PUT_MAX(rL, 4 + fo)
        if (fo != 0) bar_arrive(15, 256);
        if (fo == 3 && !(s & 1) && s > 0 && s + 2 < NSEG) load_slot(sbu, cc, (s + 2) >> 1, maps);
#pragma unroll
        for (int i = NCX - NCL; i < NCX; i++) { lds_fragv(wv[i], rG + CX + 4096 * i); lds_fragv(wv[16 + i], rG + CX + 4096 * i + 512); }
        if (fo == 0) {
                bar_sync(15, 256);
                if (s == 0) {
                    const uint32_t* np = (const uint32_t*)&g_f.norm[0] + ((rL ^ sbu) >> 2);
                    uint4 r, q; uint32_t n = 0;
#pragma unroll 1
                    while (true) {
                        r = ldg_rlx4(np); q = ldg_rlx4(np + 128);
                        const uint2 z = ldg_rlx2(&g_f.xn[(rL ^ sbu) >> 3]);
                        if (__all_sync(0xffffffffu, r.y == ep && r.w == ep && q.y == ep && q.w == ep && z.x == ep && z.y == ep)) break;
                        if (++n > SPIN_LIMIT) { ABORT(5); break; }
                    }
                    float nv = __uint_as_float(r.x) + __uint_as_float(q.x), no = __uint_as_float(r.z) + __uint_as_float(q.z);
#pragma unroll
                    for (int o = 16; o; o >>= 1) { nv += __shfl_xor_sync(0xffffffffu, nv, o); no += __shfl_xor_sync(0xffffffffu, no, o); }
                    const int lc = ((int)(FU(nv) >> 23) + (int)(FU(no) >> 23) - 252 + 9 + 1) >> 1;
                    sts32(sbu + R_MISC + 32, 140 - lc);
                    __syncwarp();
                }
                const uint4 ma = lds128uv(rL + R_STG + 1024), mb = lds128uv(rL + R_STG + 1536);
                const uint32_t m_ = amax2b(amax2b(amax2b(ma.x, ma.y), amax2b(ma.z, ma.w)), amax2b(amax2b(mb.x, mb.y), amax2b(mb.z, mb.w)));
                const int em = (int)(__reduce_max_sync(0xffffffffu, amax2b(m_, m_ << 16) & 0x7f800000u) >> 23) + (int)(rpb >> 23) - 127;
                const int es = min(max((int)lds32v_(sbu + R_MISC + 32) - max(em, 127), -60), 60);
                sts32(sbu + R_MISC + 40, (127 + es) << 23);
                TS(4, es);
        }
        bar_sync(GOBAR, 96);
        float v0[4], v1[4];
        g1<CNB, SMC>(v0, v1, wv, wv + 16, rL + R_MEMB + (fo >> 1) * 4096, sbu - s, [&](int i, const uint32_t* c_) { if (i == 0) TS(0, c_[0]); });
        TS(1, FU(v1[3]));
        const uint32_t l16 = (rL ^ sbu) | (lds32v_(rL + R_LT + 4) & 1);
        const uint32_t r8 = sbu + (l16 >> 1);
        {
            sts128(rL + R_VRED + fo * 512, v1[0], v1[1], v1[2], v1[3]);
            const uint32_t d = r8 + R_VB + ((cc & 1) * 4 + (fo & 1) * 2 + (fo >> 1)) * 256;
            const uint32_t dr = xorv(d, 0x01000000u), br = xorv(sbu + R_BAR + 8 * MB_V, 0x01000000u);
            bar_sync(6 + (fo & 1), 64);
            const float4 a0 = lds128(rL + R_VRED + (fo ^ 2) * 512);
            const float rp = __uint_as_float(rpb);
            const uint32_t w0 = pack2((v0[0] + a0.x) * rp, (v0[1] + a0.y) * rp), w1 = pack2((v0[2] + a0.z) * rp, (v0[3] + a0.w) * rp);
            st_async2(dr, w0, w1, br);
            TS(3, w1);
            sts64(d, __uint_as_float(w0), __uint_as_float(w1));
            if (fo != 1) bar_arrive(9, 192);
            __syncwarp();
            asm volatile("{\n.reg .pred p;\nsetp.eq.u32 p, %0, %1;\n@p mbarrier.arrive.expect_tx.shared::cta.b64 _, [%2], 256;\n}"
                         :: "r"(rL), "r"(sbu), "r"(sbu + R_BAR + 8 * MB_V) : "memory");
        }
        if (fo == 1) {
            bar_sync(9, 192);
            uint8_t* dst = (uint8_t*)&g_KVf[s][cc >> 1][(cc & 1) * 256] + l16;
            const uint32_t r2 = prmt(rpb, 0, 0x3232u);
#pragma unroll
            for (int i = 0; i < 2; i++) {
                const uint4 a = lds128uv(rL + R_STG + i * 512);
                stg4(dst + i * 512, make_uint4(~hmul2b(a.x, r2), ~hmul2b(a.y, r2), ~hmul2b(a.z, r2), ~hmul2b(a.w, r2)));
                const float2 b0 = lds64v(r8 + R_VB + (cc & 1) * 1024 + i * 512), b1 = lds64v(r8 + R_VB + (cc & 1) * 1024 + i * 512 + 256);
                stg4(dst + 2048 + i * 512, make_uint4(~FU(b0.x), ~FU(b0.y), ~FU(b1.x), ~FU(b1.y)));
            }
            __syncwarp();
            if (l16 == 0) { stg_rlx(&g_f.rec[cc >> 1][cc & 1], (ep << 8) | (s + 1)); if (s == NSEG - 1) GT(1500 + cc); }
            __syncwarp();
        } else {
            if (fo == 2) {
                if (l16 < ((cc & 1) ? 128 : 256)) stg4((void*)mkptr(((glo + zero_off(cc)) ^ aslot(s + 4)) + l16, ghi), make_uint4(0, 0, 0, 0));
                __syncwarp();
            } else if (fo == 3) {
                kvq = ldg_rlx(&g_f.kv[min((s + 3) >> 1, NT - 1)][cc >> 1][(l16 >> 4) & 1]);
                if (s == 0) { ring(s); load_slot(sbu, cc, 1, maps); }
            }
        }
        if (s == NSEG - 1) break;
        auto early = [&]() {
#pragma unroll
            for (int i = 0; i < NCX - NCL; i++) { lds_fragv(wv[i], rG + CX + 4096 * i); lds_fragv(wv[16 + i], rG + CX + 4096 * i + 512); }
            if (fo == 3 && (s & 1) && s + 3 < NSEG) ring(s + 1);
        };
        GATHER(1, , early(); rpb = 0x7f000000u - lds32v_(sbu + R_MISC + 40);, bar_arrive(2, 256);)
    }
}

__device__ __forceinline__ bool cand_better(float v, int i, float bv, int bi) { return v > bv || (v == bv && i < bi); }

constexpr int G_W = 0;
constexpr int G_RING = 131072;
constexpr int G_BUF = 163840;
constexpr int G_BAR = 229376;
constexpr int G_SMEM = G_BAR + 512;
enum { GB_FULL = 0, GB_EMPTY = GB_FULL + 8, GB_KV = GB_EMPTY + 8, GB_STG = GB_KV + 2, GB_FREE = GB_STG + 2, GB_XN = GB_FREE + 2, GB_T1D, GB_P0, GB_VV, GB_KVF = GB_VV + 2, GB_VF, GB_N };
constexpr int SMEM_TOTAL = 232448;

__device__ __forceinline__ void wgmma_n128(float* d, uint64_t da, uint64_t db, int scale_d) {
    asm volatile("{\n.reg .pred p;\nsetp.ne.b32 p, %66, 0;\n"
        "wgmma.mma_async.sync.aligned.m64n128k16.f32.bf16.bf16 "
        "{%0,%1,%2,%3,%4,%5,%6,%7,%8,%9,%10,%11,%12,%13,%14,%15,%16,%17,%18,%19,%20,%21,%22,%23,%24,%25,%26,%27,%28,%29,%30,%31,"
        "%32,%33,%34,%35,%36,%37,%38,%39,%40,%41,%42,%43,%44,%45,%46,%47,%48,%49,%50,%51,%52,%53,%54,%55,%56,%57,%58,%59,%60,%61,%62,%63}, "
        "%64, %65, p, 1, 1, 0, 1;\n}"
        : "+f"(d[0]), "+f"(d[1]), "+f"(d[2]), "+f"(d[3]), "+f"(d[4]), "+f"(d[5]), "+f"(d[6]), "+f"(d[7]), "+f"(d[8]), "+f"(d[9]), "+f"(d[10]), "+f"(d[11]),
          "+f"(d[12]), "+f"(d[13]), "+f"(d[14]), "+f"(d[15]), "+f"(d[16]), "+f"(d[17]), "+f"(d[18]), "+f"(d[19]), "+f"(d[20]), "+f"(d[21]), "+f"(d[22]), "+f"(d[23]),
          "+f"(d[24]), "+f"(d[25]), "+f"(d[26]), "+f"(d[27]), "+f"(d[28]), "+f"(d[29]), "+f"(d[30]), "+f"(d[31]), "+f"(d[32]), "+f"(d[33]), "+f"(d[34]), "+f"(d[35]),
          "+f"(d[36]), "+f"(d[37]), "+f"(d[38]), "+f"(d[39]), "+f"(d[40]), "+f"(d[41]), "+f"(d[42]), "+f"(d[43]), "+f"(d[44]), "+f"(d[45]), "+f"(d[46]), "+f"(d[47]),
          "+f"(d[48]), "+f"(d[49]), "+f"(d[50]), "+f"(d[51]), "+f"(d[52]), "+f"(d[53]), "+f"(d[54]), "+f"(d[55]), "+f"(d[56]), "+f"(d[57]), "+f"(d[58]), "+f"(d[59]),
          "+f"(d[60]), "+f"(d[61]), "+f"(d[62]), "+f"(d[63])
        : "l"(da), "l"(db), "r"(scale_d));
}

__device__ __forceinline__ constexpr uint32_t slot_off(int slot) {
    return slot < 2 ? G_RING + slot * 16384 : G_BUF + (slot & 1) * 32768 + (slot < 4 ? 16384 : 0);
}
constexpr int PO = (HSPLIT / 2) & 1;
template <int NSLOT, class F>
__device__ __forceinline__ void gemm_tile(float* acc, uint32_t sb, int tile, int it, int wg, bool pass, uint32_t l0, F&& hook) {
    const uint32_t bar = sb + G_BAR;
    bar_sync(3 + wg, 256);
    int prev = 0;
#pragma unroll
    for (int k = 0; k < 4; k++) {
        const int n = tile * 4 + k, slot = NSLOT == 4 ? k : n % NSLOT;
        const uint32_t sz = sb + (((it + k) << 4) & sb & 0x3f0);
        const uint64_t da = desc_sw128(sz + slot_off(slot), 16, 1024), db0 = desc_sw128(sz + G_W, 65536, 1024);
        mbar_wait_p(bar + 8 * (GB_FULL + slot), NSLOT == 4 ? (tile & 1) : ((n / NSLOT) & 1));
        if (k == 3 && pass) bar_arrive(3 + (wg ^ 1), 256);
        asm volatile("wgmma.fence.sync.aligned;" ::: "memory");
#pragma unroll
        for (int kk = 0; kk < 4; kk++) wgmma_n128(acc, da + kk * 2, db0 + k * 1024 + kk * 128, (k | kk) != 0);
        asm volatile("wgmma.commit_group.sync.aligned;" ::: "memory");
        if (k > 0) {
            asm volatile("wgmma.wait_group.sync.aligned 1;" ::: "memory");
            mbar_arrive2_if(bar + 8 * (GB_EMPTY + prev), l0);
        }
#pragma unroll
        for (int kk = 0; kk < 4; kk++) wgmma_n128(acc, da + 512 + kk * 2, db0 + k * 1024 + 512 + kk * 128, 1);
        asm volatile("wgmma.commit_group.sync.aligned;" ::: "memory");
        if (k == 1) hook();
        prev = slot;
    }
    asm volatile("wgmma.wait_group.sync.aligned 0;" ::: "memory");
    mbar_arrive2_if(bar + 8 * (GB_EMPTY + prev), l0);
}
__device__ __forceinline__ void stage_bf16(const float* acc, uint32_t buf, float s0, float s1) {
    const int lane = threadIdx.x & 31, wq = (threadIdx.x >> 5) & 3;
    const int row = wq * 16 + (lane & 7) + ((lane >> 3) & 1) * 8;
    const uint32_t base = buf + row * 128;
#pragma unroll
    for (int j = 0; j < 16; j += 2) {
        const int ch = (j & 7) + (lane >> 4);
        stsm4(base + (j >> 3) * 8192 + ((ch ^ (row & 7)) << 4),
              pack2(acc[4 * j] * s0, acc[4 * j + 1] * s0), pack2(acc[4 * j + 2] * s1, acc[4 * j + 3] * s1),
              pack2(acc[4 * j + 4] * s0, acc[4 * j + 5] * s0), pack2(acc[4 * j + 6] * s1, acc[4 * j + 7] * s1));
    }
}

__device__ __forceinline__ void store_perm(const float* acc, bf16* dst, int ld, float s0, float s1, uint32_t m) {
#pragma unroll
    for (int i = 0; i < 4; i++) {
        const float* a = acc + 16 * i;
        stg4(dst + i * 32, make_uint4(pack2(a[0] * s0, a[1] * s0) ^ m, pack2(a[4] * s0, a[5] * s0) ^ m, pack2(a[8] * s0, a[9] * s0) ^ m, pack2(a[12] * s0, a[13] * s0) ^ m));
        stg4(dst + 8 * ld + i * 32, make_uint4(pack2(a[2] * s1, a[3] * s1) ^ m, pack2(a[6] * s1, a[7] * s1) ^ m, pack2(a[10] * s1, a[11] * s1) ^ m, pack2(a[14] * s1, a[15] * s1) ^ m));
    }
}
template <int ACC>
__device__ __forceinline__ void wgmma_rs64(float* d, const uint32_t* a, uint64_t db) {
    asm volatile("{\n.reg .pred p;\nsetp.ne.b32 p, %37, 0;\n"
        "wgmma.mma_async.sync.aligned.m64n64k16.f32.bf16.bf16 {%0,%1,%2,%3,%4,%5,%6,%7,%8,%9,%10,%11,%12,%13,%14,%15,%16,%17,%18,%19,%20,%21,%22,%23,%24,%25,%26,%27,%28,%29,%30,%31}, {%32,%33,%34,%35}, %36, p, 1, 1, 0;\n}"
        : "+f"(d[0]), "+f"(d[1]), "+f"(d[2]), "+f"(d[3]), "+f"(d[4]), "+f"(d[5]), "+f"(d[6]), "+f"(d[7]), "+f"(d[8]), "+f"(d[9]), "+f"(d[10]), "+f"(d[11]), "+f"(d[12]), "+f"(d[13]), "+f"(d[14]), "+f"(d[15]), "+f"(d[16]), "+f"(d[17]), "+f"(d[18]), "+f"(d[19]), "+f"(d[20]), "+f"(d[21]), "+f"(d[22]), "+f"(d[23]), "+f"(d[24]), "+f"(d[25]), "+f"(d[26]), "+f"(d[27]), "+f"(d[28]), "+f"(d[29]), "+f"(d[30]), "+f"(d[31])
        : "r"(a[0]), "r"(a[1]), "r"(a[2]), "r"(a[3]), "l"(db), "n"(ACC));
}
template <int ACC>
__device__ __forceinline__ void wgmma_rs128t(float* d, const uint32_t* a, uint64_t db) {
    asm volatile("{\n.reg .pred p;\nsetp.ne.b32 p, %69, 0;\n"
        "wgmma.mma_async.sync.aligned.m64n128k16.f32.bf16.bf16 {%0,%1,%2,%3,%4,%5,%6,%7,%8,%9,%10,%11,%12,%13,%14,%15,%16,%17,%18,%19,%20,%21,%22,%23,%24,%25,%26,%27,%28,%29,%30,%31,%32,%33,%34,%35,%36,%37,%38,%39,%40,%41,%42,%43,%44,%45,%46,%47,%48,%49,%50,%51,%52,%53,%54,%55,%56,%57,%58,%59,%60,%61,%62,%63}, {%64,%65,%66,%67}, %68, p, 1, 1, 1;\n}"
        : "+f"(d[0]), "+f"(d[1]), "+f"(d[2]), "+f"(d[3]), "+f"(d[4]), "+f"(d[5]), "+f"(d[6]), "+f"(d[7]), "+f"(d[8]), "+f"(d[9]), "+f"(d[10]), "+f"(d[11]), "+f"(d[12]), "+f"(d[13]), "+f"(d[14]), "+f"(d[15]), "+f"(d[16]), "+f"(d[17]), "+f"(d[18]), "+f"(d[19]), "+f"(d[20]), "+f"(d[21]), "+f"(d[22]), "+f"(d[23]), "+f"(d[24]), "+f"(d[25]), "+f"(d[26]), "+f"(d[27]), "+f"(d[28]), "+f"(d[29]), "+f"(d[30]), "+f"(d[31]), "+f"(d[32]), "+f"(d[33]), "+f"(d[34]), "+f"(d[35]), "+f"(d[36]), "+f"(d[37]), "+f"(d[38]), "+f"(d[39]), "+f"(d[40]), "+f"(d[41]), "+f"(d[42]), "+f"(d[43]), "+f"(d[44]), "+f"(d[45]), "+f"(d[46]), "+f"(d[47]), "+f"(d[48]), "+f"(d[49]), "+f"(d[50]), "+f"(d[51]), "+f"(d[52]), "+f"(d[53]), "+f"(d[54]), "+f"(d[55]), "+f"(d[56]), "+f"(d[57]), "+f"(d[58]), "+f"(d[59]), "+f"(d[60]), "+f"(d[61]), "+f"(d[62]), "+f"(d[63])
        : "r"(a[0]), "r"(a[1]), "r"(a[2]), "r"(a[3]), "l"(db), "n"(ACC));
}
__device__ __forceinline__ void attention_tile(float* acc, uint32_t sb, int tile, int h, int wg, int wq, uint32_t l0, uint32_t epoch, uint4* km, uint4* vm) {
    const uint32_t buf = sb + G_BUF + ((tile << 4) & sb & 0x3f0);
    const int lane = threadIdx.x & 31, g = lane >> 2, t = lane & 3;
    const int sg = wq >> 1, hf = wq & 1, seg = tile * 2 + sg;
    uint32_t qf[8][4];
#pragma unroll
    for (int kk = 0; kk < 8; kk++) {
        qf[kk][0] = pack2(acc[8 * kk], acc[8 * kk + 1]); qf[kk][1] = pack2(acc[8 * kk + 2], acc[8 * kk + 3]);
        qf[kk][2] = pack2(acc[8 * kk + 4], acc[8 * kk + 5]); qf[kk][3] = pack2(acc[8 * kk + 6], acc[8 * kk + 7]);
    }
    uint32_t* kvf = &g_KVf[seg][h][lane * 4];
    auto kv_valid = [&]() {
        uint32_t mn = 0xffffffffu;
#pragma unroll
        for (int i = 0; i < 4; i++) mn = min(min(min(mn, min(km[i].x, km[i].y)), min(km[i].z, km[i].w)), min(min(vm[i].x, vm[i].y), min(vm[i].z, vm[i].w)));
        return __all_sync(0xffffffffu, mn != 0);
    };
    float sc[5][4];
    auto mem_scores = [&]() {
        float sb_[4];
#pragma unroll
        for (int i = 0; i < 4; i++) { MMAF(i == 0, sc[4], qf[2 * i], ~km[i].x, ~km[i].y); MMAF(i == 0, sb_, qf[2 * i + 1], ~km[i].z, ~km[i].w); }
#pragma unroll
        for (int i = 0; i < 4; i++) sc[4][i] += sb_[i];
    };
    mbar_wait_p(sb + G_BAR + 8 * (GB_KV + wg), (tile >> 1) & 1);
    if (h == 5 && (threadIdx.x & 127) == 0 && tile < 6) GT(1750 + tile * 8 + 2);
    bool fast;
    {
        const uint64_t dk = desc_sw128(buf, 16, 1024);
        asm volatile("wgmma.fence.sync.aligned;" ::: "memory");
#pragma unroll
        for (int kk = 0; kk < 8; kk++) {
            if (kk == 0) wgmma_rs64<0>(acc, qf[kk], dk); else wgmma_rs64<1>(acc, qf[kk], dk + (kk >> 2) * 512 + (kk & 3) * 2);
        }
        asm volatile("wgmma.commit_group.sync.aligned;" ::: "memory");
        mem_scores();
        fast = kv_valid();
        asm volatile("wgmma.wait_group.sync.aligned 0;" ::: "memory");
        mbar_arrive_if(sb + G_BAR + 8 * GB_KVF, l0);
#pragma unroll
        for (int i = 0; i < 32; i++) asm volatile("" : "+f"(acc[i]) :: "memory");
#pragma unroll
        for (int b = 0; b < 4; b++)
#pragma unroll
            for (int i = 0; i < 4; i++) sc[b][i] = sg ? acc[16 + 4 * b + i] : acc[4 * b + i];
#pragma unroll
        for (int i = 0; i < 4; i++) sc[4][i] = fast ? sc[4][i] : -INFINITY;
    }
    const float cexp = 0.08838834764831845f * 1.4426950408889634f;
    const int r0 = hf * 16 + g, r1 = r0 + 8;
#pragma unroll
    for (int b = 0; b < 4; b++) {
        const int j = b * 8 + 2 * t;
        if (j > r0) sc[b][0] = -INFINITY;
        if (j + 1 > r0) sc[b][1] = -INFINITY;
        if (j > r1) sc[b][2] = -INFINITY;
        if (j + 1 > r1) sc[b][3] = -INFINITY;
    }
    float m0 = -INFINITY, m1 = -INFINITY;
#pragma unroll
    for (int b = 0; b < 5; b++) { m0 = fmaxf(m0, fmaxf(sc[b][0], sc[b][1])); m1 = fmaxf(m1, fmaxf(sc[b][2], sc[b][3])); }
    m0 = fmaxf(m0, __shfl_xor_sync(0xffffffffu, m0, 1)); m1 = fmaxf(m1, __shfl_xor_sync(0xffffffffu, m1, 1));
    m0 = fmaxf(m0, __shfl_xor_sync(0xffffffffu, m0, 2)); m1 = fmaxf(m1, __shfl_xor_sync(0xffffffffu, m1, 2));
    float z0 = 0.f, z1 = 0.f;
    uint32_t p0, p1;
    {
        const float c0 = -m0 * cexp, c1 = -m1 * cexp;
        uint32_t pf[5][2];
#pragma unroll
        for (int b = 0; b < 5; b++) {
            pf[b][0] = pack2(ex2(fmaf(sc[b][0], cexp, c0)), ex2(fmaf(sc[b][1], cexp, c0)));
            pf[b][1] = pack2(ex2(fmaf(sc[b][2], cexp, c1)), ex2(fmaf(sc[b][3], cexp, c1)));
        }
        p0 = pf[4][0]; p1 = pf[4][1];
        uint32_t pa[4][4];
#pragma unroll
        for (int kk = 0; kk < 4; kk++)
#pragma unroll
            for (int i = 0; i < 4; i++) pa[kk][i] = (kk >> 1) == sg ? pf[(kk & 1) * 2 + (i >> 1)][i & 1] : 0u;
        const uint64_t dv = desc_sw128(buf + 32768, 8192, 1024);
        mbar_wait_p(sb + G_BAR + 8 * (GB_VV + wg), (tile >> 1) & 1);
        asm volatile("wgmma.fence.sync.aligned;" ::: "memory");
#pragma unroll
        for (int kk = 0; kk < 4; kk++) { if (kk == 0) wgmma_rs128t<0>(acc, pa[kk], dv); else wgmma_rs128t<1>(acc, pa[kk], dv + kk * 128); }
        asm volatile("wgmma.commit_group.sync.aligned;" ::: "memory");
#pragma unroll
        for (int b = 0; b < 5; b++) { z0 += bf_lo(pf[b][0]) + bf_hi(pf[b][0]); z1 += bf_lo(pf[b][1]) + bf_hi(pf[b][1]); }
        asm volatile("wgmma.wait_group.sync.aligned 0;" ::: "memory");
#pragma unroll
        for (int i = 0; i < 64; i++) asm volatile("" : "+f"(acc[i]) :: "memory");
    }
    mbar_arrive_if(sb + G_BAR + 8 * GB_VF, l0);
    if (h == 5 && (threadIdx.x & 127) == 0 && tile < 6) GT(1750 + tile * 8 + 3);
    if (!fast) {
        wait_rec(&g_f.rec[h][0], epoch, seg + 1);
        if (seg == 63 && (threadIdx.x & 63) == 0) GT(1570 + h);
        uint32_t n = 0;
#pragma unroll 1
        do {
#pragma unroll
            for (int i = 0; i < 4; i++) { km[i] = ldg_rlx4(kvf + i * 128); vm[i] = ldg_rlx4(kvf + 512 + i * 128); }
            if (++n > SPIN_LIMIT) { ABORT(4); break; }
        } while (!kv_valid());
        mem_scores();
        float n0 = fmaxf(sc[4][0], sc[4][1]), n1 = fmaxf(sc[4][2], sc[4][3]);
        n0 = fmaxf(n0, __shfl_xor_sync(0xffffffffu, n0, 1)); n1 = fmaxf(n1, __shfl_xor_sync(0xffffffffu, n1, 1));
        n0 = fmaxf(n0, __shfl_xor_sync(0xffffffffu, n0, 2)); n1 = fmaxf(n1, __shfl_xor_sync(0xffffffffu, n1, 2));
        n0 = fmaxf(n0, m0); n1 = fmaxf(n1, m1);
        const float a0 = ex2((m0 - n0) * cexp), a1 = ex2((m1 - n1) * cexp);
        const float c0 = -n0 * cexp, c1 = -n1 * cexp;
        p0 = pack2(ex2(fmaf(sc[4][0], cexp, c0)), ex2(fmaf(sc[4][1], cexp, c0)));
        p1 = pack2(ex2(fmaf(sc[4][2], cexp, c1)), ex2(fmaf(sc[4][3], cexp, c1)));
        z0 = fmaf(z0, a0, bf_lo(p0) + bf_hi(p0)); z1 = fmaf(z1, a1, bf_lo(p1) + bf_hi(p1));
#pragma unroll
        for (int j = 0; j < 16; j++) { float* o = acc + 4 * j; o[0] *= a0; o[1] *= a0; o[2] *= a1; o[3] *= a1; }
    }
    if (h == 5 && (threadIdx.x & 127) == 0 && tile < 6) GT(1750 + tile * 8 + 4);
    if (hf) bar_arrive(5 + wg * 2 + sg, 64);
#pragma unroll
    for (int i = 0; i < 4; i++) {
        mma1688(acc + 16 * i, p0, p1, ~vm[i].x); mma1688(acc + 16 * i + 4, p0, p1, ~vm[i].y);
        mma1688(acc + 16 * i + 8, p0, p1, ~vm[i].z); mma1688(acc + 16 * i + 12, p0, p1, ~vm[i].w);
    }
    z0 += __shfl_xor_sync(0xffffffffu, z0, 1); z1 += __shfl_xor_sync(0xffffffffu, z1, 1);
    z0 += __shfl_xor_sync(0xffffffffu, z0, 2); z1 += __shfl_xor_sync(0xffffffffu, z1, 2);
    if (h == 5 && (threadIdx.x & 127) == 0 && tile < 6) GT(1750 + tile * 8 + 5);
    if (tile >= 2) mbar_wait_p(sb + G_BAR + 8 * (GB_FREE + wg), ((tile >> 1) - 1 + PO) & 1);
    store_perm(acc, g_O + (size_t)(tile * 64 + wq * 16 + g) * HD + h * 128 + t * 8, HD, rcpf(z0), rcpf(z1), 0);
    mbar_arrive(sb + G_BAR + 8 * (GB_STG + wg));
    if (!hf) {
        bar_sync(5 + wg * 2 + sg, 64);
#pragma unroll
        for (int i = 0; i < 8; i++) stg4_h(kvf + i * 128, make_uint4(0, 0, 0, 0), pol_ef(3));
    }
}

constexpr int NWK = FF / 32;
constexpr int F_WG = 0, F_WU = 32768, F_WD = 65536, F_RED = 98304, F_ACT = F_RED + 8192, F_SEL = F_ACT + 256;
__device__ __noinline__ void ffn_phase(const Maps& maps, bf16* __restrict__ out) {
    extern __shared__ __align__(1024) uint8_t smem[];
    const uint32_t sb = smem_u32(smem);
    const int c = ((volatile int*)(smem + SH_OFF))[8];
    const uint32_t epoch = ((volatile uint32_t*)(smem + SH_OFF))[9];
    const int tid = threadIdx.x;
    const bool worker = c < NWK;
    bar_sync(0, 384);
    const uint32_t mb = sb + R_BAR + 8 * MB_W0;
    if (tid == 352 && worker) {
        if (FFW) __nanosleep(FFW);
        asm volatile("fence.proxy.async.shared::cta;" ::: "memory");
        mbar_expect_tx(mb, 98304);
#pragma unroll 1
        for (int j = 0; j < 6; j++) {
            if (j < 4) tma2d_h(sb + j * 16384, j < 2 ? &maps.wg : &maps.wu, c * 32, (j & 1) * 256, mb, pol_ef(5));
            else for (int i = 0; i < 4; i++) tma2d_h(sb + F_WD + ((j - 4) * 4 + i) * 4096, &maps.wd, ((j - 4) * 4 + i) * 64, c * 32, mb, pol_ef(5));
            if (FFS) __nanosleep(FFS);
        }
    }
    int p0 = -1, p1 = -1;
    float pb = 0.f;
#pragma unroll 1
    for (int pass = 0; pass < 2; pass++) {
        if (tid < 32) {
            const uint32_t tag = epoch & 0xfffffu;
            uint4 r[4]; uint32_t n = 0;
            const int t3 = tid + 96 < NFW ? tid + 96 : tid;
#pragma unroll 1
            while (true) {
                bool ok = true;
#pragma unroll
                for (int i = 0; i < 4; i++) r[i] = ldg_rlx4((const uint32_t*)&g_f.cand[pass][i < 3 ? tid + 32 * i : t3]);
#pragma unroll
                for (int i = 0; i < 4; i++) ok = ok && (r[i].y >> 12) == tag && (r[i].w >> 12) == tag;
                if (__all_sync(0xffffffffu, ok)) break;
                if (pass == 0) __nanosleep(100);
                if (++n > SPIN_LIMIT) { ABORT(7); break; }
            }
            bool chg = pass == 0;
#pragma unroll
            for (int i = 0; i < 4; i++) {
                const int j0 = r[i].y & 4095, j1 = r[i].w & 4095;
                chg = chg || (j0 != p0 && cand_better(__uint_as_float(r[i].x), j0, pb, p1)) || (j1 != p0 && cand_better(__uint_as_float(r[i].z), j1, pb, p1));
            }
            int* sel = (int*)(smem + F_SEL);
            if (__any_sync(0xffffffffu, chg)) {
                float b0 = __uint_as_float(r[0].x), b1 = __uint_as_float(r[0].z); int i0 = r[0].y & 4095, i1 = r[0].w & 4095;
#pragma unroll
                for (int i = 1; i < 9; i++) {
                    float c0, c1; int j0, j1;
                    if (i < 4) { c0 = __uint_as_float(r[i].x); c1 = __uint_as_float(r[i].z); j0 = r[i].y & 4095; j1 = r[i].w & 4095; }
                    else {
                        const int o = 1 << (i - 4);
                        c0 = __shfl_xor_sync(0xffffffffu, b0, o); c1 = __shfl_xor_sync(0xffffffffu, b1, o);
                        j0 = __shfl_xor_sync(0xffffffffu, i0, o); j1 = __shfl_xor_sync(0xffffffffu, i1, o);
                    }
                    if (i != 3 || t3 != tid) {
                        if (cand_better(c0, j0, b0, i0)) {
                            if (cand_better(c1, j1, b0, i0)) { b1 = c1; i1 = j1; } else { b1 = b0; i1 = i0; }
                            b0 = c0; i0 = j0;
                        } else if (cand_better(c0, j0, b1, i1)) { b1 = c0; i1 = j0; }
                    }
                }
                n = 0;
#pragma unroll 1
                while (!__all_sync(0xffffffffu, (ldg_rlx(&g_f.rows[pass][tid]) == epoch) & (ldg_rlx(&g_f.rows[pass][tid + 32]) == epoch) &
                                                   (ldg_rlx(&g_f.rows[pass][tid + 64]) == epoch) & (ldg_rlx(&g_f.rows[pass][t3]) == epoch))) { if (++n > SPIN_LIMIT) { ABORT(7); break; } }
                if (tid == 0) { sel[0] = min(i0, SQ - 1); sel[1] = min(i1, SQ - 1); ((float*)sel)[2] = b0; ((float*)sel)[3] = b1; }
            }
            if (pass && tid == 0 && c == 3) GT(1440);
        }
        bar_sync(0, 384);
        const int t0 = ((int*)(smem + F_SEL))[0], t1 = ((int*)(smem + F_SEL))[1];
        if (c == 3 && tid == 0 && pass == 0) GT(1430);
        if (t0 == p0 && t1 == p1) break;
        pb = ((float*)(smem + F_SEL))[3];
        const uint32_t ytag = epoch * 2 + pass + 1;
        if (worker) {
            const int lane = tid & 31, w = tid >> 5, g = lane >> 2, t = lane & 3;
            const int lrow = ((lane >> 4) << 3) + (lane & 7), lsel = (lane >> 3) & 1;
            float2* red = (float2*)(smem + F_RED);
            if (w < 8) {
                const uint32_t* xp = (const uint32_t*)(g_hn + (size_t)((g & 1) ? t1 : t0) * DM) + w * 32 + t;
                uint32_t xb[8];
#pragma unroll
                for (int i = 0; i < 8; i++) xb[i] = __ldcg(xp + i * 4);
                mbar_wait(mb, 1);
                if (c == 3 && tid == 0 && pass == 0) GT(1431);
                float d[4][4];
#pragma unroll
                for (int kk = 0; kk < 4; kk++) {
                    const int row = w * 64 + kk * 16 + lrow;
#pragma unroll
                    for (int m = 0; m < 4; m++) {
                        uint32_t a[4];
                        ldsm4t(a, sb + (m >> 1) * F_WU + row * 64 + ((((m & 1) * 2 + lsel) ^ ((row >> 1) & 3)) << 4));
                        MMAF(kk == 0, d[m], a, xb[2 * kk], xb[2 * kk + 1]);
                    }
                }
                const float e0 = t == 0 ? d[0][0] : (t == 1 ? d[1][0] : (t == 2 ? d[2][0] : d[3][0])), e1 = t == 0 ? d[0][1] : (t == 1 ? d[1][1] : (t == 2 ? d[2][1] : d[3][1]));
                const float e2 = t == 0 ? d[0][2] : (t == 1 ? d[1][2] : (t == 2 ? d[2][2] : d[3][2])), e3 = t == 0 ? d[0][3] : (t == 1 ? d[1][3] : (t == 2 ? d[2][3] : d[3][3]));
                red[w * 64 + t * 16 + g] = make_float2(e0, e1); red[w * 64 + t * 16 + g + 8] = make_float2(e2, e3);
            }
            bar_sync(0, 384);
            if (tid < 64) {
                const float* r = (const float*)red + tid;
                float gsum = 0.f, usum = 0.f;
#pragma unroll
                for (int kg = 0; kg < 8; kg++) { gsum += r[kg * 128]; usum += r[kg * 128 + 64]; }
                gsum = rbf(gsum); usum = rbf(usum);
                const float sg = rbf(gsum / (1.f + __expf(-gsum)));
                ((bf16*)(smem + F_ACT))[(tid & 1) * 32 + (tid >> 1)] = __float2bfloat16_rn(sg * usum);
            }
            bar_sync(0, 384);
            if (w < 8) {
                const uint32_t* ap = (const uint32_t*)(smem + F_ACT) + (g & 1) * 16 + t;
                float d[4][4];
#pragma unroll
                for (int kk = 0; kk < 2; kk++) {
                    const uint32_t b0 = ap[kk * 8], b1 = ap[kk * 8 + 4];
#pragma unroll
                    for (int m = 0; m < 4; m++) {
                        uint32_t a[4];
                        ldsm4t(a, sb + F_WD + w * 4096 + (kk * 16 + lrow) * 128 + (((m * 2 + lsel) ^ (lane & 7)) << 4));
                        MMAF(kk == 0, d[m], a, b0, b1);
                    }
                }
                const float e0 = t == 0 ? d[0][0] : (t == 1 ? d[1][0] : (t == 2 ? d[2][0] : d[3][0])), e1 = t == 0 ? d[0][1] : (t == 1 ? d[1][1] : (t == 2 ? d[2][1] : d[3][1]));
                const float e2 = t == 0 ? d[0][2] : (t == 1 ? d[1][2] : (t == 2 ? d[2][2] : d[3][2])), e3 = t == 0 ? d[0][3] : (t == 1 ? d[1][3] : (t == 2 ? d[2][3] : d[3][3]));
                uint4* yp = &g_yp[pass][c][w * 64 + t * 16 + g];
                stg4(yp, make_uint4(FU(e0), ytag, FU(e1), ytag)); stg4(yp + 8, make_uint4(FU(e2), ytag, FU(e3), ytag));
            }
            if (c == 3 && tid == 0 && pass == 0) GT(1432);
        } else {
            const int j = tid & 63, part = tid >> 6, col = (c - NWK) * 64 + j;
            const int tok = part ? t1 : t0, old = part ? p1 : p0;
            float hv = 0.f, nv = 0.f;
            if (part < 2) {
                hv = __bfloat162float(__ldcg(g_h + (size_t)tok * DM + col)); nv = __bfloat162float(__ldcg(g_hn + (size_t)tok * DM + col));
                if (old >= 0 && old != t0 && old != t1)
                    out[(size_t)old * DM + col] = __float2bfloat16_rn(__bfloat162float(__ldcg(g_h + (size_t)old * DM + col)) + __bfloat162float(__ldcg(g_hn + (size_t)old * DM + col)));
            }
            float s0 = 0.f, s1 = 0.f;
            uint4 v[10]; uint32_t n = 0;
            bool ok;
#pragma unroll 1
            do {
                ok = true;
#pragma unroll
                for (int i = 0; i < 10; i++) {
                    const int src = part + 6 * i;
                    v[i] = src < NWK ? ldg_rlx4((const uint32_t*)&g_yp[pass][src][col]) : make_uint4(0, ytag, 0, ytag);
                }
#pragma unroll
                for (int i = 0; i < 10; i++) ok = ok && v[i].y == ytag && v[i].w == ytag;
                if (!ok) __nanosleep(100);
                if (++n > SPIN_LIMIT) { ABORT(7); break; }
            } while (!ok);
#pragma unroll
            for (int i = 0; i < 10; i++) { s0 += __uint_as_float(v[i].x); s1 += __uint_as_float(v[i].z); }
            float2* red = (float2*)(smem + F_RED);
            red[part * 64 + j] = make_float2(s0, s1);
            bar_sync(0, 384);
            if (part < 2) {
                float y = 0.f;
#pragma unroll
                for (int i = 0; i < 6; i++) y += ((const float*)red)[(i * 64 + j) * 2 + part];
                const float rs = rbf(1.f / (1.f + __expf(-((float*)(smem + F_SEL))[2 + part])));
                out[(size_t)tok * DM + col] = __float2bfloat16_rn(hv + rbf(nv + rbf(rbf(y) * rs)));
            }
            if (tid == 0 && pass == 0 && c == NWK) GT(1434);
        }
        p0 = t0; p1 = t1;
        if (c == 3 && tid == 0 && pass == 0) GT(1433);
        bar_sync(0, 384);
    }
}

__device__ __forceinline__ void g_consumer(uint32_t sb_, int g_, int wg_, uint32_t epoch) {
    const uint32_t sb = uni(sb_);
    const int g = uni(g_), wg = uni(wg_), wq = uni((threadIdx.x >> 5) & 3);
    const uint32_t l0 = opaque((threadIdx.x & 31) == 0);
    const uint32_t bar = sb + G_BAR, buf = sb + G_BUF + wg * 32768;
    const int lane = threadIdx.x & 31;
    float acc[64];
    if (wg == 1) bar_arrive(3, 256);
    const int n1 = g < 32 ? HSPLIT / 2 : NT - HSPLIT / 2;
#pragma unroll 1
    for (int i = 0; i < n1; i++) {
        gemm_tile<4>(acc, sb, wg, i, wg, true, l0, []() {});
        if (threadIdx.x == 0 && i == 0) GT((64 + g) * 8 + 1);
        if (threadIdx.x == 128 && i == 3) GT((64 + g) * 8 + 2);
        if (i > 0) mbar_wait_p(bar + 8 * (GB_FREE + wg), (i - 1) & 1);
        stage_bf16(acc, buf, 1.f, 1.f);
        asm volatile("fence.proxy.async.shared::cta;" ::: "memory");
        mbar_arrive(bar + 8 * (GB_STG + wg));
    }
    if (threadIdx.x == 128) GT((64 + g) * 8 + 3);
    if (g < 32) {
#pragma unroll 1
        for (int i = 0; i < NT / 2; i++) {
            const int tile = 2 * i + wg;
            const uint2 rec = ldg_rlx2(&g_f.rec[g][0]);
            uint4 km[4], vm[4];
            gemm_tile<4>(acc, sb, tile, i, wg, tile != NT - 1, l0, [&]() {
                const uint32_t seg = tile * 2 + (wq >> 1);
                const uint32_t* kvf = &g_KVf[seg][g][lane * 4];
                const bool early = (rec.x >> 8) == epoch && (rec.y >> 8) == epoch && (rec.x & 255) > seg && (rec.y & 255) > seg;
#pragma unroll
                for (int j = 0; j < 4; j++) { km[j] = ldg_rlx4_if(kvf + j * 128, early); vm[j] = ldg_rlx4_if(kvf + 512 + j * 128, early); }
            });
            if (threadIdx.x == 0 && i == 0) GT((64 + g) * 8 + 4);
            if (threadIdx.x == 128 && i == 3) GT((64 + g) * 8 + 5);
            if (g == 5 && (threadIdx.x & 127) == 0 && tile < 6) GT(1750 + tile * 8 + 1);
            attention_tile(acc, sb, tile, g, wg, wq, l0, epoch, km, vm);
            if (g == 5 && (threadIdx.x & 127) == 0 && tile < 6) GT(1750 + tile * 8 + 6);
        }
    } else {
#pragma unroll 1
        for (int i = 0; i < NT / 2; i++) {
            const int tile = 2 * i + wg;
            gemm_tile<NS3>(acc, sb, tile, i, wg, tile != NT - 1, l0, []() {});
            if (threadIdx.x == 0 && i == 0) GT((64 + g) * 8 + 4);
            if (threadIdx.x == 128 && i == 3) GT((64 + g) * 8 + 5);
            mbar_wait_p(bar + 8 * (GB_FREE + wg), (i - 1 + PO) & 1);
            store_perm(acc, g_P + (size_t)(((g - 32) >> 2) * SQ + tile * 64 + wq * 16 + (lane >> 2)) * DM + ((g - 32) & 3) * 128 + (lane & 3) * 8, DM, 1.f, 1.f, 0xffffffffu);
            mbar_arrive(bar + 8 * (GB_STG + wg));
        }
    }
}

__device__ __forceinline__ void load_w(uint32_t sb, const CUtensorMap* tm, int col, int k) {
    tma2d_h(sb + G_W + k * 16384, tm, col, k * 128, sb + G_BAR + 8 * (GB_FULL + k), pol_ef(5));
    tma2d_h(sb + G_W + 65536 + k * 16384, tm, col + 64, k * 128, sb + G_BAR + 8 * (GB_FULL + k), pol_ef(5));
}

__device__ __forceinline__ void rbf2(float& a, float& b) { uint32_t w = pack2(a, b); a = bf_lo(w); b = bf_hi(w); }
__device__ __forceinline__ void warp_sum2(float& a, float& b) {
#pragma unroll
    for (int o = 16; o; o >>= 1) { float c = __shfl_xor_sync(0xffffffffu, a, o), d = __shfl_xor_sync(0xffffffffu, b, o); a += c; b += d; }
}
__device__ __forceinline__ float sum16(const float* v) {
    return (((v[0] + v[1]) + (v[2] + v[3])) + ((v[4] + v[5]) + (v[6] + v[7]))) + (((v[8] + v[9]) + (v[10] + v[11])) + ((v[12] + v[13]) + (v[14] + v[15])));
}
__device__ __forceinline__ void ln_row2(float* v, float* u) {
    float sv = sum16(v), su = sum16(u);
    warp_sum2(sv, su);
    const float mv = sv * (1.f / DM), mu = su * (1.f / DM);
    float qv = 0.f, qu = 0.f, qv2 = 0.f, qu2 = 0.f;
#pragma unroll
    for (int i = 0; i < 16; i += 2) {
        float d0 = v[i] - mv, d1 = v[i + 1] - mv, e0 = u[i] - mu, e1 = u[i + 1] - mu;
        qv = fmaf(d0, d0, qv); qv2 = fmaf(d1, d1, qv2); qu = fmaf(e0, e0, qu); qu2 = fmaf(e1, e1, qu2);
    }
    qv += qv2; qu += qu2;
    warp_sum2(qv, qu);
    const float rv = rbf(mv), ru = rbf(mu);
    const float iv = __frcp_rn(rbf(sqrtf(rbf(rbf(qv * (1.f / DM)) + 1e-5f)))), iu = __frcp_rn(rbf(sqrtf(rbf(rbf(qu * (1.f / DM)) + 1e-5f))));
#pragma unroll
    for (int i = 0; i < 16; i += 2) {
        float a = v[i] - rv, b = v[i + 1] - rv, c = u[i] - ru, d = u[i + 1] - ru;
        rbf2(a, b); rbf2(c, d);
        a *= iv; b *= iv; c *= iu; d *= iu;
        rbf2(a, b); rbf2(c, d);
        v[i] = a; v[i + 1] = b; u[i] = c; u[i + 1] = d;
    }
}

__device__ __forceinline__ void ln_row1(float* v) {
    const float pv = __shfl_sync(0xffffffffu, v[0], 0);
    float sv = 0.f, sv2 = 0.f, qv = 0.f, qv2 = 0.f;
#pragma unroll
    for (int i = 0; i < 16; i += 2) { const float d0 = v[i] - pv, d1 = v[i + 1] - pv; sv += d0; sv2 += d1; qv = fmaf(d0, d0, qv); qv2 = fmaf(d1, d1, qv2); }
    sv += sv2; qv += qv2;
    warp_sum2(sv, qv);
    const float dm = sv * (1.f / DM), mv = pv + dm;
    qv = fmaxf(fmaf(-dm, sv, qv), 0.f);
    const float rv = rbf(mv);
    float sq, iv;
    asm("sqrt.approx.f32 %0, %1;" : "=f"(sq) : "f"(rbf(rbf(qv * (1.f / DM)) + 1e-5f)));
    asm("rcp.approx.f32 %0, %1;" : "=f"(iv) : "f"(rbf(sq)));
#pragma unroll
    for (int i = 0; i < 16; i += 2) {
        float a = v[i] - rv, b = v[i + 1] - rv;
        rbf2(a, b);
        a *= iv; b *= iv;
        rbf2(a, b);
        v[i] = a; v[i + 1] = b;
    }
}
constexpr int FSPLIT = 28;
__device__ __forceinline__ int fin_row(int id, int i) {
    if (id < 64) { const int tile = i < FSPLIT / 2 ? 2 * i : i + FSPLIT / 2; return tile < NT ? tile * 64 + id : -1; }
    const int j = id - 64 + i * 48;
    return j < FSPLIT * 32 ? (j >> 6) * 128 + 64 + (j & 63) : -1;
}
__device__ __forceinline__ void finalizer(int id, const bf16* __restrict__ x, const bf16* __restrict__ wr, bf16* __restrict__ out, uint32_t epoch, const bf16* pf) {
    const int lane = threadIdx.x & 31;
    float b0 = -INFINITY, b1 = -INFINITY; int i0 = 0x7fffffff, i1 = 0x7fffffff;
    const uint32_t tag = (epoch & 0xfffffu) << 12;
    uint32_t fl = ~epoch;
    int row = fin_row(id, 0);
    const uint4 ra = *(const uint4*)(wr + lane * 8), rb = *(const uint4*)(wr + 256 + lane * 8);
    uint4 xa = *(const uint4*)(x + (size_t)row * DM + lane * 8), xb = *(const uint4*)(x + (size_t)row * DM + lane * 8 + 256);
#pragma unroll 1
    for (int it = 0; row >= 0; it++) {
        const int tile = row >> 6, nxt = fin_row(id, it + 1);
        const size_t o0 = (size_t)row * DM + lane * 8;
        uint32_t n = 0;
#pragma unroll 1
        while (!__all_sync(0xffffffffu, fl == epoch)) {
            if (n && tile < NT - 1) __nanosleep(it ? 64 : 1000);
            fl = ldg_rlx(&g_f.p[tile][lane]);
            if (++n > SPIN_LIMIT) { ABORT(12); break; }
        }
        if (tile == NT - 1 && id == 63 && lane == 0) GT(1438);
        if ((id == 63 || id == 3 || id == 70) && lane == 0) GT(1800 + (id == 3) * 32 + tile);
        if (PFF && pf && lane == 0 && (unsigned)(it - PFF) < 7u)
            asm volatile("cp.async.bulk.prefetch.L2.global [%0], %1;" :: "l"(pf + (size_t)((id & 15) * 7 + it - PFF) * 8192), "r"(16384) : "memory");
        float v[16];
        {
            uint4 pa[8][2];
            n = 0;
#pragma unroll 1
            while (true) {
#pragma unroll
                for (int k = 0; k < 8; k++) {
                    pa[k][0] = ldg4_h(g_P + (size_t)k * SQ * DM + o0, pol_ef(2));
                    pa[k][1] = ldg4_h(g_P + (size_t)k * SQ * DM + o0 + 256, pol_ef(2));
                }
                fl = ldg_rlx(&g_f.p[max(nxt, 0) >> 6][lane]);
                uint32_t mn = 0xffffffffu;
#pragma unroll
                for (int k = 0; k < 8; k++) mn = min(min(min(mn, min(pa[k][0].x, pa[k][0].y)), min(pa[k][0].z, pa[k][0].w)), min(min(pa[k][1].x, pa[k][1].y), min(pa[k][1].z, pa[k][1].w)));
                if (__all_sync(0xffffffffu, mn != 0)) break;
                if (++n > SPIN_LIMIT) { ABORT(11); break; }
            }
            if (tile == NT - 1 && id == 63 && lane == 0) GT(1443);
#pragma unroll
            for (int j = 0; j < 2; j++) {
#pragma unroll
                for (int i = 0; i < 4; i++) {
                    uint32_t w[8];
#pragma unroll
                    for (int k = 0; k < 8; k++) w[k] = ~(i == 0 ? pa[k][j].x : (i == 1 ? pa[k][j].y : (i == 2 ? pa[k][j].z : pa[k][j].w)));
                    v[j * 8 + 2 * i] = ((bf_lo(w[0]) + bf_lo(w[1])) + (bf_lo(w[2]) + bf_lo(w[3]))) + ((bf_lo(w[4]) + bf_lo(w[5])) + (bf_lo(w[6]) + bf_lo(w[7])));
                    v[j * 8 + 2 * i + 1] = ((bf_hi(w[0]) + bf_hi(w[1])) + (bf_hi(w[2]) + bf_hi(w[3]))) + ((bf_hi(w[4]) + bf_hi(w[5])) + (bf_hi(w[6]) + bf_hi(w[7])));
                }
            }
        }
        uint32_t hw[8];
        {
            const uint32_t xw[8] = {xa.x, xa.y, xa.z, xa.w, xb.x, xb.y, xb.z, xb.w};
            uint32_t aw[8];
#pragma unroll
            for (int i = 0; i < 8; i++) aw[i] = pack2(v[2 * i], v[2 * i + 1]);
#pragma unroll
            for (int d = 1; d <= 2; d++) {
                const bool up = lane & d;
#pragma unroll
                for (int i = 0; i < 8; i++) {
                    if (!(i & d)) {
                        const uint32_t r = __shfl_xor_sync(0xffffffffu, up ? aw[i] : aw[i | d], d);
                        if (up) aw[i] = r; else aw[i | d] = r;
                    }
                }
            }
#pragma unroll
            for (int i = 0; i < 8; i++) {
                hw[i] = pack2(bf_lo(aw[i]) + bf_lo(xw[i]), bf_hi(aw[i]) + bf_hi(xw[i]));
                v[2 * i] = bf_lo(hw[i]); v[2 * i + 1] = bf_hi(hw[i]);
            }
        }
        xa = *(const uint4*)(x + (size_t)max(nxt, 0) * DM + lane * 8); xb = *(const uint4*)(x + (size_t)max(nxt, 0) * DM + lane * 8 + 256);
        ln_row1(v);
        float r0 = 0.f, r1 = 0.f;
        {
            const uint32_t ww[8] = {ra.x, ra.y, ra.z, ra.w, rb.x, rb.y, rb.z, rb.w};
#pragma unroll
            for (int i = 0; i < 8; i++) { r0 = fmaf(v[2 * i], bf_lo(ww[i]), r0); r1 = fmaf(v[2 * i + 1], bf_hi(ww[i]), r1); }
        }
        r0 += r1;
#pragma unroll
        for (int o = 16; o; o >>= 1) r0 += __shfl_xor_sync(0xffffffffu, r0, o);
        r0 = rbf(r0);
        if (cand_better(r0, row, b0, i0)) { b1 = b0; i1 = i0; b0 = r0; i0 = row; }
        else if (cand_better(r0, row, b1, i1)) { b1 = r0; i1 = row; }
        if (tile == NT - 1 && id == 63 && lane == 0) GT(1439);
        const bool keep = i0 == row || i1 == row || i1 >= SQ || row == SQ - 1;
        const bool last = nxt < 0, spec = tile < SPEC_TILES && (last || (nxt >> 6) >= SPEC_TILES);
        const bool pub = (lane == 0 && spec) || (lane == 1 && last);
        if (pub)
            asm volatile("st.relaxed.gpu.global.v4.b32 [%0], {%1,%2,%3,%4};" :: "l"(&g_f.cand[lane][id]),
                         "r"(FU(b0)), "r"(tag | (uint32_t)min(i0, 4095)), "r"(FU(b1)), "r"(tag | (uint32_t)min(i1, 4095)) : "memory");
#pragma unroll
        for (int j = 0; j < 2; j++) {
            const uint32_t* hh = hw + j * 4; const float* nn = v + j * 8;
            stg4_h(out + o0 + j * 256, make_uint4(pack2(bf_lo(hh[0]) + nn[0], bf_hi(hh[0]) + nn[1]), pack2(bf_lo(hh[1]) + nn[2], bf_hi(hh[1]) + nn[3]),
                                                  pack2(bf_lo(hh[2]) + nn[4], bf_hi(hh[2]) + nn[5]), pack2(bf_lo(hh[3]) + nn[6], bf_hi(hh[3]) + nn[7])), pol_ef(4));
            if (keep) {
                *(uint4*)(g_h + o0 + j * 256) = make_uint4(hh[0], hh[1], hh[2], hh[3]);
                *(uint4*)(g_hn + o0 + j * 256) = make_uint4(pack2(nn[0], nn[1]), pack2(nn[2], nn[3]), pack2(nn[4], nn[5]), pack2(nn[6], nn[7]));
            }
        }
        if (keep) { __threadfence(); __syncwarp(); }
        if (pub) stg_rlx(&g_f.rows[lane][id], epoch);
        if (tile >= LLT) {
#pragma unroll
            for (int k = 0; k < 8; k++) { stg4(g_P + (size_t)k * SQ * DM + o0, make_uint4(0, 0, 0, 0)); stg4(g_P + (size_t)k * SQ * DM + o0 + 256, make_uint4(0, 0, 0, 0)); }
        }
        row = nxt;
    }
    if (id == 0 && lane == 0) { g_epoch = epoch; if (epoch == 0xffffffu) { g_ticket[0] = 0; g_ticket[32] = 0; } }
}

__device__ __forceinline__ void g_producer(uint32_t sb, int g, const Maps& maps, uint32_t epoch, const bf16* __restrict__ x, const bf16* __restrict__ wr, bf16* __restrict__ out) {
    const uint32_t bar = sb + G_BAR;
    const int warp = (threadIdx.x >> 5) - 8;
    if (threadIdx.x == 256 && g == 5) GT(1410);
    if (threadIdx.x == 256 && g == 5) GT(1411);
    if (warp == 3) {
        wait_eq4(&g_f.xn[(threadIdx.x & 31) * 4], epoch, 13);
        __syncwarp();
        if ((threadIdx.x & 31) == 0) mbar_arrive(bar + 8 * GB_XN);
        finalizer(g, x, wr, out, epoch, nullptr);
        if (g == 63 && (threadIdx.x & 31) == 0) GT(128 * 8 + 6);
    }
    if ((threadIdx.x & 31) != 0) return;
    if (threadIdx.x == 256 && g == 5) GT(1412);
    if (warp == 0) {
        wait_eq4(&g_f.xn[0], epoch, 13);
        const int rk = g & 1;
        const int m1 = g < 32 ? HSPLIT : 2 * NT - HSPLIT;
        const int mx = g < 32 ? m1 + NT : m1;
#pragma unroll 1
        for (int it = 0; it < mx; it++) {
            const int tile = g < 32 ? (it < m1 ? it : it - m1) : (it < NT ? it : it - NT + HSPLIT);
            if (it == 1) wait_eq4(&g_f.xn[4], epoch, 13);
            if (it == 2) mbar_wait(bar + 8 * GB_XN, 0);
            if (it == HP) mbar_wait(bar + 8 * GB_P0, 0);
            const bool nw = it == 0 || it == (g < 32 ? m1 : NT);
#pragma unroll
            for (int k = 0; k < 4; k++) {
                mbar_wait(bar + 8 * (GB_EMPTY + k), (it & 1) ^ 1);
                mbar_expect_tx(bar + 8 * (GB_FULL + k), nw ? 49152 : 16384);
                tma2d_mc(sb + slot_off(k) + rk * 8192, &maps.xn2, (k * 2 + rk) * 64, tile * 64, bar + 8 * (GB_FULL + k));
                if (nw && (it > 0 || k >= WK0))
                    load_w(sb, it > 0 && g < 32 ? &maps.wq4 : ((g & 1) ? &maps.wv4 : &maps.wk4), it == 0 ? (g >> 1) * 128 : (g < 32 ? g * 128 : ((g - 32) >> 1) * 128), k);
            }
        }
        if (g >= 32) {
            const int u = g - 32, ks = u >> 2, ns = u & 3;
            int slot = 0, ph = 1;
#pragma unroll 1
            for (int tile = 0; tile < NT; tile++) {
                if (tile > 0) wait_eq4(&g_f.o[tile][ks][0], epoch, 9);
                if (g == 40 && tile == NT - 1) GT(1437);
                if (tile == NT - 1) GT(1690 + g - 32);
#pragma unroll 1
                for (int k = 0; k < 4; k++) {
                    mbar_wait(bar + 8 * (GB_EMPTY + slot), slot < 4 ? ph : ph ^ 1);
                    mbar_expect_tx(bar + 8 * (GB_FULL + slot), tile == 0 ? 49152 : 16384);
                    if (tile == 0) {
#pragma unroll
                        for (int nh = 0; nh < 2; nh++)
                            asm volatile("cp.async.bulk.tensor.5d.shared::cluster.global.mbarrier::complete_tx::bytes [%0], [%1, {%3, %4, %4, %4, %5}], [%2];"
                                :: "r"(sb + G_W + nh * 65536 + k * 16384), "l"((uint64_t)&maps.wo2), "r"(bar + 8 * (GB_FULL + k)), "r"(ns * 128 + nh * 64), "r"(0), "r"(ks * 16 + k * 4) : "memory");
                        if (k == 0) wait_eq4(&g_f.o[0][ks][0], epoch, 9);
                    }
                    tma2d_mc_h(sb + slot_off(slot) + rk * 8192, &maps.ox2, (ks * 8 + k * 2 + rk) * 64, tile * 64, bar + 8 * (GB_FULL + slot), pol_ef(1));
                    if (++slot == NS3) { slot = 0; ph ^= 1; }
                }
            }
        }
    } else if (warp < 3) {
        const int wg = warp - 1;
        const uint32_t buf = sb + G_BUF + wg * 32768;
        const CUtensorMap* tkv = (g & 1) ? &maps.vx3 : &maps.kx3;
        const int n1 = g < 32 ? HSPLIT / 2 : NT - HSPLIT / 2;
#pragma unroll 1
        for (int i = 0; i < n1; i++) {
            const int tile = (i < NT / 2 ? 2 * i : 2 * i - NT + HSPLIT) + wg, hd = (i < NT / 2 ? g : g - 32) >> 1;
            mbar_wait(bar + 8 * (GB_STG + wg), i & 1);
            tma_store3d(tkv, buf, tile * 64, hd * 2);
            asm volatile("cp.async.bulk.commit_group;" ::: "memory");
            asm volatile("cp.async.bulk.wait_group.read 0;" ::: "memory");
            mbar_arrive(bar + 8 * (GB_FREE + wg));
            asm volatile("cp.async.bulk.wait_group 0;" ::: "memory");
            PUBLISH(&g_f.kv[tile][hd][g & 1], epoch);
            if (tile == 0) { mbar_arrive(bar + 8 * GB_P0); if (g == 6) GT(1429); }
        }
        if (wg == 0) mbar_arrive(bar + 8 * GB_T1D);
        if (g >= 32) for (int i = 0; i < 4; i++) mbar_arrive2_if(bar + 8 * (GB_EMPTY + 4 + wg), 1);
        if (g < 32 && wg == 1) {
            mbar_wait(bar + 8 * GB_T1D, 0);
#pragma unroll 1
            for (int tile = 0; tile < NT; tile++) {
                wait_eq2(&g_f.kv[tile][g][0], epoch, 10);
                if (tile > 0) mbar_wait(bar + 8 * GB_KVF, (tile - 1) & 1);
                mbar_expect_tx(bar + 8 * (GB_KV + (tile & 1)), 16384);
                tma3d_h(sb + G_BUF, &maps.kx3, tile * 64, g * 2, bar + 8 * (GB_KV + (tile & 1)), pol_ef(0));
                if (tile > 0) mbar_wait(bar + 8 * GB_VF, (tile - 1) & 1);
                mbar_expect_tx(bar + 8 * (GB_VV + (tile & 1)), 16384);
                tma3d_h(sb + G_BUF + 32768, &maps.vx3, tile * 64, g * 2, bar + 8 * (GB_VV + (tile & 1)), pol_ef(0));
                if (PFK && tile + PFK < NT) {
                    const uint2 v = ldg_rlx2(&g_f.kv[tile + PFK][g][0]);
                    if (v.x == epoch && v.y == epoch) { tma_pf3d(&maps.kx3, (tile + PFK) * 64, g * 2); tma_pf3d(&maps.vx3, (tile + PFK) * 64, g * 2); }
                }
            }
        } else {
#pragma unroll 1
            for (int tile = g < 32 ? 0 : wg; tile < NT; tile += g < 32 ? 1 : 2) {
                mbar_wait(bar + 8 * (GB_STG + (tile & 1)), ((tile >> 1) + PO) & 1);
                mbar_arrive(bar + 8 * (GB_FREE + (tile & 1)));
                if (g < 32 || tile < LLT) PUBLISH(g < 32 ? &g_f.o[tile][g >> 2][g & 3] : &g_f.p[tile][g - 32], epoch);
                else stg_rlx(&g_f.p[tile][g - 32], epoch);
                if (g == 3 && tile == NT - 1) GT(1436);
                if (g == 3) GT(1896 + tile);
                if (g < 32 && tile == NT - 1) GT(1610 + g);
                if (g == 40 && tile == NT - 1) GT(1435);
                if (g == 40) GT(1864 + tile);
                if (g >= 32 && tile == NT - 1) GT(1650 + g - 32);
            }
        }
    }
}

struct WPtr { const bf16 *q, *k, *v, *o, *g, *u; };
__device__ __forceinline__ int startup(uint8_t* smem, const bf16* __restrict__ x, const Maps& maps, uint32_t& epoch, const WPtr& pw) {
    const int tid = threadIdx.x, lane = tid & 31, w = tid >> 5, cta = blockIdx.x;
    volatile uint32_t* sh = (volatile uint32_t*)(smem + SH_OFF);
    if (cta == 4 && tid == 0) GT(1399);
    epoch = (ldg_rlx(&g_epoch) + 1) & 0x00ffffffu;
    if (w < 4) {
        if (!(cta & 1)) {
            uint32_t* pp = (uint32_t*)(xpage() + ((XR3 ^ 0x3000u) ^ ((w == 1 || w == 2) ? 0x1000u : 0u) ^ ((w & 2) << 13))) + (cta >> 1) * 8;
            if (lane < 8) stg_rlx(pp + lane, 0u);
            __syncwarp();
            if (lane == 0) {
                uint32_t best = 0xffffffffu, a = 0;
#pragma unroll 1
                for (int r = 0; r < NPROBE; r++) {
                    uint32_t t0 = clk32();
                    asm volatile("atom.relaxed.gpu.global.add.u32 %0, [%1], %2;" : "=r"(a) : "l"(pp), "r"(a + 1) : "memory");
                    if (a == 0x7fffffffu) ABORT(15);
                    uint32_t t1 = clk32();
                    if (cta == 4 && w == 1) GT(1404 + r);
                    if (r > 0) best = min(best, t1 - t0);
                }
                sh[w] = best;
            }
        }
        if (!(cta & 1)) bar_sync(1, 160);
        if (cta == 4 && tid == 0) GT(1400);
        if (w == 0) {
            asm volatile("barrier.cluster.wait.aligned;" ::: "memory");
            if (lane == 0) {
                uint32_t rp;
                if (!(cta & 1)) {
                    uint32_t a = sh[0], b = sh[1], c = sh[2], d = sh[3];
                    uint32_t mid = (min(min(a, b), min(c, d)) + max(max(a, b), max(c, d))) >> 1;
                    const int dd = (int)min(a, d) - (int)min(b, c);
                    uint32_t cls = abs(dd) > 60 ? dd > 0 : a > mid;
                    uint32_t t = atomicAdd(&g_ticket[cls * 32], 1u) & 255;
                    if (t >= (cls ? 34u : 32u)) { cls ^= 1; t = atomicAdd(&g_ticket[cls * 32], 1u) & 255; }
                    rp = min(cls ? 32 + t : t, 65u);
                    asm volatile("st.relaxed.cluster.shared::cluster.u32 [%0], %1;" :: "r"((smem_u32(smem) + SH_OFF + 44) ^ 0x01000000u), "r"(rp) : "memory");
                } else {
                    uint32_t n = 0;
#pragma unroll 1
                    while ((rp = sh[11]) > 255) { if (++n > SPIN_LIMIT * 16) { ABORT(14); rp = 65; break; } }
                }
                if (cta == 4) GT(1407);
                if (cta == 5) GT(1408);
                const int role = rp * 2 + (cta & 1);
                sh[8] = role; sh[9] = epoch;
                while (sh[10] != epoch + 1 && cta < NWAITLN) {}
                if (RDEL && role < 64) __nanosleep(RDEL);
                if (role < 64) rec_first_loads(smem_u32(smem), role, maps);
                else if (role < 128) for (int k = 0; k < WK0; k++) load_w(smem_u32(smem), (role & 1) ? &maps.wv4 : &maps.wk4, ((role - 64) >> 1) * 128, k);
                if (cta == 4) GT(1401);
            }
        }
    } else {
        uint4 u[2][2];
        const int row0 = min(cta, 127) * 16 + (w - 4) * 2;
#pragma unroll
        for (int r = 0; r < 2; r++)
#pragma unroll
            for (int j = 0; j < 2; j++) u[r][j] = *(const uint4*)(x + (size_t)(row0 + r) * DM + j * 256 + lane * 8);
        if (w == 11 && !(cta & 1)) {
            if (lane < 2 && atomicMax(&g_ticket[lane * 32], epoch << 8) == 0xffffffffu) ABORT(15);
            __syncwarp();
            bar_arrive(1, 160);
        }
      if (cta < 128) {
        if (cta < 32) {
            const uint32_t off = acc_base((cta >> 3) * 2) ^ aslot(cta & 7);
            *(uint4*)(xpage() + off + (tid - 128) * 16) = make_uint4(0, 0, 0, 0);
        }
        float v[2][16];
#pragma unroll
        for (int r = 0; r < 2; r++)
#pragma unroll
            for (int j = 0; j < 2; j++) {
                uint32_t ww[4] = {u[r][j].x, u[r][j].y, u[r][j].z, u[r][j].w};
#pragma unroll
                for (int i = 0; i < 4; i++) { v[r][j * 8 + 2 * i] = bf_lo(ww[i]); v[r][j * 8 + 2 * i + 1] = bf_hi(ww[i]); }
            }
        ln_row2(v[0], v[1]);
#pragma unroll
        for (int r = 0; r < 2; r++)
#pragma unroll
            for (int j = 0; j < 2; j++)
                *(uint4*)(g_xn + (size_t)(row0 + r) * DM + j * 256 + lane * 8) =
                    make_uint4(pack2(v[r][j * 8], v[r][j * 8 + 1]), pack2(v[r][j * 8 + 2], v[r][j * 8 + 3]), pack2(v[r][j * 8 + 4], v[r][j * 8 + 5]), pack2(v[r][j * 8 + 6], v[r][j * 8 + 7]));
        bar_sync(2, 256);
        if (tid == 160 && cta < NWAITLN) { st_rel(&g_f.xn[cta], epoch); sh[10] = epoch + 1; }
        if (cta == 4 && tid == 160) GT(1403);
        __syncwarp();
      }
    }
    if (cta == 4 && tid == 128) GT(1402);
    __syncthreads();
    if (tid == 160 && cta >= NWAITLN && cta < 128) st_rel(&g_f.xn[cta], epoch);
    __syncwarp();
    const int role = sh[8];
    return role;
}

__global__ void __cluster_dims__(2, 1, 1) __launch_bounds__(384, 1)
main_kernel(const __grid_constant__ Maps maps, const bf16* __restrict__ x, const bf16* __restrict__ mem0, const bf16* __restrict__ wr,
            const bf16* __restrict__ wd, bf16* __restrict__ out, const WPtr pw) {
    extern __shared__ __align__(1024) uint8_t smem[];
    const uint32_t sb = smem_u32(smem);
    if (threadIdx.x == 0) {
        for (int i = 0; i < MB_N; i++) mbar_init(sb + R_BAR + 8 * i, i == MB_V ? 4 : 1);
        for (int i = 0; i < GB_N; i++)
            mbar_init(sb + G_BAR + 8 * i, i >= GB_EMPTY && i < GB_KV ? 8 : (i >= GB_KVF ? 4 : (i >= GB_STG && i < GB_FREE ? 128 : 1)));
        ((volatile uint32_t*)(smem + SH_OFF))[11] = 0xffffffffu;
        asm volatile("fence.mbarrier_init.release.cluster;" ::: "memory");
        if (((volatile uint32_t*)(smem + SH_OFF))[11] != 0xffffffffu) ABORT(14);
    }
    __syncwarp();
    asm volatile("barrier.cluster.arrive.relaxed.aligned;" ::: "memory");
    if (threadIdx.x >= 352 && threadIdx.x < 352 + (int)(sizeof(Maps) / sizeof(CUtensorMap)))
        asm volatile("prefetch.tensormap [%0];" :: "l"((const CUtensorMap*)&maps + (threadIdx.x - 352)) : "memory");
    uint32_t epoch;
    asm volatile("fence.proxy.async.shared::cta;" ::: "memory");
    const int role = uni(startup(smem, x, maps, epoch, pw));
    if (threadIdx.x >= 32) asm volatile("barrier.cluster.wait.aligned;" ::: "memory");
    const int wg = uni(threadIdx.x >> 7);
    if (role < 64) {
#define SETREG(n) do { if ((n) < 168) asm volatile("setmaxnreg.dec.sync.aligned.u32 %0;" :: "n"(n)); if ((n) > 168) asm volatile("setmaxnreg.inc.sync.aligned.u32 %0;" :: "n"(n)); } while (0)
#define RESREG(n) do { if ((n) < 168) asm volatile("setmaxnreg.inc.sync.aligned.u32 168;"); if ((n) > 168) asm volatile("setmaxnreg.dec.sync.aligned.u32 168;"); } while (0)
        if (wg == WGA) {
            SETREG(RGA);
            rec_a(sb, role, mem0, epoch);
            RESREG(RGA);
        } else if (wg == WGB) {
            SETREG(RGB);
            rec_b(sb, role, epoch);
            RESREG(RGB);
        } else {
            SETREG(RGC);
            rec_c(sb, role, mem0, maps, epoch);
            RESREG(RGC);
        }
        ffn_phase(maps, out);
        if (threadIdx.x == 0) GT(((volatile int*)(smem + SH_OFF))[8] * 8 + 6);
    } else if (role < 128) {
        if (wg < 2) {
            asm volatile("setmaxnreg.inc.sync.aligned.u32 184;");
            g_consumer(sb, role - 64, wg, epoch);
            if (threadIdx.x == 128) GT(role * 8 + 6);
        } else {
            asm volatile("setmaxnreg.dec.sync.aligned.u32 136;");
            g_producer(sb, role - 64, maps, epoch, x, wr, out);
        }
    } else {
        const int id = (threadIdx.x >> 5) * 4 + role - 128;
        finalizer(64 + id, x, wr, out, epoch, id < 16 ? pw.g : (id < 32 ? pw.u : wd));

    }
}

typedef CUresult (*EncodeFn)(CUtensorMap*, CUtensorMapDataType, cuuint32_t, void*, const cuuint64_t*, const cuuint64_t*, const cuuint32_t*, const cuuint32_t*,
                             CUtensorMapInterleave, CUtensorMapSwizzle, CUtensorMapL2promotion, CUtensorMapFloatOOBfill);
static void make_map3(EncodeFn fn, CUtensorMap* m, const void* ptr, uint64_t cols, uint64_t rows) {
    cuuint64_t dims[3] = {64, rows, cols / 64};
    cuuint64_t strides[2] = {cols * 2, 128};
    cuuint32_t box[3] = {64, 64, 2};
    cuuint32_t es[3] = {1, 1, 1};
    fn(m, CU_TENSOR_MAP_DATA_TYPE_BFLOAT16, 3, (void*)ptr, dims, strides, box, es, CU_TENSOR_MAP_INTERLEAVE_NONE, CU_TENSOR_MAP_SWIZZLE_128B,
       CU_TENSOR_MAP_L2_PROMOTION_L2_256B, CU_TENSOR_MAP_FLOAT_OOB_FILL_NONE);
}
static void make_map(EncodeFn fn, CUtensorMap* m, const void* ptr, uint64_t cols, uint64_t rows, uint32_t bcols, uint32_t brows,
                     bool f32 = false, CUtensorMapSwizzle sw = CU_TENSOR_MAP_SWIZZLE_128B) {
    cuuint64_t dims[2] = {cols, rows};
    cuuint64_t strides[1] = {cols * (f32 ? 4 : 2)};
    cuuint32_t box[2] = {bcols, brows};
    cuuint32_t es[2] = {1, 1};
    fn(m, f32 ? CU_TENSOR_MAP_DATA_TYPE_FLOAT32 : CU_TENSOR_MAP_DATA_TYPE_BFLOAT16, 2, (void*)ptr, dims, strides, box, es, CU_TENSOR_MAP_INTERLEAVE_NONE, sw,
       CU_TENSOR_MAP_L2_PROMOTION_L2_256B, CU_TENSOR_MAP_FLOAT_OOB_FILL_NONE);
}

extern "C" void kernel_launch(void* const* d_in, const int* in_sizes, int n_in, void* d_out, int out_size) {
    const bf16* x = (const bf16*)d_in[0];
    const bf16* mem0 = (const bf16*)d_in[1];
    const bf16* Wq = (const bf16*)d_in[2];
    const bf16* Wk = (const bf16*)d_in[3];
    const bf16* Wv = (const bf16*)d_in[4];
    const bf16* Wo = (const bf16*)d_in[5];
    const bf16* wr = (const bf16*)d_in[8];
    const bf16* wg = (const bf16*)d_in[9];
    const bf16* wu = (const bf16*)d_in[10];
    const bf16* wd = (const bf16*)d_in[11];
    bf16* out = (bf16*)d_out;

    static EncodeFn enc = nullptr;
    static void *pxn, *pK, *pV, *pO, *pacc;
    if (!enc) {
        cudaDriverEntryPointQueryResult qr;
        void* fn = nullptr;
        cudaGetDriverEntryPoint("cuTensorMapEncodeTiled", &fn, cudaEnableDefault, &qr);
        enc = (EncodeFn)fn;
        cudaGetSymbolAddress(&pxn, g_xn); cudaGetSymbolAddress(&pK, g_K); cudaGetSymbolAddress(&pV, g_V);
        cudaGetSymbolAddress(&pO, g_O); cudaGetSymbolAddress(&pacc, g_P);
        cudaFuncSetAttribute(main_kernel, cudaFuncAttributeMaxDynamicSharedMemorySize, SMEM_TOTAL);
    }
    Maps m;
    make_map(enc, &m.wq, Wq, HD, DM, 64, 256);
    make_map(enc, &m.wk, Wk, HD, DM, 64, 256);
    make_map(enc, &m.wv, Wv, HD, DM, 64, 256);
    make_map(enc, &m.wq4, Wq, HD, DM, 64, 128); make_map(enc, &m.wk4, Wk, HD, DM, 64, 128); make_map(enc, &m.wv4, Wv, HD, DM, 64, 128);
    make_map(enc, &m.wo, Wo, DM, HD, 64, 128);
    {
        cuuint64_t dims[5] = {DM, 2, 4, 4, HD / 32};
        cuuint64_t strides[4] = {DM * 2, 8 * DM * 2, 2 * DM * 2, 32 * DM * 2};
        cuuint32_t box[5] = {64, 2, 4, 4, 4};
        cuuint32_t es[5] = {1, 1, 1, 1, 1};
        enc(&m.wo2, CU_TENSOR_MAP_DATA_TYPE_BFLOAT16, 5, (void*)Wo, dims, strides, box, es, CU_TENSOR_MAP_INTERLEAVE_NONE, CU_TENSOR_MAP_SWIZZLE_128B,
            CU_TENSOR_MAP_L2_PROMOTION_L2_256B, CU_TENSOR_MAP_FLOAT_OOB_FILL_NONE);
    }
    make_map(enc, &m.kx, pK, HD, SQ, 64, 64);
    make_map(enc, &m.ox2, pO, HD, SQ, 64, 64);
    make_map(enc, &m.xn2, pxn, DM, SQ, 64, 64);
    make_map3(enc, &m.kx3, pK, HD, SQ); make_map3(enc, &m.vx3, pV, HD, SQ);
    make_map(enc, &m.wg, wg, FF, DM, 32, 256, false, CU_TENSOR_MAP_SWIZZLE_64B);
    make_map(enc, &m.wu, wu, FF, DM, 32, 256, false, CU_TENSOR_MAP_SWIZZLE_64B);
    make_map(enc, &m.wd, wd, DM, FF, 64, 32);

    cudaStream_t st = cudaStreamPerThread;
    main_kernel<<<NCTA, 384, SMEM_TOTAL, st>>>(m, x, mem0, wr, wd, out, WPtr{Wq, Wk, Wv, Wo, wg, wu});
}
```
